```python
import torch

def _softmax(x, axis=-1):
    return torch.softmax(x, dim=axis)

def _gelu(x):
    return torch.nn.functional.gelu(x, approximate='tanh')

def _silu(x):
    return torch.nn.functional.silu(x)

def _sigmoid(x):
    return torch.sigmoid(x)

def _layernorm(x, axis=-1, eps=1e-05):
    m = x.mean(dim=axis, keepdim=True)
    v = x.var(dim=axis, keepdim=True, unbiased=False)
    return (x - m) / torch.sqrt(v + eps)

def _scatter_add(tgt, idx, src, axis=0):
    return tgt.clone().index_add_(axis, idx, src)

def _segment_sum(src, seg, n):
    out = torch.zeros((n,) + src.shape[1:], dtype=src.dtype)
    return out.index_add_(0, seg, src)

def _pad(x, pw):
    flat = tuple((v for pair in reversed(pw) for v in pair))
    return torch.nn.functional.pad(x, flat)
kernel_name = 'concat_heads__ssm_conv_s5__memory_aug_recurrent_mem_tr__prompt'

def setup_inputs():

    _w = lambda a: (lambda t: t.to(torch.bfloat16) if t.is_floating_point() else t)(torch.as_tensor(a))

    def _A_setup():
        B, S, D = (1, 2048, 1024)
        P = D
        Lambda_re = -0.5 * (lambda _x: torch.exp(torch.as_tensor(_x)))((lambda *s: torch.randn(*s, dtype=torch.bfloat16) * 0.8)(P))
        Lambda_im = (lambda *s: torch.randn(*s, dtype=torch.bfloat16) * 0.8)(P) * 1.0
        B_re = (lambda *s: torch.randn(*s, dtype=torch.bfloat16) * 0.8)(P, D) * D ** (-0.5)
        B_im = (lambda *s: torch.randn(*s, dtype=torch.bfloat16) * 0.8)(P, D) * D ** (-0.5)
        C_re = (lambda *s: torch.randn(*s, dtype=torch.bfloat16) * 0.8)(D, P) * P ** (-0.5)
        C_im = (lambda *s: torch.randn(*s, dtype=torch.bfloat16) * 0.8)(D, P) * P ** (-0.5)
        log_dt = (lambda *s: torch.randn(*s, dtype=torch.bfloat16) * 0.8)(P) * 0.3 - 2.0
        Dskip = (lambda *s: torch.randn(*s, dtype=torch.bfloat16) * 0.8)(D)
        return {'x': _w((lambda *s: torch.randn(*s, dtype=torch.bfloat16) * 0.05)(B, S, D)), 'Lambda_re': _w(Lambda_re), 'Lambda_im': _w(Lambda_im), 'B_re': _w(B_re), 'B_im': _w(B_im), 'C_re': _w(C_re), 'C_im': _w(C_im), 'log_dt': _w(log_dt), 'Dskip': _w(Dskip)}
    _A_in = _A_setup()

    def _B_setup():
        B, S, Dm = (1, 2048, 1024)
        H, Dh = (32, 128)
        M, seg = (8, 32)
        seg = min(seg, S)
        S = S // seg * seg
        return {'x': _w((lambda *s: torch.randn(*s, dtype=torch.bfloat16) * 0.05)(B, S, Dm)), 'mem0': _w((lambda *s: torch.randn(*s, dtype=torch.bfloat16) * 0.8)(B, M, Dm)), 'Wq': _w((lambda *s: torch.randn(*s, dtype=torch.bfloat16) * 3.2)(Dm, H, Dh) * Dm ** (-0.5)), 'Wk': _w((lambda *s: torch.randn(*s, dtype=torch.bfloat16) * 3.2)(Dm, H, Dh) * Dm ** (-0.5)), 'Wv': _w((lambda *s: torch.randn(*s, dtype=torch.bfloat16) * 0.8)(Dm, H, Dh) * Dm ** (-0.5)), 'Wo': _w((lambda *s: torch.randn(*s, dtype=torch.bfloat16) * 0.8)(H, Dh, Dm) * (H * Dh) ** (-0.5)), 'seg_len': seg}
    _B_in = _B_setup()
    return {'A_x': _A_in['x'], 'A_Lambda_re': _A_in['Lambda_re'], 'A_Lambda_im': _A_in['Lambda_im'], 'A_B_re': _A_in['B_re'], 'A_B_im': _A_in['B_im'], 'A_C_re': _A_in['C_re'], 'A_C_im': _A_in['C_im'], 'A_log_dt': _A_in['log_dt'], 'A_Dskip': _A_in['Dskip'], 'B_x': _B_in['x'], 'B_mem0': _B_in['mem0'], 'B_Wq': _B_in['Wq'], 'B_Wk': _B_in['Wk'], 'B_Wv': _B_in['Wv'], 'B_Wo': _B_in['Wo'], 'B_seg_len': _B_in['seg_len']}

def reference(A_x, A_Lambda_re, A_Lambda_im, A_B_re, A_B_im, A_C_re, A_C_im, A_log_dt, A_Dskip, B_x, B_mem0, B_Wq, B_Wk, B_Wv, B_Wo, B_seg_len):

    def _A_ref(x, Lambda_re, Lambda_im, B_re, B_im, C_re, C_im, log_dt, Dskip):
        Bsz, L, H = x.shape
        Lam = Lambda_re + 1j * Lambda_im
        Bmat = B_re + 1j * B_im
        Cmat = C_re + 1j * C_im
        dt = torch.exp(log_dt)
        Lam_bar = torch.exp(dt * Lam)
        B_bar = ((Lam_bar - 1.0) / Lam)[:, None] * Bmat
        Bu = torch.einsum('bld,pd->blp', x + 0j, B_bar)
        h = torch.zeros_like(Bu[:, 0, :])
        hs = []
        for t in range(L):
            h = Lam_bar[None, :] * h + Bu[:, t, :]
            hs.append(h)
        hseq = torch.stack(hs, 1)
        y = 2.0 * torch.einsum('blp,dp->bld', hseq, Cmat).real + x * Dskip[None, None, :]
        return y

    def _B_ref(x, mem0, Wq, Wk, Wv, Wo, seg_len):
        B, S, Dm = x.shape
        H, Dh = (Wq.shape[1], Wq.shape[2])
        M = mem0.shape[1]
        scale = Dh ** (-0.5)
        n_seg = S // seg_len
        L = M + seg_len
        idx = torch.arange(L)
        mask = (idx[:, None] < M) | (idx[:, None] >= idx[None, :])
        mem = mem0
        outs = []
        for s in range(n_seg):
            xs = x[:, s * seg_len:(s + 1) * seg_len, :].clone()
            h = torch.concatenate([mem, xs], axis=1)
            q = torch.einsum('btd,dhe->bhte', h, Wq)
            k = torch.einsum('btd,dhe->bhte', h, Wk)
            v = torch.einsum('btd,dhe->bhte', h, Wv)
            scores = torch.einsum('bhqe,bhke->bhqk', q, k) * scale
            scores = torch.where(mask[None, None], scores, -1000000000.0)
            p = _softmax(scores, axis=-1)
            o = torch.einsum('bhqk,bhke->bhqe', p, v)
            o = torch.einsum('bhte,hed->btd', o, Wo)
            mem = o[:, :M, :].clone()
            outs.append(o[:, M:, :])
        return torch.concatenate(outs, axis=1)
    a = _A_ref(A_x, A_Lambda_re, A_Lambda_im, A_B_re, A_B_im, A_C_re, A_C_im, A_log_dt, A_Dskip)
    b = _B_ref(B_x, B_mem0, B_Wq, B_Wk, B_Wv, B_Wo, B_seg_len)
    return torch.concatenate([a, b], axis=-1)
```

```cpp
#include <cuda_runtime.h>
#include <cuda_bf16.h>
#include <cuda.h>
#include <stdint.h>
#include <string.h>

typedef __nv_bfloat16 bf16;

namespace {

constexpr int SPIN_LIMIT = 1 << 22;
constexpr int NPAIR = 66;
constexpr int NCHAIN = 48;
enum { T_KV = 0, T_QA = 1, T_OP = 2, T_A1 = 3, T_A2 = 4, T_CHAIN = 5, T_OPH = 6, T_A2H = 7 };
enum { M_BX = 0, M_WQ, M_WK, M_WV, M_WO, M_OA, M_AB, M_AX, M_HT, M_CRE, M_CIM, M_KVO, M_HTS, M_WOH, M_CREH, M_CIMH, M_CQ, M_CK, M_CV, M_CO, M_CO1, M_COUNT };
enum { C_KV = 0, C_O = 8, C_HT = 16, C_DONE = 24, C_EPOCH = 25, C_COEF = 26, C_FLAG = 32 };

struct Params {
    CUtensorMap tm[M_COUNT];
    const bf16 *Wq, *Wk, *Wv, *Wo, *mem0, *Lre, *Lim, *logdt, *Dskip;
    float* out;
    uint8_t* gm;
    int swap_ri, zero;
    uint32_t two26;
    int ds, da, db, dk, tight, extra;
#define DBGF(x) false
};

constexpr int NPRE = 1;
__constant__ uint16_t c_off[67] = {0, 4, 8, 12, 16, 20, 24, 28, 32, 37, 42, 47, 52, 57, 62, 67, 72, 77, 82, 87, 92, 97, 102, 107, 112, 117, 122, 127, 132, 136, 140, 144, 148, 152, 156, 160, 164, 168, 172, 176, 180, 184, 188, 192, 196, 200, 204, 209, 214, 234, 254, 274, 294, 314, 334, 354, 374, 393, 412, 430, 448, 466, 484, 502, 520, 540, 560};
__constant__ uint16_t c_items[640] = {
    0, 1280, 452, 704, 33, 1280, 453, 705, 3, 1280, 454, 706, 36, 1280, 455, 707, 6, 1280, 456, 736, 39, 1280, 457, 737,
    9, 1280, 458, 738, 42, 1280, 459, 739, 12, 1280, 460, 898, 1120, 45, 1280, 461, 899, 1121, 15, 1280, 462, 900, 1122, 48,
    1280, 463, 901, 1123, 18, 1280, 480, 902, 1152, 51, 1280, 481, 903, 1153, 21, 1280, 482, 928, 1154, 54, 1280, 483, 929, 1155,
    32, 1280, 484, 930, 1184, 2, 1280, 485, 931, 1185, 35, 1280, 486, 932, 1186, 5, 1280, 487, 933, 1187, 38, 1280, 488, 934,
    1216, 8, 1280, 489, 935, 1217, 41, 1280, 490, 960, 1218, 11, 1280, 491, 961, 1219, 44, 1280, 492, 962, 1248, 14, 1280, 493,
    963, 1249, 47, 1280, 494, 964, 1250, 17, 1280, 495, 965, 1251, 50, 1280, 768, 546, 20, 1280, 769, 547, 53, 1280, 770, 576,
    23, 1280, 771, 577, 1, 1280, 772, 578, 34, 1280, 773, 579, 4, 1280, 774, 608, 37, 1280, 775, 609, 7, 1280, 800, 610,
    40, 1280, 801, 611, 10, 1280, 802, 640, 43, 1280, 803, 641, 13, 1280, 804, 642, 46, 1280, 805, 643, 16, 1280, 806, 672,
    49, 1280, 807, 673, 19, 1280, 832, 674, 52, 1280, 833, 675, 22, 1280, 834, 896, 1026, 55, 1280, 835, 897, 1027, 24, 66,
    84, 102, 256, 124, 288, 144, 162, 180, 198, 208, 226, 244, 334, 384, 418, 836, 966, 1056, 56, 67, 85, 103, 257, 125,
    289, 145, 163, 181, 199, 209, 227, 245, 335, 385, 419, 837, 967, 1057, 25, 68, 86, 104, 258, 126, 290, 146, 164, 182,
    200, 210, 228, 246, 352, 386, 420, 838, 992, 1058, 57, 69, 87, 105, 259, 127, 291, 147, 165, 183, 201, 211, 229, 247,
    353, 387, 421, 839, 993, 1059, 26, 70, 88, 106, 260, 128, 292, 148, 166, 184, 202, 212, 230, 248, 354, 388, 422, 864,
    994, 1088, 58, 71, 89, 107, 261, 129, 293, 149, 167, 185, 203, 213, 231, 249, 355, 389, 423, 865, 995, 1089, 27, 72,
    90, 108, 262, 130, 294, 150, 168, 186, 204, 214, 232, 250, 356, 390, 424, 866, 996, 1090, 59, 73, 91, 109, 263, 131,
    295, 151, 169, 187, 205, 215, 233, 251, 357, 391, 425, 867, 997, 1091, 28, 74, 92, 110, 264, 132, 296, 152, 170, 188,
    320, 218, 236, 254, 360, 394, 428, 870, 1024, 60, 75, 93, 111, 265, 133, 297, 153, 171, 189, 321, 219, 237, 255, 361,
    395, 429, 871, 1025, 29, 76, 94, 112, 266, 134, 298, 154, 172, 190, 322, 220, 238, 328, 362, 396, 430, 512, 61, 77,
    95, 113, 267, 135, 299, 155, 173, 191, 323, 221, 239, 329, 363, 397, 431, 513, 30, 78, 96, 114, 268, 136, 300, 156,
    174, 192, 324, 222, 240, 330, 364, 398, 448, 514, 62, 79, 97, 115, 269, 137, 301, 157, 175, 193, 325, 223, 241, 331,
    365, 399, 449, 515, 31, 80, 98, 116, 270, 138, 302, 158, 176, 194, 326, 224, 242, 332, 366, 416, 450, 544, 63, 81,
    99, 117, 271, 139, 303, 159, 177, 195, 327, 225, 243, 333, 367, 417, 451, 545, 64, 82, 100, 118, 120, 122, 140, 142,
    160, 178, 196, 206, 216, 234, 252, 358, 392, 426, 868, 998, 65, 83, 101, 119, 121, 123, 141, 143, 161, 179, 197, 207,
    217, 235, 253, 359, 393, 427, 869, 999,
};
#define ITEM_OFF(p) c_off[p]
#define ITEM(i) c_items[i]

__device__ __align__(1024) bf16 g_kvo[3 * 2048 * 4096];
__device__ __align__(1024) bf16 g_ht[2048 * 2048];
__device__ __align__(1024) uint8_t g_m[9 * 32768];
__device__ __align__(1024) uint8_t g_f[8 * 49152];
__device__ __align__(1024) uint32_t g_km[64 * 32 * 512];
__device__ __align__(1024) uint32_t g_vmt[64 * 32 * 512];
__device__ __align__(1024) float2 g_agg[8 * 1024];
__device__ __align__(1024) float4 g_coef[1024];
__device__ __align__(1024) uint32_t g_cntl[128 * 32];
#define g_cnt(i) g_cntl[(i) * 32]
__device__ __align__(1024) uint32_t g_hint[6144 + 96 * 32];
#define PROF(i)
#define GT_EDGE(o)
constexpr int M_SLOT = 32768, F_SLOT = 49152;

constexpr int STAGE = 49152, NSTAGE = 4;
constexpr int S_STG = NSTAGE * STAGE;
constexpr int S_BAR = S_STG + 32768;
constexpr int B_FULL = S_BAR, B_EMPTY = S_BAR + 32, B_RESUME = S_BAR + 64, B_KVFULL = S_BAR + 72, B_GO = S_BAR + 88, B_K = S_BAR + 96, B_PERS = S_BAR + 104, B_INIT = S_BAR + 112, B_RELA = S_BAR + 120, B_V = S_BAR + 128, B_WO = S_BAR + 136,
              B_SFULL = S_BAR + 144, B_SFREE = S_BAR + 160, S_DESC = S_BAR + 176, S_EPOCH = S_BAR + 208, B_RELB = S_BAR + 216, B_KVGO = S_BAR + 224;
constexpr int S_TOTAL = S_BAR + 256 + 512;
constexpr int S_W1 = 0;
constexpr int S_O = 24 * 4096, S_VL = S_O + 2048, S_MX = 25 * 4096, S_SC = S_MX + 64, S_SUM = S_MX + 128;
constexpr int S_KL = 26 * 4096;
constexpr int S_W2 = 27 * 4096;
constexpr int S_KV = S_W2 + 65536;
constexpr int S_P1 = S_W2 + 98304;
constexpr int S_QX = S_P1 + 16384;
constexpr int S_SX = S_QX + 2048;
static_assert(S_SX + 1280 <= S_BAR, "chain smem overlaps barriers");
constexpr int NR = 40, NS = 64 - NR;

__device__ __forceinline__ uint32_t logical_cta(uint32_t b) {
    const uint32_t c = b / 6, r = b - c * 6;
    return gridDim.x != 96 ? 96 + b : ((r >> 1) + (c >= 8) + (c >= 15)) % 3 * 32 + c * 2 + (r & 1);
}
__device__ __forceinline__ uint32_t cluster_rank() { uint32_t r; asm("mov.u32 %0, %%cluster_ctarank;" : "=r"(r)); return r; }
__device__ __forceinline__ uint16_t pair_mask() { return (uint16_t)(3u << (cluster_rank() & 6)); }
__device__ __forceinline__ void spin_fault() { asm volatile("st.global.u32 [%0], 0;" ::"l"(0ull) : "memory"); }
__device__ __forceinline__ uint32_t smem_u32(const void* p) { return (uint32_t)__cvta_generic_to_shared(p); }
__device__ __forceinline__ uint32_t opq(uint32_t x, int lane) { return __shfl_sync(0xffffffffu, x, lane); }
__device__ __forceinline__ uint32_t mapa(uint32_t a, uint32_t r) { uint32_t d; asm volatile("mapa.shared::cluster.u32 %0, %1, %2;" : "=r"(d) : "r"(a), "r"(r)); return d; }
__device__ __forceinline__ void mma16816(float* d, uint32_t a0, uint32_t a1, uint32_t a2, uint32_t a3, uint32_t b0, uint32_t b1) {
    asm("mma.sync.aligned.m16n8k16.row.col.f32.bf16.bf16.f32 {%0,%1,%2,%3}, {%4,%5,%6,%7}, {%8,%9}, {%0,%1,%2,%3};"
        : "+f"(d[0]), "+f"(d[1]), "+f"(d[2]), "+f"(d[3]) : "r"(a0), "r"(a1), "r"(a2), "r"(a3), "r"(b0), "r"(b1));
}
__device__ __forceinline__ void mma1688(float* d, uint32_t a0, uint32_t a1, uint32_t b0) {
    asm("mma.sync.aligned.m16n8k8.row.col.f32.bf16.bf16.f32 {%0,%1,%2,%3}, {%4,%5}, {%6}, {%0,%1,%2,%3};"
        : "+f"(d[0]), "+f"(d[1]), "+f"(d[2]), "+f"(d[3]) : "r"(a0), "r"(a1), "r"(b0));
}
__device__ __forceinline__ void ldsm4(uint32_t* r, uint32_t a) {
    asm volatile("ldmatrix.sync.aligned.m8n8.x4.shared.b16 {%0,%1,%2,%3}, [%4];" : "=r"(r[0]), "=r"(r[1]), "=r"(r[2]), "=r"(r[3]) : "r"(a));
}
__device__ __forceinline__ void ldsm4t(uint32_t* r, uint32_t a) {
    asm volatile("ldmatrix.sync.aligned.m8n8.x4.trans.shared.b16 {%0,%1,%2,%3}, [%4];" : "=r"(r[0]), "=r"(r[1]), "=r"(r[2]), "=r"(r[3]) : "r"(a));
}
__device__ __forceinline__ void stsm4(uint32_t a, uint32_t r0, uint32_t r1, uint32_t r2, uint32_t r3) {
    asm volatile("stmatrix.sync.aligned.m8n8.x4.shared.b16 [%0], {%1,%2,%3,%4};" ::"r"(a), "r"(r0), "r"(r1), "r"(r2), "r"(r3) : "memory");
}
__device__ __forceinline__ void stsm4t(uint32_t a, uint32_t r0, uint32_t r1, uint32_t r2, uint32_t r3) {
    asm volatile("stmatrix.sync.aligned.m8n8.x4.trans.shared.b16 [%0], {%1,%2,%3,%4};" ::"r"(a), "r"(r0), "r"(r1), "r"(r2), "r"(r3) : "memory");
}
__device__ __forceinline__ uint32_t pack2(float lo, float hi) { uint32_t d; asm("cvt.rn.bf16x2.f32 %0, %1, %2;" : "=r"(d) : "f"(hi), "f"(lo)); return d; }
__device__ __forceinline__ float bf_lo(uint32_t u) { return __uint_as_float(u << 16); }
__device__ __forceinline__ float bf_hi(uint32_t u) { return __uint_as_float(u & 0xffff0000u); }
__device__ __forceinline__ float ex2(float x) { float y; asm("ex2.approx.ftz.f32 %0, %1;" : "=f"(y) : "f"(x)); return y; }
__device__ __forceinline__ float rcp(float x) { float y; asm("rcp.approx.ftz.f32 %0, %1;" : "=f"(y) : "f"(x)); return y; }
__device__ __forceinline__ void st_relaxed4(const void* p, uint32_t a, uint32_t b, uint32_t c, uint32_t d) {
    asm volatile("{\n.reg .b128 t;\nmov.b128 t, {%1,%2,%3,%4};\nst.relaxed.gpu.global.b128 [%0], t;\n}" ::"l"(p), "r"(a), "r"(b), "r"(c), "r"(d) : "memory");
}
__device__ __forceinline__ void st_relaxed2(const void* p, uint32_t a, uint32_t b) {
    asm volatile("{\n.reg .b64 t;\nmov.b64 t, {%1,%2};\nst.relaxed.gpu.global.b64 [%0], t;\n}" ::"l"(p), "r"(a), "r"(b) : "memory");
}
__device__ __forceinline__ void ld_relaxed2_if(uint32_t& a, uint32_t& b, const void* p, bool on) {
    asm volatile("{\n.reg .pred P;\n.reg .b64 t;\nsetp.ne.u32 P, %3, 0;\nmov.b64 t, {%0,%1};\n@P ld.relaxed.gpu.global.b64 t, [%2];\nmov.b64 {%0,%1}, t;\n}" : "+r"(a), "+r"(b) : "l"(p), "r"((uint32_t)on) : "memory");
}
__device__ __forceinline__ uint32_t ld_relaxed1(const void* p) { uint32_t v; asm volatile("ld.relaxed.gpu.global.u32 %0, [%1];" : "=r"(v) : "l"(p) : "memory"); return v; }
__device__ __forceinline__ void st_relaxed1(const void* p, uint32_t v) { asm volatile("st.relaxed.gpu.global.u32 [%0], %1;" ::"l"(p), "r"(v) : "memory"); }
__device__ __forceinline__ uint32_t ld_acquire(const void* p) { uint32_t v; asm volatile("ld.acquire.gpu.global.u32 %0, [%1];" : "=r"(v) : "l"(p) : "memory"); return v; }
__device__ __forceinline__ void red_release(void* p) { asm volatile("red.release.gpu.global.add.u32 [%0], 1;" ::"l"(p) : "memory"); }
__device__ __forceinline__ void st_stream2(float* p, float a, float b) { asm volatile("st.global.cs.v2.f32 [%0], {%1, %2};" ::"l"(p), "f"(a), "f"(b) : "memory"); }
__device__ __forceinline__ void fence_gpu() { asm volatile("fence.acq_rel.gpu;" ::: "memory"); }
__device__ __forceinline__ void fence_async() { asm volatile("fence.proxy.async;" ::: "memory"); }
__device__ __forceinline__ void fence_async_smem() { asm volatile("fence.proxy.async.shared::cta;" ::: "memory"); }
__device__ __forceinline__ void wait_count(const uint32_t* p, uint32_t target) {
    int n = 0;
    while ((int32_t)(ld_acquire(p) - target) < 0) { __nanosleep(200); if (++n > SPIN_LIMIT) spin_fault(); }
}
__device__ __forceinline__ void bar_sync(int id, int n) { asm volatile("bar.sync %0, %1;" ::"r"(id), "r"(n) : "memory"); }
__device__ __forceinline__ bool bar_and(int id, bool v) {
    uint32_t r;
    asm volatile("{\n.reg .pred P, Q;\nsetp.ne.u32 Q, %2, 0;\nbar.red.and.pred P, %1, 128, Q;\nselp.u32 %0, 1, 0, P;\n}" : "=r"(r) : "r"(id), "r"((uint32_t)v) : "memory");
    return r;
}
__device__ __forceinline__ void lds128(uint32_t* v, uint32_t a) { asm volatile("ld.shared.v4.b32 {%0,%1,%2,%3}, [%4];" : "=r"(v[0]), "=r"(v[1]), "=r"(v[2]), "=r"(v[3]) : "r"(a) : "memory"); }
__device__ __forceinline__ uint32_t lds32(uint32_t a) { uint32_t v; asm volatile("ld.shared.b32 %0, [%1];" : "=r"(v) : "r"(a) : "memory"); return v; }
__device__ __forceinline__ void lds64(uint32_t* v, uint32_t a) { asm volatile("ld.shared.v2.b32 {%0,%1}, [%2];" : "=r"(v[0]), "=r"(v[1]) : "r"(a) : "memory"); }
__device__ __forceinline__ void lds64f(float* v, uint32_t a) { asm volatile("ld.shared.v2.f32 {%0,%1}, [%2];" : "=f"(v[0]), "=f"(v[1]) : "r"(a) : "memory"); }
__device__ __forceinline__ void sts128(uint32_t a, const uint32_t* v) { asm volatile("st.shared.v4.b32 [%0], {%1,%2,%3,%4};" ::"r"(a), "r"(v[0]), "r"(v[1]), "r"(v[2]), "r"(v[3]) : "memory"); }
__device__ __forceinline__ void sts64(uint32_t a, uint32_t x, uint32_t y) { asm volatile("st.shared.v2.b32 [%0], {%1,%2};" ::"r"(a), "r"(x), "r"(y) : "memory"); }
__device__ __forceinline__ void sts32(uint32_t a, uint32_t x) { asm volatile("st.shared.b32 [%0], %1;" ::"r"(a), "r"(x) : "memory"); }
__device__ __forceinline__ bool mbar_try(uint32_t b, uint32_t par) {
    uint32_t ok;
    asm volatile("{\n.reg .pred P;\nmbarrier.try_wait.parity.shared::cta.b64 P, [%1], %2;\nselp.u32 %0, 1, 0, P;\n}" : "=r"(ok) : "r"(b), "r"(par) : "memory");
    return ok;
}
__device__ __forceinline__ void mbar_wait(uint32_t b, uint32_t par) { int n = 0; while (!mbar_try(b, par)) { if (++n > SPIN_LIMIT) spin_fault(); } }
__device__ __forceinline__ void mbar_init(uint32_t b, uint32_t n) { asm volatile("mbarrier.init.shared::cta.b64 [%0], %1;" ::"r"(b), "r"(n) : "memory"); }
__device__ __forceinline__ void mbar_expect(uint32_t b, uint32_t bytes) { asm volatile("mbarrier.arrive.expect_tx.shared::cta.b64 _, [%0], %1;" ::"r"(b), "r"(bytes) : "memory"); }
__device__ __forceinline__ void mbar_arrive(uint32_t b) { asm volatile("mbarrier.arrive.shared::cta.b64 _, [%0];" ::"r"(b) : "memory"); }
__device__ __forceinline__ void mbar_arrive_cluster(uint32_t b) { asm volatile("mbarrier.arrive.shared::cluster.b64 _, [%0];" ::"r"(b) : "memory"); }
__device__ __forceinline__ void st_async1(uint32_t a, uint32_t x, uint32_t bar) {
    asm volatile("st.async.weak.shared::cluster.mbarrier::complete_tx::bytes.b32 [%0], %1, [%2];" ::"r"(a), "r"(x), "r"(bar) : "memory");
}
__device__ __forceinline__ void st_async2(uint32_t a, uint32_t x, uint32_t y, uint32_t bar) {
    asm volatile("st.async.weak.shared::cluster.mbarrier::complete_tx::bytes.v2.b32 [%0], {%1,%2}, [%3];" ::"r"(a), "r"(x), "r"(y), "r"(bar) : "memory");
}
__device__ __forceinline__ void cluster_sync() { asm volatile("barrier.cluster.arrive.aligned;\nbarrier.cluster.wait.aligned;" ::: "memory"); }
__device__ __forceinline__ void tma2d(uint32_t dst, const CUtensorMap* m, int c0, int c1, uint32_t bar) {
    asm volatile("cp.async.bulk.tensor.2d.shared::cluster.global.mbarrier::complete_tx::bytes [%0], [%1, {%2, %3}], [%4];" ::"r"(dst), "l"(m), "r"(c0), "r"(c1), "r"(bar) : "memory");
}
__device__ __forceinline__ void tma2d_mc(uint32_t dst, const CUtensorMap* m, int c0, int c1, uint32_t bar) {
    asm volatile("cp.async.bulk.tensor.2d.shared::cluster.global.mbarrier::complete_tx::bytes.multicast::cluster [%0], [%1, {%2, %3}], [%4], %5;" ::"r"(dst), "l"(m), "r"(c0), "r"(c1), "r"(bar), "h"(pair_mask()) : "memory");
}
__device__ __forceinline__ void tma3d(uint32_t dst, const CUtensorMap* m, int c0, int c1, int c2, uint32_t bar) {
    asm volatile("cp.async.bulk.tensor.3d.shared::cluster.global.mbarrier::complete_tx::bytes [%0], [%1, {%2, %3, %4}], [%5];" ::"r"(dst), "l"(m), "r"(c0), "r"(c1), "r"(c2), "r"(bar) : "memory");
}
__device__ __forceinline__ void tma3d_mc(uint32_t dst, const CUtensorMap* m, int c0, int c1, int c2, uint32_t bar) {
    asm volatile("cp.async.bulk.tensor.3d.shared::cluster.global.mbarrier::complete_tx::bytes.multicast::cluster [%0], [%1, {%2, %3, %4}], [%5], %6;" ::"r"(dst), "l"(m), "r"(c0), "r"(c1), "r"(c2), "r"(bar), "h"(pair_mask()) : "memory");
}
__device__ __forceinline__ void tma4d(uint32_t dst, const CUtensorMap* m, int c0, int c3, uint32_t bar) {
    asm volatile("cp.async.bulk.tensor.4d.shared::cluster.global.mbarrier::complete_tx::bytes [%0], [%1, {%2, 0, 0, %3}], [%4];" ::"r"(dst), "l"(m), "r"(c0), "r"(c3), "r"(bar) : "memory");
}
__device__ __forceinline__ void tma4d_mc(uint32_t dst, const CUtensorMap* m, int c0, int c3, uint32_t bar) {
    asm volatile("cp.async.bulk.tensor.4d.shared::cluster.global.mbarrier::complete_tx::bytes.multicast::cluster [%0], [%1, {%2, 0, 0, %3}], [%4], %5;" ::"r"(dst), "l"(m), "r"(c0), "r"(c3), "r"(bar), "h"(pair_mask()) : "memory");
}
__device__ __forceinline__ void tma_prefetch2d(const CUtensorMap* m, int c0, int c1) {
    asm volatile("cp.async.bulk.prefetch.tensor.2d.L2.global [%0, {%1, %2}];" ::"l"(m), "r"(c0), "r"(c1) : "memory");
}
__device__ __forceinline__ void map_prefetch(const CUtensorMap* m) { asm volatile("prefetch.tensormap [%0];" ::"l"(m) : "memory"); }
__device__ __forceinline__ void l2_prefetch(const void* src, uint32_t bytes) { asm volatile("cp.async.bulk.prefetch.L2.global [%0], %1;" ::"l"(src), "r"(bytes) : "memory"); }
__device__ __forceinline__ void bulk_g2s(uint32_t dst, const void* src, uint32_t bytes, uint32_t bar) {
    asm volatile("cp.async.bulk.shared::cluster.global.mbarrier::complete_tx::bytes [%0], [%1], %2, [%3];" ::"r"(dst), "l"(src), "r"(bytes), "r"(bar) : "memory");
}
__device__ __forceinline__ void tma_store2d(const CUtensorMap* m, int c0, int c1, uint32_t src) {
    asm volatile("cp.async.bulk.tensor.2d.global.shared::cta.bulk_group [%0, {%1, %2}], [%3];" ::"l"(m), "r"(c0), "r"(c1), "r"(src) : "memory");
}
__device__ __forceinline__ void bulk_commit() { asm volatile("cp.async.bulk.commit_group;" ::: "memory"); }
__device__ __forceinline__ void bulk_wait_read() { asm volatile("cp.async.bulk.wait_group.read 0;" ::: "memory"); }
__device__ __forceinline__ void bulk_wait_all() { asm volatile("cp.async.bulk.wait_group 0;" ::: "memory"); }
__device__ __forceinline__ uint64_t mkdesc(uint32_t addr, uint32_t lbo, uint32_t sbo, uint32_t swz) {
    return (uint64_t)((addr & 0x3FFFF) >> 4) | ((uint64_t)(lbo >> 4) << 16) | ((uint64_t)(sbo >> 4) << 32) | ((uint64_t)swz << 62);
}
__device__ __forceinline__ void wg_fence() { asm volatile("wgmma.fence.sync.aligned;" ::: "memory"); }
__device__ __forceinline__ void wg_commit() { asm volatile("wgmma.commit_group.sync.aligned;" ::: "memory"); }
template <int N> __device__ __forceinline__ void wg_wait() { asm volatile("wgmma.wait_group.sync.aligned %0;" ::"n"(N) : "memory"); }
template <typename T> __device__ __forceinline__ void pin_ptr(T*& p) { asm volatile("" : "+l"(p)); }
template <int N> __device__ __forceinline__ void pin(uint32_t* d) {
#pragma unroll
    for (int i = 0; i < N; i++) asm volatile("" : "+r"(d[i])::"memory");
}
template <int N> __device__ __forceinline__ void pin(float* d) {
#pragma unroll
    for (int i = 0; i < N; i++) asm volatile("" : "+f"(d[i])::"memory");
}

template <int TA, int TB>
__device__ __forceinline__ void wgmma_ss256(float* d, uint64_t da, uint64_t db) {
    asm volatile("wgmma.mma_async.sync.aligned.m64n256k16.f32.bf16.bf16 "
        "{%0, %1, %2, %3, %4, %5, %6, %7, %8, %9, %10, %11, %12, %13, %14, %15, %16, %17, %18, %19, %20, %21, %22, %23, %24, %25, %26, %27, %28, %29, %30, %31, %32, %33, %34, %35, %36, %37, %38, %39, %40, %41, %42, %43, %44, %45, %46, %47, %48, %49, %50, %51, %52, %53, %54, %55, %56, %57, %58, %59, %60, %61, %62, %63, %64, %65, %66, %67, %68, %69, %70, %71, %72, %73, %74, %75, %76, %77, %78, %79, %80, %81, %82, %83, %84, %85, %86, %87, %88, %89, %90, %91, %92, %93, %94, %95, %96, %97, %98, %99, %100, %101, %102, %103, %104, %105, %106, %107, %108, %109, %110, %111, %112, %113, %114, %115, %116, %117, %118, %119, %120, %121, %122, %123, %124, %125, %126, %127}, %128, %129, 1, 1, 1, %130, %131;"
        : "+f"(d[0]), "+f"(d[1]), "+f"(d[2]), "+f"(d[3]), "+f"(d[4]), "+f"(d[5]), "+f"(d[6]), "+f"(d[7]), "+f"(d[8]), "+f"(d[9]), "+f"(d[10]), "+f"(d[11]), "+f"(d[12]), "+f"(d[13]), "+f"(d[14]), "+f"(d[15]), "+f"(d[16]), "+f"(d[17]), "+f"(d[18]), "+f"(d[19]), "+f"(d[20]), "+f"(d[21]), "+f"(d[22]), "+f"(d[23]), "+f"(d[24]), "+f"(d[25]), "+f"(d[26]), "+f"(d[27]), "+f"(d[28]), "+f"(d[29]), "+f"(d[30]), "+f"(d[31]), "+f"(d[32]), "+f"(d[33]), "+f"(d[34]), "+f"(d[35]), "+f"(d[36]), "+f"(d[37]), "+f"(d[38]), "+f"(d[39]), "+f"(d[40]), "+f"(d[41]), "+f"(d[42]), "+f"(d[43]), "+f"(d[44]), "+f"(d[45]), "+f"(d[46]), "+f"(d[47]), "+f"(d[48]), "+f"(d[49]), "+f"(d[50]), "+f"(d[51]), "+f"(d[52]), "+f"(d[53]), "+f"(d[54]), "+f"(d[55]), "+f"(d[56]), "+f"(d[57]), "+f"(d[58]), "+f"(d[59]), "+f"(d[60]), "+f"(d[61]), "+f"(d[62]), "+f"(d[63]), "+f"(d[64]), "+f"(d[65]), "+f"(d[66]), "+f"(d[67]), "+f"(d[68]), "+f"(d[69]), "+f"(d[70]), "+f"(d[71]), "+f"(d[72]), "+f"(d[73]), "+f"(d[74]), "+f"(d[75]), "+f"(d[76]), "+f"(d[77]), "+f"(d[78]), "+f"(d[79]), "+f"(d[80]), "+f"(d[81]), "+f"(d[82]), "+f"(d[83]), "+f"(d[84]), "+f"(d[85]), "+f"(d[86]), "+f"(d[87]), "+f"(d[88]), "+f"(d[89]), "+f"(d[90]), "+f"(d[91]), "+f"(d[92]), "+f"(d[93]), "+f"(d[94]), "+f"(d[95]), "+f"(d[96]), "+f"(d[97]), "+f"(d[98]), "+f"(d[99]), "+f"(d[100]), "+f"(d[101]), "+f"(d[102]), "+f"(d[103]), "+f"(d[104]), "+f"(d[105]), "+f"(d[106]), "+f"(d[107]), "+f"(d[108]), "+f"(d[109]), "+f"(d[110]), "+f"(d[111]), "+f"(d[112]), "+f"(d[113]), "+f"(d[114]), "+f"(d[115]), "+f"(d[116]), "+f"(d[117]), "+f"(d[118]), "+f"(d[119]), "+f"(d[120]), "+f"(d[121]), "+f"(d[122]), "+f"(d[123]), "+f"(d[124]), "+f"(d[125]), "+f"(d[126]), "+f"(d[127])
        : "l"(da), "l"(db), "n"(TA), "n"(TB));
}
template <int TA, int TB>
__device__ __forceinline__ void wgmma_ss256_first(float* d, uint64_t da, uint64_t db) {
    asm volatile("wgmma.mma_async.sync.aligned.m64n256k16.f32.bf16.bf16 "
        "{%0, %1, %2, %3, %4, %5, %6, %7, %8, %9, %10, %11, %12, %13, %14, %15, %16, %17, %18, %19, %20, %21, %22, %23, %24, %25, %26, %27, %28, %29, %30, %31, %32, %33, %34, %35, %36, %37, %38, %39, %40, %41, %42, %43, %44, %45, %46, %47, %48, %49, %50, %51, %52, %53, %54, %55, %56, %57, %58, %59, %60, %61, %62, %63, %64, %65, %66, %67, %68, %69, %70, %71, %72, %73, %74, %75, %76, %77, %78, %79, %80, %81, %82, %83, %84, %85, %86, %87, %88, %89, %90, %91, %92, %93, %94, %95, %96, %97, %98, %99, %100, %101, %102, %103, %104, %105, %106, %107, %108, %109, %110, %111, %112, %113, %114, %115, %116, %117, %118, %119, %120, %121, %122, %123, %124, %125, %126, %127}, %128, %129, 0, 1, 1, %130, %131;"
        : "=f"(d[0]), "=f"(d[1]), "=f"(d[2]), "=f"(d[3]), "=f"(d[4]), "=f"(d[5]), "=f"(d[6]), "=f"(d[7]), "=f"(d[8]), "=f"(d[9]), "=f"(d[10]), "=f"(d[11]), "=f"(d[12]), "=f"(d[13]), "=f"(d[14]), "=f"(d[15]), "=f"(d[16]), "=f"(d[17]), "=f"(d[18]), "=f"(d[19]), "=f"(d[20]), "=f"(d[21]), "=f"(d[22]), "=f"(d[23]), "=f"(d[24]), "=f"(d[25]), "=f"(d[26]), "=f"(d[27]), "=f"(d[28]), "=f"(d[29]), "=f"(d[30]), "=f"(d[31]), "=f"(d[32]), "=f"(d[33]), "=f"(d[34]), "=f"(d[35]), "=f"(d[36]), "=f"(d[37]), "=f"(d[38]), "=f"(d[39]), "=f"(d[40]), "=f"(d[41]), "=f"(d[42]), "=f"(d[43]), "=f"(d[44]), "=f"(d[45]), "=f"(d[46]), "=f"(d[47]), "=f"(d[48]), "=f"(d[49]), "=f"(d[50]), "=f"(d[51]), "=f"(d[52]), "=f"(d[53]), "=f"(d[54]), "=f"(d[55]), "=f"(d[56]), "=f"(d[57]), "=f"(d[58]), "=f"(d[59]), "=f"(d[60]), "=f"(d[61]), "=f"(d[62]), "=f"(d[63]), "=f"(d[64]), "=f"(d[65]), "=f"(d[66]), "=f"(d[67]), "=f"(d[68]), "=f"(d[69]), "=f"(d[70]), "=f"(d[71]), "=f"(d[72]), "=f"(d[73]), "=f"(d[74]), "=f"(d[75]), "=f"(d[76]), "=f"(d[77]), "=f"(d[78]), "=f"(d[79]), "=f"(d[80]), "=f"(d[81]), "=f"(d[82]), "=f"(d[83]), "=f"(d[84]), "=f"(d[85]), "=f"(d[86]), "=f"(d[87]), "=f"(d[88]), "=f"(d[89]), "=f"(d[90]), "=f"(d[91]), "=f"(d[92]), "=f"(d[93]), "=f"(d[94]), "=f"(d[95]), "=f"(d[96]), "=f"(d[97]), "=f"(d[98]), "=f"(d[99]), "=f"(d[100]), "=f"(d[101]), "=f"(d[102]), "=f"(d[103]), "=f"(d[104]), "=f"(d[105]), "=f"(d[106]), "=f"(d[107]), "=f"(d[108]), "=f"(d[109]), "=f"(d[110]), "=f"(d[111]), "=f"(d[112]), "=f"(d[113]), "=f"(d[114]), "=f"(d[115]), "=f"(d[116]), "=f"(d[117]), "=f"(d[118]), "=f"(d[119]), "=f"(d[120]), "=f"(d[121]), "=f"(d[122]), "=f"(d[123]), "=f"(d[124]), "=f"(d[125]), "=f"(d[126]), "=f"(d[127])
        : "l"(da), "l"(db), "n"(TA), "n"(TB));
}
template <int TA, int TB>
__device__ __forceinline__ void wgmma_ss128(float* d, uint64_t da, uint64_t db) {
    asm volatile("wgmma.mma_async.sync.aligned.m64n128k16.f32.bf16.bf16 "
        "{%0, %1, %2, %3, %4, %5, %6, %7, %8, %9, %10, %11, %12, %13, %14, %15, %16, %17, %18, %19, %20, %21, %22, %23, %24, %25, %26, %27, %28, %29, %30, %31, %32, %33, %34, %35, %36, %37, %38, %39, %40, %41, %42, %43, %44, %45, %46, %47, %48, %49, %50, %51, %52, %53, %54, %55, %56, %57, %58, %59, %60, %61, %62, %63}, %64, %65, 1, 1, 1, %66, %67;"
        : "+f"(d[0]), "+f"(d[1]), "+f"(d[2]), "+f"(d[3]), "+f"(d[4]), "+f"(d[5]), "+f"(d[6]), "+f"(d[7]), "+f"(d[8]), "+f"(d[9]), "+f"(d[10]), "+f"(d[11]), "+f"(d[12]), "+f"(d[13]), "+f"(d[14]), "+f"(d[15]), "+f"(d[16]), "+f"(d[17]), "+f"(d[18]), "+f"(d[19]), "+f"(d[20]), "+f"(d[21]), "+f"(d[22]), "+f"(d[23]), "+f"(d[24]), "+f"(d[25]), "+f"(d[26]), "+f"(d[27]), "+f"(d[28]), "+f"(d[29]), "+f"(d[30]), "+f"(d[31]), "+f"(d[32]), "+f"(d[33]), "+f"(d[34]), "+f"(d[35]), "+f"(d[36]), "+f"(d[37]), "+f"(d[38]), "+f"(d[39]), "+f"(d[40]), "+f"(d[41]), "+f"(d[42]), "+f"(d[43]), "+f"(d[44]), "+f"(d[45]), "+f"(d[46]), "+f"(d[47]), "+f"(d[48]), "+f"(d[49]), "+f"(d[50]), "+f"(d[51]), "+f"(d[52]), "+f"(d[53]), "+f"(d[54]), "+f"(d[55]), "+f"(d[56]), "+f"(d[57]), "+f"(d[58]), "+f"(d[59]), "+f"(d[60]), "+f"(d[61]), "+f"(d[62]), "+f"(d[63])
        : "l"(da), "l"(db), "n"(TA), "n"(TB));
}
template <int TA, int TB>
__device__ __forceinline__ void wgmma_ss128_first(float* d, uint64_t da, uint64_t db) {
    asm volatile("wgmma.mma_async.sync.aligned.m64n128k16.f32.bf16.bf16 "
        "{%0, %1, %2, %3, %4, %5, %6, %7, %8, %9, %10, %11, %12, %13, %14, %15, %16, %17, %18, %19, %20, %21, %22, %23, %24, %25, %26, %27, %28, %29, %30, %31, %32, %33, %34, %35, %36, %37, %38, %39, %40, %41, %42, %43, %44, %45, %46, %47, %48, %49, %50, %51, %52, %53, %54, %55, %56, %57, %58, %59, %60, %61, %62, %63}, %64, %65, 0, 1, 1, %66, %67;"
        : "=f"(d[0]), "=f"(d[1]), "=f"(d[2]), "=f"(d[3]), "=f"(d[4]), "=f"(d[5]), "=f"(d[6]), "=f"(d[7]), "=f"(d[8]), "=f"(d[9]), "=f"(d[10]), "=f"(d[11]), "=f"(d[12]), "=f"(d[13]), "=f"(d[14]), "=f"(d[15]), "=f"(d[16]), "=f"(d[17]), "=f"(d[18]), "=f"(d[19]), "=f"(d[20]), "=f"(d[21]), "=f"(d[22]), "=f"(d[23]), "=f"(d[24]), "=f"(d[25]), "=f"(d[26]), "=f"(d[27]), "=f"(d[28]), "=f"(d[29]), "=f"(d[30]), "=f"(d[31]), "=f"(d[32]), "=f"(d[33]), "=f"(d[34]), "=f"(d[35]), "=f"(d[36]), "=f"(d[37]), "=f"(d[38]), "=f"(d[39]), "=f"(d[40]), "=f"(d[41]), "=f"(d[42]), "=f"(d[43]), "=f"(d[44]), "=f"(d[45]), "=f"(d[46]), "=f"(d[47]), "=f"(d[48]), "=f"(d[49]), "=f"(d[50]), "=f"(d[51]), "=f"(d[52]), "=f"(d[53]), "=f"(d[54]), "=f"(d[55]), "=f"(d[56]), "=f"(d[57]), "=f"(d[58]), "=f"(d[59]), "=f"(d[60]), "=f"(d[61]), "=f"(d[62]), "=f"(d[63])
        : "l"(da), "l"(db), "n"(TA), "n"(TB));
}
template <int TB>
__device__ __forceinline__ void wgmma_rs128(float* d, const uint32_t* a, uint64_t db, uint32_t acc) {
    asm volatile("{\n.reg .pred P;\nsetp.ne.u32 P, %69, 0;\nwgmma.mma_async.sync.aligned.m64n128k16.f32.bf16.bf16 "
        "{%0, %1, %2, %3, %4, %5, %6, %7, %8, %9, %10, %11, %12, %13, %14, %15, %16, %17, %18, %19, %20, %21, %22, %23, %24, %25, %26, %27, %28, %29, %30, %31, %32, %33, %34, %35, %36, %37, %38, %39, %40, %41, %42, %43, %44, %45, %46, %47, %48, %49, %50, %51, %52, %53, %54, %55, %56, %57, %58, %59, %60, %61, %62, %63}, {%64, %65, %66, %67}, %68, P, 1, 1, %70;\n}"
        : "+f"(d[0]), "+f"(d[1]), "+f"(d[2]), "+f"(d[3]), "+f"(d[4]), "+f"(d[5]), "+f"(d[6]), "+f"(d[7]), "+f"(d[8]), "+f"(d[9]), "+f"(d[10]), "+f"(d[11]), "+f"(d[12]), "+f"(d[13]), "+f"(d[14]), "+f"(d[15]), "+f"(d[16]), "+f"(d[17]), "+f"(d[18]), "+f"(d[19]), "+f"(d[20]), "+f"(d[21]), "+f"(d[22]), "+f"(d[23]), "+f"(d[24]), "+f"(d[25]), "+f"(d[26]), "+f"(d[27]), "+f"(d[28]), "+f"(d[29]), "+f"(d[30]), "+f"(d[31]), "+f"(d[32]), "+f"(d[33]), "+f"(d[34]), "+f"(d[35]), "+f"(d[36]), "+f"(d[37]), "+f"(d[38]), "+f"(d[39]), "+f"(d[40]), "+f"(d[41]), "+f"(d[42]), "+f"(d[43]), "+f"(d[44]), "+f"(d[45]), "+f"(d[46]), "+f"(d[47]), "+f"(d[48]), "+f"(d[49]), "+f"(d[50]), "+f"(d[51]), "+f"(d[52]), "+f"(d[53]), "+f"(d[54]), "+f"(d[55]), "+f"(d[56]), "+f"(d[57]), "+f"(d[58]), "+f"(d[59]), "+f"(d[60]), "+f"(d[61]), "+f"(d[62]), "+f"(d[63])
        : "r"(a[0]), "r"(a[1]), "r"(a[2]), "r"(a[3]), "l"(db), "r"(acc), "n"(TB));
}
template <int TB>
__device__ __forceinline__ void wgmma_rs64(float* d, const uint32_t* a, uint64_t db, uint32_t acc) {
    asm volatile("{\n.reg .pred P;\nsetp.ne.u32 P, %37, 0;\nwgmma.mma_async.sync.aligned.m64n64k16.f32.bf16.bf16 "
        "{%0, %1, %2, %3, %4, %5, %6, %7, %8, %9, %10, %11, %12, %13, %14, %15, %16, %17, %18, %19, %20, %21, %22, %23, %24, %25, %26, %27, %28, %29, %30, %31}, {%32, %33, %34, %35}, %36, P, 1, 1, %38;\n}"
        : "+f"(d[0]), "+f"(d[1]), "+f"(d[2]), "+f"(d[3]), "+f"(d[4]), "+f"(d[5]), "+f"(d[6]), "+f"(d[7]), "+f"(d[8]), "+f"(d[9]), "+f"(d[10]), "+f"(d[11]), "+f"(d[12]), "+f"(d[13]), "+f"(d[14]), "+f"(d[15]), "+f"(d[16]), "+f"(d[17]), "+f"(d[18]), "+f"(d[19]), "+f"(d[20]), "+f"(d[21]), "+f"(d[22]), "+f"(d[23]), "+f"(d[24]), "+f"(d[25]), "+f"(d[26]), "+f"(d[27]), "+f"(d[28]), "+f"(d[29]), "+f"(d[30]), "+f"(d[31])
        : "r"(a[0]), "r"(a[1]), "r"(a[2]), "r"(a[3]), "l"(db), "r"(acc), "n"(TB));
}
template <int TB>
__device__ __forceinline__ void wgmma_rs16(float* d, const uint32_t* a, uint64_t db, uint32_t acc) {
    asm volatile("{\n.reg .pred P;\nsetp.ne.u32 P, %13, 0;\nwgmma.mma_async.sync.aligned.m64n16k16.f32.bf16.bf16 "
        "{%0, %1, %2, %3, %4, %5, %6, %7}, {%8, %9, %10, %11}, %12, P, 1, 1, %14;\n}"
        : "+f"(d[0]), "+f"(d[1]), "+f"(d[2]), "+f"(d[3]), "+f"(d[4]), "+f"(d[5]), "+f"(d[6]), "+f"(d[7])
        : "r"(a[0]), "r"(a[1]), "r"(a[2]), "r"(a[3]), "l"(db), "r"(acc), "n"(TB));
}

__device__ __forceinline__ uint32_t delay_loop(int n, uint32_t x0) {
    uint32_t z;
    asm volatile("{\n.reg .pred P;\n.reg .u32 c, x;\nmov.u32 c, %1;\nmov.u32 x, %2;\nDL: mad.lo.u32 x, x, 1664525, 1013904223;\nadd.u32 c, c, -1;\nsetp.gt.s32 P, c, 0;\n@P bra DL;\n"
                 "setp.eq.u32 P, x, 0x7fffffff;\nselp.u32 %0, 16, 0, P;\n}" : "=r"(z) : "r"(n), "r"(x0) : "memory");
    return z;
}
__device__ __forceinline__ uint32_t gtime() { uint32_t t; asm volatile("mov.u32 %0, %%globaltimer_lo;" : "=r"(t)); return t; }
__device__ __forceinline__ void stamp(int idx, uint32_t seq) { st_relaxed1(g_hint + idx, (gtime() & ~31u) | (seq & 31u)); }
__device__ __forceinline__ void wait_time(uint32_t t, uint32_t sb) { while ((int32_t)(gtime() - t) < (int32_t)delay_loop(2, sb)) {} }
template <int N, int STRIDE>
__device__ __forceinline__ uint32_t latest_stamp(const uint32_t* p, uint32_t seq, uint32_t ref, uint32_t sb, int tight, int extra) {
    int n = 0;
    while (true) {
        uint32_t bad = 0; int32_t m = INT32_MIN, l = INT32_MAX;
#pragma unroll
        for (int i = 0; i < N; i++) {
            const uint32_t v = ld_relaxed1(p + i * STRIDE);
            const int32_t d = (int32_t)((v & ~31u) - ref);
            bad |= (v ^ seq) & 31u; m = max(m, d); l = min(l, d);
        }
        if (__all_sync(0xffffffffu, bad == 0)) {
            m = __reduce_max_sync(0xffffffffu, m);
            return ref + m + (__any_sync(0xffffffffu, m - l > tight) ? extra : 0);
        }
        p += delay_loop(60, sb);
        if (++n > SPIN_LIMIT) spin_fault();
    }
}
__device__ __forceinline__ void release_at(uint32_t t, uint32_t sb, uint32_t bar, int lane) {
    wait_time(t, sb);
    if (lane == 0) mbar_arrive(sb + bar);
}
__host__ __device__ constexpr int col_group(int j) { return (0x17643520 >> (4 * j)) & 7; }
__host__ __device__ constexpr int frag_word(int u, int f) { return u < 3 ? (f < 2 ? 2 * u + f : 4 * u + 2) : u == 3 ? 14 + f : 4 * u - 9 + f; }

constexpr uint32_t CLEAR_LO = 0xFE000000u, CLEAR_HI = 0x5A7FEFEFu;
__device__ __forceinline__ void clear_slot(const Params& P, int slot, int cta, int lane) {
    const int i = cta * 2 + (lane >> 3), x = i & 63;
    if (lane < 16) st_relaxed4(P.gm + slot * M_SLOT + (x >> 1) * 1024 + (x & 1) * 256 + (i >> 7) * 512 + ((i >> 6) & 1) * 128 + (lane & 7) * 16, CLEAR_LO, CLEAR_HI, CLEAR_LO, CLEAR_HI);
    st_relaxed4(g_f + slot * F_SLOT + cta * 512 + lane * 16, 0, 0, 0, 0);
}
__device__ __forceinline__ uint32_t pack_mem0(const Params& P, int cta, int lane) {
    uint32_t m = 0;
#pragma unroll 2
    for (int i = 0; i < 32; i++) {
        const uint4 x = __ldg((const uint4*)P.mem0 + i * 32 + lane);
        m = __vmaxu2(__vmaxu2(__vmaxu2(x.x & 0x7fff7fffu, x.y & 0x7fff7fffu), __vmaxu2(x.z & 0x7fff7fffu, x.w & 0x7fff7fffu)), m);
    }
    const uint32_t e = __reduce_max_sync(0xffffffffu, max(m >> 16, m & 0xffffu)) >> 7;
    if (e < 64 || e > 192) return 0x3F803F80u;
    const int i = cta * 2 + (lane >> 4), u = (i >> 5), x = i & 63, L = (i & 3) * 8 + ((lane & 15) >> 1);
    uint64_t w = 32;
#pragma unroll 1
    for (int f = 0; f < (u % 3 ? 3 : 2); f++) {
        const int fw = frag_word(u, f);
        const float v = __bfloat162float(P.mem0[(L >> 2) * 1024 + col_group(fw >> 1) * 128 + ((i >> 2) & 7) * 16 + (fw & 1) * 8 + (L & 3) * 2 + (lane & 1)]);
        w += (uint64_t)(int64_t)__float2int_rn(v * __uint_as_float((271 - e) << 23)) << (45 - 19 * f);
    }
    st_relaxed2(P.gm + 7 * M_SLOT + (x >> 1) * 1024 + (x & 1) * 256 + (i >> 7) * 512 + ((i >> 6) & 1) * 128 + (lane & 15) * 8, (uint32_t)w, (uint32_t)(w >> 32));
    return (e - 30) * 0x00800080u;
}
__device__ __forceinline__ void pacer(const Params& P, const uint32_t sb, const int lane, const int pair, const int rank) {
    constexpr uint32_t base = 2;
    const int cta = pair * 2 + rank;
#pragma unroll 1
    for (int i = 0; i < 8; i++) clear_slot(P, i, cta, lane);
    __syncwarp();
    const uint32_t u0 = pack_mem0(P, cta, lane);
    fence_gpu();
    __syncwarp();
    mbar_wait(sb + B_GO, 0);
    if (lane < 8) sts32(sb + S_SC + lane * 4, u0);
    if (lane == 0) stamp(6144 + cta * 32, lds32(sb + S_EPOCH) + 1);
    latest_stamp<3, 1024>(g_hint + 6144 + lane * 32, lds32(sb + S_EPOCH) + 1, gtime(), sb, 0, 0);
    fence_gpu();
    __syncwarp();
    if (lane == 0) { mbar_arrive(sb + B_RELA); mbar_arrive(sb + B_RELB); }
#pragma unroll 1
    for (int s = 0; s < 63; s++) {
        mbar_wait(sb + B_GO, (s + 1) & 1);
        const uint32_t t0 = gtime();
        if (lane < 4) st_relaxed1(g_hint + ((s & 1) * 4 + lane) * 768 + (cta >> 5) * 256 + (cta & 31), (t0 & ~31u) | ((base + s) & 31u));
        wait_time(t0 + P.ds, sb);
        const uint32_t t = latest_stamp<3, 256>(g_hint + ((s & 1) * 4 + (pair & 3)) * 768 + lane, base + s, t0, sb, P.tight, P.extra);
        release_at(t + P.da, sb, B_RELA, lane);
        release_at(t + P.db, sb, B_RELB, lane);
        if (!DBGF(16)) fence_gpu();
        __syncwarp();
        wait_time(t + P.db + 320, sb);
        clear_slot(P, (s + 6) & 7, cta, lane);
        if (s == 61) {
            sts32(sb + S_EPOCH + 4, ITEM(ITEM_OFF(pair) + NPRE + 1) + ITEM_OFF(pair + 1) + (uint32_t)(uintptr_t)P.out);
            if (lane < M_CQ) map_prefetch(&P.tm[lane]);
        }
    }
}
__device__ __forceinline__ uint32_t xor_or(uint32_t a, uint32_t b, uint32_t t) { uint32_t d; asm("lop3.b32 %0, %1, %2, %3, 0x7E;" : "=r"(d) : "r"(a), "r"(b), "r"(t)); return d; }
__device__ __forceinline__ bool tags_ok(uint32_t bad) { return __all_sync(0xffffffffu, (bad & 1) == 0); }
#define RETRY(k)
#define RETRY_STAT(a, b)
#define SFENCE() asm volatile("pmevent 1;" ::: "memory")
#define PF1 10
static_assert(NS == 24, "fragment residency");
__host__ __device__ constexpr bool in_smem(int n) { return n < 4 || n == 13 || n == 15; }
__host__ __device__ constexpr int unit_pos(int n) { return n < 4 ? n : n < 13 ? n - 4 : n == 13 ? 4 : n == 14 ? 9 : 5; }

__device__ __forceinline__ uint32_t spare_unit(int u) { return u < 6 ? 98304 + u * 2048 : S_P1 + (u - 6) * 2048; }
__device__ __forceinline__ void load_unit(const Params& P, uint32_t dst, int role, int h, int warp, int n, uint32_t bar) {
    tma2d(dst, &P.tm[M_CQ + role], h * 128 + (n & 1) * 64, col_group(n >> 1) * 128 + warp * 16, bar);
}
__device__ __forceinline__ void chain_load1(const Params& P, uint32_t sb, int pair, int rank, int warp, int lane, bool late) {
    const int role = pair >> 4, h = (pair & 15) * 2 + rank;
    if (lane < 8) {
        const uint32_t dst = lane < 6 ? warp * 12288 + lane * 2048 : spare_unit(warp * 2 + lane - 6);
        if (lane == 0 && !late) mbar_expect(sb + B_INIT, 8 * 2048);
        __syncwarp(0xff);
        if (late == (dst >= S_STG)) load_unit(P, sb + dst, role, h, warp, 4 + lane, sb + B_INIT);
    }
}

constexpr uint32_t QBITS = 0x4B002000u;
constexpr uint64_t W_BIAS = ((uint64_t)QBITS << 45) + ((uint64_t)QBITS << 26) + (uint32_t)(QBITS << 7), W_CLEAR = 0 - 32 * W_BIAS;
static_assert(W_CLEAR == ((uint64_t)CLEAR_HI << 32 | CLEAR_LO), "clear value");
__host__ __device__ constexpr int unit_off(int u) { return (u & 1) * 16384 + (u >> 2) * 512 + ((u >> 1) & 1) * 128; }
__device__ __forceinline__ void red_add64(const uint8_t* p, uint64_t v) { asm volatile("red.relaxed.gpu.global.add.u64 [%0], %1;" ::"l"(p), "l"(v) : "memory"); }
template <int NF>
__device__ __forceinline__ uint64_t encode(const float* x, float S, uint32_t two26, uint32_t& bad) {
    uint32_t b[3];
#pragma unroll
    for (int i = 0; i < 3; i++) b[i] = i < NF ? __float_as_uint(fmaf(x[i], S, 8396800.f)) : QBITS;
    bad = xor_or(b[0], b[1], 0x4B000000u) | (NF == 3 ? b[2] ^ 0x4B000000u : 0);
    uint64_t w;
    asm("{\n.reg .b64 t;\nmov.b64 t, {%2, %3};\nmad.wide.u32 %0, %1, %4, t;\n}" : "=l"(w) : "r"(b[1]), "r"(b[2] << 7), "r"(b[0] << 13), "r"(two26));
    return w;
}
template <int NF>
__device__ __forceinline__ bool emit(const float (*x)[3], const float* S, uint32_t two26, uint32_t lim, const uint8_t* p) {
    uint32_t bad[2];
    const uint64_t w0 = encode<NF>(x[0], S[0], two26, bad[0]), w1 = encode<NF>(x[1], S[1], two26, bad[1]);
    const bool ok = (bad[0] | bad[1]) < lim;
    red_add64(p, w0 | ok); red_add64(p + 1024, w1 | ok);
    return ok;
}
template <int NF>
__device__ __forceinline__ void repair(bool ok, const float (*x)[3], const float* S, uint32_t two26, const uint8_t* p, const uint8_t* pf) {
    if (!ok) {
#pragma unroll
        for (int j = 0; j < 2; j++) {
            const float T = S[j] * 8192.f;
            asm volatile("red.relaxed.gpu.global.add.v4.f32 [%0], {%1,%2,%3,%4};" ::"l"(pf + j * 512), "f"(x[j][0] * T), "f"(x[j][1] * T), "f"(NF == 3 ? x[j][2] * T : 0.f), "f"(0.f) : "memory");
        }
        fence_gpu();
#pragma unroll
        for (int j = 0; j < 2; j++) {
            uint32_t bad;
            asm volatile("red.relaxed.gpu.global.or.b64 [%0], 64;" ::"l"(p + j * 1024) : "memory");
            red_add64(p + j * 1024, W_BIAS + 1 - encode<NF>(x[j], S[j], two26, bad));
        }
    }
    __syncwarp();
}
__device__ __forceinline__ void ld_words(uint32_t* v, const uint8_t* p) {
    asm volatile("{\n.reg .b64 a, b;\nld.relaxed.gpu.global.L1::no_allocate.v2.b64 {a, b}, [%4];\nmov.b64 {%0,%1}, a;\nmov.b64 {%2,%3}, b;\n}" : "=r"(v[0]), "=r"(v[1]), "=r"(v[2]), "=r"(v[3]) : "l"(p) : "memory");
}
__device__ __forceinline__ float field(const uint32_t* w, int f) { return __int2float_rn((int)(f == 0 ? w[1] : f == 1 ? __funnelshift_l(w[0], w[1], 19) : w[0] << 6)); }
template <int U>
__device__ __forceinline__ void decode(uint32_t* b, const uint32_t* v) {
#pragma unroll
    for (int f = 0; f < (U % 3 ? 3 : 2); f++) b[frag_word(U, f)] = pack2(field(v, f), field(v + 2, f));
}
__device__ __forceinline__ uint32_t status(const uint32_t (*v)[4], uint32_t c32) { return xor_or(v[0][0], v[0][2], c32) | xor_or(v[1][0], v[1][2], c32) | xor_or(v[2][0], v[2][2], c32); }
__device__ __forceinline__ void gather_slow(const Params& P, uint32_t* b, const uint8_t* pm, int s, int warp, uint32_t ln, uint32_t u2) {
    if (s == 0 && u2 == 0x3F803F80u) {
#pragma unroll
        for (int i = 0; i < 16; i++) b[i] = __ldg((const uint32_t*)(P.mem0 + (ln >> 2) * 1024 + col_group(i >> 1) * 128 + warp * 16 + (i & 1) * 8 + (ln & 3) * 2));
        return;
    }
    uint32_t v[6][4], st;
    for (int n = 0;; n++) {
#pragma unroll
        for (int u = 0; u < 6; u++) ld_words(v[u], pm + unit_off(u));
        st = status(v, 32) | status(v + 3, 32);
        if (!__any_sync(0xffffffffu, st & 32)) break;
        __nanosleep(200);
        if (n > SPIN_LIMIT) spin_fault();
    }
    const bool side = __any_sync(0xffffffffu, st & 64);
    if (side) fence_gpu();
    const uint8_t* pf = g_f + ((s + 7) & 7) * F_SLOT + warp * 1024 + ln * 32;
#pragma unroll
    for (int u = 0; u < 6; u++) {
        float x[2][4] = {};
#pragma unroll
        for (int k = 0; k < 2; k++)
            asm volatile("{\n.reg .pred P;\nsetp.ne.u32 P, %5, 0;\n@P ld.relaxed.gpu.global.v4.f32 {%0,%1,%2,%3}, [%4];\n}"
                         : "+f"(x[k][0]), "+f"(x[k][1]), "+f"(x[k][2]), "+f"(x[k][3]) : "l"(pf + u * 8192 + k * 16), "r"((uint32_t)side) : "memory");
#pragma unroll
        for (int f = 0; f < (u % 3 ? 3 : 2); f++) b[frag_word(u, f)] = pack2(field(v[u], f) + x[0][f], field(v[u] + 2, f) + x[1][f]);
    }
}
__device__ __forceinline__ uint32_t max_abs2(uint32_t a, uint32_t b) { uint32_t d; asm("max.NaN.xorsign.abs.bf16x2 %0, %1, %2;" : "=r"(d) : "r"(a), "r"(b)); return d; }
__device__ __forceinline__ uint32_t warp_max6(const uint32_t* b) {
    const uint32_t m = max_abs2(max_abs2(max_abs2(b[0], b[1]), max_abs2(b[2], b[3])), max_abs2(b[4], b[5]));
    return __reduce_max_sync(0xffffffffu, max(m & 0x7fff0000u, (m << 16) & 0x7fff0000u));
}

template <bool TR>
__device__ __forceinline__ void put_partials(uint32_t a, const float* x, const float* y) {
    if (TR) stsm4t(a, pack2(x[0], x[1]), pack2(x[2], x[3]), pack2(y[0], y[1]), pack2(y[2], y[3]));
    else stsm4(a, pack2(x[0], x[1]), pack2(x[2], x[3]), pack2(y[0], y[1]), pack2(y[2], y[3]));
}
__device__ __forceinline__ void reduce8(uint32_t a, uint32_t l8, uint32_t u2, uint32_t& r0, uint32_t& r1) {
    uint32_t x[4][4];
#pragma unroll
    for (int i = 0; i < 4; i++) ldsm4t(x[i], a + i * 256);
    float d[2][4];
#pragma unroll
    for (int i = 0; i < 2; i++) { d[i][0] = d[i][1] = d[i][2] = d[i][3] = 0.f; }
#pragma unroll
    for (int i = 0; i < 4; i++)
        mma16816(d[i & 1], x[i][0], x[i][1], x[i][2], x[i][3], (l8 & 224) == i * 64 ? u2 : 0u, (l8 & 224) == i * 64 + 32 ? u2 : 0u);
    r0 = pack2(d[0][0] + d[1][0], d[0][1] + d[1][1]);
    r1 = pack2(d[0][2] + d[1][2], d[0][3] + d[1][3]);
}
template <typename F>
__device__ __forceinline__ void scores(float* S, const uint32_t (*qa)[4], const uint32_t (*kf)[4], F mid) {
    float SA[2][4], SB[2][4];
#pragma unroll
    for (int n = 0; n < 2; n++) { SA[n][0] = SA[n][1] = SA[n][2] = SA[n][3] = 0.f; SB[n][0] = SB[n][1] = SB[n][2] = SB[n][3] = 0.f; }
#pragma unroll
    for (int w = 0; w < 4; w++) {
        mma16816(SA[w & 1], qa[w][0], qa[w][1], qa[w][2], qa[w][3], kf[w][0], kf[w][1]);
        mma16816(SB[w & 1], qa[w][0], qa[w][1], qa[w][2], qa[w][3], kf[w][2], kf[w][3]);
        if (w == 1) mid();
    }
    S[0] = (SA[0][0] + SA[1][0]) + (SB[0][2] + SB[1][2]);
    S[1] = (SA[0][1] + SA[1][1]) + (SB[0][3] + SB[1][3]);
}
__device__ __forceinline__ float quad_max(float m) {
    m = fmaxf(m, __shfl_xor_sync(0xffffffffu, m, 1));
    return fmaxf(m, __shfl_xor_sync(0xffffffffu, m, 2));
}

#define ISTAMP(i)
__device__ __forceinline__ float next_scale(uint32_t sb, int slot, int warp, uint32_t u2) {
    uint32_t x[2][4];
    lds128(x[0], sb + S_MX + slot * 32); lds128(x[1], sb + S_MX + slot * 32 + 16);
    const uint32_t mx = max(max(max(x[0][0], x[0][1]), max(x[0][2], x[0][3])), max(max(x[1][0], x[1][1]), max(x[1][2], x[1][3])));
    const float top = fminf(fmaxf(__uint_as_float(mx) * bf_hi(u2), 0x1p-40f), 0x1p40f) * (1.f / (12288.f * 8192.f));
    const uint32_t un = pack2(top, top);
    sts32(sb + S_SC + warp * 4, un);
    return rcp(bf_hi(un) * 8192.f);
}
#define NEARLY 0
#define PACE 1
#define PF2 12
__host__ __device__ constexpr int w2_t(int i) { return i < 16 ? i & 1 : 2; }
__host__ __device__ constexpr int w2_k(int i) { return i < 16 ? i >> 1 : i - 16; }
template <int ROLE>
__device__ __forceinline__ void chain_role(const Params& P, const uint32_t sb, const int h, const int warp, const int lane) {
    constexpr int NU = ROLE == 0 ? 2 : 3;
    const bool att = ROLE == 0 && warp < 4;
    uint32_t wr[NR][4];
    const uint32_t frag = ((lane & 7) + (lane >> 4) * 8) * 128 + ((((lane >> 3) & 1) ^ (lane & 7)) << 4);
    {
        const uint32_t bar = sb + B_INIT, spare = sb + spare_unit(warp * 2);
        mbar_wait(bar, 0);
        ISTAMP(0)
#pragma unroll
        for (int f = 0; f < 32; f++) ldsm4t(wr[f], (f < 24 ? sb + warp * 12288 + (f >> 2) * 2048 : spare + ((f - 24) >> 2) * 2048) + (frag ^ ((f & 3) << 5)));
        fence_async_smem();
        __syncwarp();
        if (lane < 8) {
            if (lane == 0) mbar_expect(bar, 8 * 2048);
            __syncwarp(0xff);
            load_unit(P, lane < 6 ? sb + warp * 12288 + lane * 2048 : spare + (lane - 6) * 2048, ROLE, h, warp, lane < 4 ? lane : lane < 6 ? lane * 2 + 5 : lane * 2, bar);
        }
        ISTAMP(1)
        mbar_wait(bar, 1);
        if (lane == 0) {
            if (warp < 2 * NU) {
                mbar_expect(sb + B_WO, 16384);
                for (int e = 0; e < 2; e++) tma4d(sb + S_W2 + warp * 16384 + e * 8192, &P.tm[M_CO + e], (ROLE == 0 ? 0 : ROLE == 1 ? 256 : 640) + warp * 64, h * 8, sb + B_WO);
            } else mbar_arrive(sb + B_WO);
        }
        ISTAMP(2)
#pragma unroll
        for (int f = 32; f < 40; f++) ldsm4t(wr[f], spare + ((f - 32) >> 2) * 2048 + (frag ^ ((f & 3) << 5)));
#pragma unroll 2
        for (int u = 0; u < 6; u++) {
            const uint32_t ub = sb + warp * 12288 + u * 2048;
            uint32_t x[4][4];
#pragma unroll
            for (int i = 0; i < 4; i++) lds128(x[i], ub + (frag ^ (i << 5)));
            __syncwarp();
#pragma unroll
            for (int i = 0; i < 4; i++) sts128(ub + i * 512 + lane * 16, x[i]);
        }
        bar_sync(1, 256);
    }
    uint32_t l8 = opq(sb + lane * 8, lane);
    const uint8_t* persu = (const uint8_t*)((ROLE == 1 ? g_km : g_vmt) + h * 512 + warp * 64) - (sb >> 1);
#define PERS_STORE() { uint32_t* pp = (uint32_t*)(persu + s * 65536 + (l8 >> 1)); pp[0] = r0; pp[32] = r1; }
    const uint32_t rdelta = __shfl_sync(0xffffffffu, mapa(sb, (cluster_rank() + (ROLE == 1 ? 4 : 2)) % 6) - sb, 0);
    const uint32_t vdelta = ROLE ? 0 : __shfl_sync(0xffffffffu, mapa(sb, (cluster_rank() + 4) % 6) - sb, 0);
    ISTAMP(3)
    if (warp == 7 && lane == 0) mbar_arrive(sb + B_GO);
    __syncwarp();
    for (int s = 0; s < (ROLE == 0 ? 63 : 64); s++) {
        const int slot = s & 1;
        l8 += s & P.zero;
        const uint32_t w1a = l8 * 2 + (S_W1 + warp * 12288 - sb);
        PROF(9)
        uint32_t u2;
        {
            uint32_t mo = opq(((s + 7) & 7) * M_SLOT + warp * 2048 + (l8 & 56) * 2 + (l8 & 64) * 4 + (l8 & 128) * 8, l8 >> 3);
#define pm (P.gm + mo)
            uint32_t as[24][4], b[16], v[6][4];
            float acc[8][4];
#define W1LD(n) _Pragma("unroll") for (int i_ = 0; i_ < 4; i_++) ldsm4t(as[unit_pos(n) * 4 + i_], w1a + (unit_pos(n) * 4 + i_) * 512);
#define W1MMA(n) _Pragma("unroll") for (int i_ = 0; i_ < 4; i_++) { const uint32_t* a_ = in_smem(n) ? as[unit_pos(n) * 4 + i_] : wr[unit_pos(n) * 4 + i_]; \
                                                                   mma16816(acc[((n) & 1) * 4 + i_], a_[0], a_[1], a_[2], a_[3], b[(n) & 14], b[(n) | 1]); }
#pragma unroll
            for (int T = 0; T < 8; T++) { acc[T][0] = acc[T][1] = acc[T][2] = acc[T][3] = 0.f; }
            mbar_wait(sb + B_RELA, slot);
            PROF(12)
#pragma unroll
            for (int u = 0; u < 3; u++) ld_words(v[u], pm + unit_off(u));
            __syncwarp();
#pragma unroll
            for (int i = 0; i < PF1; i++) ldsm4t(as[i], w1a + i * 512);
            __syncwarp();
            mo += mbar_try(sb + B_RELB, slot) & P.zero;
            PROF(13)
#pragma unroll
            for (int u = 3; u < 6; u++) ld_words(v[u], pm + unit_off(u));
            uint32_t st = status(v, ((uint32_t)((uintptr_t)pm >> 32) & P.zero) + 32);
            pin<1>(&st);
            SFENCE();
            PROF(0)
            decode<0>(b, v[0]); decode<1>(b, v[1]); decode<2>(b, v[2]);
#pragma unroll
            for (int i = PF1; i < 12; i++) ldsm4t(as[i], w1a + i * 512);
            W1MMA(0) W1MMA(1) W1MMA(2)
            W1LD(3)
            SFENCE();
            W1MMA(5) W1MMA(4)
            const uint32_t mxa = sb + S_MX + slot * 32 + warp * 4;
            sts32(mxa, warp_max6(b));
            SFENCE();
            PROF(10)
            W1MMA(3)
            RETRY_STAT(st, status(v + 3, 32))
            const bool redo = __any_sync(0xffffffffu, (st | status(v + 3, 32)) & 96);
            decode<3>(b, v[3]); decode<4>(b, v[4]); decode<5>(b, v[5]);
            l8 += v[3][1] & P.zero;
            const uint32_t pst = (l8 - sb) * 16 + ((warp * 16) ^ ((l8 * 2) & 112)) + (sb + S_P1);
            W1MMA(6) W1MMA(8) W1MMA(10) W1MMA(12) W1MMA(14)
            W1LD(13)
            if (ROLE == 0) mbar_wait(sb + B_KVFULL + slot * 8, (s >> 1) & 1);
            SFENCE();
            PROF(14)
            put_partials<ROLE == 2>(pst, acc[0], acc[1]); put_partials<ROLE == 2>(pst + 4096, acc[2], acc[3]);
            u2 = lds32(sb + S_SC + warp * 4);
            W1LD(15)
            W1MMA(7) W1MMA(9) W1MMA(11) W1MMA(13) W1MMA(15)
            put_partials<ROLE == 2>(pst + 8192, acc[4], acc[5]); put_partials<ROLE == 2>(pst + 12288, acc[6], acc[7]);
            if (__builtin_expect(redo, 0)) {
                RETRY(3)
                gather_slow(P, b, pm, s, warp, (l8 - sb) >> 3, u2);
                sts32(mxa, warp_max6(b));
#pragma unroll
                for (int T = 0; T < 8; T++) { acc[T][0] = acc[T][1] = acc[T][2] = acc[T][3] = 0.f; }
#pragma unroll
                for (int n = 0; n < 16; n++) {
                    if (in_smem(n)) { W1LD(n) }
                    W1MMA(n)
                }
#pragma unroll
                for (int i = 0; i < 4; i++) put_partials<ROLE == 2>(pst + i * 4096, acc[2 * i], acc[2 * i + 1]);
            }
#undef pm
        }
        PROF(1)
        uint32_t kf[4][4] = {};
        if (att) {
            const uint32_t kaddr = (l8 & 56) * 16 + (((l8 >> 2) ^ (l8 * 2)) & 48) + ((l8 * 2) & 64) + (sb + S_KV + warp * 1024 + slot * 16384);
#pragma unroll
            for (int i = 0; i < 4; i++) ldsm4(kf[i], (kaddr ^ ((i & 1) * 64)) + (i >> 1) * 4096);
        }
        bar_sync(1, 256);
        uint32_t r0, r1;
        reduce8((l8 & 64) * 16 + (l8 & 128) + (l8 & 56) * 2 + (sb + S_P1 + warp * 2048), l8, u2, r0, r1);
        if (ROLE == 0) {
            const uint32_t qa_ = l8 * 2 - sb + S_QX + (warp >> 1) * 512 + (warp & 1) * 4;
            sts32(qa_, r0); sts32(qa_ + 8, r1);
            bar_sync(2, 256);
        } else {
            if (s == 63) {
                PERS_STORE()
                __syncwarp();
                if (l8 == sb) mbar_arrive(sb + B_PERS);
                break;
            }
            st_async2(l8 + (rdelta + (ROLE == 1 ? S_KL : S_VL) + warp * 256), r0, r1, sb + rdelta + (ROLE == 1 ? B_K : B_V));
        }
        PROF(2)
        const uint32_t ln = (l8 - sb) >> 3;
        uint32_t w2a = sb + S_W2 + (ROLE ? (warp >> 2) * 16384 : att ? 32768 : 0) + ((((ln & 7) + (ln >> 4) * 8) * 128 + ((((ln >> 3) & 1) ^ (ln & 7)) << 4)) ^ ((warp & 3) << 5));
        uint32_t ro = (s & 7) * M_SLOT + (ROLE ? warp * 2048 + unit_off(ROLE) : (warp & 3) * 2048 + (att ? unit_off(3) : 0)) + (ln & 2) * 128 + (ln & 1) * 64 + (ln >> 2) * 8;
        constexpr int RO2 = ROLE ? unit_off(ROLE + 3) - unit_off(ROLE) : 8192;
        float Sj[2];
        uint32_t w[24][4], ob[4][4];
        float S;
#define W2LD(i) ldsm4t(w[i], w2a + w2_t(i) * (ROLE ? 32768 : 16384) + (w2_k(i) & 1) * 8192 + (w2_k(i) >> 1) * 2048)
#define W2MMA(d, i) mma16816(d, w[i][0], w[i][1], w[i][2], w[i][3], ob[w2_k(i) >> 1][(w2_k(i) & 1) * 2], ob[w2_k(i) >> 1][(w2_k(i) & 1) * 2 + 1])
#define LEADER(wp) (l8 == sb + ((wp) - warp) * 256)
        if (att) {
            const float cs = 0.08838834764831845f * 1.4426950408889634f;
            uint32_t qa[4][4], vf[4][4], vv[4];
            float T[5][2];
#pragma unroll
            for (int i = 0; i < 4; i++) lds128(qa[i], l8 * 2 - sb + S_QX + i * 512);
            scores(T[0], qa, kf, []() {});
            sts64(l8 + S_SX + warp * 256, __float_as_uint(T[0][0]), __float_as_uint(T[0][1]));
            PROF(4)
            bar_sync(4, 128);
#pragma unroll
            for (int n = 0; n < 4; n++) lds64f(T[n], l8 + S_SX + n * 256);
            uint32_t vaddr = (l8 & 56) * 16 + (l8 & 128) * 8 + (((warp & 1) * 64 + ((l8 >> 2) & 16)) ^ ((l8 * 2) & 112)) + (sb + S_KV + 8192 + (warp >> 1) * 4096 + slot * 16384);
            pin<1>(&vaddr);
            mbar_wait(sb + B_K, slot);
            PROF(11)
#pragma unroll
            for (int i = 0; i < 8; i++) lds64(kf[i >> 1] + (i & 1) * 2, l8 + S_KL + i * 256);
            const float mx = cs * quad_max(fmaxf(fmaxf(fmaxf(T[0][0], T[0][1]), fmaxf(T[1][0], T[1][1])), fmaxf(fmaxf(T[2][0], T[2][1]), fmaxf(T[3][0], T[3][1]))));
            scores(T[4], qa, kf, [&]() {
#pragma unroll
                for (int n = 0; n < 4; n++) { T[n][0] = fmaf(T[n][0], cs, -mx); T[n][1] = fmaf(T[n][1], cs, -mx); }
                pin<8>(&T[0][0]);
                mbar_wait(sb + B_V, slot);
#pragma unroll
                for (int i = 0; i < 4; i++) ldsm4t(vf[i], (vaddr ^ ((i & 1) << 5)) + (i >> 1) * 2048);
                lds64(vv, l8 + S_VL + warp * 512); lds64(vv + 2, l8 + S_VL + warp * 512 + 256);
            });
#pragma unroll
            for (int n = 0; n < 4; n++) { T[n][0] = ex2(T[n][0]); T[n][1] = ex2(T[n][1]); }
            float sum = ((T[0][0] + T[0][1]) + (T[1][0] + T[1][1])) + ((T[2][0] + T[2][1]) + (T[3][0] + T[3][1]));
            const float m = fmaxf(mx, cs * quad_max(fmaxf(T[4][0], T[4][1])));
            const float al = ex2(mx - m);
            T[4][0] = ex2(fmaf(T[4][0], cs, -m)); T[4][1] = ex2(fmaf(T[4][1], cs, -m));
            uint32_t pa[5];
#pragma unroll
            for (int n = 0; n < 4; n++) pa[n] = pack2(T[n][0] * al, T[n][1] * al);
            pa[4] = pack2(T[4][0], T[4][1]);
            sum = fmaf(sum, al, T[4][0] + T[4][1]);
            PROF(3)
            const uint32_t lo = sb + S_O + warp * 512 + (ln & 3) * 64 + (ln >> 2) * 8, ls = sb + S_SUM + (ln & 3) * 32 + (ln & 4) * 4 + (ln >> 3) * 4;
            const uint32_t sdelta = warp < 2 ? rdelta : vdelta;
            sum += __shfl_xor_sync(0xffffffffu, sum, 1);
            sum += __shfl_xor_sync(0xffffffffu, sum, 2);
            float O[2][4];
#pragma unroll
            for (int i = 0; i < 2; i++) { O[i][0] = O[i][1] = O[i][2] = O[i][3] = 0.f; }
#pragma unroll
            for (int i = 0; i < 2; i++) {
                mma16816(O[0], vf[2 * i][0], vf[2 * i][1], vf[2 * i][2], vf[2 * i][3], pa[2 * i], pa[2 * i + 1]);
                mma16816(O[1], vf[2 * i + 1][0], vf[2 * i + 1][1], vf[2 * i + 1][2], vf[2 * i + 1][3], pa[2 * i], pa[2 * i + 1]);
            }
            mma1688(O[0], vv[0], vv[1], pa[4]);
            mma1688(O[1], vv[2], vv[3], pa[4]);
            uint32_t o[2][2];
#pragma unroll
            for (int j = 0; j < 2; j++) { o[j][0] = pack2(O[0][j], O[0][2 + j]); o[j][1] = pack2(O[1][j], O[1][2 + j]); }
#pragma unroll
            for (int j = 0; j < 2; j++) st_async2(lo + rdelta + j * 256, o[j][0], o[j][1], sb + rdelta + B_K);
            st_async1(ls + sdelta + (warp & 1) * 128, __float_as_uint(sum), sb + sdelta + B_K);
#pragma unroll
            for (int j = 0; j < 2; j++) st_async2(lo + vdelta + j * 256, o[j][0], o[j][1], sb + vdelta + B_K);
#pragma unroll
            for (int j = 0; j < 2; j++) sts64(lo + j * 256, o[j][0], o[j][1]);
            sts32(ls + warp * 128, __float_as_uint(sum));
            PROF(5)
            bar_sync(3, 256);
            S = next_scale(sb, slot, warp, u2);
            if (s == 0) mbar_wait(sb + B_WO, 0);
            pin<1>(&S);
            SFENCE();
#pragma unroll
            for (int j = 0; j < 4; j++) lds128(ob[j], l8 * 2 - sb + S_O + j * 512);
            lds64f(Sj, sb + S_SUM + (l8 & 24));
#pragma unroll
            for (int i = 0; i < PF2; i++) W2LD(i);
        } else {
            if (LEADER(7)) mbar_arrive(sb + B_GO);
            if (ROLE != 0 && (s & 3) == 0 && s > 0 && l8 == sb) mbar_arrive(sb + B_PERS);
            S = next_scale(sb, slot, warp, u2);
            if (s == 0) mbar_wait(sb + B_WO, 0);
            if (ROLE != 0) { l8 += delay_loop(40, l8); if (!DBGF(4)) PERS_STORE() }
#pragma unroll
            for (int i = 0; i < PF2; i++) {
                W2LD(i);
                if (ROLE == 0 && (i & PACE) == PACE) w2a += w[i][0] & P.zero;
            }
            ro = opq(ro, ln);
            const uint32_t sa = opq(sb + S_SUM + (l8 & 24), ln), oa = opq(l8 * 2 - sb + S_O, ln);
            if (ROLE == 0) bar_sync(3, 256); else mbar_wait(sb + B_K, slot);
            lds64f(Sj, sa);
#pragma unroll
            for (int j = 0; j < 4; j++) lds128(ob[j], oa + j * 512);
        }
        SFENCE();
        PROF(6)
        {
            const uint8_t* pr = P.gm + ro;
            float c[4][4];
            Sj[0] = S * rcp(Sj[0]); Sj[1] = S * rcp(Sj[1]);
            uint32_t lim = 0;
#pragma unroll
            for (int i = 0; i < 4; i++) { c[i][0] = c[i][1] = c[i][2] = c[i][3] = 0.f; }
#pragma unroll
            for (int i = 0; i < 16; i++) {
                W2MMA(c[i & (ROLE ? 1 : 3)], i);
                if (i + PF2 < (ROLE ? 16 + NEARLY : 16)) W2LD(i + PF2);
                if (i == 9) lim = __any_sync(0xffffffffu, fmaxf(fmaxf(fabsf(c[0][0]), fabsf(c[0][2])), fmaxf(fabsf(c[1][0]), fabsf(c[1][2]))) * Sj[0] >= (ROLE ? 32.f : 24.f)) ? 16384 : 0;
            }
            if (ROLE == 0) {
#pragma unroll
                for (int i = 0; i < 8; i++) c[i >> 2][i & 3] += c[2 + (i >> 2)][i & 3];
            }
            const float x[2][3] = {{c[0][0], c[0][2], c[1][0]}, {c[0][1], c[0][3], c[1][1]}};
            const bool ok0 = emit<NU>(x, Sj, P.two26, lim, pr);
            PROF(7)
            if (ROLE) {
                SFENCE();
#pragma unroll
                for (int i = 16 + NEARLY; i < 24; i++) { W2LD(i); __syncwarp(); }
                SFENCE();
#pragma unroll
                for (int i = 16; i < 24; i++) W2MMA(c[2 + (i & 1)], i);
#pragma unroll
                for (int i = 0; i < 4; i++) c[2][i] += c[3][i];
            }
            const float y[2][3] = {{ROLE ? c[1][2] : c[1][0], ROLE ? c[2][0] : c[1][2], c[2][2]}, {ROLE ? c[1][3] : c[1][1], ROLE ? c[2][1] : c[1][3], c[2][3]}};
            const bool ok1 = emit<NU>(y, Sj, P.two26, lim, pr + RO2);
            if (__builtin_expect(!__all_sync(0xffffffffu, ok0 && ok1), 0)) {
                RETRY(5)
                const uint8_t* pf = g_f + (s & 7) * F_SLOT + (ROLE ? ROLE * 8192 + warp * 1024 : (warp & 3) * 1024 + (att ? 24576 : 0)) + (ln & 3) * 128 + (ln >> 2) * 16;
                repair<NU>(ok0, x, Sj, P.two26, pr, pf);
                repair<NU>(ok1, y, Sj, P.two26, pr + RO2, pf + (ROLE ? 24576 : 4096));
            }
            if (LEADER(7)) {
                mbar_expect(sb + B_K, ROLE ? 2304 : 2048);
                if (ROLE == 0) { mbar_expect(sb + B_V, 2048); mbar_arrive(sb + B_KVGO + slot * 8); }
            }
        }
        PROF(8)
    }
}
struct Pipe { uint32_t stage, phase; };
struct Cons {
    uint32_t sb, rel;
    int wg, wq, lane, rank, pair;
    uint32_t atag, nst;
    Pipe p;
};
__device__ __forceinline__ void pipe_next(Pipe& p) { p.stage = (p.stage + 1) & (NSTAGE - 1); p.phase ^= (p.stage == 0); }
__device__ __forceinline__ void release(const Cons& c, uint32_t stage) { if (c.lane < 2) mbar_arrive_cluster(c.rel + stage * 8); }

enum { PEND_NONE = 0, PEND_KVO = 1, PEND_HT = 2, PEND_OUT = 3, PEND_OUTH = 4 };
struct Pend { uint32_t pk[64]; int kind, row, col, cnt; };

__device__ __forceinline__ void staging_wait(const Cons& c) { if (c.nst) mbar_wait(c.sb + B_SFREE + c.wg * 8, (c.nst - 1) & 1); }
__device__ __forceinline__ void staging_post(Cons& c, int kind, int row, int col, int cnt) {
    __syncwarp();
    if (c.lane == 0) {
        if (c.wq == 0) { const uint32_t x[4] = {(uint32_t)kind, (uint32_t)row, (uint32_t)col, (uint32_t)cnt}; sts128(c.sb + S_DESC + c.wg * 16, x); }
        mbar_arrive(c.sb + B_SFULL + c.wg * 8);
    }
    c.nst++;
}
template <int HF, bool KVONLY = false>
__device__ __forceinline__ void drain(const Params& P, Cons& c, const Pend& d) {
    const uint32_t* pk = d.pk + HF * 32;
    if (!KVONLY && d.kind >= PEND_OUT) {
        if (HF == 1 && d.kind == PEND_OUTH) return;
        float* o = P.out + (size_t)(d.row + c.wq * 16 + (c.lane >> 2)) * 2048 + d.col + HF * 128 + (c.lane & 3) * 2;
#pragma unroll
        for (int j = 0; j < 16; j++) {
            st_stream2(o + j * 8, bf_lo(pk[j * 2]), bf_hi(pk[j * 2]));
            st_stream2(o + 8 * 2048 + j * 8, bf_lo(pk[j * 2 + 1]), bf_hi(pk[j * 2 + 1]));
        }
    } else if (d.kind != PEND_NONE) {
        const bool ht = !KVONLY && d.kind == PEND_HT;
        const int hi = (c.lane >> 3) & 1;
        const uint32_t base = c.sb + S_STG + c.wg * 16384 + ((ht ? hi * 32 + c.wq * 8 : c.wq * 16 + hi * 8) + (c.lane & 7)) * 128;
        staging_wait(c);
#pragma unroll
        for (int j = 0; j < 8; j++) {
            const int ch = (j & 3) * 2 + (c.lane >> 4);
            stsm4(base + (j >> 2) * 8192 + ((ch ^ (c.lane & 7)) << 4), pk[j * 4], pk[j * 4 + 1], pk[j * 4 + 2], pk[j * 4 + 3]);
        }
        fence_async_smem();
        staging_post(c, d.kind, d.row, d.col + HF * 128, HF ? d.cnt : -1);
    }
}
__device__ __forceinline__ void drain_all(const Params& P, Cons& c, Pend& d) { drain<0>(P, c, d); drain<1>(P, c, d); d.kind = PEND_NONE; }

__device__ __forceinline__ void store_warp(const Params& P, uint32_t sb, int wg) {
    const uint32_t stg = sb + S_STG + wg * 16384;
#pragma unroll 1
    for (uint32_t n = 0;; n++) {
        mbar_wait(sb + B_SFULL + wg * 8, n & 1);
        uint32_t x[4];
        lds128(x, sb + S_DESC + wg * 16);
        if (x[0] == PEND_NONE) break;
        const bool ht = x[0] == PEND_HT;
        const CUtensorMap* m = &P.tm[ht ? M_HTS : M_KVO];
#pragma unroll 1
        for (int i = 0; i < 4; i++) tma_store2d(m, x[2] + (i >> 1) * 64, x[1] + (i & 1) * (ht ? 1024 : 32), stg + i * 4096);
        bulk_commit();
        bulk_wait_read();
        mbar_arrive(sb + B_SFREE + wg * 8);
        if ((int)x[3] >= 0) { bulk_wait_all(); fence_async(); red_release(&g_cnt(x[3])); }
    }
}

template <int N, int TA, int TB, bool FIRST>
__device__ __forceinline__ void issue_ktile(float* acc, const Cons& c) {
    mbar_wait(c.sb + B_FULL + c.p.stage * 8, c.p.phase);
    const uint32_t a = c.sb + c.p.stage * STAGE + c.wg * 8192, b = c.sb + c.p.stage * STAGE + 16384;
    const uint64_t da = mkdesc(a, TA ? 8192 : 16, 1024, 1), db = mkdesc(b, TB ? 8192 : 16, 1024, 1);
    wg_fence();
#pragma unroll
    for (int k = 0; k < 4; k++) {
        const uint64_t x = da + (TA ? 128 : 2) * k, y = db + (TB ? 128 : 2) * k;
        if (N == 256) { if (FIRST && k == 0) wgmma_ss256_first<TA, TB>(acc, x, y); else wgmma_ss256<TA, TB>(acc, x, y); }
        else { if (FIRST && k == 0) wgmma_ss128_first<TA, TB>(acc, x, y); else wgmma_ss128<TA, TB>(acc, x, y); }
    }
    wg_commit();
}
template <int N, bool FIRST>
__device__ __forceinline__ void issue_any(float* acc, const Cons& c, int type) {
    if (N == 256 && type == T_A1) issue_ktile<N, 0, 0, FIRST>(acc, c);
    else if (type == (N == 256 ? T_A2 : T_A2H)) issue_ktile<N, 1, 0, FIRST>(acc, c);
    else issue_ktile<N, 0, 1, FIRST>(acc, c);
}
template <int N, bool KVONLY = false>
__device__ __forceinline__ void mainloop(float* acc, const Params& P, Cons& c, Pend& d, int type) {
    const int nk = (type == T_OP || type == T_OPH) ? 64 : (type == T_A2 || type == T_A2H) ? 32 : 16;
    issue_any<N, true>(acc, c, type);
    drain<0, KVONLY>(P, c, d);
    uint32_t prev = c.p.stage;
    pipe_next(c.p);
    for (int kt = 1; kt < nk; kt++) {
        issue_any<N, false>(acc, c, type);
        wg_wait<1>();
        release(c, prev);
        if (kt == 2) drain<1, KVONLY>(P, c, d);
        prev = c.p.stage;
        pipe_next(c.p);
    }
    d.kind = PEND_NONE;
    wg_wait<0>();
    pin<N / 2>(acc);
    release(c, prev);
}
__device__ __forceinline__ void pack_half(uint32_t* pk, const float* a) {
#pragma unroll
    for (int i = 0; i < 32; i++) pk[i] = pack2(a[2 * i], a[2 * i + 1]);
}

__device__ __forceinline__ void epi_kv(const float* acc, const Cons& c, Pend& d, int mb, int nb) {
    pack_half(d.pk, acc); pack_half(d.pk + 32, acc + 64);
    d.kind = PEND_KVO; d.row = (nb >> 4) * 2048 + mb * 256 + c.rank * 128 + c.wg * 64; d.col = (nb & 15) * 256; d.cnt = C_KV + mb;
}

__device__ __forceinline__ void epi_qa(const float* acc, Cons& c, Pend& d, int mb, int nb) {
    uint32_t q[64];
    pack_half(q, acc);
    pack_half(q + 32, acc + 64);
#pragma unroll
    for (int i = 0; i < 32; i++) d.pk[32 + i] = 0;
    const int g = c.lane >> 2, t = c.lane & 3;
    const bool sg = c.wq >= 2;
    const int i0 = (c.wq & 1) * 16 + g;
#pragma unroll 1
    for (int hh = 0; hh < 2; hh++) {
        uint32_t pa[5][4];
        {
            float S[32] = {}, Sm[8] = {};
            mbar_wait(c.sb + B_FULL + c.p.stage * 8, c.p.phase);
            const uint32_t st = c.sb + c.p.stage * STAGE;
            const uint64_t dk = mkdesc(st + c.wg * 8192, 16, 1024, 1), dm = mkdesc(st + 32768 + c.wg * 4096, 128, 2048, 0);
            pin<32>(q); pin<32>(S); pin<8>(Sm);
            wg_fence();
#pragma unroll
            for (int i = 0; i < 8; i++) wgmma_rs64<0>(S, q + i * 4, dk + (i >> 2) * 1024 + (i & 3) * 2, i != 0);
#pragma unroll
            for (int i = 0; i < 8; i++) wgmma_rs16<0>(Sm, q + i * 4, dm + i * 16, i != 0);
            wg_commit();
            wg_wait<0>();
            pin<32>(S); pin<8>(Sm);
            release(c, c.p.stage);
            pipe_next(c.p);
            const float scale = 0.08838834764831845f, l2e = 1.4426950408889634f;
            float x[2][10];
#pragma unroll
            for (int r = 0; r < 2; r++) {
#pragma unroll
                for (int j = 0; j < 4; j++)
#pragma unroll
                    for (int e = 0; e < 2; e++) {
                        const float v = sg ? S[16 + j * 4 + r * 2 + e] : S[j * 4 + r * 2 + e];
                        x[r][j * 2 + e] = (j * 8 + 2 * t + e > i0 + r * 8) ? -1e9f : v * scale;
                    }
                x[r][8] = (sg ? Sm[4 + r * 2] : Sm[r * 2]) * scale;
                x[r][9] = (sg ? Sm[5 + r * 2] : Sm[1 + r * 2]) * scale;
                float m = x[r][0];
#pragma unroll
                for (int i = 1; i < 10; i++) m = fmaxf(m, x[r][i]);
                m = fmaxf(m, __shfl_xor_sync(0xffffffffu, m, 1));
                m = fmaxf(m, __shfl_xor_sync(0xffffffffu, m, 2));
                float sum = 0.f;
#pragma unroll
                for (int i = 0; i < 10; i++) { x[r][i] = ex2((x[r][i] - m) * l2e); sum += x[r][i]; }
                sum += __shfl_xor_sync(0xffffffffu, sum, 1);
                sum += __shfl_xor_sync(0xffffffffu, sum, 2);
                const float inv = rcp(sum);
#pragma unroll
                for (int i = 0; i < 10; i++) x[r][i] *= inv;
            }
#pragma unroll
            for (int ks = 0; ks < 2; ks++)
#pragma unroll
                for (int i = 0; i < 4; i++) {
                    const uint32_t p = pack2(x[i & 1][ks * 4 + (i >> 1) * 2], x[i & 1][ks * 4 + (i >> 1) * 2 + 1]);
                    pa[ks][i] = sg ? 0u : p;
                    pa[2 + ks][i] = sg ? p : 0u;
                }
#pragma unroll
            for (int r = 0; r < 2; r++) {
                const uint32_t p = pack2(x[r][8], x[r][9]);
                pa[4][r] = sg ? 0u : p;
                pa[4][2 + r] = sg ? p : 0u;
            }
        }
        float O[64] = {};
        mbar_wait(c.sb + B_FULL + c.p.stage * 8, c.p.phase);
        const uint32_t st = c.sb + c.p.stage * STAGE;
        const uint64_t dv = mkdesc(st + c.wg * 8192, 16384, 1024, 1), dm = mkdesc(st + 32768 + c.wg * 4096, 2048, 128, 0);
        pin<20>(&pa[0][0]); pin<64>(O);
        wg_fence();
#pragma unroll
        for (int ks = 0; ks < 4; ks++) wgmma_rs128<1>(O, pa[ks], dv + ks * 128, ks != 0);
        wgmma_rs128<0>(O, pa[4], dm, 1);
        wg_commit();
        wg_wait<0>();
        pin<64>(O);
        release(c, c.p.stage);
        pipe_next(c.p);
#pragma unroll
        for (int i = 0; i < 32; i++) { q[i] = q[32 + i]; q[32 + i] = d.pk[32 + i]; }
        pack_half(d.pk + 32, O);
    }
#pragma unroll
    for (int i = 0; i < 32; i++) d.pk[i] = q[32 + i];
    d.kind = PEND_KVO; d.row = 4096 + mb * 256 + c.rank * 128 + c.wg * 64; d.col = nb * 256; d.cnt = C_O + mb;
}

__device__ __forceinline__ void epi_op(const float* acc, const Cons& c, Pend& d, int mb, int nb) {
    pack_half(d.pk, acc); pack_half(d.pk + 32, acc + 64);
    d.kind = PEND_OUT; d.row = mb * 256 + c.rank * 128 + c.wg * 64; d.col = 1024 + nb * 256;
}

__device__ __forceinline__ void epi_oph(const float* acc, const Cons& c, Pend& d, int mb, int nb) {
    pack_half(d.pk, acc);
    d.kind = PEND_OUTH; d.row = mb * 256 + c.rank * 128 + c.wg * 64; d.col = 1024 + nb * 128;
}

template <int HF>
__device__ __forceinline__ void epi_a2_half(const float* acc, const Params& P, Cons& c, int mb, int col0) {
    const int g = c.lane >> 2, t = c.lane & 3;
    const int row = mb * 256 + (g >> 1) * 64 + (c.rank * 16 + c.wg * 8 + c.wq * 2) * 2 + (g & 1);
    float* o = P.out + (size_t)row * 2048 + col0 + HF * 128 + t * 2;
    mbar_wait(c.sb + B_FULL + c.p.stage * 8, c.p.phase);
    const uint32_t st = c.sb + c.p.stage * STAGE, xa = st + (c.wg * 64 + c.wq * 16 + g) * 128 + t * 4 + (g << 4), da = st + 32768 + t * 4;
#pragma unroll
    for (int j = 0; j < 16; j++) {
        const float* a = acc + HF * 64 + j * 4;
        const uint32_t ad = (xa ^ ((j & 7) << 4)) + (j >> 3) * 16384;
        const uint32_t x0 = lds32(ad), x1 = lds32(ad + 1024), dv = lds32(da + j * 16);
        const uint32_t u0 = pack2(bf_lo(x0) * bf_lo(dv), bf_hi(x0) * bf_hi(dv)), u1 = pack2(bf_lo(x1) * bf_lo(dv), bf_hi(x1) * bf_hi(dv));
        st_stream2(o + j * 8, a[0] + bf_lo(u0), a[1] + bf_hi(u0));
        st_stream2(o + 2 * 2048 + j * 8, a[2] + bf_lo(u1), a[3] + bf_hi(u1));
    }
    __syncwarp();
    release(c, c.p.stage);
    pipe_next(c.p);
}

#define TSTAMP(i)
__device__ __forceinline__ float2 cmul(float2 a, float2 b) { return make_float2(fmaf(a.x, b.x, -a.y * b.y), fmaf(a.x, b.y, a.y * b.x)); }
__device__ __forceinline__ float2 cfma(float2 a, float2 b, float2 u) { return make_float2(fmaf(a.x, b.x, fmaf(-a.y, b.y, u.x)), fmaf(a.x, b.y, fmaf(a.y, b.x, u.y))); }
__device__ __forceinline__ float4 ssm_coef(float lre, float lim, float logdt) {
    const float dt = __bfloat162float(__float2bfloat16(expf(logdt)));
    const float ea = expf(dt * lre);
    float sn, cn;
    sincosf(dt * lim, &sn, &cn);
    const float br = ea * cn, bi = ea * sn, nr = br - 1.f;
    float cr, ci;
    if (fabsf(lre) >= fabsf(lim)) { const float r = lim / lre, dn = lre + lim * r; cr = (nr + bi * r) / dn; ci = (bi - nr * r) / dn; }
    else { const float r = lre / lim, dn = lre * r + lim; cr = (nr * r + bi) / dn; ci = (bi * r - nr) / dn; }
    return make_float4(br, bi, cr, ci);
}
__device__ __forceinline__ void epi_a1(const float* acc, const Params& P, const Cons& c, Pend& d, int mb, int nb, uint32_t atag) {
    const int t = c.lane & 3;
    const int p = nb * 128 + c.rank * 64 + c.wg * 32 + c.wq * 8 + (c.lane >> 2);
    const float4 cf = __ldcg(&g_coef[p]);
    TSTAMP(1)
    const float2 lam = make_float2(cf.x, P.swap_ri ? -cf.y : cf.y);
    const float a0 = P.swap_ri ? -2.f * cf.w : 2.f * cf.z, a1 = P.swap_ri ? 2.f * cf.z : -2.f * cf.w;
    const float b0 = P.swap_ri ? -2.f * cf.z : -2.f * cf.w, b1 = P.swap_ri ? -2.f * cf.w : -2.f * cf.z;
    float2 h = make_float2(0.f, 0.f);
#pragma unroll
    for (int round = 0; round < 2; round++) {
#pragma unroll
        for (int j = 0; j < 32; j++) {
            h = cfma(lam, h, make_float2(acc[j * 4], acc[j * 4 + 2]));
            const float r0 = fmaf(a0, h.x, a1 * h.y), m0 = fmaf(b0, h.x, b1 * h.y);
            h = cfma(lam, h, make_float2(acc[j * 4 + 1], acc[j * 4 + 3]));
            d.pk[j * 2] = pack2(r0, fmaf(a0, h.x, a1 * h.y));
            d.pk[j * 2 + 1] = pack2(m0, fmaf(b0, h.x, b1 * h.y));
        }
        if (round) break;
        float2 l64 = lam;
#pragma unroll
        for (int i = 0; i < 6; i++) l64 = cmul(l64, l64);
        const float2 l128 = cmul(l64, l64), l256 = cmul(l128, l128);
        float2 o = make_float2(__shfl_up_sync(0xffffffffu, h.x, 1), __shfl_up_sync(0xffffffffu, h.y, 1));
        if (t >= 1) h = cfma(l64, o, h);
        o = make_float2(__shfl_up_sync(0xffffffffu, h.x, 2), __shfl_up_sync(0xffffffffu, h.y, 2));
        if (t >= 2) h = cfma(l128, o, h);
        TSTAMP(2)
        if (t == 3) st_relaxed2(&g_agg[mb * 1024 + p], (__float_as_uint(h.x) & ~1u) | atag, __float_as_uint(h.y));
        h = make_float2(__shfl_up_sync(0xffffffffu, h.x, 1), __shfl_up_sync(0xffffffffu, h.y, 1));
        if (t == 0) h = make_float2(0.f, 0.f);
        uint32_t ax[7], ay[7];
        int n = 0;
        while (true) {
            uint32_t bad = 0;
#pragma unroll
            for (int j = 0; j < 7; j++) { ax[j] = atag; ay[j] = 0; ld_relaxed2_if(ax[j], ay[j], &g_agg[j * 1024 + p], j < mb); }
#pragma unroll
            for (int j = 0; j < 7; j++) bad |= ax[j] ^ atag;
            if (tags_ok(bad)) break;
            __nanosleep(400);
            if (++n > SPIN_LIMIT) spin_fault();
        }
        float2 carry = make_float2(0.f, 0.f);
#pragma unroll
        for (int j = 0; j < 7; j++) if (j < mb) carry = cfma(l256, carry, make_float2(__uint_as_float(ax[j]), __uint_as_float(ay[j])));
        float2 w = (t & 1) ? l64 : make_float2(1.f, 0.f);
        if (t & 2) w = cmul(w, l128);
        h = cfma(w, carry, h);
        TSTAMP(3)
    }
    TSTAMP(4)
    d.kind = PEND_HT; d.row = nb * 128 + c.rank * 64 + c.wg * 32; d.col = mb * 256; d.cnt = C_HT + mb;
}

__device__ __forceinline__ uint32_t acquire_stage(uint32_t sb, Pipe& p, uint32_t bytes) {
    mbar_wait(sb + B_EMPTY + p.stage * 8, p.phase ^ 1);
    mbar_expect(sb + B_FULL + p.stage * 8, bytes);
    return p.stage;
}
__device__ __forceinline__ void producer(const Params& P, const uint32_t sb, const int pair, const int rank, const uint32_t epoch) {
    Pipe p = {0, 0};
    const uint32_t e1 = epoch + 1;
    for (int it = ITEM_OFF(pair); it < ITEM_OFF(pair + 1); it++) {
        const int item = ITEM(it), type = item >> 8, mb = (item >> 5) & 7, nb = item & 31;
        if (type == T_CHAIN) {
            if (pair < 16) {
#pragma unroll 1
                for (int s = 0; s < 63; s++) {
                    if (s == 0) mbar_wait(sb + B_GO, 0);
                    if (s >= 2) { mbar_wait(sb + B_KVGO + (s & 1) * 8, ((s >> 1) + 1) & 1); wait_time(gtime() + P.dk, sb); }
                    if (s == 0 && !DBGF(1)) { wait_count(&g_cnt(C_KV), e1 * 128); fence_async(); }
                    const uint32_t bar = sb + B_KVFULL + (s & 1) * 8, dst = sb + S_KV + (s & 1) * 16384;
                    if (DBGF(2)) { mbar_arrive(bar); continue; }
                    mbar_expect(bar, 16384);
#pragma unroll 1
                    for (int i = 0; i < 4; i++) tma2d(dst + i * 4096, &P.tm[M_KVO], (pair * 2 + rank) * 128 + (i & 1) * 64, (i >> 1) * 2048 + (DBGF(32) ? s & 7 : s) * 32, bar);
                    if (s < 62) {
                        if ((s & 7) == 7 && !DBGF(1)) { wait_count(&g_cnt(C_KV + 1 + (s >> 3)), e1 * 128); fence_async(); }
#pragma unroll 1
                        for (int i = 0; i < 4; i++) if (!DBGF(64)) tma_prefetch2d(&P.tm[M_KVO], (pair * 2 + rank) * 128 + (i & 1) * 64, (i >> 1) * 2048 + s * 32 + 32);
                    }
                }
            } else {
                uint32_t* flag = &g_cnt(C_FLAG + pair * 2 + rank - 32);
#pragma unroll 1
                for (int s = 0; s < 16; s++) {
                    mbar_wait(sb + B_PERS, s & 1);
                    if (!DBGF(8)) asm volatile("st.release.gpu.global.u32 [%0], %1;" ::"l"(flag), "r"(epoch * 64 + s * 4 + 4) : "memory");
                }
            }
            if (!DBGF(32)) wait_count(&g_cnt(C_COEF), e1 * 4);
            mbar_wait(sb + B_RESUME, 0);
            continue;
        }
        const int m0 = mb * 256 + rank * 128;
        if (type <= T_OP) {
            const CUtensorMap* ma = &P.tm[type == T_OP ? M_OA : M_BX];
            const CUtensorMap* mw = &P.tm[type == T_OP ? M_WO : type == T_QA ? M_WQ : nb < 16 ? M_WK : M_WV];
            const int nk = type == T_OP ? 64 : 16, nc = (nb & 15) * 4 + rank * 2, ma0 = type == T_OP ? 4096 + m0 : m0;
            if (type == T_OP) { wait_count(&g_cnt(C_O + mb), e1 * 64); fence_async(); }
            if (type == T_QA) {
                wait_count(&g_cnt(C_KV + mb), e1 * 128);
                fence_async();
            }
#pragma unroll 1
            for (int kt = 0; kt < nk; kt++) {
                const uint32_t st = acquire_stage(sb, p, STAGE), bar = sb + B_FULL + st * 8;
                tma2d(sb + st * STAGE, ma, kt * 64, ma0, bar);
                tma3d_mc(sb + st * STAGE + 16384 + rank * 16384, mw, 0, kt * 64, nc, bar);
                if (type == T_QA && kt < 8) tma_prefetch2d(&P.tm[M_OA], nb * 256 + (kt & 3) * 64, (kt >> 2) * 2048 + m0);
                pipe_next(p);
            }
            if (type == T_QA) {
                const uint32_t need = epoch * 64 + mb * 8 + rank * 4 + 4;
#pragma unroll 1
                for (int i = 0; i < 4; i++) wait_count(&g_cnt(C_FLAG + (i >> 1) * 32 + nb * 2 + (i & 1)), need);
                fence_async();
#pragma unroll 1
                for (int e = 0; e < 4; e++) {
                    const uint32_t st = acquire_stage(sb, p, 40960), bar = sb + B_FULL + st * 8, dst = sb + st * STAGE;
                    tma2d(dst, &P.tm[M_OA], nb * 256 + (e >> 1) * 128, (e & 1) * 2048 + m0, bar);
                    tma2d(dst + 16384, &P.tm[M_OA], nb * 256 + (e >> 1) * 128 + 64, (e & 1) * 2048 + m0, bar);
                    const uint32_t* src = ((e & 1) ? g_vmt : g_km) + ((mb * 8 + rank * 4) * 32 + nb * 2 + (e >> 1)) * 512;
#pragma unroll 1
                    for (int i = 0; i < 4; i++) bulk_g2s(dst + 32768 + i * 2048, src + i * 32 * 512, 2048, bar);
                    pipe_next(p);
                }
            }
        } else if (type == T_OPH) {
            wait_count(&g_cnt(C_O + mb), e1 * 64);
            fence_async();
#pragma unroll 1
            for (int kt = 0; kt < 64; kt++) {
                const uint32_t st = acquire_stage(sb, p, 32768), bar = sb + B_FULL + st * 8;
                tma2d(sb + st * STAGE, &P.tm[M_OA], kt * 64, 4096 + m0, bar);
                tma2d_mc(sb + st * STAGE + 16384 + rank * 8192, &P.tm[M_WOH], nb * 128 + rank * 64, kt * 64, bar);
                pipe_next(p);
            }
        } else if (type == T_A1) {
            if (pair >= NCHAIN) wait_count(&g_cnt(C_COEF), e1 * 4);
#pragma unroll 1
            for (int kt = 0; kt < 16; kt++) {
                const uint32_t st = acquire_stage(sb, p, STAGE), bar = sb + B_FULL + st * 8;
                tma4d(sb + st * STAGE, &P.tm[M_AB], kt * 64, nb * 16 + rank * 8, bar);
                tma4d_mc(sb + st * STAGE + 16384 + rank * 16384, &P.tm[M_AX], kt * 64, mb * 128 + rank * 16, bar);
                pipe_next(p);
            }
        } else {
            wait_count(&g_cnt(C_HT + mb), e1 * 32);
            fence_async();
            const int hw = type == T_A2H ? 64 : 128;
            const CUtensorMap* mc = &P.tm[type == T_A2H ? M_CREH : M_CRE];
#pragma unroll 1
            for (int kt = 0; kt < 32; kt++) {
                const uint32_t st = acquire_stage(sb, p, 16384 + hw * 256), bar = sb + B_FULL + st * 8;
                tma3d(sb + st * STAGE, &P.tm[M_HT], 0, kt * 64, mb * 4 + rank * 2, bar);
                tma2d_mc(sb + st * STAGE + 16384 + rank * hw * 128, mc + (kt >> 4), (kt & 15) * 64, (nb * 2 + rank) * hw, bar);
                pipe_next(p);
            }
#pragma unroll 1
            for (int col = nb * 2 * hw; col < (nb + 1) * 2 * hw; col += 128) {
                const uint32_t st = acquire_stage(sb, p, 32768 + 256), bar = sb + B_FULL + st * 8;
                tma4d(sb + st * STAGE, &P.tm[M_AX], col, mb * 128 + rank * 16, bar);
                tma4d(sb + st * STAGE + 16384, &P.tm[M_AX], col + 64, mb * 128 + rank * 16, bar);
                bulk_g2s(sb + st * STAGE + 32768, P.Dskip + col, 256, bar);
                pipe_next(p);
            }
        }
    }
}

__device__ __forceinline__ uint32_t fresh_tid() { uint32_t t; asm volatile("mov.u32 %0, %%tid.x;" : "=r"(t)); return t; }
__device__ __forceinline__ uint32_t fresh_ctaid() { uint32_t t; asm volatile("mov.u32 %0, %%ctaid.x;" : "=r"(t)); return logical_cta(t); }
__device__ __forceinline__ void reset_state(Cons& c, Pend& d, uint32_t sb, bool resumed) {
    const uint32_t t = fresh_tid(), b = fresh_ctaid();
    const int w = __shfl_sync(0xffffffffu, t >> 5, 0);
    c.sb = sb; c.wg = w >> 2; c.wq = w & 3; c.lane = t & 31;
    c.rank = __shfl_sync(0xffffffffu, b & 1, 0); c.pair = __shfl_sync(0xffffffffu, b >> 1, 0);
    c.rel = mapa(sb + B_EMPTY, cluster_rank() ^ (c.lane & 1));
    c.atag = (lds32(sb + S_EPOCH) + 1) & 1;
    c.p.stage = 0; c.p.phase = 0;
    c.nst = resumed && c.pair < NCHAIN ? 2 * NPRE : 0;
    d = Pend{};
}
#define PROF_ITEM(i)

__global__ void __launch_bounds__(384, 1) fused_kernel(const __grid_constant__ Params P) {
    extern __shared__ __align__(1024) uint8_t smem[];
    const uint32_t sb = smem_u32(smem);
    asm volatile("griddepcontrol.launch_dependents;");
    const int tid = threadIdx.x, lane = tid & 31;
    const int warp = __shfl_sync(0xffffffffu, tid >> 5, 0);
    const int pair = __shfl_sync(0xffffffffu, logical_cta(blockIdx.x) >> 1, 0), rank = __shfl_sync(0xffffffffu, blockIdx.x & 1, 0);
    if (tid == 0) {
        if (sb & 1023) spin_fault();
        sts32(sb + S_EPOCH, ld_relaxed1(&g_cnt(C_EPOCH)));
        for (int i = 0; i < NSTAGE; i++) { mbar_init(sb + B_FULL + i * 8, 1); mbar_init(sb + B_EMPTY + i * 8, 16); }
        mbar_init(sb + B_RESUME, 2);
        mbar_init(sb + B_KVFULL, 1); mbar_init(sb + B_KVFULL + 8, 1);
        mbar_init(sb + B_GO, 1); mbar_init(sb + B_KVGO, 1); mbar_init(sb + B_KVGO + 8, 1); mbar_init(sb + B_K, 1); mbar_init(sb + B_V, 1); mbar_init(sb + B_PERS, 8); mbar_init(sb + B_INIT, 8);
        mbar_init(sb + B_WO, 8);
        for (int i = 0; i < 2; i++) { mbar_init(sb + B_SFULL + i * 8, 4); mbar_init(sb + B_SFREE + i * 8, 1); }
        mbar_init(sb + B_RELA, 1); mbar_init(sb + B_RELB, 1);
        asm volatile("fence.mbarrier_init.release.cluster;" ::: "memory");
        mbar_expect(sb + B_K, pair < 16 ? 2048 : 2304); mbar_expect(sb + B_V, 2048);
    }
    cluster_sync();
    if (warp >= 8) {
        asm volatile("setmaxnreg.dec.sync.aligned.u32 24;");
        if (warp == 9 && pair < 64) {
            const char* src = (const char*)(rank ? P.Wo : P.Wq) + (size_t)(pair * 32 + lane) * 4096;
            l2_prefetch(src, 4096);
        }
        if (warp == 9 && pair < NCHAIN) pacer(P, sb, lane, pair, rank);
        if (warp >= 10 && lane == 0) store_warp(P, sb, warp - 10);
        if (warp == 8) {
            if (lane == 0) producer(P, sb, pair, rank, lds32(sb + S_EPOCH));
            __syncwarp();
            asm volatile("barrier.cluster.arrive.relaxed.aligned;\nbarrier.cluster.wait.aligned;" ::: "memory");
        }
    } else {
        asm volatile("setmaxnreg.inc.sync.aligned.u32 240;");
        Cons c;
        Pend d;
        if (pair < NCHAIN) {
            reset_state(c, d, sb, false);
#pragma unroll 1
            for (int i = 0; i < NPRE; i++) {
                PROF_ITEM(i)
                const int item = ITEM(ITEM_OFF(pair) + i);
                float acc[128];
                mainloop<256, true>(acc, P, c, d, T_KV);
                epi_kv(acc, c, d, (item >> 5) & 7, item & 31);
            }
            ISTAMP(4)
            drain<0, true>(P, c, d);
            bar_sync(1, 256);
            chain_load1(P, sb, pair, rank, warp, lane, false);
            drain<1, true>(P, c, d);
            staging_wait(c);
            PROF_ITEM(NPRE)
            bar_sync(1, 256);
            chain_load1(P, sb, pair, rank, warp, lane, true);
            const int h = (pair & 15) * 2 + rank;
            if (pair < 16) chain_role<0>(P, sb, h, warp, lane);
            else if (pair < 32) chain_role<1>(P, sb, h, warp, lane);
            else chain_role<2>(P, sb, h, warp, lane);
            fence_async_smem();
            bar_sync(1, 256);
            const uint32_t t2 = fresh_tid();
            if (t2 < 2) mbar_arrive_cluster(mapa(sb + B_RESUME, cluster_rank() ^ t2));
        } else if (pair >= NPAIR - 2) {
            const int ch = (pair - (NPAIR - 2)) * 512 + rank * 256 + tid;
            g_coef[ch] = ssm_coef(__bfloat162float(P.Lre[ch]), __bfloat162float(P.Lim[ch]), __bfloat162float(P.logdt[ch]));
            bar_sync(1, 256);
            if (tid == 0) red_release(&g_cnt(C_COEF));
        }
        reset_state(c, d, sb, true);
        for (int it = ITEM_OFF(c.pair) + (c.pair < NCHAIN ? NPRE + 1 : 0);; it++) {
            const bool last = it == ITEM_OFF(c.pair + 1);
            if (d.kind != PEND_NONE && (last || !bar_and(5 + c.wg, mbar_try(sb + B_FULL + c.p.stage * 8, c.p.phase)))) drain_all(P, c, d);
            if (last) break;
            const int item = ITEM(it), type = item >> 8, mb = (item >> 5) & 7, nb = item & 31;
            PROF_ITEM(it - ITEM_OFF(c.pair))
            if (type >= T_OPH) {
                float acc[64];
                mainloop<128>(acc, P, c, d, type);
                if (type == T_OPH) epi_oph(acc, c, d, mb, nb);
                else epi_a2_half<0>(acc, P, c, mb, nb * 128);
            } else {
                float acc[128];
                mainloop<256>(acc, P, c, d, type);
                if (type == T_KV) epi_kv(acc, c, d, mb, nb);
                else if (type == T_QA) epi_qa(acc, c, d, mb, nb);
                else if (type == T_OP) epi_op(acc, c, d, mb, nb);
                else if (type == T_A1) epi_a1(acc, P, c, d, mb, nb, c.atag);
                else { epi_a2_half<0>(acc, P, c, mb, nb * 256); epi_a2_half<1>(acc, P, c, mb, nb * 256); }
            }
        }
        staging_wait(c);
        staging_post(c, PEND_NONE, 0, 0, 0);
        cluster_sync();
        if (c.wg == 0 && c.wq == 0 && c.lane == 0 && atomicInc(&g_cnt(C_DONE), DBGF(32) ? 95 : NPAIR * 2 - 1) == (DBGF(32) ? 95 : NPAIR * 2 - 1)) atomicAdd(&g_cnt(C_EPOCH), 1);
    }
}

typedef CUresult (*EncodeFn)(CUtensorMap*, CUtensorMapDataType, cuuint32_t, void*, const cuuint64_t*, const cuuint64_t*, const cuuint32_t*, const cuuint32_t*,
                             CUtensorMapInterleave, CUtensorMapSwizzle, CUtensorMapL2promotion, CUtensorMapFloatOOBfill);
void encode(EncodeFn fn, CUtensorMap* m, const void* base, int rank, const uint64_t* dims, const uint64_t* strides, const uint32_t* box, CUtensorMapSwizzle swz = CU_TENSOR_MAP_SWIZZLE_128B) {
    cuuint64_t d[5], s[5]; cuuint32_t b[5], e[5];
    for (int i = 0; i < rank; i++) { d[i] = dims[i]; b[i] = box[i]; e[i] = 1; if (i) s[i - 1] = strides[i - 1]; }
    fn(m, CU_TENSOR_MAP_DATA_TYPE_BFLOAT16, rank, (void*)base, d, s, b, e, CU_TENSOR_MAP_INTERLEAVE_NONE, swz,
       CU_TENSOR_MAP_L2_PROMOTION_L2_256B, CU_TENSOR_MAP_FLOAT_OOB_FILL_NONE);
}
void map_kmajor(EncodeFn fn, CUtensorMap* m, const void* base, uint64_t rows, uint64_t cols, uint32_t box_rows) {
    const uint64_t d[2] = {cols, rows}, s[1] = {cols * 2}; const uint32_t b[2] = {64, box_rows};
    encode(fn, m, base, 2, d, s, b);
}
void map_mnmajor(EncodeFn fn, CUtensorMap* m, const void* base, uint64_t krows, uint64_t cols) {
    const uint64_t d[3] = {64, krows, cols / 64}, s[2] = {cols * 2, 128}; const uint32_t b[3] = {64, 64, 2};
    encode(fn, m, base, 3, d, s, b);
}

}

extern "C" void kernel_launch(void* const* d_in, const int* in_sizes, int n_in, void* d_out, int out_size) {
    static Params P;
    static EncodeFn fn = nullptr;
    if (!fn) {
        cudaDriverEntryPointQueryResult q;
        cudaGetDriverEntryPoint("cuTensorMapEncodeTiled", (void**)&fn, cudaEnableDefault, &q);
        cudaFuncSetAttribute(fused_kernel, cudaFuncAttributeMaxDynamicSharedMemorySize, S_TOTAL);
    }
    const bf16* in[15];
    for (int i = 0; i < 15; i++) in[i] = (const bf16*)d_in[i];
    void *kvo, *ht, *gm;
    cudaGetSymbolAddress(&gm, g_m);
    P.gm = (uint8_t*)(((uintptr_t)gm + 32767) & ~(uintptr_t)32767);
    cudaGetSymbolAddress(&kvo, g_kvo);
    cudaGetSymbolAddress(&ht, g_ht);
    map_kmajor(fn, &P.tm[M_BX], in[9], 2048, 1024, 128);
    map_mnmajor(fn, &P.tm[M_WQ], in[11], 1024, 4096);
    map_mnmajor(fn, &P.tm[M_WK], in[12], 1024, 4096);
    map_mnmajor(fn, &P.tm[M_WV], in[13], 1024, 4096);
    map_mnmajor(fn, &P.tm[M_WO], in[14], 4096, 1024);
    map_kmajor(fn, &P.tm[M_OA], kvo, 3 * 2048, 4096, 128);
    P.swap_ri = in[4] < in[3];
    {
        const bf16* lo = P.swap_ri ? in[4] : in[3];
        const uint64_t diff = (uint64_t)((const char*)(P.swap_ri ? in[3] : in[4]) - (const char*)lo);
        const uint64_t d[4] = {1024, 8, 2, 128}, s[3] = {2048, diff, 16384}; const uint32_t b[4] = {64, 8, 2, 8};
        encode(fn, &P.tm[M_AB], lo, 4, d, s, b);
    }
    {
        const uint64_t d[4] = {1024, 2, 4, 1024}, s[3] = {2048, 64 * 2048, 4096}; const uint32_t b[4] = {64, 2, 4, 16};
        encode(fn, &P.tm[M_AX], in[0], 4, d, s, b);
    }
    map_mnmajor(fn, &P.tm[M_HT], ht, 2048, 2048);
    map_kmajor(fn, &P.tm[M_CRE], in[5], 1024, 1024, 128);
    map_kmajor(fn, &P.tm[M_CIM], in[6], 1024, 1024, 128);
    map_kmajor(fn, &P.tm[M_KVO], kvo, 3 * 2048, 4096, 32);
    map_kmajor(fn, &P.tm[M_HTS], ht, 2048, 2048, 32);
    map_kmajor(fn, &P.tm[M_WOH], in[14], 4096, 1024, 64);
    map_kmajor(fn, &P.tm[M_CREH], in[5], 1024, 1024, 64);
    map_kmajor(fn, &P.tm[M_CIMH], in[6], 1024, 1024, 64);
    for (int i = 0; i < 3; i++) map_kmajor(fn, &P.tm[M_CQ + i], in[11 + i], 1024, 4096, 16);
    for (int e = 0; e < 2; e++) {
        const uint64_t d[4] = {1024, 2, 4, 256}, s[3] = {8 * 2048, 2 * 2048, 16 * 2048}; const uint32_t b[4] = {64, 2, 4, 8};
        encode(fn, &P.tm[M_CO + e], in[14] + e * 1024, 4, d, s, b);
    }
    P.Wq = in[11]; P.Wk = in[12]; P.Wv = in[13]; P.Wo = in[14]; P.mem0 = in[10];
    P.Lre = in[1]; P.Lim = in[2]; P.logdt = in[7]; P.Dskip = in[8];
    P.out = (float*)d_out;
    P.two26 = 1u << 26;
    P.ds = 400; P.da = 1088; P.db = 1288; P.dk = 300; P.tight = 200; P.extra = 0;
    for (int i = 0; i < (DBGF(32) ? 1 : 2); i++) {
        cudaLaunchConfig_t cfg = {};
        cfg.gridDim = dim3(i ? 36 : 96); cfg.blockDim = dim3(384); cfg.dynamicSmemBytes = S_TOTAL; cfg.stream = cudaStreamPerThread;
        cudaLaunchAttribute at[2];
        at[0].id = cudaLaunchAttributeClusterDimension; at[0].val.clusterDim.x = i ? 2 : 6; at[0].val.clusterDim.y = at[0].val.clusterDim.z = 1;
        at[1].id = cudaLaunchAttributeProgrammaticStreamSerialization; at[1].val.programmaticStreamSerializationAllowed = 1;
        cfg.attrs = at; cfg.numAttrs = 1 + i;
        cudaLaunchKernelEx(&cfg, fused_kernel, P);
    }
}
```

```cpp
#include <cuda_runtime.h>
#include <cuda_bf16.h>
#include <cuda.h>
#include <stdint.h>
#include <string.h>

typedef __nv_bfloat16 bf16;

namespace {

constexpr int SPIN_LIMIT = 1 << 22;
constexpr int NPAIR = 66;
constexpr int NCHAIN = 48;
enum { T_KV = 0, T_QA = 1, T_OP = 2, T_A1 = 3, T_A2 = 4, T_CHAIN = 5, T_OPH = 6, T_A2H = 7 };
enum { M_BX = 0, M_WQ, M_WK, M_WV, M_WO, M_OA, M_AB, M_AX, M_HT, M_CRE, M_CIM, M_KVO, M_HTS, M_WOH, M_CREH, M_CIMH, M_CQ, M_CK, M_CV, M_CO, M_CO1, M_COUNT };
enum { C_KV = 0, C_HT = 8, C_DONE = 24, C_EPOCH = 25, C_COEF = 26, C_FLAG = 32, C_O = 96 };

struct Params {
    CUtensorMap tm[M_COUNT];
    const bf16 *Wq, *Wk, *Wv, *Wo, *mem0, *Lre, *Lim, *logdt, *Dskip;
    float* out;
    uint8_t* gm;
    int swap_ri, zero;
    uint32_t two26;
    int ds, da, db, dk, dv, tight, extra;
#define DBGF(x) false
};

constexpr int NPRE = 1;
__constant__ uint16_t c_off[67] = {0, 4, 8, 12, 16, 20, 24, 28, 32, 37, 42, 47, 52, 57, 62, 67, 72, 77, 82, 87, 92, 97, 102, 107, 112, 117, 122, 127, 132, 136, 140, 144, 148, 152, 156, 160, 164, 168, 172, 176, 180, 184, 188, 192, 196, 200, 204, 209, 214, 234, 254, 274, 294, 314, 334, 354, 374, 393, 412, 430, 448, 466, 484, 502, 520, 540, 560};
__constant__ uint16_t c_items[640] = {
    0, 1280, 452, 704, 33, 1280, 453, 705, 3, 1280, 454, 706, 36, 1280, 455, 707, 6, 1280, 456, 736, 39, 1280, 457, 737,
    9, 1280, 458, 738, 42, 1280, 459, 739, 12, 1280, 460, 898, 1120, 45, 1280, 461, 899, 1121, 15, 1280, 462, 900, 1122, 48,
    1280, 463, 901, 1123, 18, 1280, 480, 902, 1152, 51, 1280, 481, 903, 1153, 21, 1280, 482, 928, 1154, 54, 1280, 483, 929, 1155,
    32, 1280, 484, 930, 1184, 2, 1280, 485, 931, 1185, 35, 1280, 486, 932, 1186, 5, 1280, 487, 933, 1187, 38, 1280, 488, 934,
    1216, 8, 1280, 489, 935, 1217, 41, 1280, 490, 960, 1218, 11, 1280, 491, 961, 1219, 44, 1280, 492, 962, 1248, 14, 1280, 493,
    963, 1249, 47, 1280, 494, 964, 1250, 17, 1280, 495, 965, 1251, 50, 1280, 768, 546, 20, 1280, 769, 547, 53, 1280, 770, 576,
    23, 1280, 771, 577, 1, 1280, 772, 578, 34, 1280, 773, 579, 4, 1280, 774, 608, 37, 1280, 775, 609, 7, 1280, 800, 610,
    40, 1280, 801, 611, 10, 1280, 802, 640, 43, 1280, 803, 641, 13, 1280, 804, 642, 46, 1280, 805, 643, 16, 1280, 806, 672,
    49, 1280, 807, 673, 19, 1280, 832, 674, 52, 1280, 833, 675, 22, 1280, 834, 896, 1026, 55, 1280, 835, 897, 1027, 24, 66,
    84, 102, 256, 124, 288, 144, 162, 180, 198, 208, 226, 244, 334, 384, 418, 836, 966, 1056, 56, 67, 85, 103, 257, 125,
    289, 145, 163, 181, 199, 209, 227, 245, 335, 385, 419, 837, 967, 1057, 25, 68, 86, 104, 258, 126, 290, 146, 164, 182,
    200, 210, 228, 246, 352, 386, 420, 838, 992, 1058, 57, 69, 87, 105, 259, 127, 291, 147, 165, 183, 201, 211, 229, 247,
    353, 387, 421, 839, 993, 1059, 26, 70, 88, 106, 260, 128, 292, 148, 166, 184, 202, 212, 230, 248, 354, 388, 422, 864,
    994, 1088, 58, 71, 89, 107, 261, 129, 293, 149, 167, 185, 203, 213, 231, 249, 355, 389, 423, 865, 995, 1089, 27, 72,
    90, 108, 262, 130, 294, 150, 168, 186, 204, 214, 232, 250, 356, 390, 424, 866, 996, 1090, 59, 73, 91, 109, 263, 131,
    295, 151, 169, 187, 205, 215, 233, 251, 357, 391, 425, 867, 997, 1091, 28, 74, 92, 110, 264, 132, 296, 152, 170, 188,
    320, 218, 236, 254, 360, 394, 428, 870, 1024, 60, 75, 93, 111, 265, 133, 297, 153, 171, 189, 321, 219, 237, 255, 361,
    395, 429, 871, 1025, 29, 76, 94, 112, 266, 134, 298, 154, 172, 190, 322, 220, 238, 328, 362, 396, 430, 512, 61, 77,
    95, 113, 267, 135, 299, 155, 173, 191, 323, 221, 239, 329, 363, 397, 431, 513, 30, 78, 96, 114, 268, 136, 300, 156,
    174, 192, 324, 222, 240, 330, 364, 398, 448, 514, 62, 79, 97, 115, 269, 137, 301, 157, 175, 193, 325, 223, 241, 331,
    365, 399, 449, 515, 31, 80, 98, 116, 270, 138, 302, 158, 176, 194, 326, 224, 242, 332, 366, 416, 450, 544, 63, 81,
    99, 117, 271, 139, 303, 159, 177, 195, 327, 225, 243, 333, 367, 417, 451, 545, 64, 82, 100, 118, 120, 122, 140, 142,
    160, 178, 196, 206, 216, 234, 252, 358, 392, 426, 868, 998, 65, 83, 101, 119, 121, 123, 141, 143, 161, 179, 197, 207,
    217, 235, 253, 359, 393, 427, 869, 999,
};
#define ITEM_OFF(p) c_off[p]
#define ITEM(i) c_items[i]

__device__ __align__(1024) bf16 g_kvo[3 * 2048 * 4096];
__device__ __align__(1024) bf16 g_ht[2048 * 2048];
__device__ __align__(1024) uint8_t g_m[9 * 32768];
__device__ __align__(1024) uint8_t g_f[8 * 49152];
__device__ __align__(1024) uint32_t g_km[64 * 32 * 512];
__device__ __align__(1024) uint32_t g_vmt[64 * 32 * 512];
__device__ __align__(1024) float2 g_agg[8 * 1024];
__device__ __align__(1024) float4 g_coef[1024];
__device__ __align__(1024) uint32_t g_cntl[128 * 32];
#define g_cnt(i) g_cntl[(i) * 32]
__device__ __align__(1024) uint32_t g_hint[6144 + 96 * 32];
#define PROF(i)
#define GT_EDGE(o)
constexpr int M_SLOT = 32768, F_SLOT = 49152;

constexpr int STAGE = 49152, NSTAGE = 4;
constexpr int S_STG = NSTAGE * STAGE;
constexpr int S_BAR = S_STG + 32768;
constexpr int B_FULL = S_BAR, B_EMPTY = S_BAR + 32, B_RESUME = S_BAR + 64, B_KVFULL = S_BAR + 72, B_GO = S_BAR + 88, B_K = S_BAR + 96, B_PERS = S_BAR + 104, B_INIT = S_BAR + 112, B_RELA = S_BAR + 120, B_V = S_BAR + 128, B_WO = S_BAR + 136,
              B_SFULL = S_BAR + 144, B_SFREE = S_BAR + 160, S_DESC = S_BAR + 176, S_EPOCH = S_BAR + 208, B_RELB = S_BAR + 216, B_KVGO = S_BAR + 224, S_DEP = S_BAR + 240, S_CUR = S_BAR + 244;
constexpr int S_COEF = S_BAR + 256 + 512, S_TOTAL = S_COEF + 1024;
constexpr int S_W1 = 0;
constexpr int S_O = 24 * 4096, S_VL = S_O + 2048, S_MX = 25 * 4096, S_SC = S_MX + 64, S_SUM = S_MX + 128;
constexpr int S_KL = 26 * 4096;
constexpr int S_W2 = 27 * 4096;
constexpr int S_KV = S_W2 + 65536;
constexpr int S_P1 = S_W2 + 98304;
constexpr int S_QX = S_P1 + 16384;
constexpr int S_SX = S_QX + 2048;
static_assert(S_SX + 1280 <= S_BAR, "chain smem overlaps barriers");
constexpr int NR = 40, NS = 64 - NR;

__device__ __forceinline__ uint32_t logical_cta(uint32_t b) {
    const uint32_t c = b / 6, r = b - c * 6;
    return gridDim.x != 96 ? 96 + b : ((r >> 1) + (c >= 8) + (c >= 15)) % 3 * 32 + c * 2 + (r & 1);
}
__device__ __forceinline__ uint32_t cluster_rank() { uint32_t r; asm("mov.u32 %0, %%cluster_ctarank;" : "=r"(r)); return r; }
__device__ __forceinline__ uint16_t pair_mask() { return (uint16_t)(3u << (cluster_rank() & 6)); }
__device__ __forceinline__ void spin_fault() { asm volatile("st.global.u32 [%0], 0;" ::"l"(0ull) : "memory"); }
__device__ __forceinline__ uint32_t smem_u32(const void* p) { return (uint32_t)__cvta_generic_to_shared(p); }
__device__ __forceinline__ uint32_t opq(uint32_t x, int lane) { return __shfl_sync(0xffffffffu, x, lane); }
__device__ __forceinline__ uint32_t mapa(uint32_t a, uint32_t r) { uint32_t d; asm volatile("mapa.shared::cluster.u32 %0, %1, %2;" : "=r"(d) : "r"(a), "r"(r)); return d; }
__device__ __forceinline__ void mma16816(float* d, uint32_t a0, uint32_t a1, uint32_t a2, uint32_t a3, uint32_t b0, uint32_t b1) {
    asm("mma.sync.aligned.m16n8k16.row.col.f32.bf16.bf16.f32 {%0,%1,%2,%3}, {%4,%5,%6,%7}, {%8,%9}, {%0,%1,%2,%3};"
        : "+f"(d[0]), "+f"(d[1]), "+f"(d[2]), "+f"(d[3]) : "r"(a0), "r"(a1), "r"(a2), "r"(a3), "r"(b0), "r"(b1));
}
__device__ __forceinline__ void mma1688(float* d, uint32_t a0, uint32_t a1, uint32_t b0) {
    asm("mma.sync.aligned.m16n8k8.row.col.f32.bf16.bf16.f32 {%0,%1,%2,%3}, {%4,%5}, {%6}, {%0,%1,%2,%3};"
        : "+f"(d[0]), "+f"(d[1]), "+f"(d[2]), "+f"(d[3]) : "r"(a0), "r"(a1), "r"(b0));
}
__device__ __forceinline__ void ldsm4(uint32_t* r, uint32_t a) {
    asm volatile("ldmatrix.sync.aligned.m8n8.x4.shared.b16 {%0,%1,%2,%3}, [%4];" : "=r"(r[0]), "=r"(r[1]), "=r"(r[2]), "=r"(r[3]) : "r"(a));
}
__device__ __forceinline__ void ldsm4t(uint32_t* r, uint32_t a) {
    asm volatile("ldmatrix.sync.aligned.m8n8.x4.trans.shared.b16 {%0,%1,%2,%3}, [%4];" : "=r"(r[0]), "=r"(r[1]), "=r"(r[2]), "=r"(r[3]) : "r"(a));
}
__device__ __forceinline__ void stsm4(uint32_t a, uint32_t r0, uint32_t r1, uint32_t r2, uint32_t r3) {
    asm volatile("stmatrix.sync.aligned.m8n8.x4.shared.b16 [%0], {%1,%2,%3,%4};" ::"r"(a), "r"(r0), "r"(r1), "r"(r2), "r"(r3) : "memory");
}
__device__ __forceinline__ void stsm4t(uint32_t a, uint32_t r0, uint32_t r1, uint32_t r2, uint32_t r3) {
    asm volatile("stmatrix.sync.aligned.m8n8.x4.trans.shared.b16 [%0], {%1,%2,%3,%4};" ::"r"(a), "r"(r0), "r"(r1), "r"(r2), "r"(r3) : "memory");
}
__device__ __forceinline__ uint32_t pack2(float lo, float hi) { uint32_t d; asm("cvt.rn.bf16x2.f32 %0, %1, %2;" : "=r"(d) : "f"(hi), "f"(lo)); return d; }
__device__ __forceinline__ float bf_lo(uint32_t u) { return __uint_as_float(u << 16); }
__device__ __forceinline__ float bf_hi(uint32_t u) { return __uint_as_float(u & 0xffff0000u); }
__device__ __forceinline__ uint32_t hmul2(uint32_t a, uint32_t b) { uint32_t d; asm("mul.rn.bf16x2 %0, %1, %2;" : "=r"(d) : "r"(a), "r"(b)); return d; }
__device__ __forceinline__ float ex2(float x) { float y; asm("ex2.approx.ftz.f32 %0, %1;" : "=f"(y) : "f"(x)); return y; }
__device__ __forceinline__ float rcp(float x) { float y; asm("rcp.approx.ftz.f32 %0, %1;" : "=f"(y) : "f"(x)); return y; }
__device__ __forceinline__ void st_relaxed4(const void* p, uint32_t a, uint32_t b, uint32_t c, uint32_t d) {
    asm volatile("{\n.reg .b128 t;\nmov.b128 t, {%1,%2,%3,%4};\nst.relaxed.gpu.global.b128 [%0], t;\n}" ::"l"(p), "r"(a), "r"(b), "r"(c), "r"(d) : "memory");
}
__device__ __forceinline__ void st_relaxed2(const void* p, uint32_t a, uint32_t b) {
    asm volatile("{\n.reg .b64 t;\nmov.b64 t, {%1,%2};\nst.relaxed.gpu.global.b64 [%0], t;\n}" ::"l"(p), "r"(a), "r"(b) : "memory");
}
__device__ __forceinline__ void ld_relaxed2_if(uint32_t& a, uint32_t& b, const void* p, bool on) {
    asm volatile("{\n.reg .pred P;\n.reg .b64 t;\nsetp.ne.u32 P, %3, 0;\nmov.b64 t, {%0,%1};\n@P ld.relaxed.gpu.global.b64 t, [%2];\nmov.b64 {%0,%1}, t;\n}" : "+r"(a), "+r"(b) : "l"(p), "r"((uint32_t)on) : "memory");
}
__device__ __forceinline__ uint32_t ld_relaxed1(const void* p) { uint32_t v; asm volatile("ld.relaxed.gpu.global.u32 %0, [%1];" : "=r"(v) : "l"(p) : "memory"); return v; }
__device__ __forceinline__ void st_relaxed1(const void* p, uint32_t v) { asm volatile("st.relaxed.gpu.global.u32 [%0], %1;" ::"l"(p), "r"(v) : "memory"); }
__device__ __forceinline__ uint32_t ld_acquire(const void* p) { uint32_t v; asm volatile("ld.acquire.gpu.global.u32 %0, [%1];" : "=r"(v) : "l"(p) : "memory"); return v; }
__device__ __forceinline__ void red_release(void* p) { asm volatile("red.release.gpu.global.add.u32 [%0], 1;" ::"l"(p) : "memory"); }
__device__ __forceinline__ void st_stream2(float* p, float a, float b) { asm volatile("st.global.cs.v2.f32 [%0], {%1, %2};" ::"l"(p), "f"(a), "f"(b) : "memory"); }
__device__ __forceinline__ void fence_gpu() { asm volatile("fence.acq_rel.gpu;" ::: "memory"); }
__device__ __forceinline__ void fence_async() { asm volatile("fence.proxy.async;" ::: "memory"); }
__device__ __forceinline__ void fence_async_smem() { asm volatile("fence.proxy.async.shared::cta;" ::: "memory"); }
__device__ __forceinline__ void wait_count(const uint32_t* p, uint32_t target) {
    int n = 0;
    while ((int32_t)(ld_acquire(p) - target) < 0) { __nanosleep(200); if (++n > SPIN_LIMIT) spin_fault(); }
}
__device__ __forceinline__ void bar_sync(int id, int n) { asm volatile("bar.sync %0, %1;" ::"r"(id), "r"(n) : "memory"); }
__device__ __forceinline__ void bar_arrive(int id, int n) { asm volatile("bar.arrive %0, %1;" ::"r"(id), "r"(n) : "memory"); }
__device__ __forceinline__ bool bar_and(int id, bool v) {
    uint32_t r;
    asm volatile("{\n.reg .pred P, Q;\nsetp.ne.u32 Q, %2, 0;\nbar.red.and.pred P, %1, 128, Q;\nselp.u32 %0, 1, 0, P;\n}" : "=r"(r) : "r"(id), "r"((uint32_t)v) : "memory");
    return r;
}
__device__ __forceinline__ void lds128(uint32_t* v, uint32_t a) { asm volatile("ld.shared.v4.b32 {%0,%1,%2,%3}, [%4];" : "=r"(v[0]), "=r"(v[1]), "=r"(v[2]), "=r"(v[3]) : "r"(a) : "memory"); }
__device__ __forceinline__ uint32_t lds32(uint32_t a) { uint32_t v; asm volatile("ld.shared.b32 %0, [%1];" : "=r"(v) : "r"(a) : "memory"); return v; }
__device__ __forceinline__ void lds64f(float* v, uint32_t a) { asm volatile("ld.shared.v2.f32 {%0,%1}, [%2];" : "=f"(v[0]), "=f"(v[1]) : "r"(a) : "memory"); }
__device__ __forceinline__ void sts128(uint32_t a, const uint32_t* v) { asm volatile("st.shared.v4.b32 [%0], {%1,%2,%3,%4};" ::"r"(a), "r"(v[0]), "r"(v[1]), "r"(v[2]), "r"(v[3]) : "memory"); }
__device__ __forceinline__ void sts64(uint32_t a, uint32_t x, uint32_t y) { asm volatile("st.shared.v2.b32 [%0], {%1,%2};" ::"r"(a), "r"(x), "r"(y) : "memory"); }
__device__ __forceinline__ void sts32(uint32_t a, uint32_t x) { asm volatile("st.shared.b32 [%0], %1;" ::"r"(a), "r"(x) : "memory"); }
__device__ __forceinline__ bool mbar_try(uint32_t b, uint32_t par) {
    uint32_t ok;
    asm volatile("{\n.reg .pred P;\nmbarrier.try_wait.parity.shared::cta.b64 P, [%1], %2;\nselp.u32 %0, 1, 0, P;\n}" : "=r"(ok) : "r"(b), "r"(par) : "memory");
    return ok;
}
__device__ __forceinline__ bool mbar_test(uint32_t b, uint32_t par) {
    uint32_t ok;
    asm volatile("{\n.reg .pred P;\nmbarrier.test_wait.parity.shared::cta.b64 P, [%1], %2;\nselp.u32 %0, 1, 0, P;\n}" : "=r"(ok) : "r"(b), "r"(par) : "memory");
    return ok;
}
__device__ __forceinline__ void mbar_wait(uint32_t b, uint32_t par) { int n = 0; while (!mbar_try(b, par)) { if (++n > SPIN_LIMIT) spin_fault(); } }
__device__ __forceinline__ void mbar_init(uint32_t b, uint32_t n) { asm volatile("mbarrier.init.shared::cta.b64 [%0], %1;" ::"r"(b), "r"(n) : "memory"); }
__device__ __forceinline__ void mbar_expect(uint32_t b, uint32_t bytes) { asm volatile("mbarrier.arrive.expect_tx.shared::cta.b64 _, [%0], %1;" ::"r"(b), "r"(bytes) : "memory"); }
__device__ __forceinline__ void mbar_arrive(uint32_t b) { asm volatile("mbarrier.arrive.shared::cta.b64 _, [%0];" ::"r"(b) : "memory"); }
__device__ __forceinline__ void mbar_arrive_cluster(uint32_t b) { asm volatile("mbarrier.arrive.shared::cluster.b64 _, [%0];" ::"r"(b) : "memory"); }
__device__ __forceinline__ void st_async1(uint32_t a, uint32_t x, uint32_t bar) {
    asm volatile("st.async.weak.shared::cluster.mbarrier::complete_tx::bytes.b32 [%0], %1, [%2];" ::"r"(a), "r"(x), "r"(bar) : "memory");
}
__device__ __forceinline__ void st_async2(uint32_t a, uint32_t x, uint32_t y, uint32_t bar) {
    asm volatile("st.async.weak.shared::cluster.mbarrier::complete_tx::bytes.v2.b32 [%0], {%1,%2}, [%3];" ::"r"(a), "r"(x), "r"(y), "r"(bar) : "memory");
}
__device__ __forceinline__ void cluster_sync() { asm volatile("barrier.cluster.arrive.aligned;\nbarrier.cluster.wait.aligned;" ::: "memory"); }
__device__ __forceinline__ void tma2d(uint32_t dst, const CUtensorMap* m, int c0, int c1, uint32_t bar) {
    asm volatile("cp.async.bulk.tensor.2d.shared::cluster.global.mbarrier::complete_tx::bytes [%0], [%1, {%2, %3}], [%4];" ::"r"(dst), "l"(m), "r"(c0), "r"(c1), "r"(bar) : "memory");
}
__device__ __forceinline__ void tma2d_mc(uint32_t dst, const CUtensorMap* m, int c0, int c1, uint32_t bar) {
    asm volatile("cp.async.bulk.tensor.2d.shared::cluster.global.mbarrier::complete_tx::bytes.multicast::cluster [%0], [%1, {%2, %3}], [%4], %5;" ::"r"(dst), "l"(m), "r"(c0), "r"(c1), "r"(bar), "h"(pair_mask()) : "memory");
}
__device__ __forceinline__ void tma3d(uint32_t dst, const CUtensorMap* m, int c0, int c1, int c2, uint32_t bar) {
    asm volatile("cp.async.bulk.tensor.3d.shared::cluster.global.mbarrier::complete_tx::bytes [%0], [%1, {%2, %3, %4}], [%5];" ::"r"(dst), "l"(m), "r"(c0), "r"(c1), "r"(c2), "r"(bar) : "memory");
}
__device__ __forceinline__ void tma3d_mc(uint32_t dst, const CUtensorMap* m, int c0, int c1, int c2, uint32_t bar) {
    asm volatile("cp.async.bulk.tensor.3d.shared::cluster.global.mbarrier::complete_tx::bytes.multicast::cluster [%0], [%1, {%2, %3, %4}], [%5], %6;" ::"r"(dst), "l"(m), "r"(c0), "r"(c1), "r"(c2), "r"(bar), "h"(pair_mask()) : "memory");
}
__device__ __forceinline__ void tma4d(uint32_t dst, const CUtensorMap* m, int c0, int c3, uint32_t bar) {
    asm volatile("cp.async.bulk.tensor.4d.shared::cluster.global.mbarrier::complete_tx::bytes [%0], [%1, {%2, 0, 0, %3}], [%4];" ::"r"(dst), "l"(m), "r"(c0), "r"(c3), "r"(bar) : "memory");
}
__device__ __forceinline__ void tma4d_mc(uint32_t dst, const CUtensorMap* m, int c0, int c3, uint32_t bar) {
    asm volatile("cp.async.bulk.tensor.4d.shared::cluster.global.mbarrier::complete_tx::bytes.multicast::cluster [%0], [%1, {%2, 0, 0, %3}], [%4], %5;" ::"r"(dst), "l"(m), "r"(c0), "r"(c3), "r"(bar), "h"(pair_mask()) : "memory");
}
__device__ __forceinline__ void tma_prefetch2d(const CUtensorMap* m, int c0, int c1) {
    asm volatile("cp.async.bulk.prefetch.tensor.2d.L2.global [%0, {%1, %2}];" ::"l"(m), "r"(c0), "r"(c1) : "memory");
}
__device__ __forceinline__ void map_prefetch(const CUtensorMap* m) { asm volatile("prefetch.tensormap [%0];" ::"l"(m) : "memory"); }
__device__ __forceinline__ void l2_prefetch(const void* src, uint32_t bytes) { asm volatile("cp.async.bulk.prefetch.L2.global [%0], %1;" ::"l"(src), "r"(bytes) : "memory"); }
__device__ __forceinline__ void bulk_g2s(uint32_t dst, const void* src, uint32_t bytes, uint32_t bar) {
    asm volatile("cp.async.bulk.shared::cluster.global.mbarrier::complete_tx::bytes [%0], [%1], %2, [%3];" ::"r"(dst), "l"(src), "r"(bytes), "r"(bar) : "memory");
}
__device__ __forceinline__ void tma_store2d(const CUtensorMap* m, int c0, int c1, uint32_t src) {
    asm volatile("cp.async.bulk.tensor.2d.global.shared::cta.bulk_group [%0, {%1, %2}], [%3];" ::"l"(m), "r"(c0), "r"(c1), "r"(src) : "memory");
}
__device__ __forceinline__ void bulk_commit() { asm volatile("cp.async.bulk.commit_group;" ::: "memory"); }
__device__ __forceinline__ void bulk_wait_read() { asm volatile("cp.async.bulk.wait_group.read 0;" ::: "memory"); }
__device__ __forceinline__ void bulk_wait_all() { asm volatile("cp.async.bulk.wait_group 0;" ::: "memory"); }
__device__ __forceinline__ uint64_t mkdesc(uint32_t addr, uint32_t lbo, uint32_t sbo, uint32_t swz) {
    return (uint64_t)((addr & 0x3FFFF) >> 4) | ((uint64_t)(lbo >> 4) << 16) | ((uint64_t)(sbo >> 4) << 32) | ((uint64_t)swz << 62);
}
__device__ __forceinline__ void wg_fence() { asm volatile("wgmma.fence.sync.aligned;" ::: "memory"); }
__device__ __forceinline__ void wg_commit() { asm volatile("wgmma.commit_group.sync.aligned;" ::: "memory"); }
template <int N> __device__ __forceinline__ void wg_wait() { asm volatile("wgmma.wait_group.sync.aligned %0;" ::"n"(N) : "memory"); }
template <typename T> __device__ __forceinline__ void pin_ptr(T*& p) { asm volatile("" : "+l"(p)); }
template <int N> __device__ __forceinline__ void pin(uint32_t* d) {
#pragma unroll
    for (int i = 0; i < N; i++) asm volatile("" : "+r"(d[i])::"memory");
}
template <int N> __device__ __forceinline__ void pin(float* d) {
#pragma unroll
    for (int i = 0; i < N; i++) asm volatile("" : "+f"(d[i])::"memory");
}

template <int TA, int TB>
__device__ __forceinline__ void wgmma_ss256(float* d, uint64_t da, uint64_t db) {
    asm volatile("wgmma.mma_async.sync.aligned.m64n256k16.f32.bf16.bf16 "
        "{%0, %1, %2, %3, %4, %5, %6, %7, %8, %9, %10, %11, %12, %13, %14, %15, %16, %17, %18, %19, %20, %21, %22, %23, %24, %25, %26, %27, %28, %29, %30, %31, %32, %33, %34, %35, %36, %37, %38, %39, %40, %41, %42, %43, %44, %45, %46, %47, %48, %49, %50, %51, %52, %53, %54, %55, %56, %57, %58, %59, %60, %61, %62, %63, %64, %65, %66, %67, %68, %69, %70, %71, %72, %73, %74, %75, %76, %77, %78, %79, %80, %81, %82, %83, %84, %85, %86, %87, %88, %89, %90, %91, %92, %93, %94, %95, %96, %97, %98, %99, %100, %101, %102, %103, %104, %105, %106, %107, %108, %109, %110, %111, %112, %113, %114, %115, %116, %117, %118, %119, %120, %121, %122, %123, %124, %125, %126, %127}, %128, %129, 1, 1, 1, %130, %131;"
        : "+f"(d[0]), "+f"(d[1]), "+f"(d[2]), "+f"(d[3]), "+f"(d[4]), "+f"(d[5]), "+f"(d[6]), "+f"(d[7]), "+f"(d[8]), "+f"(d[9]), "+f"(d[10]), "+f"(d[11]), "+f"(d[12]), "+f"(d[13]), "+f"(d[14]), "+f"(d[15]), "+f"(d[16]), "+f"(d[17]), "+f"(d[18]), "+f"(d[19]), "+f"(d[20]), "+f"(d[21]), "+f"(d[22]), "+f"(d[23]), "+f"(d[24]), "+f"(d[25]), "+f"(d[26]), "+f"(d[27]), "+f"(d[28]), "+f"(d[29]), "+f"(d[30]), "+f"(d[31]), "+f"(d[32]), "+f"(d[33]), "+f"(d[34]), "+f"(d[35]), "+f"(d[36]), "+f"(d[37]), "+f"(d[38]), "+f"(d[39]), "+f"(d[40]), "+f"(d[41]), "+f"(d[42]), "+f"(d[43]), "+f"(d[44]), "+f"(d[45]), "+f"(d[46]), "+f"(d[47]), "+f"(d[48]), "+f"(d[49]), "+f"(d[50]), "+f"(d[51]), "+f"(d[52]), "+f"(d[53]), "+f"(d[54]), "+f"(d[55]), "+f"(d[56]), "+f"(d[57]), "+f"(d[58]), "+f"(d[59]), "+f"(d[60]), "+f"(d[61]), "+f"(d[62]), "+f"(d[63]), "+f"(d[64]), "+f"(d[65]), "+f"(d[66]), "+f"(d[67]), "+f"(d[68]), "+f"(d[69]), "+f"(d[70]), "+f"(d[71]), "+f"(d[72]), "+f"(d[73]), "+f"(d[74]), "+f"(d[75]), "+f"(d[76]), "+f"(d[77]), "+f"(d[78]), "+f"(d[79]), "+f"(d[80]), "+f"(d[81]), "+f"(d[82]), "+f"(d[83]), "+f"(d[84]), "+f"(d[85]), "+f"(d[86]), "+f"(d[87]), "+f"(d[88]), "+f"(d[89]), "+f"(d[90]), "+f"(d[91]), "+f"(d[92]), "+f"(d[93]), "+f"(d[94]), "+f"(d[95]), "+f"(d[96]), "+f"(d[97]), "+f"(d[98]), "+f"(d[99]), "+f"(d[100]), "+f"(d[101]), "+f"(d[102]), "+f"(d[103]), "+f"(d[104]), "+f"(d[105]), "+f"(d[106]), "+f"(d[107]), "+f"(d[108]), "+f"(d[109]), "+f"(d[110]), "+f"(d[111]), "+f"(d[112]), "+f"(d[113]), "+f"(d[114]), "+f"(d[115]), "+f"(d[116]), "+f"(d[117]), "+f"(d[118]), "+f"(d[119]), "+f"(d[120]), "+f"(d[121]), "+f"(d[122]), "+f"(d[123]), "+f"(d[124]), "+f"(d[125]), "+f"(d[126]), "+f"(d[127])
        : "l"(da), "l"(db), "n"(TA), "n"(TB));
}
template <int TA, int TB>
__device__ __forceinline__ void wgmma_ss256_first(float* d, uint64_t da, uint64_t db) {
    asm volatile("wgmma.mma_async.sync.aligned.m64n256k16.f32.bf16.bf16 "
        "{%0, %1, %2, %3, %4, %5, %6, %7, %8, %9, %10, %11, %12, %13, %14, %15, %16, %17, %18, %19, %20, %21, %22, %23, %24, %25, %26, %27, %28, %29, %30, %31, %32, %33, %34, %35, %36, %37, %38, %39, %40, %41, %42, %43, %44, %45, %46, %47, %48, %49, %50, %51, %52, %53, %54, %55, %56, %57, %58, %59, %60, %61, %62, %63, %64, %65, %66, %67, %68, %69, %70, %71, %72, %73, %74, %75, %76, %77, %78, %79, %80, %81, %82, %83, %84, %85, %86, %87, %88, %89, %90, %91, %92, %93, %94, %95, %96, %97, %98, %99, %100, %101, %102, %103, %104, %105, %106, %107, %108, %109, %110, %111, %112, %113, %114, %115, %116, %117, %118, %119, %120, %121, %122, %123, %124, %125, %126, %127}, %128, %129, 0, 1, 1, %130, %131;"
        : "=f"(d[0]), "=f"(d[1]), "=f"(d[2]), "=f"(d[3]), "=f"(d[4]), "=f"(d[5]), "=f"(d[6]), "=f"(d[7]), "=f"(d[8]), "=f"(d[9]), "=f"(d[10]), "=f"(d[11]), "=f"(d[12]), "=f"(d[13]), "=f"(d[14]), "=f"(d[15]), "=f"(d[16]), "=f"(d[17]), "=f"(d[18]), "=f"(d[19]), "=f"(d[20]), "=f"(d[21]), "=f"(d[22]), "=f"(d[23]), "=f"(d[24]), "=f"(d[25]), "=f"(d[26]), "=f"(d[27]), "=f"(d[28]), "=f"(d[29]), "=f"(d[30]), "=f"(d[31]), "=f"(d[32]), "=f"(d[33]), "=f"(d[34]), "=f"(d[35]), "=f"(d[36]), "=f"(d[37]), "=f"(d[38]), "=f"(d[39]), "=f"(d[40]), "=f"(d[41]), "=f"(d[42]), "=f"(d[43]), "=f"(d[44]), "=f"(d[45]), "=f"(d[46]), "=f"(d[47]), "=f"(d[48]), "=f"(d[49]), "=f"(d[50]), "=f"(d[51]), "=f"(d[52]), "=f"(d[53]), "=f"(d[54]), "=f"(d[55]), "=f"(d[56]), "=f"(d[57]), "=f"(d[58]), "=f"(d[59]), "=f"(d[60]), "=f"(d[61]), "=f"(d[62]), "=f"(d[63]), "=f"(d[64]), "=f"(d[65]), "=f"(d[66]), "=f"(d[67]), "=f"(d[68]), "=f"(d[69]), "=f"(d[70]), "=f"(d[71]), "=f"(d[72]), "=f"(d[73]), "=f"(d[74]), "=f"(d[75]), "=f"(d[76]), "=f"(d[77]), "=f"(d[78]), "=f"(d[79]), "=f"(d[80]), "=f"(d[81]), "=f"(d[82]), "=f"(d[83]), "=f"(d[84]), "=f"(d[85]), "=f"(d[86]), "=f"(d[87]), "=f"(d[88]), "=f"(d[89]), "=f"(d[90]), "=f"(d[91]), "=f"(d[92]), "=f"(d[93]), "=f"(d[94]), "=f"(d[95]), "=f"(d[96]), "=f"(d[97]), "=f"(d[98]), "=f"(d[99]), "=f"(d[100]), "=f"(d[101]), "=f"(d[102]), "=f"(d[103]), "=f"(d[104]), "=f"(d[105]), "=f"(d[106]), "=f"(d[107]), "=f"(d[108]), "=f"(d[109]), "=f"(d[110]), "=f"(d[111]), "=f"(d[112]), "=f"(d[113]), "=f"(d[114]), "=f"(d[115]), "=f"(d[116]), "=f"(d[117]), "=f"(d[118]), "=f"(d[119]), "=f"(d[120]), "=f"(d[121]), "=f"(d[122]), "=f"(d[123]), "=f"(d[124]), "=f"(d[125]), "=f"(d[126]), "=f"(d[127])
        : "l"(da), "l"(db), "n"(TA), "n"(TB));
}
template <int TA, int TB>
__device__ __forceinline__ void wgmma_ss128(float* d, uint64_t da, uint64_t db) {
    asm volatile("wgmma.mma_async.sync.aligned.m64n128k16.f32.bf16.bf16 "
        "{%0, %1, %2, %3, %4, %5, %6, %7, %8, %9, %10, %11, %12, %13, %14, %15, %16, %17, %18, %19, %20, %21, %22, %23, %24, %25, %26, %27, %28, %29, %30, %31, %32, %33, %34, %35, %36, %37, %38, %39, %40, %41, %42, %43, %44, %45, %46, %47, %48, %49, %50, %51, %52, %53, %54, %55, %56, %57, %58, %59, %60, %61, %62, %63}, %64, %65, 1, 1, 1, %66, %67;"
        : "+f"(d[0]), "+f"(d[1]), "+f"(d[2]), "+f"(d[3]), "+f"(d[4]), "+f"(d[5]), "+f"(d[6]), "+f"(d[7]), "+f"(d[8]), "+f"(d[9]), "+f"(d[10]), "+f"(d[11]), "+f"(d[12]), "+f"(d[13]), "+f"(d[14]), "+f"(d[15]), "+f"(d[16]), "+f"(d[17]), "+f"(d[18]), "+f"(d[19]), "+f"(d[20]), "+f"(d[21]), "+f"(d[22]), "+f"(d[23]), "+f"(d[24]), "+f"(d[25]), "+f"(d[26]), "+f"(d[27]), "+f"(d[28]), "+f"(d[29]), "+f"(d[30]), "+f"(d[31]), "+f"(d[32]), "+f"(d[33]), "+f"(d[34]), "+f"(d[35]), "+f"(d[36]), "+f"(d[37]), "+f"(d[38]), "+f"(d[39]), "+f"(d[40]), "+f"(d[41]), "+f"(d[42]), "+f"(d[43]), "+f"(d[44]), "+f"(d[45]), "+f"(d[46]), "+f"(d[47]), "+f"(d[48]), "+f"(d[49]), "+f"(d[50]), "+f"(d[51]), "+f"(d[52]), "+f"(d[53]), "+f"(d[54]), "+f"(d[55]), "+f"(d[56]), "+f"(d[57]), "+f"(d[58]), "+f"(d[59]), "+f"(d[60]), "+f"(d[61]), "+f"(d[62]), "+f"(d[63])
        : "l"(da), "l"(db), "n"(TA), "n"(TB));
}
template <int TA, int TB>
__device__ __forceinline__ void wgmma_ss128_first(float* d, uint64_t da, uint64_t db) {
    asm volatile("wgmma.mma_async.sync.aligned.m64n128k16.f32.bf16.bf16 "
        "{%0, %1, %2, %3, %4, %5, %6, %7, %8, %9, %10, %11, %12, %13, %14, %15, %16, %17, %18, %19, %20, %21, %22, %23, %24, %25, %26, %27, %28, %29, %30, %31, %32, %33, %34, %35, %36, %37, %38, %39, %40, %41, %42, %43, %44, %45, %46, %47, %48, %49, %50, %51, %52, %53, %54, %55, %56, %57, %58, %59, %60, %61, %62, %63}, %64, %65, 0, 1, 1, %66, %67;"
        : "=f"(d[0]), "=f"(d[1]), "=f"(d[2]), "=f"(d[3]), "=f"(d[4]), "=f"(d[5]), "=f"(d[6]), "=f"(d[7]), "=f"(d[8]), "=f"(d[9]), "=f"(d[10]), "=f"(d[11]), "=f"(d[12]), "=f"(d[13]), "=f"(d[14]), "=f"(d[15]), "=f"(d[16]), "=f"(d[17]), "=f"(d[18]), "=f"(d[19]), "=f"(d[20]), "=f"(d[21]), "=f"(d[22]), "=f"(d[23]), "=f"(d[24]), "=f"(d[25]), "=f"(d[26]), "=f"(d[27]), "=f"(d[28]), "=f"(d[29]), "=f"(d[30]), "=f"(d[31]), "=f"(d[32]), "=f"(d[33]), "=f"(d[34]), "=f"(d[35]), "=f"(d[36]), "=f"(d[37]), "=f"(d[38]), "=f"(d[39]), "=f"(d[40]), "=f"(d[41]), "=f"(d[42]), "=f"(d[43]), "=f"(d[44]), "=f"(d[45]), "=f"(d[46]), "=f"(d[47]), "=f"(d[48]), "=f"(d[49]), "=f"(d[50]), "=f"(d[51]), "=f"(d[52]), "=f"(d[53]), "=f"(d[54]), "=f"(d[55]), "=f"(d[56]), "=f"(d[57]), "=f"(d[58]), "=f"(d[59]), "=f"(d[60]), "=f"(d[61]), "=f"(d[62]), "=f"(d[63])
        : "l"(da), "l"(db), "n"(TA), "n"(TB));
}
template <int TB>
__device__ __forceinline__ void wgmma_rs128(float* d, const uint32_t* a, uint64_t db, uint32_t acc) {
    asm volatile("{\n.reg .pred P;\nsetp.ne.u32 P, %69, 0;\nwgmma.mma_async.sync.aligned.m64n128k16.f32.bf16.bf16 "
        "{%0, %1, %2, %3, %4, %5, %6, %7, %8, %9, %10, %11, %12, %13, %14, %15, %16, %17, %18, %19, %20, %21, %22, %23, %24, %25, %26, %27, %28, %29, %30, %31, %32, %33, %34, %35, %36, %37, %38, %39, %40, %41, %42, %43, %44, %45, %46, %47, %48, %49, %50, %51, %52, %53, %54, %55, %56, %57, %58, %59, %60, %61, %62, %63}, {%64, %65, %66, %67}, %68, P, 1, 1, %70;\n}"
        : "+f"(d[0]), "+f"(d[1]), "+f"(d[2]), "+f"(d[3]), "+f"(d[4]), "+f"(d[5]), "+f"(d[6]), "+f"(d[7]), "+f"(d[8]), "+f"(d[9]), "+f"(d[10]), "+f"(d[11]), "+f"(d[12]), "+f"(d[13]), "+f"(d[14]), "+f"(d[15]), "+f"(d[16]), "+f"(d[17]), "+f"(d[18]), "+f"(d[19]), "+f"(d[20]), "+f"(d[21]), "+f"(d[22]), "+f"(d[23]), "+f"(d[24]), "+f"(d[25]), "+f"(d[26]), "+f"(d[27]), "+f"(d[28]), "+f"(d[29]), "+f"(d[30]), "+f"(d[31]), "+f"(d[32]), "+f"(d[33]), "+f"(d[34]), "+f"(d[35]), "+f"(d[36]), "+f"(d[37]), "+f"(d[38]), "+f"(d[39]), "+f"(d[40]), "+f"(d[41]), "+f"(d[42]), "+f"(d[43]), "+f"(d[44]), "+f"(d[45]), "+f"(d[46]), "+f"(d[47]), "+f"(d[48]), "+f"(d[49]), "+f"(d[50]), "+f"(d[51]), "+f"(d[52]), "+f"(d[53]), "+f"(d[54]), "+f"(d[55]), "+f"(d[56]), "+f"(d[57]), "+f"(d[58]), "+f"(d[59]), "+f"(d[60]), "+f"(d[61]), "+f"(d[62]), "+f"(d[63])
        : "r"(a[0]), "r"(a[1]), "r"(a[2]), "r"(a[3]), "l"(db), "r"(acc), "n"(TB));
}
template <int TB>
__device__ __forceinline__ void wgmma_rs64(float* d, const uint32_t* a, uint64_t db, uint32_t acc) {
    asm volatile("{\n.reg .pred P;\nsetp.ne.u32 P, %37, 0;\nwgmma.mma_async.sync.aligned.m64n64k16.f32.bf16.bf16 "
        "{%0, %1, %2, %3, %4, %5, %6, %7, %8, %9, %10, %11, %12, %13, %14, %15, %16, %17, %18, %19, %20, %21, %22, %23, %24, %25, %26, %27, %28, %29, %30, %31}, {%32, %33, %34, %35}, %36, P, 1, 1, %38;\n}"
        : "+f"(d[0]), "+f"(d[1]), "+f"(d[2]), "+f"(d[3]), "+f"(d[4]), "+f"(d[5]), "+f"(d[6]), "+f"(d[7]), "+f"(d[8]), "+f"(d[9]), "+f"(d[10]), "+f"(d[11]), "+f"(d[12]), "+f"(d[13]), "+f"(d[14]), "+f"(d[15]), "+f"(d[16]), "+f"(d[17]), "+f"(d[18]), "+f"(d[19]), "+f"(d[20]), "+f"(d[21]), "+f"(d[22]), "+f"(d[23]), "+f"(d[24]), "+f"(d[25]), "+f"(d[26]), "+f"(d[27]), "+f"(d[28]), "+f"(d[29]), "+f"(d[30]), "+f"(d[31])
        : "r"(a[0]), "r"(a[1]), "r"(a[2]), "r"(a[3]), "l"(db), "r"(acc), "n"(TB));
}
template <int TB>
__device__ __forceinline__ void wgmma_rs16(float* d, const uint32_t* a, uint64_t db, uint32_t acc) {
    asm volatile("{\n.reg .pred P;\nsetp.ne.u32 P, %13, 0;\nwgmma.mma_async.sync.aligned.m64n16k16.f32.bf16.bf16 "
        "{%0, %1, %2, %3, %4, %5, %6, %7}, {%8, %9, %10, %11}, %12, P, 1, 1, %14;\n}"
        : "+f"(d[0]), "+f"(d[1]), "+f"(d[2]), "+f"(d[3]), "+f"(d[4]), "+f"(d[5]), "+f"(d[6]), "+f"(d[7])
        : "r"(a[0]), "r"(a[1]), "r"(a[2]), "r"(a[3]), "l"(db), "r"(acc), "n"(TB));
}

__device__ __forceinline__ uint32_t delay_loop(int n, uint32_t x0) {
    uint32_t z;
    asm volatile("{\n.reg .pred P;\n.reg .u32 c, x;\nmov.u32 c, %1;\nmov.u32 x, %2;\nDL: mad.lo.u32 x, x, 1664525, 1013904223;\nadd.u32 c, c, -1;\nsetp.gt.s32 P, c, 0;\n@P bra DL;\n"
                 "setp.eq.u32 P, x, 0x7fffffff;\nselp.u32 %0, 16, 0, P;\n}" : "=r"(z) : "r"(n), "r"(x0) : "memory");
    return z;
}
__device__ __forceinline__ uint32_t gtime() { uint32_t t; asm volatile("mov.u32 %0, %%globaltimer_lo;" : "=r"(t)); return t; }
__device__ __forceinline__ void stamp(int idx, uint32_t seq) { st_relaxed1(g_hint + idx, (gtime() & ~31u) | (seq & 31u)); }
__device__ __forceinline__ void wait_time(uint32_t t, uint32_t sb) { while ((int32_t)(gtime() - t) < (int32_t)delay_loop(2, sb)) {} }
template <int N, int STRIDE>
__device__ __forceinline__ uint32_t latest_stamp(const uint32_t* p, uint32_t seq, uint32_t ref, uint32_t sb, int tight, int extra) {
    int n = 0;
    while (true) {
        uint32_t bad = 0; int32_t m = INT32_MIN, l = INT32_MAX;
#pragma unroll
        for (int i = 0; i < N; i++) {
            const uint32_t v = ld_relaxed1(p + i * STRIDE);
            const int32_t d = (int32_t)((v & ~31u) - ref);
            bad |= (v ^ seq) & 31u; m = max(m, d); l = min(l, d);
        }
        if (__all_sync(0xffffffffu, bad == 0)) {
            m = __reduce_max_sync(0xffffffffu, m);
            return ref + m + (__any_sync(0xffffffffu, m - l > tight) ? extra : 0);
        }
        p += delay_loop(60, sb);
        if (++n > SPIN_LIMIT) spin_fault();
    }
}
__device__ __forceinline__ void release_at(uint32_t t, uint32_t sb, uint32_t bar, int lane) {
    wait_time(t, sb);
    if (lane == 0) mbar_arrive(sb + bar);
}
__host__ __device__ constexpr int frag_word(int u, int f) { return (u == 0 ? 0 : u < 3 ? 3 * u - 1 : u == 3 ? 14 : 3 * u - 4) + f; }
__host__ __device__ constexpr int word_col(int e) { return ((0x32FED987CBA65410ull >> (4 * e)) & 14) * 64 + ((0x32FED987CBA65410ull >> (4 * e)) & 1) * 8; }

constexpr uint32_t CLEAR_LO = 0xFE000000u, CLEAR_HI = 0x5A7FEFEFu;
__device__ __forceinline__ void clear_slot(const Params& P, int slot, int cta, int lane) {
    const int i = cta * 2 + (lane >> 3), x = i & 63;
    if (lane < 16) st_relaxed4(P.gm + slot * M_SLOT + (x >> 1) * 1024 + (x & 1) * 256 + (i >> 7) * 512 + ((i >> 6) & 1) * 128 + (lane & 7) * 16, CLEAR_LO, CLEAR_HI, CLEAR_LO, CLEAR_HI);
    st_relaxed4(g_f + slot * F_SLOT + cta * 512 + lane * 16, 0, 0, 0, 0);
}
__device__ __forceinline__ uint32_t pack_mem0(const Params& P, int cta, int lane) {
    uint32_t m = 0;
#pragma unroll 2
    for (int i = 0; i < 32; i++) {
        const uint4 x = __ldg((const uint4*)P.mem0 + i * 32 + lane);
        m = __vmaxu2(__vmaxu2(__vmaxu2(x.x & 0x7fff7fffu, x.y & 0x7fff7fffu), __vmaxu2(x.z & 0x7fff7fffu, x.w & 0x7fff7fffu)), m);
    }
    const uint32_t e = __reduce_max_sync(0xffffffffu, max(m >> 16, m & 0xffffu)) >> 7;
    if (e < 64 || e > 192) return 0x3F803F80u;
    const int i = cta * 2 + (lane >> 4), u = (i >> 5), x = i & 63, L = (i & 3) * 8 + ((lane & 15) >> 1);
    uint64_t w = 32;
#pragma unroll 1
    for (int f = 0; f < (u % 3 ? 3 : 2); f++) {
        const float v = __bfloat162float(P.mem0[(L >> 2) * 1024 + word_col(frag_word(u, f)) + ((i >> 2) & 7) * 16 + (L & 3) * 2 + (lane & 1)]);
        w += (uint64_t)(int64_t)__float2int_rn(v * __uint_as_float((271 - e) << 23)) << (45 - 19 * f);
    }
    st_relaxed2(P.gm + 7 * M_SLOT + (x >> 1) * 1024 + (x & 1) * 256 + (i >> 7) * 512 + ((i >> 6) & 1) * 128 + (lane & 15) * 8, (uint32_t)w, (uint32_t)(w >> 32));
    return (e - 30) * 0x00800080u;
}
__device__ __forceinline__ void pacer(const Params& P, const uint32_t sb, const int lane, const int pair, const int rank) {
    constexpr uint32_t base = 2;
    const int cta = pair * 2 + rank;
#pragma unroll 1
    for (int i = 0; i < 8; i++) clear_slot(P, i, cta, lane);
    __syncwarp();
    const uint32_t u0 = pack_mem0(P, cta, lane);
    fence_gpu();
    __syncwarp();
    mbar_wait(sb + B_GO, 0);
    if (lane < 8) sts32(sb + S_SC + lane * 4, u0);
    if (lane == 0) stamp(6144 + cta * 32, lds32(sb + S_EPOCH) + 1);
    latest_stamp<3, 1024>(g_hint + 6144 + lane * 32, lds32(sb + S_EPOCH) + 1, gtime(), sb, 0, 0);
    fence_gpu();
    __syncwarp();
    if (lane == 0) { mbar_arrive(sb + B_RELA); mbar_arrive(sb + B_RELB); }
#pragma unroll 1
    for (int s = 0; s < 63; s++) {
        mbar_wait(sb + B_GO, (s + 1) & 1);
        const uint32_t t0 = gtime();
        if (lane < 4) st_relaxed1(g_hint + ((s & 1) * 4 + lane) * 768 + (cta >> 5) * 256 + (cta & 31), ((t0 - (pair >= 32 ? P.dv : 0)) & ~31u) | ((base + s) & 31u));
        wait_time(t0 + P.ds, sb);
        const uint32_t t = latest_stamp<3, 256>(g_hint + ((s & 1) * 4 + (pair & 3)) * 768 + lane, base + s, t0, sb, P.tight, P.extra);
        release_at(t + P.da, sb, B_RELA, lane);
        release_at(t + P.db, sb, B_RELB, lane);
        if (!DBGF(16)) fence_gpu();
        __syncwarp();
        wait_time(t + P.db + 320, sb);
        clear_slot(P, (s + 6) & 7, cta, lane);
        if (s == 61) {
            sts32(sb + S_EPOCH + 4, ITEM(ITEM_OFF(pair) + NPRE + 1) + ITEM_OFF(pair + 1) + (uint32_t)(uintptr_t)P.out);
            if (lane < M_CQ) map_prefetch(&P.tm[lane]);
        }
    }
}
__device__ __forceinline__ uint32_t xor_or(uint32_t a, uint32_t b, uint32_t t) { uint32_t d; asm("lop3.b32 %0, %1, %2, %3, 0x7E;" : "=r"(d) : "r"(a), "r"(b), "r"(t)); return d; }
__device__ __forceinline__ bool tags_ok(uint32_t bad) { return __all_sync(0xffffffffu, (bad & 1) == 0); }
#define RETRY(k)
#define RETRY_STAT(a, b)
#define SFENCE() asm volatile("pmevent 1;" ::: "memory")
#define PF1 10
static_assert(NS == 24, "fragment residency");
__host__ __device__ constexpr bool in_smem(int n) { return n < 4 || n == 13 || n == 15; }
__host__ __device__ constexpr int unit_pos(int n) { return n < 4 ? n : n < 13 ? n - 4 : n == 13 ? 4 : n == 14 ? 9 : 5; }

__device__ __forceinline__ uint32_t spare_unit(int u) { return u < 6 ? 98304 + u * 2048 : S_P1 + (u - 6) * 2048; }
__device__ __forceinline__ void load_unit(const Params& P, uint32_t dst, int role, int h, int warp, int n, uint32_t bar) {
    for (int e = 0; e < 2; e++) tma2d(dst + e * 1024, &P.tm[M_CQ + role], h * 128 + (n & 1) * 64, word_col((n & 14) + e) + warp * 16, bar);
}
__device__ __forceinline__ void chain_load1(const Params& P, uint32_t sb, int pair, int rank, int warp, int lane, bool late) {
    const int role = pair >> 4, h = (pair & 15) * 2 + rank;
    if (lane < 8) {
        const uint32_t dst = lane < 6 ? warp * 12288 + lane * 2048 : spare_unit(warp * 2 + lane - 6);
        if (lane == 0 && !late) mbar_expect(sb + B_INIT, 8 * 2048);
        __syncwarp(0xff);
        if (late == (dst >= S_STG)) load_unit(P, sb + dst, role, h, warp, 4 + lane, sb + B_INIT);
    }
}

constexpr uint32_t QBITS = 0x4B002000u;
constexpr uint64_t W_BIAS = ((uint64_t)QBITS << 45) + ((uint64_t)QBITS << 26) + (uint32_t)(QBITS << 7), W_CLEAR = 0 - 32 * W_BIAS;
static_assert(W_CLEAR == ((uint64_t)CLEAR_HI << 32 | CLEAR_LO), "clear value");
__host__ __device__ constexpr int unit_off(int u) { return (u & 1) * 16384 + (u >> 2) * 512 + ((u >> 1) & 1) * 128; }
__device__ __forceinline__ void red_add64(const uint8_t* p, uint64_t v) { asm volatile("red.relaxed.gpu.global.add.u64 [%0], %1;" ::"l"(p), "l"(v) : "memory"); }
template <int NF>
__device__ __forceinline__ uint64_t encode(const float* x, float S, uint32_t two26, uint32_t& bad) {
    uint32_t b[3];
#pragma unroll
    for (int i = 0; i < 3; i++) b[i] = i < NF ? __float_as_uint(fmaf(x[i], S, 8396800.f)) : QBITS;
    bad = xor_or(b[0], b[1], 0x4B000000u) | (NF == 3 ? b[2] ^ 0x4B000000u : 0);
    uint64_t w;
    asm("{\n.reg .b64 t;\nmov.b64 t, {%2, %3};\nmad.wide.u32 %0, %1, %4, t;\n}" : "=l"(w) : "r"(b[1]), "r"(b[2] << 7), "r"(b[0] << 13), "r"(two26));
    return w;
}
template <int NF>
__device__ __forceinline__ void emit(uint64_t* w, const float (*x)[3], const float* S, uint32_t two26, uint32_t lim, const uint8_t* p) {
    uint32_t bad[2];
    w[0] = encode<NF>(x[0], S[0], two26, bad[0]); w[1] = encode<NF>(x[1], S[1], two26, bad[1]);
    const bool ok = (bad[0] | bad[1]) < lim;
    w[0] |= ok; w[1] |= ok;
    red_add64(p, w[0]); red_add64(p + 1024, w[1]);
}
template <int NF>
__device__ __forceinline__ void repair(const uint64_t* w, const float (*x)[3], const float* S, const uint8_t* p, const uint8_t* pf) {
    if (!(w[0] & 1)) {
#pragma unroll
        for (int j = 0; j < 2; j++) {
            const float T = S[j] * 8192.f;
            asm volatile("red.relaxed.gpu.global.add.v4.f32 [%0], {%1,%2,%3,%4};" ::"l"(pf + j * 512), "f"(x[j][0] * T), "f"(x[j][1] * T), "f"(NF == 3 ? x[j][2] * T : 0.f), "f"(0.f) : "memory");
        }
        fence_gpu();
#pragma unroll
        for (int j = 0; j < 2; j++) {
            asm volatile("red.relaxed.gpu.global.or.b64 [%0], 64;" ::"l"(p + j * 1024) : "memory");
            red_add64(p + j * 1024, W_BIAS + 1 - w[j]);
        }
    }
    __syncwarp();
}
__device__ __forceinline__ void ld_words(uint32_t* v, const uint8_t* p) {
    asm volatile("{\n.reg .b64 a, b;\nld.relaxed.gpu.global.L1::no_allocate.v2.b64 {a, b}, [%4];\nmov.b64 {%0,%1}, a;\nmov.b64 {%2,%3}, b;\n}" : "=r"(v[0]), "=r"(v[1]), "=r"(v[2]), "=r"(v[3]) : "l"(p) : "memory");
}
__device__ __forceinline__ float field(const uint32_t* w, int f) { return __int2float_rn((int)(f == 0 ? w[1] : f == 1 ? __funnelshift_l(w[0], w[1], 19) : w[0] << 6)); }
template <int U>
__device__ __forceinline__ void decode(uint32_t* b, const uint32_t* v) {
#pragma unroll
    for (int f = 0; f < (U % 3 ? 3 : 2); f++) b[frag_word(U, f)] = pack2(field(v, f), field(v + 2, f));
}
__device__ __forceinline__ uint32_t status(const uint32_t (*v)[4], uint32_t c32) { return xor_or(v[0][0], v[0][2], c32) | xor_or(v[1][0], v[1][2], c32) | xor_or(v[2][0], v[2][2], c32); }
__device__ __forceinline__ void gather_slow(const Params& P, uint32_t* b, const uint8_t* pm, int s, int warp, uint32_t ln, uint32_t u2) {
    if (s == 0 && u2 == 0x3F803F80u) {
#pragma unroll
        for (int i = 0; i < 16; i++) b[i] = __ldg((const uint32_t*)(P.mem0 + (ln >> 2) * 1024 + word_col(i) + warp * 16 + (ln & 3) * 2));
        return;
    }
    uint32_t v[6][4], st;
    for (int n = 0;; n++) {
#pragma unroll
        for (int u = 0; u < 6; u++) ld_words(v[u], pm + unit_off(u));
        st = status(v, 32) | status(v + 3, 32);
        if (!__any_sync(0xffffffffu, st & 32)) break;
        __nanosleep(200);
        if (n > SPIN_LIMIT) spin_fault();
    }
    const bool side = __any_sync(0xffffffffu, st & 64);
    if (side) fence_gpu();
    const uint8_t* pf = g_f + ((s + 7) & 7) * F_SLOT + warp * 1024 + ln * 32;
#pragma unroll
    for (int u = 0; u < 6; u++) {
        float x[2][4] = {};
#pragma unroll
        for (int k = 0; k < 2; k++)
            asm volatile("{\n.reg .pred P;\nsetp.ne.u32 P, %5, 0;\n@P ld.relaxed.gpu.global.v4.f32 {%0,%1,%2,%3}, [%4];\n}"
                         : "+f"(x[k][0]), "+f"(x[k][1]), "+f"(x[k][2]), "+f"(x[k][3]) : "l"(pf + u * 8192 + k * 16), "r"((uint32_t)side) : "memory");
#pragma unroll
        for (int f = 0; f < (u % 3 ? 3 : 2); f++) b[frag_word(u, f)] = pack2(field(v[u], f) + x[0][f], field(v[u] + 2, f) + x[1][f]);
    }
}
__device__ __forceinline__ uint32_t max_abs2(uint32_t a, uint32_t b) { uint32_t d; asm("max.NaN.xorsign.abs.bf16x2 %0, %1, %2;" : "=r"(d) : "r"(a), "r"(b)); return d; }
__device__ __forceinline__ uint32_t max6(const uint32_t* b) {
    const uint32_t m = max_abs2(max_abs2(max_abs2(b[0], b[1]), max_abs2(b[2], b[3])), max_abs2(b[4], b[5]));
    return max(m & 0x7fff0000u, (m << 16) & 0x7fff0000u);
}

template <bool TR>
__device__ __forceinline__ void put_partials(uint32_t a, const float* x, const float* y) {
    if (TR) stsm4t(a, pack2(x[0], x[1]), pack2(x[2], x[3]), pack2(y[0], y[1]), pack2(y[2], y[3]));
    else stsm4(a, pack2(x[0], x[1]), pack2(x[2], x[3]), pack2(y[0], y[1]), pack2(y[2], y[3]));
}
__device__ __forceinline__ void reduce_load(uint32_t (*x)[4], uint32_t a) { ldsm4t(x[0], a); ldsm4t(x[1], a + 512); }
__device__ __forceinline__ uint32_t reduce8(const uint32_t (*x)[4], uint32_t l8, uint32_t u2) {
    uint32_t p[2];
#pragma unroll
    for (int i = 0; i < 2; i++) {
        float d[4] = {};
        mma16816(d, x[i][0], x[i][1], x[i][2], x[i][3], (l8 & 32) ? 0u : u2, (l8 & 32) ? u2 : 0u);
        p[i] = pack2((l8 & 8) ? d[2] : d[0], (l8 & 8) ? d[3] : d[1]);
    }
    return (l8 & 16) ? p[1] : p[0];
}
__device__ __forceinline__ void score_half(float (*a)[4], const uint32_t (*qa)[4], const uint32_t (*kf)[4]) {
#pragma unroll
    for (int w = 0; w < 2; w++) {
        mma16816(a[w], qa[w][0], qa[w][1], qa[w][2], qa[w][3], kf[w][0], kf[w][1]);
        mma16816(a[2 + w], qa[w][0], qa[w][1], qa[w][2], qa[w][3], kf[w][2], kf[w][3]);
    }
}
__device__ __forceinline__ void score_sum(float* S, const float (*a)[4]) {
    S[0] = (a[0][0] + a[1][0]) + (a[2][2] + a[3][2]);
    S[1] = (a[0][1] + a[1][1]) + (a[2][3] + a[3][3]);
}
__device__ __forceinline__ float quad_max(float m) {
    m = fmaxf(m, __shfl_xor_sync(0xffffffffu, m, 1));
    return fmaxf(m, __shfl_xor_sync(0xffffffffu, m, 2));
}

#define ISTAMP(i)
__device__ __forceinline__ float next_scale(uint32_t sb, int slot, int warp, uint32_t u2) {
    uint32_t x[2][4];
    lds128(x[0], sb + S_MX + slot * 32); lds128(x[1], sb + S_MX + slot * 32 + 16);
    const uint32_t mx = max(max(max(x[0][0], x[0][1]), max(x[0][2], x[0][3])), max(max(x[1][0], x[1][1]), max(x[1][2], x[1][3])));
    const float top = fminf(fmaxf(__uint_as_float(mx) * bf_hi(u2), 0x1p-40f), 0x1p40f) * (1.f / (12288.f * 8192.f));
    const uint32_t un = pack2(top, top);
    sts32(sb + S_SC + warp * 4, un);
    return rcp(bf_hi(un) * 8192.f);
}
#define NEARLY 1
#define U3POS 1
#define VPOS 1
#define ROT 0
#define BPOS 1
#define ONLINE 0
#define NBAR 1
#define RPOS 1
#define AF 0
#define AFENCE(i) if ((AF >> (i)) & 1) SFENCE();
#define FPOS 99
#define PACE 1
#define PF2 12
__host__ __device__ constexpr int w2_t(int i) { return i < 16 ? i & 1 : 2; }
__host__ __device__ constexpr int w2_k(int i) { return i < 16 ? i >> 1 : i - 16; }
template <int ROLE>
__device__ __forceinline__ void chain_role(const Params& P, const uint32_t sb, const int h, const int warp, const int lane) {
    constexpr int NU = ROLE == 0 ? 2 : 3;
    const bool att = ROLE == 0 && warp < 4;
    uint32_t wr[NR][4];
    const uint32_t frag = ((lane & 7) + (lane >> 4) * 8) * 128 + ((((lane >> 3) & 1) ^ (lane & 7)) << 4);
    {
        const uint32_t bar = sb + B_INIT, spare = sb + spare_unit(warp * 2);
        mbar_wait(bar, 0);
        ISTAMP(0)
#pragma unroll
        for (int f = 0; f < 32; f++) ldsm4t(wr[f], (f < 24 ? sb + warp * 12288 + (f >> 2) * 2048 : spare + ((f - 24) >> 2) * 2048) + (frag ^ ((f & 3) << 5)));
        fence_async_smem();
        __syncwarp();
        if (lane < 8) {
            if (lane == 0) mbar_expect(bar, 8 * 2048);
            __syncwarp(0xff);
            load_unit(P, lane < 6 ? sb + warp * 12288 + lane * 2048 : spare + (lane - 6) * 2048, ROLE, h, warp, lane < 4 ? lane : lane < 6 ? lane * 2 + 5 : lane * 2, bar);
        }
        ISTAMP(1)
        mbar_wait(bar, 1);
        if (lane == 0) {
            if (warp < 2 * NU) {
                mbar_expect(sb + B_WO, 16384);
                for (int e = 0; e < 2; e++) tma4d(sb + S_W2 + warp * 16384 + e * 8192, &P.tm[M_CO + e], (ROLE == 0 ? 0 : ROLE == 1 ? 256 : 640) + warp * 64, h * 8, sb + B_WO);
            } else mbar_arrive(sb + B_WO);
        }
        ISTAMP(2)
#pragma unroll
        for (int f = 32; f < 40; f++) ldsm4t(wr[f], spare + ((f - 32) >> 2) * 2048 + (frag ^ ((f & 3) << 5)));
#pragma unroll 2
        for (int u = 0; u < 6; u++) {
            const uint32_t ub = sb + warp * 12288 + u * 2048;
            uint32_t x[4][4];
#pragma unroll
            for (int i = 0; i < 4; i++) lds128(x[i], ub + (frag ^ (i << 5)));
            __syncwarp();
#pragma unroll
            for (int i = 0; i < 4; i++) sts128(ub + i * 512 + lane * 16, x[i]);
        }
        bar_sync(1, 256);
    }
    uint32_t l8 = opq(sb + lane * 8, lane);
    const uint8_t* persu = (const uint8_t*)((ROLE == 1 ? g_km : g_vmt) + h * 512 + warp * 32) - (sb >> 1);
#define PERS_STORE() { uint32_t* pp = (uint32_t*)(persu + s * 65536 + (l8 >> 1)); pp[0] = r0; pp[256] = r1; }
    const uint32_t rdelta = __shfl_sync(0xffffffffu, mapa(sb, (cluster_rank() + (ROLE == 1 ? 4 : 2)) % 6) - sb, 0);
    const uint32_t vdelta = ROLE ? 0 : __shfl_sync(0xffffffffu, mapa(sb, (cluster_rank() + 4) % 6) - sb, 0);
    ISTAMP(3)
    if (warp == 7 && lane == 0) mbar_arrive(sb + B_GO);
    __syncwarp();
#define GATHER_OFF(s) ((((s) + 7) & 7) * M_SLOT + warp * 2048 + (l8 & 56) * 2 + (l8 & 64) * 4 + (l8 & 128) * 8)
    uint32_t mo = GATHER_OFF(0);
    if (ROT) mbar_wait(sb + B_RELA, 0);
    for (int s = 0; s < (ROLE == 0 ? 63 : 64); s++) {
        const int slot = s & 1;
        l8 += s & P.zero;
        const uint32_t w1a = l8 * 2 + (S_W1 + warp * 12288 - sb);
        PROF(9)
        uint32_t u2, r0, r1, pld, pub, pbar, x[2][4];
        {
#define pm (P.gm + mo)
            uint32_t as[24][4], b[16], v[6][4];
            float acc[8][4];
#define W1LD(n) _Pragma("unroll") for (int i_ = 0; i_ < 4; i_++) ldsm4t(as[unit_pos(n) * 4 + i_], w1a + (unit_pos(n) * 4 + i_) * 512);
#define W1MMA(n) _Pragma("unroll") for (int i_ = 0; i_ < 4; i_++) { const uint32_t* a_ = in_smem(n) ? as[unit_pos(n) * 4 + i_] : wr[unit_pos(n) * 4 + i_]; \
                                                                   mma16816(acc[((n) & 1) * 4 + i_], a_[0], a_[1], a_[2], a_[3], b[(n) & 14], b[(n) | 1]); }
#pragma unroll
            for (int T = 0; T < 8; T++) { acc[T][0] = acc[T][1] = acc[T][2] = acc[T][3] = 0.f; }
            if (!ROT) mbar_wait(sb + B_RELA, slot);
            PROF(12)
#pragma unroll
            for (int u = 0; u < 3; u++) ld_words(v[u], pm + unit_off(u));
            __syncwarp();
#pragma unroll
            for (int i = 0; i < PF1; i++) ldsm4t(as[i], w1a + i * 512);
            __syncwarp();
            mo += mbar_try(sb + B_RELB, slot) & P.zero;
            PROF(13)
#pragma unroll
            for (int u = 3; u < 6; u++) ld_words(v[u], pm + unit_off(u));
            uint32_t st = status(v, ((uint32_t)((uintptr_t)pm >> 32) & P.zero) + 32);
            pin<1>(&st);
            SFENCE();
            PROF(0)
            decode<0>(b, v[0]); decode<1>(b, v[1]); decode<2>(b, v[2]);
#pragma unroll
            for (int i = PF1; i < 12; i++) ldsm4t(as[i], w1a + i * 512);
            W1MMA(0) W1MMA(1) W1MMA(2)
            W1LD(3)
            SFENCE();
            W1MMA(5) W1MMA(4) W1MMA(7) W1MMA(6)
            if (U3POS == 0) W1MMA(3)
            uint32_t mx = max6(b);
            pin<1>(&mx);
            SFENCE();
            PROF(10)
            if (U3POS == 1) W1MMA(3)
            const uint32_t mxa = sb + S_MX + slot * 32 + warp * 4;
            sts32(mxa, __reduce_max_sync(0xffffffffu, mx));
            RETRY_STAT(st, status(v + 3, 32))
            const bool redo = __any_sync(0xffffffffu, (st | status(v + 3, 32)) & 96);
            const bool kvok = ROLE || mbar_test(sb + B_KVFULL + slot * 8, (s >> 1) & 1);
            decode<4>(b, v[4]); decode<5>(b, v[5]); decode<3>(b, v[3]);
            u2 = lds32(sb + S_SC + warp * 4);
            W1MMA(8) W1MMA(10) W1MMA(12) W1MMA(14)
            W1LD(13)
            if (__builtin_expect(redo || !kvok, 0)) {
                if (redo) {
                    RETRY(3)
                    gather_slow(P, b, pm, s, warp, (l8 - sb) >> 3, u2);
                    sts32(mxa, __reduce_max_sync(0xffffffffu, max6(b)));
#pragma unroll
                    for (int T = 0; T < 8; T++) { acc[T][0] = acc[T][1] = acc[T][2] = acc[T][3] = 0.f; }
#pragma unroll
                    for (int n = 0; n < 15; n += n < 8 ? 1 : 2) {
                        if (in_smem(n)) { W1LD(n) }
                        W1MMA(n)
                    }
                    W1LD(13)
                }
                if (ROLE == 0) mbar_wait(sb + B_KVFULL + slot * 8, (s >> 1) & 1);
            }
#undef pm
            PROF(14)
            const uint32_t pst = (l8 - sb) * 16 + ((warp * 16) ^ ((l8 * 2) & 112)) + (sb + S_P1);
            put_partials<ROLE == 2>(pst, acc[0], acc[1]); put_partials<ROLE == 2>(pst + 4096, acc[2], acc[3]);
            W1MMA(9)
            SFENCE();
            W1LD(15)
            pld = (l8 & 64) * 4 + (l8 & 128) + (l8 & 56) * 2 + (sb + S_P1 + warp * 1024);
            const uint32_t rd = s == 63 ? 0 : rdelta;
            pub = ((l8 - sb) >> 1) + (ROLE ? sb + rd + (ROLE == 1 ? S_KL : S_VL) + warp * 128 : sb + S_QX + (warp & 4) * 128 + (warp & 1) * 256 + (warp & 2) * 64);
            pbar = sb + rd + (ROLE == 1 && s != 63 ? B_K : B_V);
#define PUBLISH0() { r0 = reduce8(x, l8, u2); if (ROLE) st_async1(pub, r0, pbar); else sts32(pub, r0); }
            if (RPOS == 0) { bar_sync(1, 256); reduce_load(x, pld); SFENCE(); }
            W1MMA(13)
            if (RPOS == 1) { bar_sync(1, 256); reduce_load(x, pld); }
            SFENCE();
            W1MMA(11)
            if (RPOS == 0) PUBLISH0()
            if (RPOS == 2) { bar_sync(1, 256); reduce_load(x, pld); }
            SFENCE();
            W1MMA(15)
            if (RPOS == 1) PUBLISH0()
            put_partials<ROLE == 2>(pst + 8192, acc[4], acc[5]); put_partials<ROLE == 2>(pst + 12288, acc[6], acc[7]);
            if (RPOS == 2) PUBLISH0()
        }
        PROF(1)
        if (ROLE) {
            bar_sync(1, 256);
            reduce_load(x, pld + 8192);
            r1 = reduce8(x, l8, u2);
            st_async1(pub + 1024, r1, pbar);
            if (s == 63) {
                PERS_STORE()
                mbar_wait(sb + B_V, 0);
                __syncwarp();
                if (l8 == sb) mbar_arrive(sb + B_PERS);
                break;
            }
            PROF(2)
        }
        uint32_t ln, w2a, ro;
#define W2ADDR(late) { l8 += pub & P.zero; ln = (l8 - sb) >> 3; \
        w2a = sb + S_W2 + (ROLE ? (warp >> 2) * 16384 : late * 32768) + ((((ln & 7) + (ln >> 4) * 8) * 128 + ((((ln >> 3) & 1) ^ (ln & 7)) << 4)) ^ ((warp & 3) << 5)); \
        ro = (s & 7) * M_SLOT + (ROLE ? warp * 2048 + unit_off(ROLE) : (warp & 3) * 2048 + late * unit_off(3)) + (ln & 2) * 128 + (ln & 1) * 64 + (ln >> 2) * 8; }
        constexpr int RO2 = ROLE ? unit_off(ROLE + 3) - unit_off(ROLE) : 8192;
        float Sj[2];
        uint32_t w[24][4], ob[4][4];
        float S;
#define W2LD(i) ldsm4t(w[i], w2a + w2_t(i) * (ROLE ? 32768 : 16384) + (w2_k(i) & 1) * 8192 + (w2_k(i) >> 1) * 2048)
#define W2MMA(d, i) mma16816(d, w[i][0], w[i][1], w[i][2], w[i][3], ob[w2_k(i) >> 1][(w2_k(i) & 1) * 2], ob[w2_k(i) >> 1][(w2_k(i) & 1) * 2 + 1])
#define LEADER(wp) (l8 == sb + ((wp) - warp) * 256)
        if (att) {
            const float cs = 0.08838834764831845f * 1.4426950408889634f;
            uint32_t qa[4][4], kf[4][4], vf[4][4], vv[4];
            float T[5][2], sa[4][4] = {};
            const uint32_t l16 = l8 * 2 - sb;
            const uint32_t kaddr = (l8 & 56) * 16 + (((l8 >> 2) ^ (l8 * 2)) & 48) + ((l8 * 2) & 64) + (sb + S_KV + warp * 1024 + slot * 16384);
            bar_sync(1, 256);
            reduce_load(x, pld + 8192);
            __syncwarp();
#pragma unroll
            for (int i = 0; i < 2; i++) { ldsm4(qa[i], l16 + S_QX + i * 512); ldsm4(kf[i], kaddr ^ (i * 64)); }
            AFENCE(0)
            sts32(pub + 1024, reduce8(x, l8, u2));
            __syncwarp();
#pragma unroll
            for (int i = 2; i < 4; i++) ldsm4(kf[i], (kaddr ^ ((i & 1) * 64)) + 4096);
            score_half(sa, qa, kf);
            bar_sync(2, 256);
            PROF(2)
#pragma unroll
            for (int i = 2; i < 4; i++) ldsm4(qa[i], l16 + S_QX + i * 512);
            float sm[4][4] = {};
            score_half(sa, qa + 2, kf + 2);
            score_sum(T[0], sa);
            sts64(l8 + S_SX + warp * 256, __float_as_uint(T[0][0]), __float_as_uint(T[0][1]));
            PROF(4)
            if (BPOS == 0) bar_sync(4, 128);
            mbar_wait(sb + B_K, slot);
            PROF(11)
#pragma unroll
            for (int i = 0; i < 4; i++) ldsm4(kf[i], l16 + S_KL + i * 512);
            if (BPOS == 1) bar_sync(4, 128); else __syncwarp();
#pragma unroll
            for (int n = 0; n < 4; n++) lds64f(T[n], l8 + S_SX + n * 256);
            score_half(sm, qa, kf);
            score_half(sm, qa + 2, kf + 2);
            const uint32_t vaddr = (l8 & 56) * 16 + (l8 & 128) * 8 + (((warp & 1) * 64 + ((l8 >> 2) & 16)) ^ ((l8 * 2) & 112)) + (sb + S_KV + 8192 + (warp >> 1) * 4096 + slot * 16384);
            float mx = fmaxf(fmaxf(fmaxf(T[0][0], T[0][1]), fmaxf(T[1][0], T[1][1])), fmaxf(fmaxf(T[2][0], T[2][1]), fmaxf(T[3][0], T[3][1])));
            score_sum(T[4], sm);
            float m = quad_max(fmaxf(mx, fmaxf(T[4][0], T[4][1])));
            if (VPOS == 0) {
#pragma unroll
                for (int i = 0; i < 4; i++) ldsm4t(vf[i], (vaddr ^ ((i & 1) << 5)) + (i >> 1) * 2048);
            }
            mbar_wait(sb + B_V, slot);
            if (VPOS == 1) {
#pragma unroll
                for (int i = 0; i < 4; i++) ldsm4t(vf[i], (vaddr ^ ((i & 1) << 5)) + (i >> 1) * 2048);
            }
            ldsm4(vv, l16 + S_VL + warp * 512);
            uint32_t pa[5];
            m *= cs;
#pragma unroll
            for (int n = 0; n < 5; n++) { T[n][0] = ex2(fmaf(T[n][0], cs, -m)); T[n][1] = ex2(fmaf(T[n][1], cs, -m)); pa[n] = pack2(T[n][0], T[n][1]); }
            float sum = (((T[0][0] + T[0][1]) + (T[1][0] + T[1][1])) + ((T[2][0] + T[2][1]) + (T[3][0] + T[3][1]))) + (T[4][0] + T[4][1]);
            PROF(3)
            W2ADDR(1)
            const uint32_t lo = sb + S_O + warp * 512 + (ln & 3) * 64 + (ln >> 2) * 8, ls = sb + S_SUM + (ln & 3) * 32 + (ln & 4) * 4 + (ln >> 3) * 4;
            const uint32_t sdelta = warp < 2 ? rdelta : vdelta;
            sum += __shfl_xor_sync(0xffffffffu, sum, 1);
            sum += __shfl_xor_sync(0xffffffffu, sum, 2);
            float O[2][4];
#pragma unroll
            for (int i = 0; i < 2; i++) { O[i][0] = O[i][1] = O[i][2] = O[i][3] = 0.f; }
#pragma unroll
            for (int i = 0; i < 2; i++) {
                mma16816(O[0], vf[2 * i][0], vf[2 * i][1], vf[2 * i][2], vf[2 * i][3], pa[2 * i], pa[2 * i + 1]);
                mma16816(O[1], vf[2 * i + 1][0], vf[2 * i + 1][1], vf[2 * i + 1][2], vf[2 * i + 1][3], pa[2 * i], pa[2 * i + 1]);
            }
            mma1688(O[0], vv[0], vv[1], pa[4]);
            mma1688(O[1], vv[2], vv[3], pa[4]);
            uint32_t o[2][2];
#pragma unroll
            for (int j = 0; j < 2; j++) { o[j][0] = pack2(O[0][j], O[0][2 + j]); o[j][1] = pack2(O[1][j], O[1][2 + j]); }
#pragma unroll
            for (int j = 0; j < 2; j++) st_async2(lo + rdelta + j * 256, o[j][0], o[j][1], sb + rdelta + B_K);
            st_async1(ls + sdelta + (warp & 1) * 128, __float_as_uint(sum), sb + sdelta + B_K);
#pragma unroll
            for (int j = 0; j < 2; j++) st_async2(lo + vdelta + j * 256, o[j][0], o[j][1], sb + vdelta + B_K);
#pragma unroll
            for (int j = 0; j < 2; j++) sts64(lo + j * 256, o[j][0], o[j][1]);
            sts32(ls + warp * 128, __float_as_uint(sum));
            PROF(5)
            bar_sync(3, 256);
            if (LEADER(0)) { mbar_expect(sb + B_K, 2048); mbar_expect(sb + B_V, 2048); mbar_arrive(sb + B_KVGO + slot * 8); }
            S = next_scale(sb, slot, warp, u2);
            if (s == 0) mbar_wait(sb + B_WO, 0);
            pin<1>(&S);
            SFENCE();
#pragma unroll
            for (int j = 0; j < 4; j++) lds128(ob[j], l8 * 2 - sb + S_O + j * 512);
            lds64f(Sj, sb + S_SUM + (l8 & 24));
#pragma unroll
            for (int i = 0; i < PF2; i++) W2LD(i);
        } else {
            if (ROLE == 0) { bar_sync(1, 256); reduce_load(x, pld + 8192); sts32(pub + 1024, reduce8(x, l8, u2)); bar_arrive(2, 256); }
            if (LEADER(7)) { mbar_arrive(sb + B_GO); if (ROLE) mbar_expect(sb + B_K, 2304); }
            if (ROLE != 0 && (s & 3) == 0 && s > 0 && l8 == sb) mbar_arrive(sb + B_PERS);
            S = next_scale(sb, slot, warp, u2);
            if (s == 0) mbar_wait(sb + B_WO, 0);
            if (ROLE != 0) { l8 += delay_loop(40, l8); if (!DBGF(4)) PERS_STORE() }
            W2ADDR(0)
#pragma unroll
            for (int i = 0; i < PF2; i++) {
                W2LD(i);
                if (ROLE == 0 && (i & PACE) == PACE) w2a += w[i][0] & P.zero;
            }
            ro = opq(ro, ln);
            const uint32_t sa = opq(sb + S_SUM + (l8 & 24), ln), oa = opq(l8 * 2 - sb + S_O, ln);
            if (ROLE == 0) bar_sync(3, 256); else mbar_wait(sb + B_K, slot);
            lds64f(Sj, sa);
#pragma unroll
            for (int j = 0; j < 4; j++) lds128(ob[j], oa + j * 512);
        }
        SFENCE();
        PROF(6)
        {
            const uint8_t* pr = P.gm + ro;
            float c[4][4];
            uint32_t lim = 0;
#pragma unroll
            for (int i = 0; i < 4; i++) { c[i][0] = c[i][1] = c[i][2] = c[i][3] = 0.f; }
#pragma unroll
            for (int i = 0; i < 16; i++) {
                W2MMA(c[i & (ROLE ? 1 : 3)], i);
                if (i + PF2 < (ROLE ? 16 + NEARLY : 16)) W2LD(i + PF2);
                if (i == 5) {
                    const uint32_t z = __float_as_uint(c[1][0]) & P.zero;
                    Sj[0] = S * rcp(__uint_as_float(__float_as_uint(Sj[0]) | z)); Sj[1] = S * rcp(__uint_as_float(__float_as_uint(Sj[1]) | z));
                }
                if (i == 5) lim = __any_sync(0xffffffffu, fmaxf(fmaxf(fabsf(c[0][0]), fabsf(c[0][2])), fmaxf(fabsf(c[1][0]), fabsf(c[1][2]))) * Sj[0] >= (ROLE ? 24.f : 20.f)) ? 16384 : 0;
                if (i == FPOS) { pin<1>(&lim); pin<2>(Sj); pin_ptr(pr); SFENCE(); }
            }
            if (ROLE == 0) {
#pragma unroll
                for (int i = 0; i < 8; i++) c[i >> 2][i & 3] += c[2 + (i >> 2)][i & 3];
            }
            const float xa[2][3] = {{c[0][0], c[0][2], c[1][0]}, {c[0][1], c[0][3], c[1][1]}};
            uint64_t wa[2], wb[2];
            emit<NU>(wa, xa, Sj, P.two26, lim, pr);
            PROF(7)
            mo = GATHER_OFF(s + 1);
            pin<1>(&mo);
            if (ROLE) {
                SFENCE();
#pragma unroll
                for (int i = 16 + NEARLY; i < 24; i++) { if (i == 16 + NBAR) bar_sync(2, 256); W2LD(i); __syncwarp(); }
                SFENCE();
#pragma unroll
                for (int i = 16; i < 24; i++) W2MMA(c[2 + (i & 1)], i);
#pragma unroll
                for (int i = 0; i < 4; i++) c[2][i] += c[3][i];
            }
            const float y[2][3] = {{ROLE ? c[1][2] : c[1][0], ROLE ? c[2][0] : c[1][2], c[2][2]}, {ROLE ? c[1][3] : c[1][1], ROLE ? c[2][1] : c[1][3], c[2][3]}};
            const bool released = !ROT || mbar_test(sb + B_RELA, slot ^ 1);
            emit<NU>(wb, y, Sj, P.two26, lim, pr + RO2);
            PROF(8)
            if (!__all_sync(0xffffffffu, (wa[0] & wb[0] & 1) && released)) {
                if (__builtin_expect(!__all_sync(0xffffffffu, wa[0] & wb[0] & 1), 0)) {
                    RETRY(5)
                    const uint8_t* pf = g_f + (s & 7) * F_SLOT + (ROLE ? ROLE * 8192 + warp * 1024 : (warp & 3) * 1024 + (att ? 24576 : 0)) + (ln & 3) * 128 + (ln >> 2) * 16;
                    repair<NU>(wa, xa, Sj, pr, pf);
                    repair<NU>(wb, y, Sj, pr + RO2, pf + (ROLE ? 24576 : 4096));
                }
                if (ROT) mbar_wait(sb + B_RELA, slot ^ 1);
            }
        }
    }
}
struct Pipe { uint32_t stage, phase; };
struct Cons {
    uint32_t sb, rel;
    int wg, wq, lane, rank, pair;
    uint32_t atag, nst;
    Pipe p;
};
__device__ __forceinline__ void pipe_next(Pipe& p) { p.stage = (p.stage + 1) & (NSTAGE - 1); p.phase ^= (p.stage == 0); }
__device__ __forceinline__ void release(const Cons& c, uint32_t stage) { if (c.lane < 2) mbar_arrive_cluster(c.rel + stage * 8); }

enum { PEND_NONE = 0, PEND_KVO = 1, PEND_HT = 2, PEND_OUT = 3, PEND_OUTH = 4 };
struct Pend { uint32_t pk[64]; int kind, row, col, cnt; };

__device__ __forceinline__ void staging_wait(const Cons& c) { if (c.nst) mbar_wait(c.sb + B_SFREE + c.wg * 8, (c.nst - 1) & 1); }
__device__ __forceinline__ void staging_post(Cons& c, int kind, int row, int col, int cnt) {
    __syncwarp();
    if (c.lane == 0) {
        if (c.wq == 0) { const uint32_t x[4] = {(uint32_t)kind, (uint32_t)row, (uint32_t)col, (uint32_t)cnt}; sts128(c.sb + S_DESC + c.wg * 16, x); }
        mbar_arrive(c.sb + B_SFULL + c.wg * 8);
    }
    c.nst++;
}
template <int HF, bool KVONLY = false>
__device__ __forceinline__ void drain(const Params& P, Cons& c, const Pend& d) {
    const uint32_t* pk = d.pk + HF * 32;
    if (!KVONLY && d.kind >= PEND_OUT) {
        if (HF == 1 && d.kind == PEND_OUTH) return;
        float* o = P.out + (size_t)(d.row + c.wq * 16 + (c.lane >> 2)) * 2048 + d.col + HF * 128 + (c.lane & 3) * 2;
#pragma unroll
        for (int j = 0; j < 16; j++) {
            st_stream2(o + j * 8, bf_lo(pk[j * 2]), bf_hi(pk[j * 2]));
            st_stream2(o + 8 * 2048 + j * 8, bf_lo(pk[j * 2 + 1]), bf_hi(pk[j * 2 + 1]));
        }
    } else if (d.kind != PEND_NONE) {
        const bool ht = !KVONLY && d.kind == PEND_HT;
        const int hi = (c.lane >> 3) & 1;
        const uint32_t base = c.sb + S_STG + c.wg * 16384 + ((ht ? hi * 32 + c.wq * 8 : c.wq * 16 + hi * 8) + (c.lane & 7)) * 128;
        staging_wait(c);
#pragma unroll
        for (int j = 0; j < 8; j++) {
            const int ch = (j & 3) * 2 + (c.lane >> 4);
            stsm4(base + (j >> 2) * 8192 + ((ch ^ (c.lane & 7)) << 4), pk[j * 4], pk[j * 4 + 1], pk[j * 4 + 2], pk[j * 4 + 3]);
        }
        fence_async_smem();
        staging_post(c, d.kind, d.row, d.col + HF * 128, HF ? d.cnt : -1);
    }
}
__device__ __forceinline__ void drain_all(const Params& P, Cons& c, Pend& d) { drain<0>(P, c, d); drain<1>(P, c, d); d.kind = PEND_NONE; }

__device__ __forceinline__ void store_warp(const Params& P, uint32_t sb, int wg) {
    const uint32_t stg = sb + S_STG + wg * 16384;
#pragma unroll 1
    for (uint32_t n = 0;; n++) {
        mbar_wait(sb + B_SFULL + wg * 8, n & 1);
        uint32_t x[4];
        lds128(x, sb + S_DESC + wg * 16);
        if (x[0] == PEND_NONE) break;
        const bool ht = x[0] == PEND_HT;
        const CUtensorMap* m = &P.tm[ht ? M_HTS : M_KVO];
#pragma unroll 1
        for (int i = 0; i < 4; i++) if (!(DBGF(128) && gridDim.x != 96)) tma_store2d(m, x[2] + (i >> 1) * 64, x[1] + (i & 1) * (ht ? 1024 : 32), stg + i * 4096);
        bulk_commit();
        bulk_wait_read();
        mbar_arrive(sb + B_SFREE + wg * 8);
        if ((int)x[3] >= 0) { bulk_wait_all(); fence_async(); red_release(&g_cnt(x[3])); }
    }
}

template <int N, int TA, int TB, bool FIRST>
__device__ __forceinline__ void issue_ktile(float* acc, const Cons& c) {
    mbar_wait(c.sb + B_FULL + c.p.stage * 8, c.p.phase);
    const uint32_t a = c.sb + c.p.stage * STAGE + c.wg * 8192, b = c.sb + c.p.stage * STAGE + 16384;
    const uint64_t da = mkdesc(a, TA ? 8192 : 16, 1024, 1), db = mkdesc(b, TB ? 8192 : 16, 1024, 1);
    wg_fence();
#pragma unroll
    for (int k = 0; k < 4; k++) {
        const uint64_t x = da + (TA ? 128 : 2) * k, y = db + (TB ? 128 : 2) * k;
        if (N == 256) { if (FIRST && k == 0) wgmma_ss256_first<TA, TB>(acc, x, y); else wgmma_ss256<TA, TB>(acc, x, y); }
        else { if (FIRST && k == 0) wgmma_ss128_first<TA, TB>(acc, x, y); else wgmma_ss128<TA, TB>(acc, x, y); }
    }
    wg_commit();
}
template <int N, bool FIRST>
__device__ __forceinline__ void issue_any(float* acc, const Cons& c, int type) {
    if (N == 256 && type == T_A1) issue_ktile<N, 0, 0, FIRST>(acc, c);
    else if (type == (N == 256 ? T_A2 : T_A2H)) issue_ktile<N, 1, 0, FIRST>(acc, c);
    else issue_ktile<N, 0, 1, FIRST>(acc, c);
}
template <int N, bool KVONLY = false>
__device__ __forceinline__ void mainloop(float* acc, const Params& P, Cons& c, Pend& d, int type) {
    const int nk = (type == T_OP || type == T_OPH) ? 64 : (type == T_A2 || type == T_A2H) ? 32 : 16;
    issue_any<N, true>(acc, c, type);
    drain<0, KVONLY>(P, c, d);
    uint32_t prev = c.p.stage;
    pipe_next(c.p);
    for (int kt = 1; kt < nk; kt++) {
        issue_any<N, false>(acc, c, type);
        wg_wait<1>();
        release(c, prev);
        if (kt == 2) drain<1, KVONLY>(P, c, d);
        prev = c.p.stage;
        pipe_next(c.p);
    }
    d.kind = PEND_NONE;
    wg_wait<0>();
    pin<N / 2>(acc);
    release(c, prev);
}
__device__ __forceinline__ void pack_half(uint32_t* pk, const float* a) {
#pragma unroll
    for (int i = 0; i < 32; i++) pk[i] = pack2(a[2 * i], a[2 * i + 1]);
}

__device__ __forceinline__ void epi_kv(const float* acc, const Cons& c, Pend& d, int mb, int nb) {
    pack_half(d.pk, acc); pack_half(d.pk + 32, acc + 64);
    d.kind = PEND_KVO; d.row = (nb >> 4) * 2048 + mb * 256 + c.rank * 128 + c.wg * 64; d.col = (nb & 15) * 256; d.cnt = C_KV + mb;
}

__device__ __forceinline__ void epi_qa(const float* acc, Cons& c, Pend& d, int mb, int nb) {
    uint32_t q[64];
    pack_half(q, acc);
    pack_half(q + 32, acc + 64);
#pragma unroll
    for (int i = 0; i < 32; i++) d.pk[32 + i] = 0;
    const int g = c.lane >> 2, t = c.lane & 3;
    const bool sg = c.wq >= 2;
    const int i0 = (c.wq & 1) * 16 + g;
#pragma unroll 1
    for (int hh = 0; hh < 2; hh++) {
        uint32_t pa[5][4];
        {
            float S[32] = {}, Sm[8] = {};
            mbar_wait(c.sb + B_FULL + c.p.stage * 8, c.p.phase);
            const uint32_t st = c.sb + c.p.stage * STAGE;
            const uint64_t dk = mkdesc(st + c.wg * 8192, 16, 1024, 1), dm = mkdesc(st + 32768 + c.wg * 4096, 128, 2048, 0);
            pin<32>(q); pin<32>(S); pin<8>(Sm);
            wg_fence();
#pragma unroll
            for (int i = 0; i < 8; i++) wgmma_rs64<0>(S, q + i * 4, dk + (i >> 2) * 1024 + (i & 3) * 2, i != 0);
#pragma unroll
            for (int i = 0; i < 8; i++) wgmma_rs16<0>(Sm, q + i * 4, dm + i * 16, i != 0);
            wg_commit();
            wg_wait<0>();
            pin<32>(S); pin<8>(Sm);
            release(c, c.p.stage);
            pipe_next(c.p);
            const float scale = 0.08838834764831845f, l2e = 1.4426950408889634f;
            float x[2][10];
#pragma unroll
            for (int r = 0; r < 2; r++) {
#pragma unroll
                for (int j = 0; j < 4; j++)
#pragma unroll
                    for (int e = 0; e < 2; e++) {
                        const float v = sg ? S[16 + j * 4 + r * 2 + e] : S[j * 4 + r * 2 + e];
                        x[r][j * 2 + e] = (j * 8 + 2 * t + e > i0 + r * 8) ? -1e9f : v * scale;
                    }
                x[r][8] = (sg ? Sm[4 + r * 2] : Sm[r * 2]) * scale;
                x[r][9] = (sg ? Sm[5 + r * 2] : Sm[1 + r * 2]) * scale;
                float m = x[r][0];
#pragma unroll
                for (int i = 1; i < 10; i++) m = fmaxf(m, x[r][i]);
                m = fmaxf(m, __shfl_xor_sync(0xffffffffu, m, 1));
                m = fmaxf(m, __shfl_xor_sync(0xffffffffu, m, 2));
                float sum = 0.f;
#pragma unroll
                for (int i = 0; i < 10; i++) { x[r][i] = ex2((x[r][i] - m) * l2e); sum += x[r][i]; }
                sum += __shfl_xor_sync(0xffffffffu, sum, 1);
                sum += __shfl_xor_sync(0xffffffffu, sum, 2);
                const float inv = rcp(sum);
#pragma unroll
                for (int i = 0; i < 10; i++) x[r][i] *= inv;
            }
#pragma unroll
            for (int ks = 0; ks < 2; ks++)
#pragma unroll
                for (int i = 0; i < 4; i++) {
                    const uint32_t p = pack2(x[i & 1][ks * 4 + (i >> 1) * 2], x[i & 1][ks * 4 + (i >> 1) * 2 + 1]);
                    pa[ks][i] = sg ? 0u : p;
                    pa[2 + ks][i] = sg ? p : 0u;
                }
#pragma unroll
            for (int r = 0; r < 2; r++) {
                const uint32_t p = pack2(x[r][8], x[r][9]);
                pa[4][r] = sg ? 0u : p;
                pa[4][2 + r] = sg ? p : 0u;
            }
        }
        float O[64] = {};
        mbar_wait(c.sb + B_FULL + c.p.stage * 8, c.p.phase);
        const uint32_t st = c.sb + c.p.stage * STAGE;
        const uint64_t dv = mkdesc(st + c.wg * 8192, 16384, 1024, 1), dm = mkdesc(st + 32768 + c.wg * 4096, 2048, 128, 0);
        pin<20>(&pa[0][0]); pin<64>(O);
        wg_fence();
#pragma unroll
        for (int ks = 0; ks < 4; ks++) wgmma_rs128<1>(O, pa[ks], dv + ks * 128, ks != 0);
        wgmma_rs128<0>(O, pa[4], dm, 1);
        wg_commit();
        wg_wait<0>();
        pin<64>(O);
        release(c, c.p.stage);
        pipe_next(c.p);
#pragma unroll
        for (int i = 0; i < 32; i++) { q[i] = q[32 + i]; q[32 + i] = d.pk[32 + i]; }
        pack_half(d.pk + 32, O);
    }
#pragma unroll
    for (int i = 0; i < 32; i++) d.pk[i] = q[32 + i];
    d.kind = PEND_KVO; d.row = 4096 + mb * 256 + c.rank * 128 + c.wg * 64; d.col = nb * 256; d.cnt = C_O + mb * 4 + (nb >> 2);
}

__device__ __forceinline__ void epi_op(const float* acc, const Cons& c, Pend& d, int mb, int nb) {
    pack_half(d.pk, acc); pack_half(d.pk + 32, acc + 64);
    d.kind = PEND_OUT; d.row = mb * 256 + c.rank * 128 + c.wg * 64; d.col = 1024 + nb * 256;
}

__device__ __forceinline__ void epi_oph(const float* acc, const Cons& c, Pend& d, int mb, int nb) {
    pack_half(d.pk, acc);
    d.kind = PEND_OUTH; d.row = mb * 256 + c.rank * 128 + c.wg * 64; d.col = 1024 + nb * 128;
}

template <int HF>
__device__ __forceinline__ void epi_a2_half(const float* acc, const Params& P, Cons& c, int mb, int col0) {
    const int g = c.lane >> 2, t = c.lane & 3;
    const int row = mb * 256 + (g >> 1) * 64 + (c.rank * 16 + c.wg * 8 + c.wq * 2) * 2 + (g & 1);
    float* o = P.out + (size_t)row * 2048 + col0 + HF * 128 + t * 2;
    mbar_wait(c.sb + B_FULL + c.p.stage * 8, c.p.phase);
    const uint32_t st = c.sb + c.p.stage * STAGE, da = st + 32768 + (c.lane >> 3) * 16;
    const uint32_t xa = st + (c.wg * 64 + c.wq * 16 + (c.lane & 15)) * 128 + (((c.lane >> 4) ^ (c.lane & 7)) << 4);
#pragma unroll
    for (int j4 = 0; j4 < 4; j4++) {
        uint32_t x[8], dv[4];
        ldsm4(dv, da + j4 * 64);
        ldsm4(x, (xa ^ ((j4 & 1) << 6)) + (j4 >> 1) * 16384);
        ldsm4(x + 4, (xa ^ ((j4 & 1) << 6) ^ 32) + (j4 >> 1) * 16384);
#pragma unroll
        for (int i = 0; i < 4; i++) {
            const int j = j4 * 4 + i;
            const float* a = acc + HF * 64 + j * 4;
            const uint32_t u0 = hmul2(x[2 * i], dv[i]), u1 = hmul2(x[2 * i + 1], dv[i]);
            st_stream2(o + j * 8, a[0] + bf_lo(u0), a[1] + bf_hi(u0));
            st_stream2(o + 2 * 2048 + j * 8, a[2] + bf_lo(u1), a[3] + bf_hi(u1));
        }
    }
    __syncwarp();
    release(c, c.p.stage);
    pipe_next(c.p);
}

#define TSTAMP(i)
__device__ __forceinline__ float2 cmul(float2 a, float2 b) { return make_float2(fmaf(a.x, b.x, -a.y * b.y), fmaf(a.x, b.y, a.y * b.x)); }
__device__ __forceinline__ float2 cfma(float2 a, float2 b, float2 u) { return make_float2(fmaf(a.x, b.x, fmaf(-a.y, b.y, u.x)), fmaf(a.x, b.y, fmaf(a.y, b.x, u.y))); }
__device__ __forceinline__ float4 ssm_coef(float lre, float lim, float logdt) {
    const float dt = __bfloat162float(__float2bfloat16(expf(logdt)));
    const float ea = expf(dt * lre);
    float sn, cn;
    sincosf(dt * lim, &sn, &cn);
    const float br = ea * cn, bi = ea * sn, nr = br - 1.f;
    float cr, ci;
    if (fabsf(lre) >= fabsf(lim)) { const float r = lim / lre, dn = lre + lim * r; cr = (nr + bi * r) / dn; ci = (bi - nr * r) / dn; }
    else { const float r = lre / lim, dn = lre * r + lim; cr = (nr * r + bi) / dn; ci = (bi * r - nr) / dn; }
    return make_float4(br, bi, cr, ci);
}
__device__ __forceinline__ void epi_a1(const float* acc, const Params& P, const Cons& c, Pend& d, int mb, int nb, uint32_t atag) {
    const int t = c.lane & 3;
    const int p = nb * 128 + c.rank * 64 + c.wg * 32 + c.wq * 8 + (c.lane >> 2);
    uint32_t cw[4];
    lds128(cw, c.sb + S_COEF + (p & 63) * 16);
    const float4 cf = make_float4(__uint_as_float(cw[0]), __uint_as_float(cw[1]), __uint_as_float(cw[2]), __uint_as_float(cw[3]));
    TSTAMP(1)
    const float2 lam = make_float2(cf.x, P.swap_ri ? -cf.y : cf.y);
    const float a0 = P.swap_ri ? -2.f * cf.w : 2.f * cf.z, a1 = P.swap_ri ? 2.f * cf.z : -2.f * cf.w;
    const float b0 = P.swap_ri ? -2.f * cf.z : -2.f * cf.w, b1 = P.swap_ri ? -2.f * cf.w : -2.f * cf.z;
    float2 h = make_float2(0.f, 0.f);
#pragma unroll
    for (int round = 0; round < 2; round++) {
#pragma unroll
        for (int j = 0; j < 32; j++) {
            h = cfma(lam, h, make_float2(acc[j * 4], acc[j * 4 + 2]));
            const float r0 = fmaf(a0, h.x, a1 * h.y), m0 = fmaf(b0, h.x, b1 * h.y);
            h = cfma(lam, h, make_float2(acc[j * 4 + 1], acc[j * 4 + 3]));
            d.pk[j * 2] = pack2(r0, fmaf(a0, h.x, a1 * h.y));
            d.pk[j * 2 + 1] = pack2(m0, fmaf(b0, h.x, b1 * h.y));
        }
        if (round) break;
        float2 l64 = lam;
#pragma unroll
        for (int i = 0; i < 6; i++) l64 = cmul(l64, l64);
        const float2 l128 = cmul(l64, l64), l256 = cmul(l128, l128);
        float2 o = make_float2(__shfl_up_sync(0xffffffffu, h.x, 1), __shfl_up_sync(0xffffffffu, h.y, 1));
        if (t >= 1) h = cfma(l64, o, h);
        o = make_float2(__shfl_up_sync(0xffffffffu, h.x, 2), __shfl_up_sync(0xffffffffu, h.y, 2));
        if (t >= 2) h = cfma(l128, o, h);
        TSTAMP(2)
        if (t == 3) st_relaxed2(&g_agg[mb * 1024 + p], (__float_as_uint(h.x) & ~1u) | atag, __float_as_uint(h.y));
        h = make_float2(__shfl_up_sync(0xffffffffu, h.x, 1), __shfl_up_sync(0xffffffffu, h.y, 1));
        if (t == 0) h = make_float2(0.f, 0.f);
        uint32_t ax[7], ay[7];
        int n = 0;
        while (true) {
            uint32_t bad = 0;
#pragma unroll
            for (int j = 0; j < 7; j++) { ax[j] = atag; ay[j] = 0; ld_relaxed2_if(ax[j], ay[j], &g_agg[j * 1024 + p], j < mb); }
#pragma unroll
            for (int j = 0; j < 7; j++) bad |= ax[j] ^ atag;
            if (tags_ok(bad)) break;
            __nanosleep(400);
            if (++n > SPIN_LIMIT) spin_fault();
        }
        float2 carry = make_float2(0.f, 0.f);
#pragma unroll
        for (int j = 0; j < 7; j++) if (j < mb) carry = cfma(l256, carry, make_float2(__uint_as_float(ax[j]), __uint_as_float(ay[j])));
        float2 w = (t & 1) ? l64 : make_float2(1.f, 0.f);
        if (t & 2) w = cmul(w, l128);
        h = cfma(w, carry, h);
        TSTAMP(3)
    }
    TSTAMP(4)
    d.kind = PEND_HT; d.row = nb * 128 + c.rank * 64 + c.wg * 32; d.col = mb * 256; d.cnt = C_HT + mb * 2 + (nb >> 2);
}

__device__ __forceinline__ uint32_t acquire_stage(uint32_t sb, Pipe& p, uint32_t bytes) {
    mbar_wait(sb + B_EMPTY + p.stage * 8, p.phase ^ 1);
    mbar_expect(sb + B_FULL + p.stage * 8, bytes);
    return p.stage;
}
__device__ __forceinline__ void watcher(const Params& P, const uint32_t sb, const int pair, const int rank, const int lane) {
    const uint32_t epoch = lds32(sb + S_EPOCH), e1 = epoch + 1;
    uint32_t met = 0;
#pragma unroll 1
    for (int it = ITEM_OFF(pair); it < ITEM_OFF(pair + 1); it++) {
        const int item = ITEM(it), type = item >> 8, mb = (item >> 5) & 7, nb = item & 31;
        const int n = (0x24021420 >> (type * 4)) & 7;
        for (int k = 0; (int)lds32(sb + S_CUR) < it - 1; k++) { __nanosleep(200); if (k > SPIN_LIMIT) spin_fault(); }
#pragma unroll 1
        for (int i = 0; i < n; i++) {
            int idx = n == 4 ? C_O + mb * 4 + i : C_HT + mb * 2 + i;
            uint32_t target = e1 * 16;
            if (type == T_A1) { idx = C_COEF; target = e1 * 4; }
            if (type == T_QA) {
                idx = i ? C_FLAG + (lane & 1) * 32 + nb * 2 + ((lane >> 1) & 1) : C_KV + mb;
                target = i ? epoch * 64 + mb * 8 + rank * 4 + 4 : e1 * 128;
            }
            if (lane < 4) { wait_count(&g_cnt(idx), target); fence_async(); }
            __syncwarp();
            if (lane == 0) asm volatile("st.release.cta.shared.u32 [%0], %1;" ::"r"(sb + S_DEP), "r"(++met) : "memory");
        }
    }
}
__device__ __forceinline__ bool dep_met(uint32_t sb, uint32_t n) { uint32_t v; asm volatile("ld.acquire.cta.shared.u32 %0, [%1];" : "=r"(v) : "r"(sb + S_DEP) : "memory"); return v >= n; }
__device__ __forceinline__ void dep_wait(uint32_t sb, uint32_t n) { for (int k = 0; !dep_met(sb, n); k++) { __nanosleep(32); if (k > SPIN_LIMIT * 8) spin_fault(); } }
__device__ __forceinline__ void producer(const Params& P, const uint32_t sb, const int pair, const int rank, const uint32_t epoch) {
    Pipe p = {0, 0};
    const uint32_t e1 = epoch + 1;
    uint32_t dep = 0;
    for (int it = ITEM_OFF(pair); it < ITEM_OFF(pair + 1); it++) {
        const int item = ITEM(it), type = item >> 8, mb = (item >> 5) & 7, nb = item & 31;
        sts32(sb + S_CUR, it);
        if (type == T_CHAIN) {
            if (pair < 16) {
#pragma unroll 1
                for (int s = 0; s < 63; s++) {
                    if (s == 0) mbar_wait(sb + B_GO, 0);
                    if (s >= 2) { mbar_wait(sb + B_KVGO + (s & 1) * 8, ((s >> 1) + 1) & 1); wait_time(gtime() + P.dk, sb); }
                    if (s == 0 && !DBGF(1)) { wait_count(&g_cnt(C_KV), e1 * 128); fence_async(); }
                    const uint32_t bar = sb + B_KVFULL + (s & 1) * 8, dst = sb + S_KV + (s & 1) * 16384;
                    if (DBGF(2)) { mbar_arrive(bar); continue; }
                    mbar_expect(bar, 16384);
#pragma unroll 1
                    for (int i = 0; i < 4; i++) tma2d(dst + i * 4096, &P.tm[M_KVO], (pair * 2 + rank) * 128 + (i & 1) * 64, (i >> 1) * 2048 + (DBGF(32 | 512) ? s & 7 : s) * 32, bar);
                    if (s < 62) {
                        if ((s & 7) == 7 && !DBGF(1)) { wait_count(&g_cnt(C_KV + 1 + (s >> 3)), e1 * 128); fence_async(); }
#pragma unroll 1
                        for (int i = 0; i < 4; i++) if (!DBGF(64)) tma_prefetch2d(&P.tm[M_KVO], (pair * 2 + rank) * 128 + (i & 1) * 64, (i >> 1) * 2048 + s * 32 + 32);
                    }
                }
            } else {
                uint32_t* flag = &g_cnt(C_FLAG + pair * 2 + rank - 32);
#pragma unroll 1
                for (int s = 0; s < 16; s++) {
                    mbar_wait(sb + B_PERS, s & 1);
                    if (!DBGF(8)) asm volatile("st.release.gpu.global.u32 [%0], %1;" ::"l"(flag), "r"(epoch * 64 + s * 4 + 4) : "memory");
                }
            }
            mbar_wait(sb + B_RESUME, 0);
            continue;
        }
        const int m0 = mb * 256 + rank * 128;
        if (type <= T_OP) {
            const CUtensorMap* ma = &P.tm[type == T_OP ? M_OA : M_BX];
            const CUtensorMap* mw = &P.tm[type == T_OP ? M_WO : type == T_QA ? M_WQ : nb < 16 ? M_WK : M_WV];
            const int nk = type == T_OP ? 64 : 16, nc = (nb & 15) * 4 + rank * 2, ma0 = type == T_OP ? 4096 + m0 : m0;
#pragma unroll 1
            for (int kt = 0; kt < nk; kt++) {
                if (type == T_OP && (kt & 15) == 0) dep_wait(sb, ++dep);
                if (DBGF(256) && pair >= NCHAIN) { acquire_stage(sb, p, 0); pipe_next(p); continue; }
                const uint32_t st = acquire_stage(sb, p, STAGE), bar = sb + B_FULL + st * 8;
                tma2d(sb + st * STAGE, ma, kt * 64, ma0, bar);
                tma3d_mc(sb + st * STAGE + 16384 + rank * 16384, mw, 0, kt * 64, nc, bar);
                if (type == T_QA && kt < 12 && dep_met(sb, dep + 1 + (kt >> 3))) {
                    if (kt < 8) tma_prefetch2d(&P.tm[M_OA], nb * 256 + (kt & 3) * 64, (kt >> 2) * 2048 + m0);
                    else {
                        const int o = ((mb * 8 + rank * 4 + (kt & 3)) * 32 + nb * 2) * 512;
                        l2_prefetch(g_km + o, 4096); l2_prefetch(g_vmt + o, 4096);
                    }
                }
                pipe_next(p);
            }
            if (type == T_QA) {
                dep += 2;
                dep_wait(sb, dep);
#pragma unroll 1
                for (int e = 0; e < 4; e++) {
                    const uint32_t st = acquire_stage(sb, p, 40960), bar = sb + B_FULL + st * 8, dst = sb + st * STAGE;
                    tma2d(dst, &P.tm[M_OA], nb * 256 + (e >> 1) * 128, (e & 1) * 2048 + m0, bar);
                    tma2d(dst + 16384, &P.tm[M_OA], nb * 256 + (e >> 1) * 128 + 64, (e & 1) * 2048 + m0, bar);
                    const uint32_t* src = ((e & 1) ? g_vmt : g_km) + ((mb * 8 + rank * 4) * 32 + nb * 2 + (e >> 1)) * 512;
#pragma unroll 1
                    for (int i = 0; i < 4; i++) bulk_g2s(dst + 32768 + i * 2048, src + i * 32 * 512, 2048, bar);
                    pipe_next(p);
                }
            }
        } else if (type == T_OPH) {
#pragma unroll 1
            for (int kt = 0; kt < 64; kt++) {
                if ((kt & 15) == 0) dep_wait(sb, ++dep);
                const uint32_t st = acquire_stage(sb, p, 32768), bar = sb + B_FULL + st * 8;
                tma2d(sb + st * STAGE, &P.tm[M_OA], kt * 64, 4096 + m0, bar);
                tma2d_mc(sb + st * STAGE + 16384 + rank * 8192, &P.tm[M_WOH], nb * 128 + rank * 64, kt * 64, bar);
                pipe_next(p);
            }
        } else if (type == T_A1) {
#pragma unroll 1
            for (int kt = 0; kt < 16; kt++) {
                if (kt == 15) dep_wait(sb, ++dep);
                const uint32_t st = acquire_stage(sb, p, kt == 15 ? STAGE + 1024 : STAGE), bar = sb + B_FULL + st * 8;
                if (kt == 15) bulk_g2s(sb + S_COEF, g_coef + nb * 128 + rank * 64, 1024, bar);
                tma4d(sb + st * STAGE, &P.tm[M_AB], kt * 64, nb * 16 + rank * 8, bar);
                tma4d_mc(sb + st * STAGE + 16384 + rank * 16384, &P.tm[M_AX], kt * 64, mb * 128 + rank * 16, bar);
                pipe_next(p);
            }
        } else {
            const int hw = type == T_A2H ? 64 : 128;
            const CUtensorMap* mc = &P.tm[type == T_A2H ? M_CREH : M_CRE];
#pragma unroll 1
            for (int kt = 0; kt < 32; kt++) {
                if ((kt & 15) == 0) dep_wait(sb, ++dep);
                const uint32_t st = acquire_stage(sb, p, 16384 + hw * 256), bar = sb + B_FULL + st * 8;
                tma3d(sb + st * STAGE, &P.tm[M_HT], 0, (kt & 1) * 1024 + (kt >> 1) * 64, mb * 4 + rank * 2, bar);
                tma2d_mc(sb + st * STAGE + 16384 + rank * hw * 128, mc + (kt & 1), (kt >> 1) * 64, (nb * 2 + rank) * hw, bar);
                pipe_next(p);
            }
#pragma unroll 1
            for (int col = nb * 2 * hw; col < (nb + 1) * 2 * hw; col += 128) {
                const uint32_t st = acquire_stage(sb, p, 32768 + 256), bar = sb + B_FULL + st * 8;
                tma4d(sb + st * STAGE, &P.tm[M_AX], col, mb * 128 + rank * 16, bar);
                tma4d(sb + st * STAGE + 16384, &P.tm[M_AX], col + 64, mb * 128 + rank * 16, bar);
                bulk_g2s(sb + st * STAGE + 32768, P.Dskip + col, 256, bar);
                pipe_next(p);
            }
        }
    }
}

__device__ __forceinline__ uint32_t fresh_tid() { uint32_t t; asm volatile("mov.u32 %0, %%tid.x;" : "=r"(t)); return t; }
__device__ __forceinline__ uint32_t fresh_ctaid() { uint32_t t; asm volatile("mov.u32 %0, %%ctaid.x;" : "=r"(t)); return logical_cta(t); }
__device__ __forceinline__ void reset_state(Cons& c, Pend& d, uint32_t sb, bool resumed) {
    const uint32_t t = fresh_tid(), b = fresh_ctaid();
    const int w = __shfl_sync(0xffffffffu, t >> 5, 0);
    c.sb = sb; c.wg = w >> 2; c.wq = w & 3; c.lane = t & 31;
    c.rank = __shfl_sync(0xffffffffu, b & 1, 0); c.pair = __shfl_sync(0xffffffffu, b >> 1, 0);
    c.rel = mapa(sb + B_EMPTY, cluster_rank() ^ (c.lane & 1));
    c.atag = (lds32(sb + S_EPOCH) + 1) & 1;
    c.p.stage = 0; c.p.phase = 0;
    c.nst = resumed && c.pair < NCHAIN ? 2 * NPRE : 0;
    d = Pend{};
}
#define PROF_ITEM(i)
#define PROF_MAIN(i)

__global__ void __launch_bounds__(384, 1) fused_kernel(const __grid_constant__ Params P) {
    extern __shared__ __align__(1024) uint8_t smem[];
    const uint32_t sb = smem_u32(smem);
    asm volatile("griddepcontrol.launch_dependents;");
    const int tid = threadIdx.x, lane = tid & 31;
    const int warp = __shfl_sync(0xffffffffu, tid >> 5, 0);
    const int pair = __shfl_sync(0xffffffffu, logical_cta(blockIdx.x) >> 1, 0), rank = __shfl_sync(0xffffffffu, blockIdx.x & 1, 0);
    if (tid == 0) {
        if (sb & 1023) spin_fault();
        sts32(sb + S_EPOCH, ld_relaxed1(&g_cnt(C_EPOCH)));
        sts32(sb + S_DEP, 0); sts32(sb + S_CUR, 0);
        for (int i = 0; i < NSTAGE; i++) { mbar_init(sb + B_FULL + i * 8, 1); mbar_init(sb + B_EMPTY + i * 8, 16); }
        mbar_init(sb + B_RESUME, 2);
        mbar_init(sb + B_KVFULL, 1); mbar_init(sb + B_KVFULL + 8, 1);
        mbar_init(sb + B_GO, 1); mbar_init(sb + B_KVGO, 1); mbar_init(sb + B_KVGO + 8, 1); mbar_init(sb + B_K, 1); mbar_init(sb + B_V, 1); mbar_init(sb + B_PERS, 8); mbar_init(sb + B_INIT, 8);
        mbar_init(sb + B_WO, 8);
        for (int i = 0; i < 2; i++) { mbar_init(sb + B_SFULL + i * 8, 4); mbar_init(sb + B_SFREE + i * 8, 1); }
        mbar_init(sb + B_RELA, 1); mbar_init(sb + B_RELB, 1);
        asm volatile("fence.mbarrier_init.release.cluster;" ::: "memory");
        if (pair < 16) mbar_expect(sb + B_K, 2048);
        mbar_expect(sb + B_V, 2048);
    }
    cluster_sync();
    if (warp >= 8) {
        asm volatile("setmaxnreg.dec.sync.aligned.u32 24;");
        if (warp == 9 && pair < 64) {
            const char* src = (const char*)(rank ? P.Wo : P.Wq) + (size_t)(pair * 32 + lane) * 4096;
            l2_prefetch(src, 4096);
        }
        if (warp == 9 && pair < NCHAIN) pacer(P, sb, lane, pair, rank);
        if (warp == 9) watcher(P, sb, pair, rank, lane);
        if (warp >= 10 && lane == 0) store_warp(P, sb, warp - 10);
        if (warp == 8) {
            if (lane == 0) producer(P, sb, pair, rank, lds32(sb + S_EPOCH));
            __syncwarp();
            asm volatile("barrier.cluster.arrive.relaxed.aligned;\nbarrier.cluster.wait.aligned;" ::: "memory");
        }
    } else {
        asm volatile("setmaxnreg.inc.sync.aligned.u32 240;");
        Cons c;
        Pend d;
        if (pair < NCHAIN) {
            reset_state(c, d, sb, false);
#pragma unroll 1
            for (int i = 0; i < NPRE; i++) {
                PROF_ITEM(i)
                const int item = ITEM(ITEM_OFF(pair) + i);
                float acc[128];
                mainloop<256, true>(acc, P, c, d, T_KV);
                epi_kv(acc, c, d, (item >> 5) & 7, item & 31);
            }
            ISTAMP(4)
            drain<0, true>(P, c, d);
            bar_sync(1, 256);
            chain_load1(P, sb, pair, rank, warp, lane, false);
            drain<1, true>(P, c, d);
            staging_wait(c);
            PROF_ITEM(NPRE)
            bar_sync(1, 256);
            chain_load1(P, sb, pair, rank, warp, lane, true);
            const int h = (pair & 15) * 2 + rank;
            if (pair < 16) chain_role<0>(P, sb, h, warp, lane);
            else if (pair < 32) chain_role<1>(P, sb, h, warp, lane);
            else chain_role<2>(P, sb, h, warp, lane);
            fence_async_smem();
            bar_sync(1, 256);
            const uint32_t t2 = fresh_tid();
            if (t2 < 2) mbar_arrive_cluster(mapa(sb + B_RESUME, cluster_rank() ^ t2));
        } else if (pair >= NPAIR - 2) {
            const int ch = (pair - (NPAIR - 2)) * 512 + rank * 256 + tid;
            g_coef[ch] = ssm_coef(__bfloat162float(P.Lre[ch]), __bfloat162float(P.Lim[ch]), __bfloat162float(P.logdt[ch]));
            bar_sync(1, 256);
            if (tid == 0) red_release(&g_cnt(C_COEF));
        }
        reset_state(c, d, sb, true);
        for (int it = ITEM_OFF(c.pair) + (c.pair < NCHAIN ? NPRE + 1 : 0);; it++) {
            const bool last = it == ITEM_OFF(c.pair + 1);
            if (d.kind != PEND_NONE && (last || !bar_and(5 + c.wg, mbar_test(sb + B_FULL + c.p.stage * 8, c.p.phase)))) drain_all(P, c, d);
            if (last) break;
            const int item = ITEM(it), type = item >> 8, mb = (item >> 5) & 7, nb = item & 31;
            PROF_ITEM(it - ITEM_OFF(c.pair))
            if (type >= T_OPH) {
                float acc[64];
                mainloop<128>(acc, P, c, d, type);
                PROF_MAIN(it - ITEM_OFF(c.pair))
                if (type == T_OPH) epi_oph(acc, c, d, mb, nb);
                else epi_a2_half<0>(acc, P, c, mb, nb * 128);
            } else {
                float acc[128];
                mainloop<256>(acc, P, c, d, type);
                PROF_MAIN(it - ITEM_OFF(c.pair))
                if (type == T_KV) epi_kv(acc, c, d, mb, nb);
                else if (type == T_QA) epi_qa(acc, c, d, mb, nb);
                else if (type == T_OP) epi_op(acc, c, d, mb, nb);
                else if (type == T_A1) epi_a1(acc, P, c, d, mb, nb, c.atag);
                else { epi_a2_half<0>(acc, P, c, mb, nb * 256); epi_a2_half<1>(acc, P, c, mb, nb * 256); }
            }
        }
        staging_wait(c);
        staging_post(c, PEND_NONE, 0, 0, 0);
        cluster_sync();
        if (c.wg == 0 && c.wq == 0 && c.lane == 0 && atomicInc(&g_cnt(C_DONE), DBGF(32) ? 95 : NPAIR * 2 - 1) == (DBGF(32) ? 95 : NPAIR * 2 - 1)) atomicAdd(&g_cnt(C_EPOCH), 1);
    }
}

typedef CUresult (*EncodeFn)(CUtensorMap*, CUtensorMapDataType, cuuint32_t, void*, const cuuint64_t*, const cuuint64_t*, const cuuint32_t*, const cuuint32_t*,
                             CUtensorMapInterleave, CUtensorMapSwizzle, CUtensorMapL2promotion, CUtensorMapFloatOOBfill);
void encode(EncodeFn fn, CUtensorMap* m, const void* base, int rank, const uint64_t* dims, const uint64_t* strides, const uint32_t* box, CUtensorMapSwizzle swz = CU_TENSOR_MAP_SWIZZLE_128B) {
    cuuint64_t d[5], s[5]; cuuint32_t b[5], e[5];
    for (int i = 0; i < rank; i++) { d[i] = dims[i]; b[i] = box[i]; e[i] = 1; if (i) s[i - 1] = strides[i - 1]; }
    fn(m, CU_TENSOR_MAP_DATA_TYPE_BFLOAT16, rank, (void*)base, d, s, b, e, CU_TENSOR_MAP_INTERLEAVE_NONE, swz,
       CU_TENSOR_MAP_L2_PROMOTION_L2_256B, CU_TENSOR_MAP_FLOAT_OOB_FILL_NONE);
}
void map_kmajor(EncodeFn fn, CUtensorMap* m, const void* base, uint64_t rows, uint64_t cols, uint32_t box_rows) {
    const uint64_t d[2] = {cols, rows}, s[1] = {cols * 2}; const uint32_t b[2] = {64, box_rows};
    encode(fn, m, base, 2, d, s, b);
}
void map_mnmajor(EncodeFn fn, CUtensorMap* m, const void* base, uint64_t krows, uint64_t cols) {
    const uint64_t d[3] = {64, krows, cols / 64}, s[2] = {cols * 2, 128}; const uint32_t b[3] = {64, 64, 2};
    encode(fn, m, base, 3, d, s, b);
}

}

extern "C" void kernel_launch(void* const* d_in, const int* in_sizes, int n_in, void* d_out, int out_size) {
    static Params P;
    static EncodeFn fn = nullptr;
    if (!fn) {
        cudaDriverEntryPointQueryResult q;
        cudaGetDriverEntryPoint("cuTensorMapEncodeTiled", (void**)&fn, cudaEnableDefault, &q);
        cudaFuncSetAttribute(fused_kernel, cudaFuncAttributeMaxDynamicSharedMemorySize, S_TOTAL);
    }
    const bf16* in[15];
    for (int i = 0; i < 15; i++) in[i] = (const bf16*)d_in[i];
    void *kvo, *ht, *gm;
    cudaGetSymbolAddress(&gm, g_m);
    P.gm = (uint8_t*)(((uintptr_t)gm + 32767) & ~(uintptr_t)32767);
    cudaGetSymbolAddress(&kvo, g_kvo);
    cudaGetSymbolAddress(&ht, g_ht);
    map_kmajor(fn, &P.tm[M_BX], in[9], 2048, 1024, 128);
    map_mnmajor(fn, &P.tm[M_WQ], in[11], 1024, 4096);
    map_mnmajor(fn, &P.tm[M_WK], in[12], 1024, 4096);
    map_mnmajor(fn, &P.tm[M_WV], in[13], 1024, 4096);
    map_mnmajor(fn, &P.tm[M_WO], in[14], 4096, 1024);
    map_kmajor(fn, &P.tm[M_OA], kvo, 3 * 2048, 4096, 128);
    P.swap_ri = in[4] < in[3];
    {
        const bf16* lo = P.swap_ri ? in[4] : in[3];
        const uint64_t diff = (uint64_t)((const char*)(P.swap_ri ? in[3] : in[4]) - (const char*)lo);
        const uint64_t d[4] = {1024, 8, 2, 128}, s[3] = {2048, diff, 16384}; const uint32_t b[4] = {64, 8, 2, 8};
        encode(fn, &P.tm[M_AB], lo, 4, d, s, b);
    }
    {
        const uint64_t d[4] = {1024, 2, 4, 1024}, s[3] = {2048, 64 * 2048, 4096}; const uint32_t b[4] = {64, 2, 4, 16};
        encode(fn, &P.tm[M_AX], in[0], 4, d, s, b);
    }
    map_mnmajor(fn, &P.tm[M_HT], ht, 2048, 2048);
    map_kmajor(fn, &P.tm[M_CRE], in[5], 1024, 1024, 128);
    map_kmajor(fn, &P.tm[M_CIM], in[6], 1024, 1024, 128);
    map_kmajor(fn, &P.tm[M_KVO], kvo, 3 * 2048, 4096, 32);
    map_kmajor(fn, &P.tm[M_HTS], ht, 2048, 2048, 32);
    map_kmajor(fn, &P.tm[M_WOH], in[14], 4096, 1024, 64);
    map_kmajor(fn, &P.tm[M_CREH], in[5], 1024, 1024, 64);
    map_kmajor(fn, &P.tm[M_CIMH], in[6], 1024, 1024, 64);
    for (int i = 0; i < 3; i++) map_kmajor(fn, &P.tm[M_CQ + i], in[11 + i], 1024, 4096, 8);
    for (int e = 0; e < 2; e++) {
        const uint64_t d[4] = {1024, 2, 4, 256}, s[3] = {8 * 2048, 2 * 2048, 16 * 2048}; const uint32_t b[4] = {64, 2, 4, 8};
        encode(fn, &P.tm[M_CO + e], in[14] + e * 1024, 4, d, s, b);
    }
    P.Wq = in[11]; P.Wk = in[12]; P.Wv = in[13]; P.Wo = in[14]; P.mem0 = in[10];
    P.Lre = in[1]; P.Lim = in[2]; P.logdt = in[7]; P.Dskip = in[8];
    P.out = (float*)d_out;
    P.two26 = 1u << 26;
    P.ds = 400; P.da = 1072; P.db = 1280; P.dk = 500; P.dv = 64; P.tight = 200; P.extra = 0;
    for (int i = 0; i < (DBGF(32) ? 1 : 2); i++) {
        cudaLaunchConfig_t cfg = {};
        cfg.gridDim = dim3(i ? 36 : 96); cfg.blockDim = dim3(384); cfg.dynamicSmemBytes = S_TOTAL; cfg.stream = cudaStreamPerThread;
        cudaLaunchAttribute at[2];
        at[0].id = cudaLaunchAttributeClusterDimension; at[0].val.clusterDim.x = i ? 2 : 6; at[0].val.clusterDim.y = at[0].val.clusterDim.z = 1;
        at[1].id = cudaLaunchAttributeProgrammaticStreamSerialization; at[1].val.programmaticStreamSerializationAllowed = 1;
        cfg.attrs = at; cfg.numAttrs = 1 + i;
        cudaLaunchKernelEx(&cfg, fused_kernel, P);
    }
}
```

```cpp
#include <cuda_runtime.h>
#include <cuda_bf16.h>
#include <cuda.h>
#include <stdint.h>
#include <string.h>

typedef __nv_bfloat16 bf16;

namespace {

#define POLL 200
constexpr int SPIN_LIMIT = 1 << 22;
constexpr int NPAIR = 66;
constexpr int NCHAIN = 48;
enum { T_KV = 0, T_QA = 1, T_OP = 2, T_A1 = 3, T_A2 = 4, T_CHAIN = 5, T_OPH = 6, T_A2H = 7 };
enum { M_BX = 0, M_WQ, M_WK, M_WV, M_WO, M_OA, M_AB, M_AX, M_HT, M_CRE, M_CIM, M_KVO, M_HTS, M_WOH, M_CREH, M_CIMH, M_CQ, M_CK, M_CV, M_CO, M_CO1, M_KV4, M_COUNT };
enum { C_KV = 0, C_HT = 8, C_DONE = 24, C_EPOCH = 25, C_COEF = 26, C_FLAG = 32, C_O = 96 };

struct Params {
    CUtensorMap tm[M_COUNT];
    const bf16 *Wq, *Wk, *Wv, *Wo, *mem0, *Lre, *Lim, *logdt, *Dskip;
    float* out;
    uint8_t* gm;
    int swap_ri, zero;
    uint32_t two26;
    int ds, da, db, dk, dv, back, ds0, pf0, pf1, dc, extra;
    float alpha;
#define DBGF(x) false
};

constexpr int NPRE = 1;
__constant__ uint16_t c_off[67] = {0, 4, 8, 12, 16, 20, 24, 28, 32, 37, 42, 47, 52, 57, 62, 67, 72, 77, 82, 87, 92, 97, 102, 107, 112, 117, 122, 127, 132, 136, 140, 144, 148, 152, 156, 160, 164, 168, 172, 176, 180, 184, 188, 192, 196, 200, 204, 209, 214, 234, 254, 274, 294, 314, 334, 354, 374, 393, 412, 430, 448, 466, 484, 502, 520, 540, 560};
__constant__ uint16_t c_items[640] = {
    0, 1280, 452, 704, 33, 1280, 453, 705, 3, 1280, 454, 706, 36, 1280, 455, 707, 6, 1280, 456, 736, 39, 1280, 457, 737,
    9, 1280, 458, 738, 42, 1280, 459, 739, 12, 1280, 460, 898, 1120, 45, 1280, 461, 899, 1121, 15, 1280, 462, 900, 1122, 48,
    1280, 463, 901, 1123, 18, 1280, 480, 902, 1152, 51, 1280, 481, 903, 1153, 21, 1280, 482, 928, 1154, 54, 1280, 483, 929, 1155,
    32, 1280, 484, 930, 1184, 2, 1280, 485, 931, 1185, 35, 1280, 486, 932, 1186, 5, 1280, 487, 933, 1187, 38, 1280, 488, 934,
    1216, 8, 1280, 489, 935, 1217, 41, 1280, 490, 960, 1218, 11, 1280, 491, 961, 1219, 44, 1280, 492, 962, 1248, 14, 1280, 493,
    963, 1249, 47, 1280, 494, 964, 1250, 17, 1280, 495, 965, 1251, 50, 1280, 768, 546, 20, 1280, 769, 547, 53, 1280, 770, 576,
    23, 1280, 771, 577, 1, 1280, 772, 578, 34, 1280, 773, 579, 4, 1280, 774, 608, 37, 1280, 775, 609, 7, 1280, 800, 610,
    40, 1280, 801, 611, 10, 1280, 802, 640, 43, 1280, 803, 641, 13, 1280, 804, 642, 46, 1280, 805, 643, 16, 1280, 806, 672,
    49, 1280, 807, 673, 19, 1280, 832, 674, 52, 1280, 833, 675, 22, 1280, 834, 896, 1026, 55, 1280, 835, 897, 1027, 24, 66,
    84, 102, 256, 124, 288, 144, 162, 180, 198, 208, 226, 244, 334, 384, 418, 836, 966, 1056, 56, 67, 85, 103, 257, 125,
    289, 145, 163, 181, 199, 209, 227, 245, 335, 385, 419, 837, 967, 1057, 25, 68, 86, 104, 258, 126, 290, 146, 164, 182,
    200, 210, 228, 246, 352, 386, 420, 838, 992, 1058, 57, 69, 87, 105, 259, 127, 291, 147, 165, 183, 201, 211, 229, 247,
    353, 387, 421, 839, 993, 1059, 26, 70, 88, 106, 260, 128, 292, 148, 166, 184, 202, 212, 230, 248, 354, 388, 422, 864,
    994, 1088, 58, 71, 89, 107, 261, 129, 293, 149, 167, 185, 203, 213, 231, 249, 355, 389, 423, 865, 995, 1089, 27, 72,
    90, 108, 262, 130, 294, 150, 168, 186, 204, 214, 232, 250, 356, 390, 424, 866, 996, 1090, 59, 73, 91, 109, 263, 131,
    295, 151, 169, 187, 205, 215, 233, 251, 357, 391, 425, 867, 997, 1091, 28, 74, 92, 110, 264, 132, 296, 152, 170, 188,
    320, 218, 236, 254, 360, 394, 428, 870, 1024, 60, 75, 93, 111, 265, 133, 297, 153, 171, 189, 321, 219, 237, 255, 361,
    395, 429, 871, 1025, 29, 76, 94, 112, 266, 134, 298, 154, 172, 190, 322, 220, 238, 328, 362, 396, 430, 512, 61, 77,
    95, 113, 267, 135, 299, 155, 173, 191, 323, 221, 239, 329, 363, 397, 431, 513, 30, 78, 96, 114, 268, 136, 300, 156,
    174, 192, 324, 222, 240, 330, 364, 398, 448, 514, 62, 79, 97, 115, 269, 137, 301, 157, 175, 193, 325, 223, 241, 331,
    365, 399, 449, 515, 31, 80, 98, 116, 270, 138, 302, 158, 176, 194, 326, 224, 242, 332, 366, 416, 450, 544, 63, 81,
    99, 117, 271, 139, 303, 159, 177, 195, 327, 225, 243, 333, 367, 417, 451, 545, 64, 82, 100, 118, 120, 122, 140, 142,
    160, 178, 196, 206, 216, 234, 252, 358, 392, 426, 868, 998, 65, 83, 101, 119, 121, 123, 141, 143, 161, 179, 197, 207,
    217, 235, 253, 359, 393, 427, 869, 999,
};
#define ITEM_OFF(p) c_off[p]
#define ITEM(i) c_items[i]

__device__ __align__(1024) bf16 g_kvo[3 * 2048 * 4096];
__device__ __align__(1024) bf16 g_ht[2048 * 2048];
__device__ __align__(1024) uint8_t g_m[9 * 32768];
__device__ __align__(1024) uint8_t g_f[8 * 49152];
__device__ __align__(1024) uint32_t g_km[64 * 32 * 512];
__device__ __align__(1024) uint32_t g_vmt[64 * 32 * 512];
__device__ __align__(1024) float2 g_agg[8 * 1024];
__device__ __align__(1024) float4 g_coef[1024];
__device__ __align__(1024) uint32_t g_cntl[128 * 32];
#define g_cnt(i) g_cntl[(i) * 32]
__device__ __align__(1024) uint32_t g_hint[6144 + 96];
#define SSTAMP(i, cond)
#define PROF(i)
#define GT_EDGE(o)
constexpr int M_SLOT = 32768, F_SLOT = 49152;

constexpr int STAGE = 49152, NSTAGE = 4;
constexpr int S_STG = NSTAGE * STAGE;
constexpr int S_BAR = S_STG + 32768;
constexpr int B_FULL = S_BAR, B_EMPTY = S_BAR + 32, B_RESUME = S_BAR + 64, B_KVFULL = S_BAR + 72, B_GO = S_BAR + 88, B_K = S_BAR + 96, B_PERS = S_BAR + 104, B_INIT = S_BAR + 112, B_RELA = S_BAR + 120, B_V = S_BAR + 128, B_WO = S_BAR + 136,
              B_SFULL = S_BAR + 144, B_SFREE = S_BAR + 160, S_DESC = S_BAR + 176, S_REDO = S_BAR + 256 + 512 + 64, S_EPOCH = S_BAR + 208, B_RELB = S_BAR + 216, B_KVGO = S_BAR + 224, S_DEP = S_BAR + 240, S_CUR = S_BAR + 244, S_TAIL = S_BAR + 248, S_CTA = S_BAR + 252;
constexpr int S_COEF = S_BAR + 256 + 512, S_TOTAL = S_COEF + 1024;
constexpr int S_W1 = 0;
constexpr int S_O = 24 * 4096, S_VL = S_O + 2048, S_MX = 25 * 4096, S_SC = S_MX + 64, S_SUM = S_MX + 128;
constexpr int S_KL = 26 * 4096;
constexpr int S_W2 = 27 * 4096;
constexpr int S_KV = S_W2 + 65536;
constexpr int S_P1 = S_W2 + 98304;
constexpr int S_QX = S_P1 + 16384;
constexpr int S_SX = S_QX + 2048;
static_assert(S_SX + 1280 <= S_BAR, "chain smem overlaps barriers");
constexpr int NR = 40, NS = 64 - NR;

__device__ __forceinline__ uint32_t logical_cta(uint32_t b) {
    const uint32_t c = b / 6, r = b - c * 6;
    return gridDim.x != 96 ? 96 + b : ((r >> 1) + (c >= 8) + (c >= 15)) % 3 * 32 + c * 2 + (r & 1);
}
__device__ __forceinline__ uint32_t cluster_rank() { uint32_t r; asm("mov.u32 %0, %%cluster_ctarank;" : "=r"(r)); return r; }
__device__ __forceinline__ uint16_t pair_mask() { return (uint16_t)(3u << (cluster_rank() & 6)); }
__device__ __forceinline__ void spin_fault() { asm volatile("st.global.u32 [%0], 0;" ::"l"(0ull) : "memory"); }
__device__ __forceinline__ uint32_t smem_u32(const void* p) { return (uint32_t)__cvta_generic_to_shared(p); }
__device__ __forceinline__ uint32_t opq(uint32_t x, int lane) { return __shfl_sync(0xffffffffu, x, lane); }
__device__ __forceinline__ uint32_t mapa(uint32_t a, uint32_t r) { uint32_t d; asm volatile("mapa.shared::cluster.u32 %0, %1, %2;" : "=r"(d) : "r"(a), "r"(r)); return d; }
__device__ __forceinline__ void mma16816(float* d, uint32_t a0, uint32_t a1, uint32_t a2, uint32_t a3, uint32_t b0, uint32_t b1) {
    asm("mma.sync.aligned.m16n8k16.row.col.f32.bf16.bf16.f32 {%0,%1,%2,%3}, {%4,%5,%6,%7}, {%8,%9}, {%0,%1,%2,%3};"
        : "+f"(d[0]), "+f"(d[1]), "+f"(d[2]), "+f"(d[3]) : "r"(a0), "r"(a1), "r"(a2), "r"(a3), "r"(b0), "r"(b1));
}
__device__ __forceinline__ void mma1688(float* d, uint32_t a0, uint32_t a1, uint32_t b0) {
    asm("mma.sync.aligned.m16n8k8.row.col.f32.bf16.bf16.f32 {%0,%1,%2,%3}, {%4,%5}, {%6}, {%0,%1,%2,%3};"
        : "+f"(d[0]), "+f"(d[1]), "+f"(d[2]), "+f"(d[3]) : "r"(a0), "r"(a1), "r"(b0));
}
__device__ __forceinline__ void ldsm4(uint32_t* r, uint32_t a) {
    asm volatile("ldmatrix.sync.aligned.m8n8.x4.shared.b16 {%0,%1,%2,%3}, [%4];" : "=r"(r[0]), "=r"(r[1]), "=r"(r[2]), "=r"(r[3]) : "r"(a));
}
__device__ __forceinline__ void ldsm4t(uint32_t* r, uint32_t a) {
    asm volatile("ldmatrix.sync.aligned.m8n8.x4.trans.shared.b16 {%0,%1,%2,%3}, [%4];" : "=r"(r[0]), "=r"(r[1]), "=r"(r[2]), "=r"(r[3]) : "r"(a));
}
__device__ __forceinline__ void stsm4(uint32_t a, uint32_t r0, uint32_t r1, uint32_t r2, uint32_t r3) {
    asm volatile("stmatrix.sync.aligned.m8n8.x4.shared.b16 [%0], {%1,%2,%3,%4};" ::"r"(a), "r"(r0), "r"(r1), "r"(r2), "r"(r3) : "memory");
}
__device__ __forceinline__ void stsm4t(uint32_t a, uint32_t r0, uint32_t r1, uint32_t r2, uint32_t r3) {
    asm volatile("stmatrix.sync.aligned.m8n8.x4.trans.shared.b16 [%0], {%1,%2,%3,%4};" ::"r"(a), "r"(r0), "r"(r1), "r"(r2), "r"(r3) : "memory");
}
__device__ __forceinline__ uint32_t pack2(float lo, float hi) { uint32_t d; asm("cvt.rn.bf16x2.f32 %0, %1, %2;" : "=r"(d) : "f"(hi), "f"(lo)); return d; }
__device__ __forceinline__ float bf_lo(uint32_t u) { return __uint_as_float(u << 16); }
__device__ __forceinline__ float bf_hi(uint32_t u) { return __uint_as_float(u & 0xffff0000u); }
__device__ __forceinline__ uint32_t hmul2(uint32_t a, uint32_t b) { uint32_t d; asm("mul.rn.bf16x2 %0, %1, %2;" : "=r"(d) : "r"(a), "r"(b)); return d; }
__device__ __forceinline__ float ex2(float x) { float y; asm("ex2.approx.ftz.f32 %0, %1;" : "=f"(y) : "f"(x)); return y; }
__device__ __forceinline__ float rcp(float x) { float y; asm("rcp.approx.ftz.f32 %0, %1;" : "=f"(y) : "f"(x)); return y; }
__device__ __forceinline__ void st_relaxed4(const void* p, uint32_t a, uint32_t b, uint32_t c, uint32_t d) {
    asm volatile("{\n.reg .b128 t;\nmov.b128 t, {%1,%2,%3,%4};\nst.relaxed.gpu.global.b128 [%0], t;\n}" ::"l"(p), "r"(a), "r"(b), "r"(c), "r"(d) : "memory");
}
__device__ __forceinline__ void st_relaxed2(const void* p, uint32_t a, uint32_t b) {
    asm volatile("{\n.reg .b64 t;\nmov.b64 t, {%1,%2};\nst.relaxed.gpu.global.b64 [%0], t;\n}" ::"l"(p), "r"(a), "r"(b) : "memory");
}
__device__ __forceinline__ void ld_relaxed2_if(uint32_t& a, uint32_t& b, const void* p, bool on) {
    asm volatile("{\n.reg .pred P;\n.reg .b64 t;\nsetp.ne.u32 P, %3, 0;\nmov.b64 t, {%0,%1};\n@P ld.relaxed.gpu.global.b64 t, [%2];\nmov.b64 {%0,%1}, t;\n}" : "+r"(a), "+r"(b) : "l"(p), "r"((uint32_t)on) : "memory");
}
__device__ __forceinline__ uint32_t ld_relaxed1(const void* p) { uint32_t v; asm volatile("ld.relaxed.gpu.global.u32 %0, [%1];" : "=r"(v) : "l"(p) : "memory"); return v; }
__device__ __forceinline__ void st_relaxed1(const void* p, uint32_t v) { asm volatile("st.relaxed.gpu.global.u32 [%0], %1;" ::"l"(p), "r"(v) : "memory"); }
__device__ __forceinline__ uint32_t ld_acquire(const void* p) { uint32_t v; asm volatile("ld.acquire.gpu.global.u32 %0, [%1];" : "=r"(v) : "l"(p) : "memory"); return v; }
__device__ __forceinline__ void red_release(void* p) { asm volatile("red.release.gpu.global.add.u32 [%0], 1;" ::"l"(p) : "memory"); }
__device__ __forceinline__ void st_stream2(float* p, float a, float b) { asm volatile("st.global.cs.v2.f32 [%0], {%1, %2};" ::"l"(p), "f"(a), "f"(b) : "memory"); }
__device__ __forceinline__ void fence_acquire() { asm volatile("fence.acquire.gpu;" ::: "memory"); }
__device__ __forceinline__ void fence_release() { asm volatile("fence.release.gpu;" ::: "memory"); }
__device__ __forceinline__ void fence_async() {  asm volatile("fence.proxy.async.global;" ::: "memory"); }
__device__ __forceinline__ void fence_async_smem() { asm volatile("fence.proxy.async.shared::cta;" ::: "memory"); }
__device__ __forceinline__ void wait_count(const uint32_t* p, uint32_t target) {
    int n = 0;
    while ((int32_t)(ld_acquire(p) - target) < 0) { __nanosleep(POLL); if (++n > SPIN_LIMIT) spin_fault(); }
}
__device__ __forceinline__ void bar_sync(int id, int n) { asm volatile("bar.sync %0, %1;" ::"r"(id), "r"(n) : "memory"); }
__device__ __forceinline__ void bar_arrive(int id, int n) { asm volatile("bar.arrive %0, %1;" ::"r"(id), "r"(n) : "memory"); }
__device__ __forceinline__ bool bar_and(int id, bool v) {
    uint32_t r;
    asm volatile("{\n.reg .pred P, Q;\nsetp.ne.u32 Q, %2, 0;\nbar.red.and.pred P, %1, 128, Q;\nselp.u32 %0, 1, 0, P;\n}" : "=r"(r) : "r"(id), "r"((uint32_t)v) : "memory");
    return r;
}
__device__ __forceinline__ void lds128(uint32_t* v, uint32_t a) { asm volatile("ld.shared.v4.b32 {%0,%1,%2,%3}, [%4];" : "=r"(v[0]), "=r"(v[1]), "=r"(v[2]), "=r"(v[3]) : "r"(a) : "memory"); }
__device__ __forceinline__ uint32_t lds32(uint32_t a) { uint32_t v; asm volatile("ld.shared.b32 %0, [%1];" : "=r"(v) : "r"(a) : "memory"); return v; }
__device__ __forceinline__ void lds64f(float* v, uint32_t a) { asm volatile("ld.shared.v2.f32 {%0,%1}, [%2];" : "=f"(v[0]), "=f"(v[1]) : "r"(a) : "memory"); }
__device__ __forceinline__ void sts128(uint32_t a, const uint32_t* v) { asm volatile("st.shared.v4.b32 [%0], {%1,%2,%3,%4};" ::"r"(a), "r"(v[0]), "r"(v[1]), "r"(v[2]), "r"(v[3]) : "memory"); }
__device__ __forceinline__ void sts64(uint32_t a, uint32_t x, uint32_t y) { asm volatile("st.shared.v2.b32 [%0], {%1,%2};" ::"r"(a), "r"(x), "r"(y) : "memory"); }
__device__ __forceinline__ void sts32(uint32_t a, uint32_t x) { asm volatile("st.shared.b32 [%0], %1;" ::"r"(a), "r"(x) : "memory"); }
__device__ __forceinline__ bool mbar_try(uint32_t b, uint32_t par) {
    uint32_t ok;
    asm volatile("{\n.reg .pred P;\nmbarrier.try_wait.parity.shared::cta.b64 P, [%1], %2;\nselp.u32 %0, 1, 0, P;\n}" : "=r"(ok) : "r"(b), "r"(par) : "memory");
    return ok;
}
__device__ __forceinline__ bool mbar_test(uint32_t b, uint32_t par) {
    uint32_t ok;
    asm volatile("{\n.reg .pred P;\nmbarrier.test_wait.parity.shared::cta.b64 P, [%1], %2;\nselp.u32 %0, 1, 0, P;\n}" : "=r"(ok) : "r"(b), "r"(par) : "memory");
    return ok;
}
__device__ __forceinline__ void mbar_wait(uint32_t b, uint32_t par) { int n = 0; while (!mbar_try(b, par)) { if (++n > SPIN_LIMIT) spin_fault(); } }
__device__ __forceinline__ void mbar_init(uint32_t b, uint32_t n) { asm volatile("mbarrier.init.shared::cta.b64 [%0], %1;" ::"r"(b), "r"(n) : "memory"); }
__device__ __forceinline__ void mbar_expect(uint32_t b, uint32_t bytes) { asm volatile("mbarrier.arrive.expect_tx.shared::cta.b64 _, [%0], %1;" ::"r"(b), "r"(bytes) : "memory"); }
__device__ __forceinline__ void mbar_arrive(uint32_t b) { asm volatile("mbarrier.arrive.shared::cta.b64 _, [%0];" ::"r"(b) : "memory"); }
__device__ __forceinline__ void mbar_arrive_cluster(uint32_t b) { asm volatile("mbarrier.arrive.shared::cluster.b64 _, [%0];" ::"r"(b) : "memory"); }
__device__ __forceinline__ void st_async1(uint32_t a, uint32_t x, uint32_t bar) {
    asm volatile("st.async.weak.shared::cluster.mbarrier::complete_tx::bytes.b32 [%0], %1, [%2];" ::"r"(a), "r"(x), "r"(bar) : "memory");
}
__device__ __forceinline__ void st_async2(uint32_t a, uint32_t x, uint32_t y, uint32_t bar) {
    asm volatile("st.async.weak.shared::cluster.mbarrier::complete_tx::bytes.v2.b32 [%0], {%1,%2}, [%3];" ::"r"(a), "r"(x), "r"(y), "r"(bar) : "memory");
}
__device__ __forceinline__ void cluster_sync() { asm volatile("barrier.cluster.arrive.aligned;\nbarrier.cluster.wait.aligned;" ::: "memory"); }
__device__ __forceinline__ void tma2d(uint32_t dst, const CUtensorMap* m, int c0, int c1, uint32_t bar) {
    asm volatile("cp.async.bulk.tensor.2d.shared::cluster.global.mbarrier::complete_tx::bytes [%0], [%1, {%2, %3}], [%4];" ::"r"(dst), "l"(m), "r"(c0), "r"(c1), "r"(bar) : "memory");
}
__device__ __forceinline__ void tma2d_mc(uint32_t dst, const CUtensorMap* m, int c0, int c1, uint32_t bar) {
    asm volatile("cp.async.bulk.tensor.2d.shared::cluster.global.mbarrier::complete_tx::bytes.multicast::cluster [%0], [%1, {%2, %3}], [%4], %5;" ::"r"(dst), "l"(m), "r"(c0), "r"(c1), "r"(bar), "h"(pair_mask()) : "memory");
}
__device__ __forceinline__ void tma3d(uint32_t dst, const CUtensorMap* m, int c0, int c1, int c2, uint32_t bar) {
    asm volatile("cp.async.bulk.tensor.3d.shared::cluster.global.mbarrier::complete_tx::bytes [%0], [%1, {%2, %3, %4}], [%5];" ::"r"(dst), "l"(m), "r"(c0), "r"(c1), "r"(c2), "r"(bar) : "memory");
}
__device__ __forceinline__ void tma3d_mc(uint32_t dst, const CUtensorMap* m, int c0, int c1, int c2, uint32_t bar) {
    asm volatile("cp.async.bulk.tensor.3d.shared::cluster.global.mbarrier::complete_tx::bytes.multicast::cluster [%0], [%1, {%2, %3, %4}], [%5], %6;" ::"r"(dst), "l"(m), "r"(c0), "r"(c1), "r"(c2), "r"(bar), "h"(pair_mask()) : "memory");
}
__device__ __forceinline__ void tma4d(uint32_t dst, const CUtensorMap* m, int c0, int c3, uint32_t bar) {
    asm volatile("cp.async.bulk.tensor.4d.shared::cluster.global.mbarrier::complete_tx::bytes [%0], [%1, {%2, 0, 0, %3}], [%4];" ::"r"(dst), "l"(m), "r"(c0), "r"(c3), "r"(bar) : "memory");
}
__device__ __forceinline__ void tma4d_mc(uint32_t dst, const CUtensorMap* m, int c0, int c3, uint32_t bar) {
    asm volatile("cp.async.bulk.tensor.4d.shared::cluster.global.mbarrier::complete_tx::bytes.multicast::cluster [%0], [%1, {%2, 0, 0, %3}], [%4], %5;" ::"r"(dst), "l"(m), "r"(c0), "r"(c3), "r"(bar), "h"(pair_mask()) : "memory");
}
__device__ __forceinline__ void tma_prefetch2d(const CUtensorMap* m, int c0, int c1) {
    asm volatile("cp.async.bulk.prefetch.tensor.2d.L2.global [%0, {%1, %2}];" ::"l"(m), "r"(c0), "r"(c1) : "memory");
}
__device__ __forceinline__ void map_prefetch(const CUtensorMap* m) { asm volatile("prefetch.tensormap [%0];" ::"l"(m) : "memory"); }
__device__ __forceinline__ void l2_prefetch(const void* src, uint32_t bytes) { asm volatile("cp.async.bulk.prefetch.L2.global [%0], %1;" ::"l"(src), "r"(bytes) : "memory"); }
__device__ __forceinline__ void bulk_g2s(uint32_t dst, const void* src, uint32_t bytes, uint32_t bar) {
    asm volatile("cp.async.bulk.shared::cluster.global.mbarrier::complete_tx::bytes [%0], [%1], %2, [%3];" ::"r"(dst), "l"(src), "r"(bytes), "r"(bar) : "memory");
}
__device__ __forceinline__ void tma_store2d(const CUtensorMap* m, int c0, int c1, uint32_t src) {
    asm volatile("cp.async.bulk.tensor.2d.global.shared::cta.bulk_group [%0, {%1, %2}], [%3];" ::"l"(m), "r"(c0), "r"(c1), "r"(src) : "memory");
}
__device__ __forceinline__ void bulk_commit() { asm volatile("cp.async.bulk.commit_group;" ::: "memory"); }
__device__ __forceinline__ void bulk_wait_read() { asm volatile("cp.async.bulk.wait_group.read 0;" ::: "memory"); }
__device__ __forceinline__ void bulk_wait_all() { asm volatile("cp.async.bulk.wait_group 0;" ::: "memory"); }
__device__ __forceinline__ uint64_t mkdesc(uint32_t addr, uint32_t lbo, uint32_t sbo, uint32_t swz) {
    return (uint64_t)((addr & 0x3FFFF) >> 4) | ((uint64_t)(lbo >> 4) << 16) | ((uint64_t)(sbo >> 4) << 32) | ((uint64_t)swz << 62);
}
__device__ __forceinline__ void wg_fence() { asm volatile("wgmma.fence.sync.aligned;" ::: "memory"); }
__device__ __forceinline__ void wg_commit() { asm volatile("wgmma.commit_group.sync.aligned;" ::: "memory"); }
template <int N> __device__ __forceinline__ void wg_wait() { asm volatile("wgmma.wait_group.sync.aligned %0;" ::"n"(N) : "memory"); }
template <typename T> __device__ __forceinline__ void pin_ptr(T*& p) { asm volatile("" : "+l"(p)); }
template <int N> __device__ __forceinline__ void pin(uint32_t* d) {
#pragma unroll
    for (int i = 0; i < N; i++) asm volatile("" : "+r"(d[i])::"memory");
}
template <int N> __device__ __forceinline__ void pin(float* d) {
#pragma unroll
    for (int i = 0; i < N; i++) asm volatile("" : "+f"(d[i])::"memory");
}

template <int TA, int TB>
__device__ __forceinline__ void wgmma_ss256(float* d, uint64_t da, uint64_t db) {
    asm volatile("wgmma.mma_async.sync.aligned.m64n256k16.f32.bf16.bf16 "
        "{%0, %1, %2, %3, %4, %5, %6, %7, %8, %9, %10, %11, %12, %13, %14, %15, %16, %17, %18, %19, %20, %21, %22, %23, %24, %25, %26, %27, %28, %29, %30, %31, %32, %33, %34, %35, %36, %37, %38, %39, %40, %41, %42, %43, %44, %45, %46, %47, %48, %49, %50, %51, %52, %53, %54, %55, %56, %57, %58, %59, %60, %61, %62, %63, %64, %65, %66, %67, %68, %69, %70, %71, %72, %73, %74, %75, %76, %77, %78, %79, %80, %81, %82, %83, %84, %85, %86, %87, %88, %89, %90, %91, %92, %93, %94, %95, %96, %97, %98, %99, %100, %101, %102, %103, %104, %105, %106, %107, %108, %109, %110, %111, %112, %113, %114, %115, %116, %117, %118, %119, %120, %121, %122, %123, %124, %125, %126, %127}, %128, %129, 1, 1, 1, %130, %131;"
        : "+f"(d[0]), "+f"(d[1]), "+f"(d[2]), "+f"(d[3]), "+f"(d[4]), "+f"(d[5]), "+f"(d[6]), "+f"(d[7]), "+f"(d[8]), "+f"(d[9]), "+f"(d[10]), "+f"(d[11]), "+f"(d[12]), "+f"(d[13]), "+f"(d[14]), "+f"(d[15]), "+f"(d[16]), "+f"(d[17]), "+f"(d[18]), "+f"(d[19]), "+f"(d[20]), "+f"(d[21]), "+f"(d[22]), "+f"(d[23]), "+f"(d[24]), "+f"(d[25]), "+f"(d[26]), "+f"(d[27]), "+f"(d[28]), "+f"(d[29]), "+f"(d[30]), "+f"(d[31]), "+f"(d[32]), "+f"(d[33]), "+f"(d[34]), "+f"(d[35]), "+f"(d[36]), "+f"(d[37]), "+f"(d[38]), "+f"(d[39]), "+f"(d[40]), "+f"(d[41]), "+f"(d[42]), "+f"(d[43]), "+f"(d[44]), "+f"(d[45]), "+f"(d[46]), "+f"(d[47]), "+f"(d[48]), "+f"(d[49]), "+f"(d[50]), "+f"(d[51]), "+f"(d[52]), "+f"(d[53]), "+f"(d[54]), "+f"(d[55]), "+f"(d[56]), "+f"(d[57]), "+f"(d[58]), "+f"(d[59]), "+f"(d[60]), "+f"(d[61]), "+f"(d[62]), "+f"(d[63]), "+f"(d[64]), "+f"(d[65]), "+f"(d[66]), "+f"(d[67]), "+f"(d[68]), "+f"(d[69]), "+f"(d[70]), "+f"(d[71]), "+f"(d[72]), "+f"(d[73]), "+f"(d[74]), "+f"(d[75]), "+f"(d[76]), "+f"(d[77]), "+f"(d[78]), "+f"(d[79]), "+f"(d[80]), "+f"(d[81]), "+f"(d[82]), "+f"(d[83]), "+f"(d[84]), "+f"(d[85]), "+f"(d[86]), "+f"(d[87]), "+f"(d[88]), "+f"(d[89]), "+f"(d[90]), "+f"(d[91]), "+f"(d[92]), "+f"(d[93]), "+f"(d[94]), "+f"(d[95]), "+f"(d[96]), "+f"(d[97]), "+f"(d[98]), "+f"(d[99]), "+f"(d[100]), "+f"(d[101]), "+f"(d[102]), "+f"(d[103]), "+f"(d[104]), "+f"(d[105]), "+f"(d[106]), "+f"(d[107]), "+f"(d[108]), "+f"(d[109]), "+f"(d[110]), "+f"(d[111]), "+f"(d[112]), "+f"(d[113]), "+f"(d[114]), "+f"(d[115]), "+f"(d[116]), "+f"(d[117]), "+f"(d[118]), "+f"(d[119]), "+f"(d[120]), "+f"(d[121]), "+f"(d[122]), "+f"(d[123]), "+f"(d[124]), "+f"(d[125]), "+f"(d[126]), "+f"(d[127])
        : "l"(da), "l"(db), "n"(TA), "n"(TB));
}
template <int TA, int TB>
__device__ __forceinline__ void wgmma_ss256_first(float* d, uint64_t da, uint64_t db) {
    asm volatile("wgmma.mma_async.sync.aligned.m64n256k16.f32.bf16.bf16 "
        "{%0, %1, %2, %3, %4, %5, %6, %7, %8, %9, %10, %11, %12, %13, %14, %15, %16, %17, %18, %19, %20, %21, %22, %23, %24, %25, %26, %27, %28, %29, %30, %31, %32, %33, %34, %35, %36, %37, %38, %39, %40, %41, %42, %43, %44, %45, %46, %47, %48, %49, %50, %51, %52, %53, %54, %55, %56, %57, %58, %59, %60, %61, %62, %63, %64, %65, %66, %67, %68, %69, %70, %71, %72, %73, %74, %75, %76, %77, %78, %79, %80, %81, %82, %83, %84, %85, %86, %87, %88, %89, %90, %91, %92, %93, %94, %95, %96, %97, %98, %99, %100, %101, %102, %103, %104, %105, %106, %107, %108, %109, %110, %111, %112, %113, %114, %115, %116, %117, %118, %119, %120, %121, %122, %123, %124, %125, %126, %127}, %128, %129, 0, 1, 1, %130, %131;"
        : "=f"(d[0]), "=f"(d[1]), "=f"(d[2]), "=f"(d[3]), "=f"(d[4]), "=f"(d[5]), "=f"(d[6]), "=f"(d[7]), "=f"(d[8]), "=f"(d[9]), "=f"(d[10]), "=f"(d[11]), "=f"(d[12]), "=f"(d[13]), "=f"(d[14]), "=f"(d[15]), "=f"(d[16]), "=f"(d[17]), "=f"(d[18]), "=f"(d[19]), "=f"(d[20]), "=f"(d[21]), "=f"(d[22]), "=f"(d[23]), "=f"(d[24]), "=f"(d[25]), "=f"(d[26]), "=f"(d[27]), "=f"(d[28]), "=f"(d[29]), "=f"(d[30]), "=f"(d[31]), "=f"(d[32]), "=f"(d[33]), "=f"(d[34]), "=f"(d[35]), "=f"(d[36]), "=f"(d[37]), "=f"(d[38]), "=f"(d[39]), "=f"(d[40]), "=f"(d[41]), "=f"(d[42]), "=f"(d[43]), "=f"(d[44]), "=f"(d[45]), "=f"(d[46]), "=f"(d[47]), "=f"(d[48]), "=f"(d[49]), "=f"(d[50]), "=f"(d[51]), "=f"(d[52]), "=f"(d[53]), "=f"(d[54]), "=f"(d[55]), "=f"(d[56]), "=f"(d[57]), "=f"(d[58]), "=f"(d[59]), "=f"(d[60]), "=f"(d[61]), "=f"(d[62]), "=f"(d[63]), "=f"(d[64]), "=f"(d[65]), "=f"(d[66]), "=f"(d[67]), "=f"(d[68]), "=f"(d[69]), "=f"(d[70]), "=f"(d[71]), "=f"(d[72]), "=f"(d[73]), "=f"(d[74]), "=f"(d[75]), "=f"(d[76]), "=f"(d[77]), "=f"(d[78]), "=f"(d[79]), "=f"(d[80]), "=f"(d[81]), "=f"(d[82]), "=f"(d[83]), "=f"(d[84]), "=f"(d[85]), "=f"(d[86]), "=f"(d[87]), "=f"(d[88]), "=f"(d[89]), "=f"(d[90]), "=f"(d[91]), "=f"(d[92]), "=f"(d[93]), "=f"(d[94]), "=f"(d[95]), "=f"(d[96]), "=f"(d[97]), "=f"(d[98]), "=f"(d[99]), "=f"(d[100]), "=f"(d[101]), "=f"(d[102]), "=f"(d[103]), "=f"(d[104]), "=f"(d[105]), "=f"(d[106]), "=f"(d[107]), "=f"(d[108]), "=f"(d[109]), "=f"(d[110]), "=f"(d[111]), "=f"(d[112]), "=f"(d[113]), "=f"(d[114]), "=f"(d[115]), "=f"(d[116]), "=f"(d[117]), "=f"(d[118]), "=f"(d[119]), "=f"(d[120]), "=f"(d[121]), "=f"(d[122]), "=f"(d[123]), "=f"(d[124]), "=f"(d[125]), "=f"(d[126]), "=f"(d[127])
        : "l"(da), "l"(db), "n"(TA), "n"(TB));
}
template <int TA, int TB>
__device__ __forceinline__ void wgmma_ss128(float* d, uint64_t da, uint64_t db) {
    asm volatile("wgmma.mma_async.sync.aligned.m64n128k16.f32.bf16.bf16 "
        "{%0, %1, %2, %3, %4, %5, %6, %7, %8, %9, %10, %11, %12, %13, %14, %15, %16, %17, %18, %19, %20, %21, %22, %23, %24, %25, %26, %27, %28, %29, %30, %31, %32, %33, %34, %35, %36, %37, %38, %39, %40, %41, %42, %43, %44, %45, %46, %47, %48, %49, %50, %51, %52, %53, %54, %55, %56, %57, %58, %59, %60, %61, %62, %63}, %64, %65, 1, 1, 1, %66, %67;"
        : "+f"(d[0]), "+f"(d[1]), "+f"(d[2]), "+f"(d[3]), "+f"(d[4]), "+f"(d[5]), "+f"(d[6]), "+f"(d[7]), "+f"(d[8]), "+f"(d[9]), "+f"(d[10]), "+f"(d[11]), "+f"(d[12]), "+f"(d[13]), "+f"(d[14]), "+f"(d[15]), "+f"(d[16]), "+f"(d[17]), "+f"(d[18]), "+f"(d[19]), "+f"(d[20]), "+f"(d[21]), "+f"(d[22]), "+f"(d[23]), "+f"(d[24]), "+f"(d[25]), "+f"(d[26]), "+f"(d[27]), "+f"(d[28]), "+f"(d[29]), "+f"(d[30]), "+f"(d[31]), "+f"(d[32]), "+f"(d[33]), "+f"(d[34]), "+f"(d[35]), "+f"(d[36]), "+f"(d[37]), "+f"(d[38]), "+f"(d[39]), "+f"(d[40]), "+f"(d[41]), "+f"(d[42]), "+f"(d[43]), "+f"(d[44]), "+f"(d[45]), "+f"(d[46]), "+f"(d[47]), "+f"(d[48]), "+f"(d[49]), "+f"(d[50]), "+f"(d[51]), "+f"(d[52]), "+f"(d[53]), "+f"(d[54]), "+f"(d[55]), "+f"(d[56]), "+f"(d[57]), "+f"(d[58]), "+f"(d[59]), "+f"(d[60]), "+f"(d[61]), "+f"(d[62]), "+f"(d[63])
        : "l"(da), "l"(db), "n"(TA), "n"(TB));
}
template <int TA, int TB>
__device__ __forceinline__ void wgmma_ss128_first(float* d, uint64_t da, uint64_t db) {
    asm volatile("wgmma.mma_async.sync.aligned.m64n128k16.f32.bf16.bf16 "
        "{%0, %1, %2, %3, %4, %5, %6, %7, %8, %9, %10, %11, %12, %13, %14, %15, %16, %17, %18, %19, %20, %21, %22, %23, %24, %25, %26, %27, %28, %29, %30, %31, %32, %33, %34, %35, %36, %37, %38, %39, %40, %41, %42, %43, %44, %45, %46, %47, %48, %49, %50, %51, %52, %53, %54, %55, %56, %57, %58, %59, %60, %61, %62, %63}, %64, %65, 0, 1, 1, %66, %67;"
        : "=f"(d[0]), "=f"(d[1]), "=f"(d[2]), "=f"(d[3]), "=f"(d[4]), "=f"(d[5]), "=f"(d[6]), "=f"(d[7]), "=f"(d[8]), "=f"(d[9]), "=f"(d[10]), "=f"(d[11]), "=f"(d[12]), "=f"(d[13]), "=f"(d[14]), "=f"(d[15]), "=f"(d[16]), "=f"(d[17]), "=f"(d[18]), "=f"(d[19]), "=f"(d[20]), "=f"(d[21]), "=f"(d[22]), "=f"(d[23]), "=f"(d[24]), "=f"(d[25]), "=f"(d[26]), "=f"(d[27]), "=f"(d[28]), "=f"(d[29]), "=f"(d[30]), "=f"(d[31]), "=f"(d[32]), "=f"(d[33]), "=f"(d[34]), "=f"(d[35]), "=f"(d[36]), "=f"(d[37]), "=f"(d[38]), "=f"(d[39]), "=f"(d[40]), "=f"(d[41]), "=f"(d[42]), "=f"(d[43]), "=f"(d[44]), "=f"(d[45]), "=f"(d[46]), "=f"(d[47]), "=f"(d[48]), "=f"(d[49]), "=f"(d[50]), "=f"(d[51]), "=f"(d[52]), "=f"(d[53]), "=f"(d[54]), "=f"(d[55]), "=f"(d[56]), "=f"(d[57]), "=f"(d[58]), "=f"(d[59]), "=f"(d[60]), "=f"(d[61]), "=f"(d[62]), "=f"(d[63])
        : "l"(da), "l"(db), "n"(TA), "n"(TB));
}
template <int TB>
__device__ __forceinline__ void wgmma_rs128(float* d, const uint32_t* a, uint64_t db, uint32_t acc) {
    asm volatile("{\n.reg .pred P;\nsetp.ne.u32 P, %69, 0;\nwgmma.mma_async.sync.aligned.m64n128k16.f32.bf16.bf16 "
        "{%0, %1, %2, %3, %4, %5, %6, %7, %8, %9, %10, %11, %12, %13, %14, %15, %16, %17, %18, %19, %20, %21, %22, %23, %24, %25, %26, %27, %28, %29, %30, %31, %32, %33, %34, %35, %36, %37, %38, %39, %40, %41, %42, %43, %44, %45, %46, %47, %48, %49, %50, %51, %52, %53, %54, %55, %56, %57, %58, %59, %60, %61, %62, %63}, {%64, %65, %66, %67}, %68, P, 1, 1, %70;\n}"
        : "+f"(d[0]), "+f"(d[1]), "+f"(d[2]), "+f"(d[3]), "+f"(d[4]), "+f"(d[5]), "+f"(d[6]), "+f"(d[7]), "+f"(d[8]), "+f"(d[9]), "+f"(d[10]), "+f"(d[11]), "+f"(d[12]), "+f"(d[13]), "+f"(d[14]), "+f"(d[15]), "+f"(d[16]), "+f"(d[17]), "+f"(d[18]), "+f"(d[19]), "+f"(d[20]), "+f"(d[21]), "+f"(d[22]), "+f"(d[23]), "+f"(d[24]), "+f"(d[25]), "+f"(d[26]), "+f"(d[27]), "+f"(d[28]), "+f"(d[29]), "+f"(d[30]), "+f"(d[31]), "+f"(d[32]), "+f"(d[33]), "+f"(d[34]), "+f"(d[35]), "+f"(d[36]), "+f"(d[37]), "+f"(d[38]), "+f"(d[39]), "+f"(d[40]), "+f"(d[41]), "+f"(d[42]), "+f"(d[43]), "+f"(d[44]), "+f"(d[45]), "+f"(d[46]), "+f"(d[47]), "+f"(d[48]), "+f"(d[49]), "+f"(d[50]), "+f"(d[51]), "+f"(d[52]), "+f"(d[53]), "+f"(d[54]), "+f"(d[55]), "+f"(d[56]), "+f"(d[57]), "+f"(d[58]), "+f"(d[59]), "+f"(d[60]), "+f"(d[61]), "+f"(d[62]), "+f"(d[63])
        : "r"(a[0]), "r"(a[1]), "r"(a[2]), "r"(a[3]), "l"(db), "r"(acc), "n"(TB));
}
template <int TB>
__device__ __forceinline__ void wgmma_rs64(float* d, const uint32_t* a, uint64_t db, uint32_t acc) {
    asm volatile("{\n.reg .pred P;\nsetp.ne.u32 P, %37, 0;\nwgmma.mma_async.sync.aligned.m64n64k16.f32.bf16.bf16 "
        "{%0, %1, %2, %3, %4, %5, %6, %7, %8, %9, %10, %11, %12, %13, %14, %15, %16, %17, %18, %19, %20, %21, %22, %23, %24, %25, %26, %27, %28, %29, %30, %31}, {%32, %33, %34, %35}, %36, P, 1, 1, %38;\n}"
        : "+f"(d[0]), "+f"(d[1]), "+f"(d[2]), "+f"(d[3]), "+f"(d[4]), "+f"(d[5]), "+f"(d[6]), "+f"(d[7]), "+f"(d[8]), "+f"(d[9]), "+f"(d[10]), "+f"(d[11]), "+f"(d[12]), "+f"(d[13]), "+f"(d[14]), "+f"(d[15]), "+f"(d[16]), "+f"(d[17]), "+f"(d[18]), "+f"(d[19]), "+f"(d[20]), "+f"(d[21]), "+f"(d[22]), "+f"(d[23]), "+f"(d[24]), "+f"(d[25]), "+f"(d[26]), "+f"(d[27]), "+f"(d[28]), "+f"(d[29]), "+f"(d[30]), "+f"(d[31])
        : "r"(a[0]), "r"(a[1]), "r"(a[2]), "r"(a[3]), "l"(db), "r"(acc), "n"(TB));
}
template <int TB>
__device__ __forceinline__ void wgmma_rs16(float* d, const uint32_t* a, uint64_t db, uint32_t acc) {
    asm volatile("{\n.reg .pred P;\nsetp.ne.u32 P, %13, 0;\nwgmma.mma_async.sync.aligned.m64n16k16.f32.bf16.bf16 "
        "{%0, %1, %2, %3, %4, %5, %6, %7}, {%8, %9, %10, %11}, %12, P, 1, 1, %14;\n}"
        : "+f"(d[0]), "+f"(d[1]), "+f"(d[2]), "+f"(d[3]), "+f"(d[4]), "+f"(d[5]), "+f"(d[6]), "+f"(d[7])
        : "r"(a[0]), "r"(a[1]), "r"(a[2]), "r"(a[3]), "l"(db), "r"(acc), "n"(TB));
}

__device__ __forceinline__ uint32_t delay_loop(int n, uint32_t x0) {
    uint32_t z;
    asm volatile("{\n.reg .pred P;\n.reg .u32 c, x;\nmov.u32 c, %1;\nmov.u32 x, %2;\nDL: mad.lo.u32 x, x, 1664525, 1013904223;\nadd.u32 c, c, -1;\nsetp.gt.s32 P, c, 0;\n@P bra DL;\n"
                 "setp.eq.u32 P, x, 0x7fffffff;\nselp.u32 %0, 16, 0, P;\n}" : "=r"(z) : "r"(n), "r"(x0) : "memory");
    return z;
}
__device__ __forceinline__ uint32_t gtime() { uint32_t t; asm volatile("mov.u32 %0, %%globaltimer_lo;" : "=r"(t)); return t; }
__device__ __forceinline__ void wait_time(uint32_t t, uint32_t sb) { while ((int32_t)(gtime() - t) < (int32_t)delay_loop(2, sb)) {} }
__device__ __forceinline__ uint32_t latest_stamp(const uint32_t* p, uint32_t seq, uint32_t ref, int backoff, uint32_t sb) {
    for (int n = 0;; n++) {
        uint32_t bad = 0; int32_t m = INT32_MIN;
#pragma unroll
        for (int i = 0; i < 3; i++) { const uint32_t v = ld_relaxed1(p + i * 256); bad |= (v ^ seq) & 31u; m = max(m, (int32_t)(v - (ref << 5)) >> 5); }
        if (__all_sync(0xffffffffu, bad == 0)) return ref + __reduce_max_sync(0xffffffffu, m);
        wait_time(gtime() + backoff, sb);
        if (n > SPIN_LIMIT) spin_fault();
    }
}
__device__ __forceinline__ void release_at(uint32_t t, uint32_t sb, uint32_t bar, int lane) {
    wait_time(t, sb);
    if (lane == 0) mbar_arrive(sb + bar);
}
__host__ __device__ constexpr int frag_word(int u, int f) { return (u == 0 ? 0 : u < 3 ? 3 * u - 1 : u == 3 ? 14 : 3 * u - 4) + f; }
__host__ __device__ constexpr int word_col(int e) { return ((0x32FED987CBA65410ull >> (4 * e)) & 14) * 64 + ((0x32FED987CBA65410ull >> (4 * e)) & 1) * 8; }

constexpr uint32_t CLEAR_LO = 0xFE000000u, CLEAR_HI = 0x5A7FEFEFu;
__device__ __forceinline__ void clear_slot(const Params& P, int slot, int cta, int lane) {
    const int i = cta * 2 + (lane >> 3), x = i & 63;
    if (lane < 16) st_relaxed4(P.gm + slot * M_SLOT + (x >> 1) * 1024 + (x & 1) * 256 + (i >> 7) * 512 + ((i >> 6) & 1) * 128 + (lane & 7) * 16, CLEAR_LO, CLEAR_HI, CLEAR_LO, CLEAR_HI);
    st_relaxed4(g_f + slot * F_SLOT + cta * 512 + lane * 16, 0, 0, 0, 0);
}
__device__ __forceinline__ void mem0_max(const Params& P, uint32_t sb, int tid) {
    uint32_t m = 0;
#pragma unroll
    for (int i = 0; i < 4; i++) {
        const uint4 x = __ldg((const uint4*)P.mem0 + i * 256 + tid);
        m = __vmaxu2(__vmaxu2(__vmaxu2(x.x & 0x7fff7fffu, x.y & 0x7fff7fffu), __vmaxu2(x.z & 0x7fff7fffu, x.w & 0x7fff7fffu)), m);
    }
    sts32(sb + S_COEF + (tid >> 5) * 4, __reduce_max_sync(0xffffffffu, max(m >> 16, m & 0xffffu)));
    bar_arrive(7, 288);
}
__device__ __forceinline__ uint32_t pack_mem0(const Params& P, uint32_t sb, int cta, int lane) {
    bar_sync(7, 288);
    const uint32_t e = __reduce_max_sync(0xffffffffu, lds32(sb + S_COEF + (lane & 7) * 4)) >> 7;
    if (e < 64 || e > 192) return 0x3F803F80u;
    const int i = cta * 2 + (lane >> 4), u = (i >> 5), x = i & 63, L = (i & 3) * 8 + ((lane & 15) >> 1);
    uint64_t w = 32;
#pragma unroll
    for (int f = 0; f < 3; f++) if (f < 2 || u % 3) {
        const float v = __bfloat162float(P.mem0[(L >> 2) * 1024 + word_col(frag_word(u, f)) + ((i >> 2) & 7) * 16 + (L & 3) * 2 + (lane & 1)]);
        w += (uint64_t)(int64_t)__float2int_rn(v * __uint_as_float((271 - e) << 23)) << (45 - 19 * f);
    }
    st_relaxed2(P.gm + 7 * M_SLOT + (x >> 1) * 1024 + (x & 1) * 256 + (i >> 7) * 512 + ((i >> 6) & 1) * 128 + (lane & 15) * 8, (uint32_t)w, (uint32_t)(w >> 32));
    return (e - 30) * 0x00800080u;
}
__device__ __forceinline__ void pacer(const Params& P, const uint32_t sb, const int lane) {
    constexpr uint32_t base = 2;
    int cta = lds32(sb + S_CTA);
#pragma unroll 1
    for (int i = 0; i < 8; i++) clear_slot(P, i, cta, lane);
    __syncwarp();
    if (lane == 0) { uint32_t smid; asm("mov.u32 %0, %%smid;" : "=r"(smid)); st_relaxed1(g_hint + 6144 + cta, smid >> 1); }
    sts32(sb + S_EPOCH + 4, pack_mem0(P, sb, cta, lane));
    SSTAMP(0, lane == 0)
    fence_release();
    __syncwarp();
    float rate = 0.58f;
    uint32_t c0 = 0;
#pragma unroll 1
    for (int s = -1; s < 63; s++) {
        cta = lds32(sb + S_CTA);
        const int pair = cta >> 1;
        const uint32_t ahead = s > 0 ? (uint32_t)(rate * (float)(pair >= 32 ? P.dc - P.dv : P.dc)) : 0;
        mbar_wait(sb + B_GO, s & 1);
        SSTAMP(10, lane == 0 && s == 0)
        const uint32_t t0 = gtime();
        if (lane < 4) st_relaxed1(g_hint + ((s & 1) * 4 + lane) * 768 + (cta >> 5) * 256 + (cta & 31), (t0 + ahead + (lds32(sb + S_REDO) == s ? P.extra : 0)) << 5 | ((base + s) & 31u));
        wait_time(t0 + (s < 0 ? 2000 : s == 0 && pair >= 16 ? P.ds0 : P.ds), sb);
        const uint32_t t = latest_stamp(g_hint + ((s & 1) * 4 + (pair & 3)) * 768 + lane, base + s, t0, P.back, sb);
        if (s < 0) {
            SSTAMP(2, lane == 0)
            fence_acquire();
            const uint32_t tpc = ld_relaxed1(g_hint + 6144 + (lane & 15) * 2), g = tpc < 32 ? tpc & 7 : tpc < 60 ? (tpc - 32) % 7 + 1 : (tpc - 54) & 7;
            const uint32_t key = (__popc(__match_any_sync(0xffffffffu, g)) > 4 ? 0 : g + 1) * 16 + (lane & 15);
            const uint32_t tail = (pair & 48) + __popc(__ballot_sync(0xffffffffu, key < __shfl_sync(0xffffffffu, key, pair & 15))) / 2;
            mbar_wait(sb + B_INIT, 0);
            SSTAMP(4, lane == 0)
            sts32(sb + S_TAIL, tail);
            if (lane < 8) sts32(sb + S_SC + lane * 4, lds32(sb + S_EPOCH + 4));
            __syncwarp();
        }
        release_at(t + P.da, sb, B_RELA, lane);
        SSTAMP(11, lane == 0 && s == 0)
        release_at(t + P.db, sb, B_RELB, lane);
        {
            const uint32_t c1 = clock(), g1 = gtime();
            if (s > 1) rate += P.alpha * (__fdividef((float)(g1 - lds32(sb + S_EPOCH + 4)), (float)(c1 - c0)) - rate);
            __syncwarp();
            c0 = c1; sts32(sb + S_EPOCH + 4, g1);
        }
        if (!DBGF(16) && s >= 0) fence_release();
        __syncwarp();
        wait_time(t + P.db + 320, sb);
        clear_slot(P, (s + 6) & 7, cta, lane);
        if (s == 61) {
            sts32(sb + S_COEF, ITEM(ITEM_OFF(lds32(sb + S_TAIL)) + NPRE + 1) + (uint32_t)(uintptr_t)P.out);
            if (lane < M_CQ) map_prefetch(&P.tm[lane]);
        }
    }
}
__device__ __forceinline__ uint32_t xor_or(uint32_t a, uint32_t b, uint32_t t) { uint32_t d; asm("lop3.b32 %0, %1, %2, %3, 0x7E;" : "=r"(d) : "r"(a), "r"(b), "r"(t)); return d; }
__device__ __forceinline__ bool tags_ok(uint32_t bad) { return __all_sync(0xffffffffu, (bad & 1) == 0); }
#define RETRY(k)
#define RETRY_STAT(a, b)
#define UNIT_STAT(u0)
#define SFENCE() asm volatile("pmevent 1;" ::: "memory")
#define PF1 10
static_assert(NS == 24, "fragment residency");
__host__ __device__ constexpr bool in_smem(int n) { return n < 4 || n == 13 || n == 15; }
__host__ __device__ constexpr int unit_pos(int n) { return n < 4 ? n : n < 13 ? n - 4 : n == 13 ? 4 : n == 14 ? 9 : 5; }

__host__ __device__ constexpr int fill_unit(int q) { return q < 4 ? q : q < 6 ? q * 2 + 5 : q < 15 ? q - 2 : 14; }
__host__ __device__ constexpr int frag_off(int q) { return (q >> 2) * 16384 + ((q >> 1) & 1) * 8192 + (q & 1) * 512; }

constexpr uint32_t QBITS = 0x4B002000u;
constexpr uint64_t W_BIAS = ((uint64_t)QBITS << 45) + ((uint64_t)QBITS << 26) + (uint32_t)(QBITS << 7), W_CLEAR = 0 - 32 * W_BIAS;
static_assert(W_CLEAR == ((uint64_t)CLEAR_HI << 32 | CLEAR_LO), "clear value");
__host__ __device__ constexpr int unit_off(int u) { return (u & 1) * 16384 + (u >> 2) * 512 + ((u >> 1) & 1) * 128; }
__device__ __forceinline__ void red_add64(const uint8_t* p, uint64_t v) { asm volatile("red.relaxed.gpu.global.add.u64 [%0], %1;" ::"l"(p), "l"(v) : "memory"); }
template <int NF>
__device__ __forceinline__ uint64_t encode(const float* x, float S, uint32_t two26, uint32_t& bad) {
    uint32_t b[3];
#pragma unroll
    for (int i = 0; i < 3; i++) b[i] = i < NF ? __float_as_uint(fmaf(x[i], S, 8396800.f)) : QBITS;
    bad = xor_or(b[0], b[1], 0x4B000000u) | (NF == 3 ? b[2] ^ 0x4B000000u : 0);
    uint64_t w;
    asm("{\n.reg .b64 t;\nmov.b64 t, {%2, %3};\nmad.wide.u32 %0, %1, %4, t;\n}" : "=l"(w) : "r"(b[1]), "r"(b[2] << 7), "r"(b[0] << 13), "r"(two26));
    return w;
}
template <int NF>
__device__ __forceinline__ void emit(uint64_t* w, const float (*x)[3], const float* S, uint32_t two26, uint32_t lim, const uint8_t* p) {
    uint32_t bad[2];
    w[0] = encode<NF>(x[0], S[0], two26, bad[0]); w[1] = encode<NF>(x[1], S[1], two26, bad[1]);
    const bool ok = (bad[0] | bad[1]) < lim;
    w[0] |= ok; w[1] |= ok;
    red_add64(p, w[0]); red_add64(p + 1024, w[1]);
}
template <int NF>
__device__ __forceinline__ void repair(const uint64_t* w, const float (*x)[3], const float* S, const uint8_t* p, const uint8_t* pf) {
    if (!(w[0] & 1)) {
#pragma unroll
        for (int j = 0; j < 2; j++) {
            const float T = S[j] * 8192.f;
            asm volatile("red.relaxed.gpu.global.add.v4.f32 [%0], {%1,%2,%3,%4};" ::"l"(pf + j * 512), "f"(x[j][0] * T), "f"(x[j][1] * T), "f"(NF == 3 ? x[j][2] * T : 0.f), "f"(0.f) : "memory");
        }
        fence_release();
#pragma unroll
        for (int j = 0; j < 2; j++) {
            asm volatile("red.relaxed.gpu.global.or.b64 [%0], 64;" ::"l"(p + j * 1024) : "memory");
            red_add64(p + j * 1024, W_BIAS + 1 - w[j]);
        }
    }
    __syncwarp();
}
__device__ __forceinline__ void ld_words(uint32_t* v, const uint8_t* p) {
    asm volatile("{\n.reg .b64 a, b;\nld.relaxed.gpu.global.L1::no_allocate.v2.b64 {a, b}, [%4];\nmov.b64 {%0,%1}, a;\nmov.b64 {%2,%3}, b;\n}" : "=r"(v[0]), "=r"(v[1]), "=r"(v[2]), "=r"(v[3]) : "l"(p) : "memory");
}
__device__ __forceinline__ float field(const uint32_t* w, int f) { return __int2float_rn((int)(f == 0 ? w[1] : f == 1 ? __funnelshift_l(w[0], w[1], 19) : w[0] << 6)); }
template <int U>
__device__ __forceinline__ void decode(uint32_t* b, const uint32_t* v) {
#pragma unroll
    for (int f = 0; f < (U % 3 ? 3 : 2); f++) b[frag_word(U, f)] = pack2(field(v, f), field(v + 2, f));
}
__device__ __forceinline__ uint32_t status(const uint32_t (*v)[4], uint32_t c32) { return xor_or(v[0][0], v[0][2], c32) | xor_or(v[1][0], v[1][2], c32) | xor_or(v[2][0], v[2][2], c32); }
__device__ __forceinline__ void gather_slow(const Params& P, uint32_t* b, const uint8_t* pm, int s, int warp, uint32_t ln, uint32_t u2) {
    if (s == 0 && u2 == 0x3F803F80u) {
#pragma unroll
        for (int i = 0; i < 16; i++) b[i] = __ldg((const uint32_t*)(P.mem0 + (ln >> 2) * 1024 + word_col(i) + warp * 16 + (ln & 3) * 2));
        return;
    }
    uint32_t v[6][4], st;
    for (int n = 0;; n++) {
#pragma unroll
        for (int u = 0; u < 6; u++) ld_words(v[u], pm + unit_off(u));
        st = status(v, 32) | status(v + 3, 32);
        if (!__any_sync(0xffffffffu, st & 32)) break;
        __nanosleep(200);
        if (n > SPIN_LIMIT) spin_fault();
    }
    const bool side = __any_sync(0xffffffffu, st & 64);
    if (side) fence_acquire();
    const uint8_t* pf = g_f + ((s + 7) & 7) * F_SLOT + warp * 1024 + ln * 32;
#pragma unroll
    for (int u = 0; u < 6; u++) {
        float x[2][4] = {};
#pragma unroll
        for (int k = 0; k < 2; k++)
            asm volatile("{\n.reg .pred P;\nsetp.ne.u32 P, %5, 0;\n@P ld.relaxed.gpu.global.v4.f32 {%0,%1,%2,%3}, [%4];\n}"
                         : "+f"(x[k][0]), "+f"(x[k][1]), "+f"(x[k][2]), "+f"(x[k][3]) : "l"(pf + u * 8192 + k * 16), "r"((uint32_t)side) : "memory");
#pragma unroll
        for (int f = 0; f < (u % 3 ? 3 : 2); f++) b[frag_word(u, f)] = pack2(field(v[u], f) + x[0][f], field(v[u] + 2, f) + x[1][f]);
    }
}
__device__ __forceinline__ uint32_t max_abs2(uint32_t a, uint32_t b) { uint32_t d; asm("max.NaN.xorsign.abs.bf16x2 %0, %1, %2;" : "=r"(d) : "r"(a), "r"(b)); return d; }
__device__ __forceinline__ uint32_t max6(const uint32_t* b) {
    const uint32_t m = max_abs2(max_abs2(max_abs2(b[0], b[1]), max_abs2(b[2], b[3])), max_abs2(b[4], b[5]));
    return max(m & 0x7fff0000u, (m << 16) & 0x7fff0000u);
}

template <bool TR>
__device__ __forceinline__ void put_partials(uint32_t a, const float* x, const float* y) {
    if (TR) stsm4t(a, pack2(x[0], x[1]), pack2(x[2], x[3]), pack2(y[0], y[1]), pack2(y[2], y[3]));
    else stsm4(a, pack2(x[0], x[1]), pack2(x[2], x[3]), pack2(y[0], y[1]), pack2(y[2], y[3]));
}
__device__ __forceinline__ void reduce_load(uint32_t (*x)[4], uint32_t a) { ldsm4t(x[0], a); ldsm4t(x[1], a + 512); }
__device__ __forceinline__ uint32_t reduce8(const uint32_t (*x)[4], uint32_t l8, uint32_t u2) {
    uint32_t p[2];
#pragma unroll
    for (int i = 0; i < 2; i++) {
        float d[4] = {};
        mma16816(d, x[i][0], x[i][1], x[i][2], x[i][3], (l8 & 32) ? 0u : u2, (l8 & 32) ? u2 : 0u);
        p[i] = pack2((l8 & 8) ? d[2] : d[0], (l8 & 8) ? d[3] : d[1]);
    }
    return (l8 & 16) ? p[1] : p[0];
}
__device__ __forceinline__ void score_half(float (*a)[4], const uint32_t (*qa)[4], const uint32_t (*kf)[4]) {
#pragma unroll
    for (int w = 0; w < 2; w++) {
        mma16816(a[w], qa[w][0], qa[w][1], qa[w][2], qa[w][3], kf[w][0], kf[w][1]);
        mma16816(a[2 + w], qa[w][0], qa[w][1], qa[w][2], qa[w][3], kf[w][2], kf[w][3]);
    }
}
__device__ __forceinline__ void score_sum(float* S, const float (*a)[4]) {
    S[0] = (a[0][0] + a[1][0]) + (a[2][2] + a[3][2]);
    S[1] = (a[0][1] + a[1][1]) + (a[2][3] + a[3][3]);
}
__device__ __forceinline__ float quad_max(float m) {
    m = fmaxf(m, __shfl_xor_sync(0xffffffffu, m, 1));
    return fmaxf(m, __shfl_xor_sync(0xffffffffu, m, 2));
}

#define ISTAMP(i)
__device__ __forceinline__ float next_scale(uint32_t sb, int slot, int warp, uint32_t u2) {
    uint32_t x[2][4];
    lds128(x[0], sb + S_MX + slot * 32); lds128(x[1], sb + S_MX + slot * 32 + 16);
    const uint32_t mx = max(max(max(x[0][0], x[0][1]), max(x[0][2], x[0][3])), max(max(x[1][0], x[1][1]), max(x[1][2], x[1][3])));
    const float top = fminf(fmaxf(__uint_as_float(mx) * bf_hi(u2), 0x1p-40f), 0x1p40f) * (1.f / (12288.f * 8192.f));
    const uint32_t un = pack2(top, top);
    sts32(sb + S_SC + warp * 4, un);
    return rcp(bf_hi(un) * 8192.f);
}
#define NEARLY 1
#define U3POS 1
#define VPOS 1
#define ROT 0
#define BPOS 1
#define ONLINE 0
#define NBAR 1
#define RPOS 1
#define AF 0
#define AFENCE(i) if ((AF >> (i)) & 1) SFENCE();
#define FPOS 99
#define PACE 1
#define PF2 12
__host__ __device__ constexpr int w2_t(int i) { return i < 16 ? i & 1 : 2; }
__host__ __device__ constexpr int w2_k(int i) { return i < 16 ? i >> 1 : i - 16; }
template <int ROLE>
__device__ __forceinline__ void chain_role(const Params& P, const uint32_t sb, const int h, const int warp, const int lane) {
    constexpr int NU = ROLE == 0 ? 2 : 3;
    const bool att = ROLE == 0 && warp < 4;
    uint32_t wr[NR][4];
    {
        const uint32_t frag = sb + warp * 1024 + (lane >> 4) * 8192 + (lane & 7) * 128 + ((((lane >> 3) & 1) ^ (lane & 7)) << 4);
        const uint32_t rel = mapa(sb + B_EMPTY, cluster_rank() ^ (lane & 1));
#define RELEASE(st) { fence_async_smem(); __syncwarp(); if (lane < 2) mbar_arrive_cluster(rel + (st) * 8); }
        mbar_wait(sb + B_FULL, 0); mbar_wait(sb + B_FULL + 8, 0);
        RELEASE(0) RELEASE(1)
#pragma unroll
        for (int st = 2; st < 4; st++) {
            mbar_wait(sb + B_FULL + st * 8, 0);
            ISTAMP(st - 2)
#pragma unroll
            for (int f = 0; f < 12; f++) ldsm4t(wr[st * 12 - 24 + f], (frag ^ ((f & 3) << 5)) + st * STAGE + (f >> 2) * 16384);
            RELEASE(st)
        }
#pragma unroll 2
        for (int u = 0; u < 6; u++) {
            uint32_t x[4][4];
#pragma unroll
            for (int i = 0; i < 4; i++) lds128(x[i], (frag ^ (i << 5)) + u * 16384);
            __syncwarp();
#pragma unroll
            for (int i = 0; i < 4; i++) sts128(sb + warp * 1024 + lane * 16 + u * 16384 + frag_off(i), x[i]);
        }
        mbar_wait(sb + B_FULL, 1); mbar_wait(sb + B_FULL + 8, 1);
        RELEASE(0) RELEASE(1)
#pragma unroll
        for (int st = 2; st < 4; st++) {
            mbar_wait(sb + B_FULL + st * 8, 1);
#pragma unroll
            for (int f = 0; f < (st == 2 ? 12 : 4); f++) ldsm4t(wr[st * 12 + f], (frag ^ ((f & 3) << 5)) + st * STAGE + (f >> 2) * 16384);
            RELEASE(st)
        }
        ISTAMP(2)
        bar_sync(1, 256);
        if (warp == 7 && lane < 3) mbar_arrive_cluster(mapa(sb + B_INIT, (cluster_rank() & 1) + lane * 2));
    }
    uint32_t l8 = opq(sb + lane * 8, lane);
    const uint8_t* persu = (const uint8_t*)((ROLE == 1 ? g_km : g_vmt) + h * 512 + warp * 32) - (sb >> 1);
#define PERS_STORE() { uint32_t* pp = (uint32_t*)(persu + s * 65536 + (l8 >> 1)); pp[0] = r0; pp[256] = r1; }
    const uint32_t rdelta = __shfl_sync(0xffffffffu, mapa(sb, (cluster_rank() + (ROLE == 1 ? 4 : 2)) % 6) - sb, 0);
    const uint32_t vdelta = ROLE ? 0 : __shfl_sync(0xffffffffu, mapa(sb, (cluster_rank() + 4) % 6) - sb, 0);
    ISTAMP(3)
    __syncwarp();
#define GATHER_OFF(s) ((((s) + 7) & 7) * M_SLOT + warp * 2048 + (l8 & 56) * 2 + (l8 & 64) * 4 + (l8 & 128) * 8)
    uint32_t mo = GATHER_OFF(0);
    if (ROT) mbar_wait(sb + B_RELA, 0);
    for (int s = 0; s < (ROLE == 0 ? 63 : 64);) {
        const int slot = s & 1;
        l8 += s & P.zero;
        const uint32_t w1a = l8 * 2 + (S_W1 + warp * 1024 - sb);
        PROF(9)
        uint32_t u2, r0, r1, pld, pub, pbar, x[2][4];
        {
#define pm (P.gm + mo)
            uint32_t as[24][4], b[16], v[6][4];
            float acc[8][4];
#define W1LD(n) _Pragma("unroll") for (int i_ = 0; i_ < 4; i_++) ldsm4t(as[unit_pos(n) * 4 + i_], w1a + frag_off(unit_pos(n) * 4 + i_));
#define W1MMA(n) _Pragma("unroll") for (int i_ = 0; i_ < 4; i_++) { const uint32_t* a_ = in_smem(n) ? as[unit_pos(n) * 4 + i_] : wr[unit_pos(n) * 4 + i_]; \
                                                                   mma16816(acc[((n) & 1) * 4 + i_], a_[0], a_[1], a_[2], a_[3], b[(n) & 14], b[(n) | 1]); }
#pragma unroll
            for (int T = 0; T < 8; T++) { acc[T][0] = acc[T][1] = acc[T][2] = acc[T][3] = 0.f; }
            if (!ROT) mbar_wait(sb + B_RELA, slot);
            PROF(12)
#pragma unroll
            for (int u = 0; u < 3; u++) ld_words(v[u], pm + unit_off(u));
            __syncwarp();
#pragma unroll
            for (int i = 0; i < PF1; i++) ldsm4t(as[i], w1a + frag_off(i));
            __syncwarp();
            mo += mbar_try(sb + B_RELB, slot) & P.zero;
            PROF(13)
#pragma unroll
            for (int u = 3; u < 6; u++) ld_words(v[u], pm + unit_off(u));
            uint32_t st = status(v, ((uint32_t)((uintptr_t)pm >> 32) & P.zero) + 32);
            pin<1>(&st);
            SFENCE();
            UNIT_STAT(0)
            PROF(0)
            decode<0>(b, v[0]); decode<1>(b, v[1]); decode<2>(b, v[2]);
#pragma unroll
            for (int i = PF1; i < 12; i++) ldsm4t(as[i], w1a + frag_off(i));
            W1MMA(0) W1MMA(1) W1MMA(2)
            W1LD(3)
            SFENCE();
            W1MMA(5) W1MMA(4) W1MMA(7) W1MMA(6)
            if (U3POS == 0) W1MMA(3)
            uint32_t mx = max6(b);
            pin<1>(&mx);
            SFENCE();
            PROF(10)
            if (U3POS == 1) W1MMA(3)
            const uint32_t mxa = sb + S_MX + slot * 32 + warp * 4;
            sts32(mxa, __reduce_max_sync(0xffffffffu, mx));
            UNIT_STAT(3)
            st |= status(v + 3, 32);
            const bool redo = __any_sync(0xffffffffu, st & 96);
            const bool kvok = ROLE || mbar_test(sb + B_KVFULL + slot * 8, (s >> 1) & 1);
            decode<4>(b, v[4]); decode<5>(b, v[5]); decode<3>(b, v[3]);
            u2 = lds32(sb + S_SC + warp * 4);
            W1MMA(8) W1MMA(10) W1MMA(12) W1MMA(14)
            W1LD(13)
            if (__builtin_expect(redo || !kvok, 0)) {
                if (redo) {
                    RETRY(3)
                    sts32(sb + S_REDO, s);
                    gather_slow(P, b, pm, s, warp, (l8 - sb) >> 3, u2);
                    sts32(mxa, __reduce_max_sync(0xffffffffu, max6(b)));
#pragma unroll
                    for (int T = 0; T < 8; T++) { acc[T][0] = acc[T][1] = acc[T][2] = acc[T][3] = 0.f; }
#pragma unroll
                    for (int n = 0; n < 15; n += n < 8 ? 1 : 2) {
                        if (in_smem(n)) { W1LD(n) }
                        W1MMA(n)
                    }
                    W1LD(13)
                }
                if (ROLE == 0) mbar_wait(sb + B_KVFULL + slot * 8, (s >> 1) & 1);
            }
#undef pm
            SSTAMP(7, threadIdx.x == 0 && s == 0)
            PROF(14)
            const uint32_t pst = (l8 - sb) * 16 + ((warp * 16) ^ ((l8 * 2) & 112)) + (sb + S_P1);
            put_partials<ROLE == 2>(pst, acc[0], acc[1]); put_partials<ROLE == 2>(pst + 4096, acc[2], acc[3]);
            W1MMA(9)
            SFENCE();
            W1LD(15)
            pld = (l8 & 64) * 4 + (l8 & 128) + (l8 & 56) * 2 + (sb + S_P1 + warp * 1024);
            const uint32_t rd = s == 63 ? 0 : rdelta;
            pub = ((l8 - sb) >> 1) + (ROLE ? sb + rd + (ROLE == 1 ? S_KL : S_VL) + warp * 128 : sb + S_QX + (warp & 4) * 128 + (warp & 1) * 256 + (warp & 2) * 64);
            pbar = sb + rd + (ROLE == 1 && s != 63 ? B_K : B_V);
#define PUBLISH0() { r0 = reduce8(x, l8, u2); if (ROLE) st_async1(pub, r0, pbar); else sts32(pub, r0); }
            if (RPOS == 0) { bar_sync(1, 256); reduce_load(x, pld); SFENCE(); }
            W1MMA(13)
            if (RPOS == 1) { bar_sync(1, 256); reduce_load(x, pld); }
            SFENCE();
            W1MMA(11)
            if (RPOS == 0) PUBLISH0()
            if (RPOS == 2) { bar_sync(1, 256); reduce_load(x, pld); }
            SFENCE();
            W1MMA(15)
            if (RPOS == 1) PUBLISH0()
            put_partials<ROLE == 2>(pst + 8192, acc[4], acc[5]); put_partials<ROLE == 2>(pst + 12288, acc[6], acc[7]);
            if (RPOS == 2) PUBLISH0()
        }
        SSTAMP(8, threadIdx.x == 0 && s == 0)
        PROF(1)
        if (ROLE) {
            bar_sync(1, 256);
            reduce_load(x, pld + 8192);
            r1 = reduce8(x, l8, u2);
            st_async1(pub + 1024, r1, pbar);
            if (s == 63) {
                PERS_STORE()
                mbar_wait(sb + B_V, 0);
                __syncwarp();
                if (l8 == sb) mbar_arrive(sb + B_PERS);
                break;
            }
            PROF(2)
        }
        uint32_t ln, w2a, ro;
#define W2ADDR(late) { l8 += pub & P.zero; ln = (l8 - sb) >> 3; \
        w2a = sb + S_W2 + (ROLE ? (warp >> 2) * 16384 : late * 32768) + ((((ln & 7) + (ln >> 4) * 8) * 128 + ((((ln >> 3) & 1) ^ (ln & 7)) << 4)) ^ ((warp & 3) << 5)); \
        ro = (s & 7) * M_SLOT + (ROLE ? warp * 2048 + unit_off(ROLE) : (warp & 3) * 2048 + late * unit_off(3)) + (ln & 2) * 128 + (ln & 1) * 64 + (ln >> 2) * 8; }
        constexpr int RO2 = ROLE ? unit_off(ROLE + 3) - unit_off(ROLE) : 8192;
        float Sj[2];
        uint32_t w[24][4], ob[4][4];
        float S;
#define W2LD(i) ldsm4t(w[i], w2a + w2_t(i) * (ROLE ? 32768 : 16384) + (w2_k(i) & 1) * 8192 + (w2_k(i) >> 1) * 2048)
#define W2MMA(d, i) mma16816(d, w[i][0], w[i][1], w[i][2], w[i][3], ob[w2_k(i) >> 1][(w2_k(i) & 1) * 2], ob[w2_k(i) >> 1][(w2_k(i) & 1) * 2 + 1])
#define LEADER(wp) (l8 == sb + ((wp) - warp) * 256)
        if (att) {
            const float cs = 0.08838834764831845f * 1.4426950408889634f;
            uint32_t qa[4][4], kf[4][4], vf[4][4], vv[4];
            float T[5][2], sa[4][4] = {};
            const uint32_t l16 = l8 * 2 - sb;
            const uint32_t kaddr = (l8 & 56) * 16 + (((l8 >> 2) ^ (l8 * 2)) & 48) + ((l8 * 2) & 64) + (sb + S_KV + warp * 1024 + slot * 16384);
            bar_sync(1, 256);
            reduce_load(x, pld + 8192);
            __syncwarp();
#pragma unroll
            for (int i = 0; i < 2; i++) { ldsm4(qa[i], l16 + S_QX + i * 512); ldsm4(kf[i], kaddr ^ (i * 64)); }
            AFENCE(0)
            sts32(pub + 1024, reduce8(x, l8, u2));
            __syncwarp();
#pragma unroll
            for (int i = 2; i < 4; i++) ldsm4(kf[i], (kaddr ^ ((i & 1) * 64)) + 4096);
            score_half(sa, qa, kf);
            bar_sync(2, 256);
            PROF(2)
#pragma unroll
            for (int i = 2; i < 4; i++) ldsm4(qa[i], l16 + S_QX + i * 512);
            float sm[4][4] = {};
            score_half(sa, qa + 2, kf + 2);
            score_sum(T[0], sa);
            sts64(l8 + S_SX + warp * 256, __float_as_uint(T[0][0]), __float_as_uint(T[0][1]));
            PROF(4)
            if (BPOS == 0) bar_sync(4, 128);
            mbar_wait(sb + B_K, slot);
            PROF(11)
#pragma unroll
            for (int i = 0; i < 4; i++) ldsm4(kf[i], l16 + S_KL + i * 512);
            if (BPOS == 1) bar_sync(4, 128); else __syncwarp();
#pragma unroll
            for (int n = 0; n < 4; n++) lds64f(T[n], l8 + S_SX + n * 256);
            score_half(sm, qa, kf);
            score_half(sm, qa + 2, kf + 2);
            const uint32_t vaddr = (l8 & 56) * 16 + (l8 & 128) * 8 + (((warp & 1) * 64 + ((l8 >> 2) & 16)) ^ ((l8 * 2) & 112)) + (sb + S_KV + 8192 + (warp >> 1) * 4096 + slot * 16384);
            float mx = fmaxf(fmaxf(fmaxf(T[0][0], T[0][1]), fmaxf(T[1][0], T[1][1])), fmaxf(fmaxf(T[2][0], T[2][1]), fmaxf(T[3][0], T[3][1])));
            score_sum(T[4], sm);
            float m = quad_max(fmaxf(mx, fmaxf(T[4][0], T[4][1])));
            if (VPOS == 0) {
#pragma unroll
                for (int i = 0; i < 4; i++) ldsm4t(vf[i], (vaddr ^ ((i & 1) << 5)) + (i >> 1) * 2048);
            }
            mbar_wait(sb + B_V, slot);
            if (VPOS == 1) {
#pragma unroll
                for (int i = 0; i < 4; i++) ldsm4t(vf[i], (vaddr ^ ((i & 1) << 5)) + (i >> 1) * 2048);
            }
            ldsm4(vv, l16 + S_VL + warp * 512);
            uint32_t pa[5];
            m *= cs;
#pragma unroll
            for (int n = 0; n < 5; n++) { T[n][0] = ex2(fmaf(T[n][0], cs, -m)); T[n][1] = ex2(fmaf(T[n][1], cs, -m)); pa[n] = pack2(T[n][0], T[n][1]); }
            float sum = (((T[0][0] + T[0][1]) + (T[1][0] + T[1][1])) + ((T[2][0] + T[2][1]) + (T[3][0] + T[3][1]))) + (T[4][0] + T[4][1]);
            PROF(3)
            W2ADDR(1)
            const uint32_t lo = sb + S_O + warp * 512 + (ln & 3) * 64 + (ln >> 2) * 8, ls = sb + S_SUM + (ln & 3) * 32 + (ln & 4) * 4 + (ln >> 3) * 4;
            const uint32_t sdelta = warp < 2 ? rdelta : vdelta;
            sum += __shfl_xor_sync(0xffffffffu, sum, 1);
            sum += __shfl_xor_sync(0xffffffffu, sum, 2);
            float O[2][4];
#pragma unroll
            for (int i = 0; i < 2; i++) { O[i][0] = O[i][1] = O[i][2] = O[i][3] = 0.f; }
#pragma unroll
            for (int i = 0; i < 2; i++) {
                mma16816(O[0], vf[2 * i][0], vf[2 * i][1], vf[2 * i][2], vf[2 * i][3], pa[2 * i], pa[2 * i + 1]);
                mma16816(O[1], vf[2 * i + 1][0], vf[2 * i + 1][1], vf[2 * i + 1][2], vf[2 * i + 1][3], pa[2 * i], pa[2 * i + 1]);
            }
            mma1688(O[0], vv[0], vv[1], pa[4]);
            mma1688(O[1], vv[2], vv[3], pa[4]);
            uint32_t o[2][2];
#pragma unroll
            for (int j = 0; j < 2; j++) { o[j][0] = pack2(O[0][j], O[0][2 + j]); o[j][1] = pack2(O[1][j], O[1][2 + j]); }
#pragma unroll
            for (int j = 0; j < 2; j++) st_async2(lo + rdelta + j * 256, o[j][0], o[j][1], sb + rdelta + B_K);
            st_async1(ls + sdelta + (warp & 1) * 128, __float_as_uint(sum), sb + sdelta + B_K);
#pragma unroll
            for (int j = 0; j < 2; j++) st_async2(lo + vdelta + j * 256, o[j][0], o[j][1], sb + vdelta + B_K);
#pragma unroll
            for (int j = 0; j < 2; j++) sts64(lo + j * 256, o[j][0], o[j][1]);
            sts32(ls + warp * 128, __float_as_uint(sum));
            PROF(5)
            bar_sync(3, 256);
            if (LEADER(0)) { mbar_expect(sb + B_K, 2048); mbar_expect(sb + B_V, 2048); mbar_arrive(sb + B_KVGO + slot * 8); }
            S = next_scale(sb, slot, warp, u2);
            if (s == 0) mbar_wait(sb + B_WO, 0);
            pin<1>(&S);
            SFENCE();
#pragma unroll
            for (int j = 0; j < 4; j++) lds128(ob[j], l8 * 2 - sb + S_O + j * 512);
            lds64f(Sj, sb + S_SUM + (l8 & 24));
#pragma unroll
            for (int i = 0; i < PF2; i++) W2LD(i);
        } else {
            if (ROLE == 0) { bar_sync(1, 256); reduce_load(x, pld + 8192); sts32(pub + 1024, reduce8(x, l8, u2)); bar_arrive(2, 256); }
            if (LEADER(7)) { if (s) mbar_arrive(sb + B_GO); if (ROLE) mbar_expect(sb + B_K, 2304); }
            if (ROLE != 0 && (s & 3) == 0 && s > 0 && l8 == sb) mbar_arrive(sb + B_PERS);
            S = next_scale(sb, slot, warp, u2);
            if (s == 0) mbar_wait(sb + B_WO, 0);
            if (ROLE != 0) { l8 += delay_loop(40, l8); if (!DBGF(4)) PERS_STORE() }
            W2ADDR(0)
#pragma unroll
            for (int i = 0; i < PF2; i++) {
                W2LD(i);
                if (ROLE == 0 && (i & PACE) == PACE) w2a += w[i][0] & P.zero;
            }
            ro = opq(ro, ln);
            const uint32_t sa = opq(sb + S_SUM + (l8 & 24), ln), oa = opq(l8 * 2 - sb + S_O, ln);
            if (ROLE == 0) bar_sync(3, 256); else mbar_wait(sb + B_K, slot);
            lds64f(Sj, sa);
#pragma unroll
            for (int j = 0; j < 4; j++) lds128(ob[j], oa + j * 512);
        }
        SSTAMP(9, threadIdx.x == 224 && s == 0)
        SFENCE();
        PROF(6)
        {
            const uint8_t* pr = P.gm + ro;
            float c[4][4];
            uint32_t lim = 0;
#pragma unroll
            for (int i = 0; i < 4; i++) { c[i][0] = c[i][1] = c[i][2] = c[i][3] = 0.f; }
#pragma unroll
            for (int i = 0; i < 16; i++) {
                W2MMA(c[i & (ROLE ? 1 : 3)], i);
                if (i + PF2 < (ROLE ? 16 + NEARLY : 16)) W2LD(i + PF2);
                if (i == 5) {
                    const uint32_t z = __float_as_uint(c[1][0]) & P.zero;
                    Sj[0] = S * rcp(__uint_as_float(__float_as_uint(Sj[0]) | z)); Sj[1] = S * rcp(__uint_as_float(__float_as_uint(Sj[1]) | z));
                }
                if (i == 5) lim = __any_sync(0xffffffffu, fmaxf(fmaxf(fabsf(c[0][0]), fabsf(c[0][2])), fmaxf(fabsf(c[1][0]), fabsf(c[1][2]))) * Sj[0] >= (ROLE ? 24.f : 20.f)) ? 16384 : 0;
                if (i == FPOS) { pin<1>(&lim); pin<2>(Sj); pin_ptr(pr); SFENCE(); }
            }
            if (ROLE == 0) {
#pragma unroll
                for (int i = 0; i < 8; i++) c[i >> 2][i & 3] += c[2 + (i >> 2)][i & 3];
            }
            const float xa[2][3] = {{c[0][0], c[0][2], c[1][0]}, {c[0][1], c[0][3], c[1][1]}};
            uint64_t wa[2], wb[2];
            emit<NU>(wa, xa, Sj, P.two26, lim, pr);
            PROF(7)
            mo = GATHER_OFF(s + 1);
            pin<1>(&mo);
            if (ROLE) {
                SFENCE();
#pragma unroll
                for (int i = 16 + NEARLY; i < 24; i++) { if (i == 16 + NBAR) bar_sync(2, 256); W2LD(i); __syncwarp(); }
                SFENCE();
#pragma unroll
                for (int i = 16; i < 24; i++) W2MMA(c[2 + (i & 1)], i);
#pragma unroll
                for (int i = 0; i < 4; i++) c[2][i] += c[3][i];
            }
            const float y[2][3] = {{ROLE ? c[1][2] : c[1][0], ROLE ? c[2][0] : c[1][2], c[2][2]}, {ROLE ? c[1][3] : c[1][1], ROLE ? c[2][1] : c[1][3], c[2][3]}};
            const bool released = !ROT || mbar_test(sb + B_RELA, slot ^ 1);
            emit<NU>(wb, y, Sj, P.two26, lim, pr + RO2);
            PROF(8)
            if (!__all_sync(0xffffffffu, (wa[0] & wb[0] & 1) && released && s)) {
                if (__builtin_expect(!__all_sync(0xffffffffu, wa[0] & wb[0] & 1), 0)) {
                    RETRY(5)
                    const uint8_t* pf = g_f + (s & 7) * F_SLOT + (ROLE ? ROLE * 8192 + warp * 1024 : (warp & 3) * 1024 + (att ? 24576 : 0)) + (ln & 3) * 128 + (ln >> 2) * 16;
                    repair<NU>(wa, xa, Sj, pr, pf);
                    repair<NU>(wb, y, Sj, pr + RO2, pf + (ROLE ? 24576 : 4096));
                }
                if (s == 0) { bar_sync(1, 256); if (LEADER(7)) mbar_arrive(sb + B_GO); }
                if (ROT) mbar_wait(sb + B_RELA, slot ^ 1);
            }
        }
        s++;
    }
}
struct Pipe { uint32_t stage, phase; };
struct Cons {
    uint32_t sb, rel;
    int wg, wq, lane, rank, pair;
    uint32_t atag, nst;
    Pipe p;
};
__device__ __forceinline__ void pipe_next(Pipe& p) { p.stage = (p.stage + 1) & (NSTAGE - 1); p.phase ^= (p.stage == 0); }
__device__ __forceinline__ void release(const Cons& c, uint32_t stage) { if (c.lane < 2) mbar_arrive_cluster(c.rel + stage * 8); }

enum { PEND_NONE = 0, PEND_KVO = 1, PEND_HT = 2, PEND_OUT = 3, PEND_OUTH = 4 };
struct Pend { uint32_t pk[64]; int kind, row, col, cnt; };

__device__ __forceinline__ void staging_wait(const Cons& c) { if (c.nst) mbar_wait(c.sb + B_SFREE + c.wg * 8, (c.nst - 1) & 1); }
__device__ __forceinline__ void staging_post(Cons& c, int kind, int row, int col, int cnt) {
    __syncwarp();
    if (c.lane == 0) {
        if (c.wq == 0) { const uint32_t x[4] = {(uint32_t)kind, (uint32_t)row, (uint32_t)col, (uint32_t)cnt}; sts128(c.sb + S_DESC + c.wg * 16, x); }
        mbar_arrive(c.sb + B_SFULL + c.wg * 8);
    }
    c.nst++;
}
template <int HF, bool KVONLY = false>
__device__ __forceinline__ void drain(const Params& P, Cons& c, const Pend& d) {
    const uint32_t* pk = d.pk + HF * 32;
    if (!KVONLY && d.kind >= PEND_OUT) {
        if (HF == 1 && d.kind == PEND_OUTH) return;
        float* o = P.out + (size_t)(d.row + c.wq * 16 + (c.lane >> 2)) * 2048 + d.col + HF * 128 + (c.lane & 3) * 2;
#pragma unroll
        for (int j = 0; j < 16; j++) {
            st_stream2(o + j * 8, bf_lo(pk[j * 2]), bf_hi(pk[j * 2]));
            st_stream2(o + 8 * 2048 + j * 8, bf_lo(pk[j * 2 + 1]), bf_hi(pk[j * 2 + 1]));
        }
    } else if (d.kind != PEND_NONE) {
        const bool ht = !KVONLY && d.kind == PEND_HT;
        const int hi = (c.lane >> 3) & 1;
        const uint32_t base = c.sb + S_STG + c.wg * 16384 + ((ht ? hi * 32 + c.wq * 8 : c.wq * 16 + hi * 8) + (c.lane & 7)) * 128;
        staging_wait(c);
#pragma unroll
        for (int j = 0; j < 8; j++) {
            const int ch = (j & 3) * 2 + (c.lane >> 4);
            stsm4(base + (j >> 2) * 8192 + ((ch ^ (c.lane & 7)) << 4), pk[j * 4], pk[j * 4 + 1], pk[j * 4 + 2], pk[j * 4 + 3]);
        }
        fence_async_smem();
        staging_post(c, d.kind, d.row, d.col + HF * 128, HF ? d.cnt : -1);
    }
}
__device__ __forceinline__ void drain_all(const Params& P, Cons& c, Pend& d) { drain<0>(P, c, d); drain<1>(P, c, d); d.kind = PEND_NONE; }

__device__ __forceinline__ void store_warp(const Params& P, uint32_t sb, int wg) {
    const uint32_t stg = sb + S_STG + wg * 16384;
#pragma unroll 1
    for (uint32_t n = 0;; n++) {
        mbar_wait(sb + B_SFULL + wg * 8, n & 1);
        uint32_t x[4];
        lds128(x, sb + S_DESC + wg * 16);
        if (x[0] == PEND_NONE) break;
        const bool ht = x[0] == PEND_HT;
        const CUtensorMap* m = &P.tm[ht ? M_HTS : M_KVO];
#pragma unroll 1
        for (int i = 0; i < 4; i++) if (!(DBGF(128) && gridDim.x != 96)) tma_store2d(m, x[2] + (i >> 1) * 64, x[1] + (i & 1) * (ht ? 1024 : 32), stg + i * 4096);
        bulk_commit();
        bulk_wait_read();
        mbar_arrive(sb + B_SFREE + wg * 8);
        if ((int)x[3] >= 0) { bulk_wait_all(); fence_async(); red_release(&g_cnt(x[3])); }
    }
}

template <int N, int TA, int TB, bool FIRST>
__device__ __forceinline__ void issue_ktile(float* acc, const Cons& c) {
    mbar_wait(c.sb + B_FULL + c.p.stage * 8, c.p.phase);
    const uint32_t a = c.sb + c.p.stage * STAGE + c.wg * 8192, b = c.sb + c.p.stage * STAGE + 16384;
    const uint64_t da = mkdesc(a, TA ? 8192 : 16, 1024, 1), db = mkdesc(b, TB ? 8192 : 16, 1024, 1);
    wg_fence();
#pragma unroll
    for (int k = 0; k < 4; k++) {
        const uint64_t x = da + (TA ? 128 : 2) * k, y = db + (TB ? 128 : 2) * k;
        if (N == 256) { if (FIRST && k == 0) wgmma_ss256_first<TA, TB>(acc, x, y); else wgmma_ss256<TA, TB>(acc, x, y); }
        else { if (FIRST && k == 0) wgmma_ss128_first<TA, TB>(acc, x, y); else wgmma_ss128<TA, TB>(acc, x, y); }
    }
    wg_commit();
}
template <int N, bool FIRST>
__device__ __forceinline__ void issue_any(float* acc, const Cons& c, int type) {
    if (N == 256 && type == T_A1) issue_ktile<N, 0, 0, FIRST>(acc, c);
    else if (type == (N == 256 ? T_A2 : T_A2H)) issue_ktile<N, 1, 0, FIRST>(acc, c);
    else issue_ktile<N, 0, 1, FIRST>(acc, c);
}
template <int N, bool KVONLY = false>
__device__ __forceinline__ void mainloop(float* acc, const Params& P, Cons& c, Pend& d, int type) {
    const int nk = (type == T_OP || type == T_OPH) ? 64 : (type == T_A2 || type == T_A2H) ? 32 : 16;
    issue_any<N, true>(acc, c, type);
    drain<0, KVONLY>(P, c, d);
    uint32_t prev = c.p.stage;
    pipe_next(c.p);
    for (int kt = 1; kt < nk; kt++) {
        issue_any<N, false>(acc, c, type);
        wg_wait<1>();
        release(c, prev);
        if (kt == 2) drain<1, KVONLY>(P, c, d);
        prev = c.p.stage;
        pipe_next(c.p);
    }
    d.kind = PEND_NONE;
    wg_wait<0>();
    pin<N / 2>(acc);
    release(c, prev);
}
__device__ __forceinline__ void pack_half(uint32_t* pk, const float* a) {
#pragma unroll
    for (int i = 0; i < 32; i++) pk[i] = pack2(a[2 * i], a[2 * i + 1]);
}

__device__ __forceinline__ void epi_kv(const float* acc, const Cons& c, Pend& d, int mb, int nb) {
    pack_half(d.pk, acc); pack_half(d.pk + 32, acc + 64);
    d.kind = PEND_KVO; d.row = (nb >> 4) * 2048 + mb * 256 + c.rank * 128 + c.wg * 64; d.col = (nb & 15) * 256; d.cnt = C_KV + mb;
}

__device__ __forceinline__ void epi_qa(const float* acc, Cons& c, Pend& d, int mb, int nb) {
    uint32_t q[64];
    pack_half(q, acc);
    pack_half(q + 32, acc + 64);
#pragma unroll
    for (int i = 0; i < 32; i++) d.pk[32 + i] = 0;
    const int g = c.lane >> 2, t = c.lane & 3;
    const bool sg = c.wq >= 2;
    const int i0 = (c.wq & 1) * 16 + g;
#pragma unroll 1
    for (int hh = 0; hh < 2; hh++) {
        uint32_t pa[5][4];
        {
            float S[32] = {}, Sm[8] = {};
            mbar_wait(c.sb + B_FULL + c.p.stage * 8, c.p.phase);
            const uint32_t st = c.sb + c.p.stage * STAGE;
            const uint64_t dk = mkdesc(st + c.wg * 8192, 16, 1024, 1), dm = mkdesc(st + 32768 + c.wg * 4096, 128, 2048, 0);
            pin<32>(q); pin<32>(S); pin<8>(Sm);
            wg_fence();
#pragma unroll
            for (int i = 0; i < 8; i++) wgmma_rs64<0>(S, q + i * 4, dk + (i >> 2) * 1024 + (i & 3) * 2, i != 0);
#pragma unroll
            for (int i = 0; i < 8; i++) wgmma_rs16<0>(Sm, q + i * 4, dm + i * 16, i != 0);
            wg_commit();
            wg_wait<0>();
            pin<32>(S); pin<8>(Sm);
            release(c, c.p.stage);
            pipe_next(c.p);
            const float scale = 0.08838834764831845f, l2e = 1.4426950408889634f;
            float x[2][10];
#pragma unroll
            for (int r = 0; r < 2; r++) {
#pragma unroll
                for (int j = 0; j < 4; j++)
#pragma unroll
                    for (int e = 0; e < 2; e++) {
                        const float v = sg ? S[16 + j * 4 + r * 2 + e] : S[j * 4 + r * 2 + e];
                        x[r][j * 2 + e] = (j * 8 + 2 * t + e > i0 + r * 8) ? -1e9f : v * scale;
                    }
                x[r][8] = (sg ? Sm[4 + r * 2] : Sm[r * 2]) * scale;
                x[r][9] = (sg ? Sm[5 + r * 2] : Sm[1 + r * 2]) * scale;
                float m = x[r][0];
#pragma unroll
                for (int i = 1; i < 10; i++) m = fmaxf(m, x[r][i]);
                m = fmaxf(m, __shfl_xor_sync(0xffffffffu, m, 1));
                m = fmaxf(m, __shfl_xor_sync(0xffffffffu, m, 2));
                float sum = 0.f;
#pragma unroll
                for (int i = 0; i < 10; i++) { x[r][i] = ex2((x[r][i] - m) * l2e); sum += x[r][i]; }
                sum += __shfl_xor_sync(0xffffffffu, sum, 1);
                sum += __shfl_xor_sync(0xffffffffu, sum, 2);
                const float inv = rcp(sum);
#pragma unroll
                for (int i = 0; i < 10; i++) x[r][i] *= inv;
            }
#pragma unroll
            for (int ks = 0; ks < 2; ks++)
#pragma unroll
                for (int i = 0; i < 4; i++) {
                    const uint32_t p = pack2(x[i & 1][ks * 4 + (i >> 1) * 2], x[i & 1][ks * 4 + (i >> 1) * 2 + 1]);
                    pa[ks][i] = sg ? 0u : p;
                    pa[2 + ks][i] = sg ? p : 0u;
                }
#pragma unroll
            for (int r = 0; r < 2; r++) {
                const uint32_t p = pack2(x[r][8], x[r][9]);
                pa[4][r] = sg ? 0u : p;
                pa[4][2 + r] = sg ? p : 0u;
            }
        }
        float O[64] = {};
        mbar_wait(c.sb + B_FULL + c.p.stage * 8, c.p.phase);
        const uint32_t st = c.sb + c.p.stage * STAGE;
        const uint64_t dv = mkdesc(st + c.wg * 8192, 16384, 1024, 1), dm = mkdesc(st + 32768 + c.wg * 4096, 2048, 128, 0);
        pin<20>(&pa[0][0]); pin<64>(O);
        wg_fence();
#pragma unroll
        for (int ks = 0; ks < 4; ks++) wgmma_rs128<1>(O, pa[ks], dv + ks * 128, ks != 0);
        wgmma_rs128<0>(O, pa[4], dm, 1);
        wg_commit();
        wg_wait<0>();
        pin<64>(O);
        release(c, c.p.stage);
        pipe_next(c.p);
#pragma unroll
        for (int i = 0; i < 32; i++) { q[i] = q[32 + i]; q[32 + i] = d.pk[32 + i]; }
        pack_half(d.pk + 32, O);
    }
#pragma unroll
    for (int i = 0; i < 32; i++) d.pk[i] = q[32 + i];
    d.kind = PEND_KVO; d.row = 4096 + mb * 256 + c.rank * 128 + c.wg * 64; d.col = nb * 256; d.cnt = C_O + mb * 4 + (nb >> 2);
}

__device__ __forceinline__ void epi_op(const float* acc, const Cons& c, Pend& d, int mb, int nb) {
    pack_half(d.pk, acc); pack_half(d.pk + 32, acc + 64);
    d.kind = PEND_OUT; d.row = mb * 256 + c.rank * 128 + c.wg * 64; d.col = 1024 + nb * 256;
}

__device__ __forceinline__ void epi_oph(const float* acc, const Cons& c, Pend& d, int mb, int nb) {
    pack_half(d.pk, acc);
    d.kind = PEND_OUTH; d.row = mb * 256 + c.rank * 128 + c.wg * 64; d.col = 1024 + nb * 128;
}

template <int HF>
__device__ __forceinline__ void epi_a2_half(const float* acc, const Params& P, Cons& c, int mb, int col0) {
    const int g = c.lane >> 2, t = c.lane & 3;
    const int row = mb * 256 + (g >> 1) * 64 + (c.rank * 16 + c.wg * 8 + c.wq * 2) * 2 + (g & 1);
    float* o = P.out + (size_t)row * 2048 + col0 + HF * 128 + t * 2;
    mbar_wait(c.sb + B_FULL + c.p.stage * 8, c.p.phase);
    const uint32_t st = c.sb + c.p.stage * STAGE, da = st + 32768 + (c.lane >> 3) * 16;
    const uint32_t xa = st + (c.wg * 64 + c.wq * 16 + (c.lane & 15)) * 128 + (((c.lane >> 4) ^ (c.lane & 7)) << 4);
#pragma unroll
    for (int j4 = 0; j4 < 4; j4++) {
        uint32_t x[8], dv[4];
        ldsm4(dv, da + j4 * 64);
        ldsm4(x, (xa ^ ((j4 & 1) << 6)) + (j4 >> 1) * 16384);
        ldsm4(x + 4, (xa ^ ((j4 & 1) << 6) ^ 32) + (j4 >> 1) * 16384);
#pragma unroll
        for (int i = 0; i < 4; i++) {
            const int j = j4 * 4 + i;
            const float* a = acc + HF * 64 + j * 4;
            const uint32_t u0 = hmul2(x[2 * i], dv[i]), u1 = hmul2(x[2 * i + 1], dv[i]);
            st_stream2(o + j * 8, a[0] + bf_lo(u0), a[1] + bf_hi(u0));
            st_stream2(o + 2 * 2048 + j * 8, a[2] + bf_lo(u1), a[3] + bf_hi(u1));
        }
    }
    __syncwarp();
    release(c, c.p.stage);
    pipe_next(c.p);
}

#define TSTAMP(i)
__device__ __forceinline__ float2 cmul(float2 a, float2 b) { return make_float2(fmaf(a.x, b.x, -a.y * b.y), fmaf(a.x, b.y, a.y * b.x)); }
__device__ __forceinline__ float2 cfma(float2 a, float2 b, float2 u) { return make_float2(fmaf(a.x, b.x, fmaf(-a.y, b.y, u.x)), fmaf(a.x, b.y, fmaf(a.y, b.x, u.y))); }
__device__ __forceinline__ float4 ssm_coef(float lre, float lim, float logdt) {
    const float dt = __bfloat162float(__float2bfloat16(expf(logdt)));
    const float ea = expf(dt * lre);
    float sn, cn;
    sincosf(dt * lim, &sn, &cn);
    const float br = ea * cn, bi = ea * sn, nr = br - 1.f;
    float cr, ci;
    if (fabsf(lre) >= fabsf(lim)) { const float r = lim / lre, dn = lre + lim * r; cr = (nr + bi * r) / dn; ci = (bi - nr * r) / dn; }
    else { const float r = lre / lim, dn = lre * r + lim; cr = (nr * r + bi) / dn; ci = (bi * r - nr) / dn; }
    return make_float4(br, bi, cr, ci);
}
__device__ __forceinline__ void epi_a1(const float* acc, const Params& P, const Cons& c, Pend& d, int mb, int nb, uint32_t atag) {
    const int t = c.lane & 3;
    const int p = nb * 128 + c.rank * 64 + c.wg * 32 + c.wq * 8 + (c.lane >> 2);
    uint32_t cw[4];
    lds128(cw, c.sb + S_COEF + (p & 63) * 16);
    const float4 cf = make_float4(__uint_as_float(cw[0]), __uint_as_float(cw[1]), __uint_as_float(cw[2]), __uint_as_float(cw[3]));
    TSTAMP(1)
    const float2 lam = make_float2(cf.x, P.swap_ri ? -cf.y : cf.y);
    const float a0 = P.swap_ri ? -2.f * cf.w : 2.f * cf.z, a1 = P.swap_ri ? 2.f * cf.z : -2.f * cf.w;
    const float b0 = P.swap_ri ? -2.f * cf.z : -2.f * cf.w, b1 = P.swap_ri ? -2.f * cf.w : -2.f * cf.z;
    float2 h = make_float2(0.f, 0.f);
#pragma unroll
    for (int round = 0; round < 2; round++) {
#pragma unroll
        for (int j = 0; j < 32; j++) {
            h = cfma(lam, h, make_float2(acc[j * 4], acc[j * 4 + 2]));
            const float r0 = fmaf(a0, h.x, a1 * h.y), m0 = fmaf(b0, h.x, b1 * h.y);
            h = cfma(lam, h, make_float2(acc[j * 4 + 1], acc[j * 4 + 3]));
            d.pk[j * 2] = pack2(r0, fmaf(a0, h.x, a1 * h.y));
            d.pk[j * 2 + 1] = pack2(m0, fmaf(b0, h.x, b1 * h.y));
        }
        if (round) break;
        float2 l64 = lam;
#pragma unroll
        for (int i = 0; i < 6; i++) l64 = cmul(l64, l64);
        const float2 l128 = cmul(l64, l64), l256 = cmul(l128, l128);
        float2 o = make_float2(__shfl_up_sync(0xffffffffu, h.x, 1), __shfl_up_sync(0xffffffffu, h.y, 1));
        if (t >= 1) h = cfma(l64, o, h);
        o = make_float2(__shfl_up_sync(0xffffffffu, h.x, 2), __shfl_up_sync(0xffffffffu, h.y, 2));
        if (t >= 2) h = cfma(l128, o, h);
        TSTAMP(2)
        if (t == 3) st_relaxed2(&g_agg[mb * 1024 + p], (__float_as_uint(h.x) & ~1u) | atag, __float_as_uint(h.y));
        h = make_float2(__shfl_up_sync(0xffffffffu, h.x, 1), __shfl_up_sync(0xffffffffu, h.y, 1));
        if (t == 0) h = make_float2(0.f, 0.f);
        uint32_t ax[7], ay[7];
        int n = 0;
        while (true) {
            uint32_t bad = 0;
#pragma unroll
            for (int j = 0; j < 7; j++) { ax[j] = atag; ay[j] = 0; ld_relaxed2_if(ax[j], ay[j], &g_agg[j * 1024 + p], j < mb); }
#pragma unroll
            for (int j = 0; j < 7; j++) bad |= ax[j] ^ atag;
            if (tags_ok(bad)) break;
            __nanosleep(400);
            if (++n > SPIN_LIMIT) spin_fault();
        }
        float2 carry = make_float2(0.f, 0.f);
#pragma unroll
        for (int j = 0; j < 7; j++) if (j < mb) carry = cfma(l256, carry, make_float2(__uint_as_float(ax[j]), __uint_as_float(ay[j])));
        float2 w = (t & 1) ? l64 : make_float2(1.f, 0.f);
        if (t & 2) w = cmul(w, l128);
        h = cfma(w, carry, h);
        TSTAMP(3)
    }
    TSTAMP(4)
    d.kind = PEND_HT; d.row = nb * 128 + c.rank * 64 + c.wg * 32; d.col = mb * 256; d.cnt = C_HT + mb * 2 + (nb >> 2);
}

__device__ __forceinline__ uint32_t acquire_stage(uint32_t sb, Pipe& p, uint32_t bytes) {
    mbar_wait(sb + B_EMPTY + p.stage * 8, p.phase ^ 1);
    mbar_expect(sb + B_FULL + p.stage * 8, bytes);
    return p.stage;
}
#define AHEAD 1
__device__ __forceinline__ void watcher(const Params& P, const uint32_t sb, const int rank, const int lane) {
    const int pair = lds32(sb + S_TAIL), first = ITEM_OFF(pair) + (pair < NCHAIN ? NPRE + 1 : 0);
    const uint32_t epoch = lds32(sb + S_EPOCH), e1 = epoch + 1;
    uint32_t met = 0;
#pragma unroll 1
    for (int it = first; it < ITEM_OFF(pair + 1); it++) {
        const int item = ITEM(it), type = item >> 8, mb = (item >> 5) & 7, nb = item & 31;
        const int n = (0x24021420 >> (type * 4)) & 7;
        for (int k = 0; it > first && (int)lds32(sb + S_CUR) < it - AHEAD; k++) { __nanosleep(200); if (k > SPIN_LIMIT) spin_fault(); }
#pragma unroll 1
        for (int i = 0; i < n; i++) {
            int idx = n == 4 ? C_O + mb * 4 + i : C_HT + mb * 2 + i;
            uint32_t target = e1 * 16;
            if (type == T_A1) { idx = C_COEF; target = e1 * 4; }
            if (type == T_QA) {
                idx = i ? C_FLAG + (lane & 1) * 32 + nb * 2 + ((lane >> 1) & 1) : C_KV + mb;
                target = i ? epoch * 64 + mb * 8 + rank * 4 + 4 : e1 * 128;
            }
            if (lane < 4) { wait_count(&g_cnt(idx), target); fence_async(); }
            __syncwarp();
            if (lane == 0) asm volatile("st.release.cta.shared.u32 [%0], %1;" ::"r"(sb + S_DEP), "r"(++met) : "memory");
        }
    }
}
__device__ __forceinline__ bool dep_met(uint32_t sb, uint32_t n) { uint32_t v; asm volatile("ld.acquire.cta.shared.u32 %0, [%1];" : "=r"(v) : "r"(sb + S_DEP) : "memory"); return v >= n; }
__device__ __forceinline__ void dep_wait(uint32_t sb, uint32_t n) { for (int k = 0; !dep_met(sb, n); k++) { __nanosleep(32); if (k > SPIN_LIMIT * 8) spin_fault(); } }
__device__ __forceinline__ void producer(const Params& P, const uint32_t sb, int pair, const int rank, const uint32_t epoch) {
    Pipe p = {0, 0};
    const uint32_t e1 = epoch + 1;
    uint32_t dep = 0;
    for (int it = ITEM_OFF(pair); it < ITEM_OFF(pair + 1); it++) {
        const int item = ITEM(it), type = item >> 8, mb = (item >> 5) & 7, nb = item & 31;
        if (type == T_CHAIN) {
            sts32(sb + S_CUR, 0);
            const int role = pair >> 4, h = (pair & 15) * 2 + rank;
#pragma unroll 1
            for (int i = 0, q = 0; i < 8; i++) {
                const int n = (0x13003333 >> (i * 4)) & 3;
                const uint32_t st = acquire_stage(sb, p, n * 16384);
#pragma unroll 1
                for (int k = 0; k < 2 * n; k++, q++)
                    tma3d(sb + st * STAGE + k * 8192, &P.tm[M_CQ + role], h * 128 + (fill_unit(q >> 1) & 1) * 64, word_col((fill_unit(q >> 1) & 14) + (q & 1)) & 8, word_col((fill_unit(q >> 1) & 14) + (q & 1)) >> 4, sb + B_FULL + st * 8);
                pipe_next(p);
            }
            if (role == 0 && !DBGF(1)) { wait_count(&g_cnt(C_KV), e1 * 128); fence_async(); }
            mbar_wait(sb + B_EMPTY + 16, 1); mbar_wait(sb + B_EMPTY + 24, 1);
            mbar_expect(sb + B_WO, role ? 98304 : 65536);
            if (role == 0) { mbar_expect(sb + B_KVFULL, 16384); mbar_expect(sb + B_KVFULL + 8, 16384); }
#pragma unroll 1
            for (int k = role ? 0 : -4; k < 12; k++) {
                const bool kv = role == 0 && (k & 8);
                const int sg = k > 0;
                tma4d(kv ? sb + S_KV + sg * 16384 + (k & 3) * 4096 : sb + S_W2 + k * 8192, &P.tm[kv ? M_KV4 : M_CO + (k & 1)],
                      kv ? h * 128 + (k & 1) * 64 : (role == 0 ? 0 : role == 1 ? 256 : 640) + (k >> 1) * 64, kv ? (k & 2) * 1024 + sg * 32 : h * 8, sb + (kv ? B_KVFULL + sg * 8 : B_WO));
            }
            SSTAMP(5, true)
            if (pair < 16) {
#pragma unroll 1
                for (int s = 2; s < 63; s++) {
                    mbar_wait(sb + B_KVGO + (s & 1) * 8, ((s >> 1) + 1) & 1);
                    wait_time(gtime() + P.dk, sb);
                    SSTAMP(6, s == 2)
                    const uint32_t bar = sb + B_KVFULL + (s & 1) * 8, dst = sb + S_KV + (s & 1) * 16384;
                    if (DBGF(2)) { mbar_arrive(bar); continue; }
                    mbar_expect(bar, 16384);
#pragma unroll 1
                    for (int i = 0; i < 4; i++) tma2d(dst + i * 4096, &P.tm[M_KVO], (pair * 2 + rank) * 128 + (i & 1) * 64, (i >> 1) * 2048 + (DBGF(32 | 512) ? s & 7 : s) * 32, bar);
                    if (s < 62) {
                        if ((s & 7) == 7 && !DBGF(1)) { wait_count(&g_cnt(C_KV + 1 + (s >> 3)), e1 * 128); fence_async(); }
#pragma unroll 1
                        for (int i = 0; i < 4; i++) if (!DBGF(64)) tma_prefetch2d(&P.tm[M_KVO], (pair * 2 + rank) * 128 + (i & 1) * 64, (i >> 1) * 2048 + s * 32 + 32);
                    }
                }
            } else {
                uint32_t* flag = &g_cnt(C_FLAG + pair * 2 + rank - 32);
#pragma unroll 1
                for (int s = 0; s < 16; s++) {
                    mbar_wait(sb + B_PERS, s & 1);
                    if (!DBGF(8)) asm volatile("st.release.gpu.global.u32 [%0], %1;" ::"l"(flag), "r"(epoch * 64 + s * 4 + 4) : "memory");
                }
            }
            mbar_wait(sb + B_RESUME, 0);
            pair = lds32(sb + S_TAIL);
            it = ITEM_OFF(pair) + NPRE;
            continue;
        }
        sts32(sb + S_CUR, it);
        const int m0 = mb * 256 + rank * 128;
        if (type <= T_OP) {
            const CUtensorMap* ma = &P.tm[type == T_OP ? M_OA : M_BX];
            const CUtensorMap* mw = &P.tm[type == T_OP ? M_WO : type == T_QA ? M_WQ : nb < 16 ? M_WK : M_WV];
            const int nk = type == T_OP ? 64 : 16, nc = (nb & 15) * 4 + rank * 2, ma0 = type == T_OP ? 4096 + m0 : m0;
#pragma unroll 1
            for (int kt = 0; kt < nk; kt++) {
                if (type == T_OP && (kt & 15) == 0) dep_wait(sb, ++dep);
                if (DBGF(256) && pair >= NCHAIN) { acquire_stage(sb, p, 0); pipe_next(p); continue; }
                const uint32_t st = acquire_stage(sb, p, STAGE), bar = sb + B_FULL + st * 8;
                tma2d(sb + st * STAGE, ma, kt * 64, ma0, bar);
                tma3d_mc(sb + st * STAGE + 16384 + rank * 16384, mw, 0, kt * 64, nc, bar);
                if (type == T_QA && kt < 12 && dep_met(sb, dep + 1 + (kt >> 3))) {
                    if (kt < 8) tma_prefetch2d(&P.tm[M_OA], nb * 256 + (kt & 3) * 64, (kt >> 2) * 2048 + m0);
                    else {
                        const int o = ((mb * 8 + rank * 4 + (kt & 3)) * 32 + nb * 2) * 512;
                        l2_prefetch(g_km + o, 4096); l2_prefetch(g_vmt + o, 4096);
                    }
                }
                pipe_next(p);
            }
            if (type == T_QA) {
                dep += 2;
                dep_wait(sb, dep);
#pragma unroll 1
                for (int e = 0; e < 4; e++) {
                    const uint32_t st = acquire_stage(sb, p, 40960), bar = sb + B_FULL + st * 8, dst = sb + st * STAGE;
                    tma2d(dst, &P.tm[M_OA], nb * 256 + (e >> 1) * 128, (e & 1) * 2048 + m0, bar);
                    tma2d(dst + 16384, &P.tm[M_OA], nb * 256 + (e >> 1) * 128 + 64, (e & 1) * 2048 + m0, bar);
                    const uint32_t* src = ((e & 1) ? g_vmt : g_km) + ((mb * 8 + rank * 4) * 32 + nb * 2 + (e >> 1)) * 512;
#pragma unroll 1
                    for (int i = 0; i < 4; i++) bulk_g2s(dst + 32768 + i * 2048, src + i * 32 * 512, 2048, bar);
                    pipe_next(p);
                }
            }
        } else if (type == T_OPH) {
#pragma unroll 1
            for (int kt = 0; kt < 64; kt++) {
                if ((kt & 15) == 0) dep_wait(sb, ++dep);
                const uint32_t st = acquire_stage(sb, p, 32768), bar = sb + B_FULL + st * 8;
                tma2d(sb + st * STAGE, &P.tm[M_OA], kt * 64, 4096 + m0, bar);
                tma2d_mc(sb + st * STAGE + 16384 + rank * 8192, &P.tm[M_WOH], nb * 128 + rank * 64, kt * 64, bar);
                pipe_next(p);
            }
        } else if (type == T_A1) {
#pragma unroll 1
            for (int kt = 0; kt < 16; kt++) {
                if (kt == 15) dep_wait(sb, ++dep);
                const uint32_t st = acquire_stage(sb, p, kt == 15 ? STAGE + 1024 : STAGE), bar = sb + B_FULL + st * 8;
                if (kt == 15) bulk_g2s(sb + S_COEF, g_coef + nb * 128 + rank * 64, 1024, bar);
                tma4d(sb + st * STAGE, &P.tm[M_AB], kt * 64, nb * 16 + rank * 8, bar);
                tma4d_mc(sb + st * STAGE + 16384 + rank * 16384, &P.tm[M_AX], kt * 64, mb * 128 + rank * 16, bar);
                pipe_next(p);
            }
        } else {
            const int hw = type == T_A2H ? 64 : 128;
            const CUtensorMap* mc = &P.tm[type == T_A2H ? M_CREH : M_CRE];
#pragma unroll 1
            for (int kt = 0; kt < 32; kt++) {
                if ((kt & 15) == 0) dep_wait(sb, ++dep);
                const uint32_t st = acquire_stage(sb, p, 16384 + hw * 256), bar = sb + B_FULL + st * 8;
                tma3d(sb + st * STAGE, &P.tm[M_HT], 0, (kt & 1) * 1024 + (kt >> 1) * 64, mb * 4 + rank * 2, bar);
                tma2d_mc(sb + st * STAGE + 16384 + rank * hw * 128, mc + (kt & 1), (kt >> 1) * 64, (nb * 2 + rank) * hw, bar);
                pipe_next(p);
            }
#pragma unroll 1
            for (int col = nb * 2 * hw; col < (nb + 1) * 2 * hw; col += 128) {
                const uint32_t st = acquire_stage(sb, p, 32768 + 256), bar = sb + B_FULL + st * 8;
                tma4d(sb + st * STAGE, &P.tm[M_AX], col, mb * 128 + rank * 16, bar);
                tma4d(sb + st * STAGE + 16384, &P.tm[M_AX], col + 64, mb * 128 + rank * 16, bar);
                bulk_g2s(sb + st * STAGE + 32768, P.Dskip + col, 256, bar);
                pipe_next(p);
            }
        }
    }
}

__device__ __forceinline__ uint32_t fresh_tid() { uint32_t t; asm volatile("mov.u32 %0, %%tid.x;" : "=r"(t)); return t; }
__device__ __forceinline__ uint32_t fresh_ctaid() { uint32_t t; asm volatile("mov.u32 %0, %%ctaid.x;" : "=r"(t)); return logical_cta(t); }
__device__ __forceinline__ void reset_state(Cons& c, Pend& d, uint32_t sb, bool resumed) {
    const uint32_t t = fresh_tid(), b = fresh_ctaid();
    const int w = __shfl_sync(0xffffffffu, t >> 5, 0);
    c.sb = sb; c.wg = w >> 2; c.wq = w & 3; c.lane = t & 31;
    c.rank = __shfl_sync(0xffffffffu, b & 1, 0); c.pair = __shfl_sync(0xffffffffu, lds32(sb + S_TAIL), 0);
    c.rel = mapa(sb + B_EMPTY, cluster_rank() ^ (c.lane & 1));
    c.atag = (lds32(sb + S_EPOCH) + 1) & 1;
    c.p.stage = 0; c.p.phase = 0;
    c.nst = resumed && c.pair < NCHAIN ? 2 * NPRE : 0;
    d = Pend{};
}
#define PROF_ITEM(i)
#define PROF_MAIN(i)

__global__ void __launch_bounds__(384, 1) fused_kernel(const __grid_constant__ Params P) {
    extern __shared__ __align__(1024) uint8_t smem[];
    const uint32_t sb = smem_u32(smem);
    asm volatile("griddepcontrol.launch_dependents;");
    const int tid = threadIdx.x, lane = tid & 31;
    const int warp = __shfl_sync(0xffffffffu, tid >> 5, 0);
    const int pair = __shfl_sync(0xffffffffu, logical_cta(blockIdx.x) >> 1, 0), rank = __shfl_sync(0xffffffffu, blockIdx.x & 1, 0);
    if (tid == 0) {
        if (sb & 1023) spin_fault();
        sts32(sb + S_EPOCH, ld_relaxed1(&g_cnt(C_EPOCH)));
        sts32(sb + S_DEP, 0); sts32(sb + S_CUR, 0); sts32(sb + S_TAIL, pair); sts32(sb + S_CTA, pair * 2 + rank);
        for (int i = 0; i < NSTAGE; i++) { mbar_init(sb + B_FULL + i * 8, 1); mbar_init(sb + B_EMPTY + i * 8, 16); }
        mbar_init(sb + B_RESUME, 2);
        mbar_init(sb + B_KVFULL, 1); mbar_init(sb + B_KVFULL + 8, 1);
        mbar_init(sb + B_GO, 1); mbar_init(sb + B_KVGO, 1); mbar_init(sb + B_KVGO + 8, 1); mbar_init(sb + B_K, 1); mbar_init(sb + B_V, 1); mbar_init(sb + B_PERS, 8); mbar_init(sb + B_INIT, 3);
        mbar_init(sb + B_WO, 1);
        for (int i = 0; i < 2; i++) { mbar_init(sb + B_SFULL + i * 8, 4); mbar_init(sb + B_SFREE + i * 8, 1); }
        mbar_init(sb + B_RELA, 1); mbar_init(sb + B_RELB, 1);
        asm volatile("fence.mbarrier_init.release.cluster;" ::: "memory");
        if (pair < 16) mbar_expect(sb + B_K, 2048);
        mbar_expect(sb + B_V, 2048);
    }
    cluster_sync();
    if (warp >= 8) {
        asm volatile("setmaxnreg.dec.sync.aligned.u32 24;");
        if (warp == 10 && lane < M_COUNT) map_prefetch(&P.tm[lane]);
        if (warp == 11 && lane == 0 && pair < 64) {
            const uint32_t t0 = gtime();
#pragma unroll 1
            for (int i = 0; i < 32; i++) {
                wait_time(t0 + P.pf0 + i * P.pf1, sb);
                l2_prefetch((const char*)(i < 16 ? P.Wq : P.Wo) + (size_t)((i & 15) * 128 + pair * 2 + rank) * 4096, 4096);
            }
        }
        if (warp == 9 && pair < NCHAIN) pacer(P, sb, lane);
        if (warp == 9) watcher(P, sb, rank, lane);
        if (warp >= 10 && lane == 0) store_warp(P, sb, warp - 10);
        if (warp == 8) {
            if (lane == 0) producer(P, sb, lds32(sb + S_TAIL), rank, lds32(sb + S_EPOCH));
            __syncwarp();
            asm volatile("barrier.cluster.arrive.relaxed.aligned;\nbarrier.cluster.wait.aligned;" ::: "memory");
        }
    } else {
        asm volatile("setmaxnreg.inc.sync.aligned.u32 240;");
        Cons c;
        Pend d;
        if (pair < NCHAIN) {
            mem0_max(P, sb, tid);
            reset_state(c, d, sb, false);
#pragma unroll 1
            for (int i = 0; i < NPRE; i++) {
                PROF_ITEM(i)
                const int item = ITEM(ITEM_OFF(pair) + i);
                float acc[128];
                mainloop<256, true>(acc, P, c, d, T_KV);
                epi_kv(acc, c, d, (item >> 5) & 7, item & 31);
            }
            ISTAMP(4)
            drain<0, true>(P, c, d);
            drain<1, true>(P, c, d);
            staging_wait(c);
            PROF_ITEM(NPRE)
            const int h = (pair & 15) * 2 + rank;
            if (pair < 16) chain_role<0>(P, sb, h, warp, lane);
            else if (pair < 32) chain_role<1>(P, sb, h, warp, lane);
            else chain_role<2>(P, sb, h, warp, lane);
            fence_async_smem();
            bar_sync(1, 256);
            const uint32_t t2 = fresh_tid();
            if (t2 < 2) mbar_arrive_cluster(mapa(sb + B_RESUME, cluster_rank() ^ t2));
        } else if (pair >= NPAIR - 2) {
            const int ch = (pair - (NPAIR - 2)) * 512 + rank * 256 + tid;
            g_coef[ch] = ssm_coef(__bfloat162float(P.Lre[ch]), __bfloat162float(P.Lim[ch]), __bfloat162float(P.logdt[ch]));
            bar_sync(1, 256);
            if (tid == 0) red_release(&g_cnt(C_COEF));
        }
        reset_state(c, d, sb, true);
        for (int it = ITEM_OFF(c.pair) + (c.pair < NCHAIN ? NPRE + 1 : 0);; it++) {
            const bool last = it == ITEM_OFF(c.pair + 1);
            if (d.kind != PEND_NONE && (last || !bar_and(5 + c.wg, mbar_test(sb + B_FULL + c.p.stage * 8, c.p.phase)))) drain_all(P, c, d);
            if (last) break;
            const int item = ITEM(it), type = item >> 8, mb = (item >> 5) & 7, nb = item & 31;
            PROF_ITEM(it - ITEM_OFF(c.pair))
            if (type >= T_OPH) {
                float acc[64];
                mainloop<128>(acc, P, c, d, type);
                PROF_MAIN(it - ITEM_OFF(c.pair))
                if (type == T_OPH) epi_oph(acc, c, d, mb, nb);
                else epi_a2_half<0>(acc, P, c, mb, nb * 128);
            } else {
                float acc[128];
                mainloop<256>(acc, P, c, d, type);
                PROF_MAIN(it - ITEM_OFF(c.pair))
                if (type == T_KV) epi_kv(acc, c, d, mb, nb);
                else if (type == T_QA) epi_qa(acc, c, d, mb, nb);
                else if (type == T_OP) epi_op(acc, c, d, mb, nb);
                else if (type == T_A1) epi_a1(acc, P, c, d, mb, nb, c.atag);
                else { epi_a2_half<0>(acc, P, c, mb, nb * 256); epi_a2_half<1>(acc, P, c, mb, nb * 256); }
            }
        }
        staging_wait(c);
        staging_post(c, PEND_NONE, 0, 0, 0);
        cluster_sync();
        if (c.wg == 0 && c.wq == 0 && c.lane == 0 && atomicInc(&g_cnt(C_DONE), DBGF(32) ? 95 : NPAIR * 2 - 1) == (DBGF(32) ? 95 : NPAIR * 2 - 1)) atomicAdd(&g_cnt(C_EPOCH), 1);
    }
}

typedef CUresult (*EncodeFn)(CUtensorMap*, CUtensorMapDataType, cuuint32_t, void*, const cuuint64_t*, const cuuint64_t*, const cuuint32_t*, const cuuint32_t*,
                             CUtensorMapInterleave, CUtensorMapSwizzle, CUtensorMapL2promotion, CUtensorMapFloatOOBfill);
void encode(EncodeFn fn, CUtensorMap* m, const void* base, int rank, const uint64_t* dims, const uint64_t* strides, const uint32_t* box, CUtensorMapSwizzle swz = CU_TENSOR_MAP_SWIZZLE_128B) {
    cuuint64_t d[5], s[5]; cuuint32_t b[5], e[5];
    for (int i = 0; i < rank; i++) { d[i] = dims[i]; b[i] = box[i]; e[i] = 1; if (i) s[i - 1] = strides[i - 1]; }
    fn(m, CU_TENSOR_MAP_DATA_TYPE_BFLOAT16, rank, (void*)base, d, s, b, e, CU_TENSOR_MAP_INTERLEAVE_NONE, swz,
       CU_TENSOR_MAP_L2_PROMOTION_L2_256B, CU_TENSOR_MAP_FLOAT_OOB_FILL_NONE);
}
void map_kmajor(EncodeFn fn, CUtensorMap* m, const void* base, uint64_t rows, uint64_t cols, uint32_t box_rows) {
    const uint64_t d[2] = {cols, rows}, s[1] = {cols * 2}; const uint32_t b[2] = {64, box_rows};
    encode(fn, m, base, 2, d, s, b);
}
void map_mnmajor(EncodeFn fn, CUtensorMap* m, const void* base, uint64_t krows, uint64_t cols) {
    const uint64_t d[3] = {64, krows, cols / 64}, s[2] = {cols * 2, 128}; const uint32_t b[3] = {64, 64, 2};
    encode(fn, m, base, 3, d, s, b);
}

}

extern "C" void kernel_launch(void* const* d_in, const int* in_sizes, int n_in, void* d_out, int out_size) {
    static Params P;
    static EncodeFn fn = nullptr;
    if (!fn) {
        cudaDriverEntryPointQueryResult q;
        cudaGetDriverEntryPoint("cuTensorMapEncodeTiled", (void**)&fn, cudaEnableDefault, &q);
        cudaFuncSetAttribute(fused_kernel, cudaFuncAttributeMaxDynamicSharedMemorySize, S_TOTAL);
    }
    const bf16* in[15];
    for (int i = 0; i < 15; i++) in[i] = (const bf16*)d_in[i];
    void *kvo, *ht, *gm;
    cudaGetSymbolAddress(&gm, g_m);
    P.gm = (uint8_t*)(((uintptr_t)gm + 32767) & ~(uintptr_t)32767);
    cudaGetSymbolAddress(&kvo, g_kvo);
    cudaGetSymbolAddress(&ht, g_ht);
    map_kmajor(fn, &P.tm[M_BX], in[9], 2048, 1024, 128);
    map_mnmajor(fn, &P.tm[M_WQ], in[11], 1024, 4096);
    map_mnmajor(fn, &P.tm[M_WK], in[12], 1024, 4096);
    map_mnmajor(fn, &P.tm[M_WV], in[13], 1024, 4096);
    map_mnmajor(fn, &P.tm[M_WO], in[14], 4096, 1024);
    map_kmajor(fn, &P.tm[M_OA], kvo, 3 * 2048, 4096, 128);
    P.swap_ri = in[4] < in[3];
    {
        const bf16* lo = P.swap_ri ? in[4] : in[3];
        const uint64_t diff = (uint64_t)((const char*)(P.swap_ri ? in[3] : in[4]) - (const char*)lo);
        const uint64_t d[4] = {1024, 8, 2, 128}, s[3] = {2048, diff, 16384}; const uint32_t b[4] = {64, 8, 2, 8};
        encode(fn, &P.tm[M_AB], lo, 4, d, s, b);
    }
    {
        const uint64_t d[4] = {1024, 2, 4, 1024}, s[3] = {2048, 64 * 2048, 4096}; const uint32_t b[4] = {64, 2, 4, 16};
        encode(fn, &P.tm[M_AX], in[0], 4, d, s, b);
    }
    map_mnmajor(fn, &P.tm[M_HT], ht, 2048, 2048);
    map_kmajor(fn, &P.tm[M_CRE], in[5], 1024, 1024, 128);
    map_kmajor(fn, &P.tm[M_CIM], in[6], 1024, 1024, 128);
    map_kmajor(fn, &P.tm[M_KVO], kvo, 3 * 2048, 4096, 32);
    map_kmajor(fn, &P.tm[M_HTS], ht, 2048, 2048, 32);
    map_kmajor(fn, &P.tm[M_WOH], in[14], 4096, 1024, 64);
    map_kmajor(fn, &P.tm[M_CREH], in[5], 1024, 1024, 64);
    map_kmajor(fn, &P.tm[M_CIMH], in[6], 1024, 1024, 64);
    for (int i = 0; i < 3; i++) {
        const uint64_t d[3] = {4096, 16, 64}, s[2] = {8192, 16 * 8192}; const uint32_t b[3] = {64, 8, 8};
        encode(fn, &P.tm[M_CQ + i], in[11 + i], 3, d, s, b);
    }
    {
        const uint64_t d[4] = {4096, 1, 1, 4096}, s[3] = {8192, 8192, 8192}; const uint32_t b[4] = {64, 1, 1, 32};
        encode(fn, &P.tm[M_KV4], kvo, 4, d, s, b);
    }
    for (int e = 0; e < 2; e++) {
        const uint64_t d[4] = {1024, 2, 4, 256}, s[3] = {8 * 2048, 2 * 2048, 16 * 2048}; const uint32_t b[4] = {64, 2, 4, 8};
        encode(fn, &P.tm[M_CO + e], in[14] + e * 1024, 4, d, s, b);
    }
    P.Wq = in[11]; P.Wk = in[12]; P.Wv = in[13]; P.Wo = in[14]; P.mem0 = in[10];
    P.Lre = in[1]; P.Lim = in[2]; P.logdt = in[7]; P.Dskip = in[8];
    P.out = (float*)d_out;
    P.two26 = 1u << 26;
    P.ds = 400; P.dc = 1600; P.alpha = 0.3f; P.extra = 200; P.da = 176; P.db = 384; P.dk = 600; P.dv = 112; P.pf0 = 1500; P.pf1 = 350; P.back = 150; P.ds0 = 950;
    for (int i = 0; i < (DBGF(32) ? 1 : 2); i++) {
        cudaLaunchConfig_t cfg = {};
        cfg.gridDim = dim3(i ? 36 : 96); cfg.blockDim = dim3(384); cfg.dynamicSmemBytes = S_TOTAL; cfg.stream = cudaStreamPerThread;
        cudaLaunchAttribute at[2];
        at[0].id = cudaLaunchAttributeClusterDimension; at[0].val.clusterDim.x = i ? 2 : 6; at[0].val.clusterDim.y = at[0].val.clusterDim.z = 1;
        at[1].id = cudaLaunchAttributeProgrammaticStreamSerialization; at[1].val.programmaticStreamSerializationAllowed = 1;
        cfg.attrs = at; cfg.numAttrs = 1 + i;
        cudaLaunchKernelEx(&cfg, fused_kernel, P);
    }
}
```

```cpp
#include <cuda_runtime.h>
#include <cuda_bf16.h>
#include <cuda.h>
#include <stdint.h>
#include <string.h>

typedef __nv_bfloat16 bf16;

namespace {

#define POLL 200
constexpr int SPIN_LIMIT = 1 << 22;
constexpr int NPAIR = 66;
constexpr int NCHAIN = 48;
enum { T_KV = 0, T_QA = 1, T_OP = 2, T_A1 = 3, T_A2 = 4, T_CHAIN = 5, T_OPH = 6, T_A2H = 7 };
enum { M_BX = 0, M_WQ, M_WK, M_WV, M_WO, M_OA, M_AB, M_AX, M_HT, M_CRE, M_CIM, M_KVO, M_HTS, M_WOH, M_CREH, M_CIMH, M_CQ, M_CK, M_CV, M_CO, M_CO1, M_KV4, M_COUNT };
enum { C_KV = 0, C_HT = 8, C_DONE = 24, C_EPOCH = 25, C_COEF = 26, C_FLAG = 32, C_O = 96 };

struct Params {
    CUtensorMap tm[M_COUNT];
    const bf16 *Wq, *Wk, *Wv, *Wo, *mem0, *Lre, *Lim, *logdt, *Dskip;
    float* out;
    uint8_t* gm;
    int swap_ri, zero;
    uint32_t two26;
    int ds, da, db, dk, dv, back, ds0, pf0, pf1, dc, extra;
    float alpha;
#define DBGF(x) false
};

constexpr int NPRE = 1;
__constant__ uint16_t c_off[67] = {0, 5, 10, 15, 19, 24, 28, 33, 37, 41, 45, 49, 54, 59, 64, 68, 72, 77, 81, 86, 90, 94, 99, 103, 108, 112, 116, 121, 125, 129, 134, 138, 142, 147, 152, 157, 161, 165, 170, 174, 179, 184, 189, 194, 199, 203, 208, 212, 216, 237, 257, 276, 297, 316, 336, 355, 376, 394, 412, 430, 449, 467, 486, 504, 523, 540, 560};
__constant__ uint16_t c_items[640] = {
    0, 1280, 303, 397, 1154, 33, 1280, 463, 460, 1187, 3, 1280, 367, 462, 1184, 36, 1280, 770, 611, 6, 1280, 363, 966, 1153,
    39, 1280, 491, 514, 9, 1280, 929, 456, 1088, 42, 1280, 897, 513, 12, 1280, 389, 576, 45, 1280, 421, 704, 15, 1280, 835,
    609, 48, 1280, 837, 457, 1248, 18, 1280, 806, 992, 1250, 51, 1280, 838, 994, 1251, 21, 1280, 834, 705, 54, 1280, 802, 707,
    32, 1280, 488, 396, 1026, 2, 1280, 489, 1121, 35, 1280, 324, 492, 1186, 5, 1280, 490, 672, 38, 1280, 931, 736, 8, 1280,
    930, 330, 1217, 41, 1280, 866, 673, 11, 1280, 962, 934, 1185, 44, 1280, 298, 641, 14, 1280, 362, 642, 47, 1280, 967, 270,
    1058, 17, 1280, 963, 515, 50, 1280, 933, 674, 20, 1280, 903, 902, 1090, 53, 1280, 486, 578, 23, 1280, 454, 546, 1, 1280,
    329, 461, 1152, 34, 1280, 484, 398, 1155, 4, 1280, 328, 493, 1024, 37, 1280, 485, 675, 7, 1280, 899, 739, 40, 1280, 898,
    458, 1216, 10, 1280, 869, 545, 43, 1280, 965, 870, 1057, 13, 1280, 293, 424, 431, 46, 1280, 357, 426, 429, 16, 1280, 867,
    302, 1056, 49, 1280, 871, 301, 1122, 19, 1280, 901, 738, 52, 1280, 935, 900, 1091, 22, 1280, 455, 547, 55, 1280, 487, 579,
    24, 66, 84, 102, 120, 128, 142, 160, 176, 202, 163, 223, 195, 231, 240, 422, 450, 481, 366, 999, 1219, 56, 67, 85,
    103, 121, 129, 143, 184, 179, 208, 196, 201, 204, 288, 768, 430, 482, 995, 998, 1123, 25, 68, 86, 104, 122, 130, 144,
    212, 173, 235, 237, 227, 234, 392, 335, 256, 427, 865, 512, 57, 69, 87, 105, 123, 131, 145, 214, 181, 232, 162, 239,
    203, 242, 418, 800, 836, 483, 960, 996, 1027, 26, 70, 88, 106, 124, 132, 146, 249, 219, 178, 174, 194, 334, 250, 291,
    331, 323, 417, 643, 58, 71, 89, 107, 125, 133, 147, 165, 183, 229, 247, 209, 385, 321, 386, 425, 295, 453, 269, 1059,
    27, 72, 90, 108, 126, 134, 148, 190, 166, 180, 200, 230, 390, 365, 361, 416, 263, 359, 706, 59, 73, 91, 109, 127,
    135, 149, 186, 185, 199, 206, 198, 197, 253, 355, 832, 448, 451, 332, 399, 1218, 28, 74, 92, 110, 265, 136, 150, 168,
    172, 217, 364, 353, 241, 393, 360, 459, 495, 640, 60, 75, 93, 111, 257, 137, 151, 182, 221, 189, 192, 252, 254, 233,
    420, 356, 807, 577, 29, 76, 94, 112, 262, 138, 152, 210, 188, 193, 358, 300, 327, 804, 333, 928, 452, 608, 61, 77,
    95, 113, 259, 139, 153, 171, 187, 292, 211, 236, 226, 772, 803, 299, 961, 494, 1120, 30, 78, 96, 114, 266, 140, 154,
    251, 175, 164, 216, 215, 255, 322, 354, 267, 839, 737, 62, 79, 97, 115, 271, 141, 155, 177, 161, 325, 245, 248, 769,
    326, 833, 775, 394, 964, 1025, 31, 80, 98, 116, 268, 296, 156, 213, 191, 224, 220, 290, 225, 423, 419, 320, 480, 610,
    63, 81, 99, 117, 264, 297, 157, 207, 167, 205, 289, 388, 387, 391, 428, 395, 993, 932, 1089, 64, 82, 100, 118, 261,
    294, 158, 228, 170, 771, 244, 773, 352, 864, 449, 774, 544, 65, 83, 101, 119, 260, 258, 159, 169, 218, 246, 222, 243,
    238, 384, 801, 896, 805, 868, 997, 1249,
};
#define ITEM_OFF(p) c_off[p]
#define ITEM(i) c_items[i]

__device__ __align__(1024) bf16 g_kvo[3 * 2048 * 4096];
__device__ __align__(1024) bf16 g_ht[2048 * 2048];
__device__ __align__(1024) uint8_t g_m[9 * 32768];
__device__ __align__(1024) uint8_t g_f[8 * 49152];
__device__ __align__(1024) uint32_t g_km[64 * 32 * 512];
__device__ __align__(1024) uint32_t g_vmt[64 * 32 * 512];
__device__ __align__(1024) float2 g_agg[8 * 1024];
__device__ __align__(1024) float4 g_coef[1024];
__device__ __align__(1024) uint32_t g_cntl[128 * 32];
#define g_cnt(i) g_cntl[(i) * 32]
__device__ __align__(1024) uint32_t g_hint[6144 + 96];
#define SSTAMP(i, cond)
#define PROF(i)
#define GT_EDGE(o)
constexpr int M_SLOT = 32768, F_SLOT = 49152;

constexpr int STAGE = 49152, NSTAGE = 4;
constexpr int S_STG = NSTAGE * STAGE;
constexpr int S_BAR = S_STG + 32768;
constexpr int B_FULL = S_BAR, B_EMPTY = S_BAR + 32, B_RESUME = S_BAR + 64, B_KVFULL = S_BAR + 72, B_GO = S_BAR + 88, B_K = S_BAR + 96, B_PERS = S_BAR + 104, B_INIT = S_BAR + 112, B_RELA = S_BAR + 120, B_V = S_BAR + 128, B_WO = S_BAR + 136,
              B_SFULL = S_BAR + 144, B_SFREE = S_BAR + 160, S_DESC = S_BAR + 176, S_REDO = S_BAR + 256 + 512 + 64, S_EPOCH = S_BAR + 208, B_RELB = S_BAR + 216, B_KVGO = S_BAR + 224, S_DEP = S_BAR + 240, S_CUR = S_BAR + 244, S_TAIL = S_BAR + 248, S_CTA = S_BAR + 252;
constexpr int S_COEF = S_BAR + 256 + 512, S_TOTAL = S_COEF + 1024;
constexpr int S_W1 = 0;
constexpr int S_O = 24 * 4096, S_VL = S_O + 2048, S_MX = 25 * 4096, S_SC = S_MX + 64, S_SUM = S_MX + 128;
constexpr int S_KL = 26 * 4096;
constexpr int S_W2 = 27 * 4096;
constexpr int S_KV = S_W2 + 65536;
constexpr int S_P1 = S_W2 + 98304;
constexpr int S_QX = S_P1 + 16384;
constexpr int S_SX = S_QX + 2048;
static_assert(S_SX + 1280 <= S_BAR, "chain smem overlaps barriers");
constexpr int NR = 40, NS = 64 - NR;

__device__ __forceinline__ uint32_t logical_cta(uint32_t b) {
    const uint32_t c = b / 6, r = b - c * 6;
    return gridDim.x != 96 ? 96 + b : ((r >> 1) + (c >= 8) + (c >= 15)) % 3 * 32 + c * 2 + (r & 1);
}
__device__ __forceinline__ uint32_t cluster_rank() { uint32_t r; asm("mov.u32 %0, %%cluster_ctarank;" : "=r"(r)); return r; }
__device__ __forceinline__ uint16_t pair_mask() { return (uint16_t)(3u << (cluster_rank() & 6)); }
__device__ __forceinline__ void spin_fault() { asm volatile("st.global.u32 [%0], 0;" ::"l"(0ull) : "memory"); }
__device__ __forceinline__ uint32_t smem_u32(const void* p) { return (uint32_t)__cvta_generic_to_shared(p); }
__device__ __forceinline__ uint32_t opq(uint32_t x, int lane) { return __shfl_sync(0xffffffffu, x, lane); }
__device__ __forceinline__ uint32_t mapa(uint32_t a, uint32_t r) { uint32_t d; asm volatile("mapa.shared::cluster.u32 %0, %1, %2;" : "=r"(d) : "r"(a), "r"(r)); return d; }
__device__ __forceinline__ void mma16816(float* d, uint32_t a0, uint32_t a1, uint32_t a2, uint32_t a3, uint32_t b0, uint32_t b1) {
    asm("mma.sync.aligned.m16n8k16.row.col.f32.bf16.bf16.f32 {%0,%1,%2,%3}, {%4,%5,%6,%7}, {%8,%9}, {%0,%1,%2,%3};"
        : "+f"(d[0]), "+f"(d[1]), "+f"(d[2]), "+f"(d[3]) : "r"(a0), "r"(a1), "r"(a2), "r"(a3), "r"(b0), "r"(b1));
}
__device__ __forceinline__ void mma1688(float* d, uint32_t a0, uint32_t a1, uint32_t b0) {
    asm("mma.sync.aligned.m16n8k8.row.col.f32.bf16.bf16.f32 {%0,%1,%2,%3}, {%4,%5}, {%6}, {%0,%1,%2,%3};"
        : "+f"(d[0]), "+f"(d[1]), "+f"(d[2]), "+f"(d[3]) : "r"(a0), "r"(a1), "r"(b0));
}
__device__ __forceinline__ void ldsm4(uint32_t* r, uint32_t a) {
    asm volatile("ldmatrix.sync.aligned.m8n8.x4.shared.b16 {%0,%1,%2,%3}, [%4];" : "=r"(r[0]), "=r"(r[1]), "=r"(r[2]), "=r"(r[3]) : "r"(a));
}
__device__ __forceinline__ void ldsm4t(uint32_t* r, uint32_t a) {
    asm volatile("ldmatrix.sync.aligned.m8n8.x4.trans.shared.b16 {%0,%1,%2,%3}, [%4];" : "=r"(r[0]), "=r"(r[1]), "=r"(r[2]), "=r"(r[3]) : "r"(a));
}
__device__ __forceinline__ void stsm4(uint32_t a, uint32_t r0, uint32_t r1, uint32_t r2, uint32_t r3) {
    asm volatile("stmatrix.sync.aligned.m8n8.x4.shared.b16 [%0], {%1,%2,%3,%4};" ::"r"(a), "r"(r0), "r"(r1), "r"(r2), "r"(r3) : "memory");
}
__device__ __forceinline__ void stsm4t(uint32_t a, uint32_t r0, uint32_t r1, uint32_t r2, uint32_t r3) {
    asm volatile("stmatrix.sync.aligned.m8n8.x4.trans.shared.b16 [%0], {%1,%2,%3,%4};" ::"r"(a), "r"(r0), "r"(r1), "r"(r2), "r"(r3) : "memory");
}
__device__ __forceinline__ uint32_t pack2(float lo, float hi) { uint32_t d; asm("cvt.rn.bf16x2.f32 %0, %1, %2;" : "=r"(d) : "f"(hi), "f"(lo)); return d; }
__device__ __forceinline__ float bf_lo(uint32_t u) { return __uint_as_float(u << 16); }
__device__ __forceinline__ float bf_hi(uint32_t u) { return __uint_as_float(u & 0xffff0000u); }
__device__ __forceinline__ uint32_t hmul2(uint32_t a, uint32_t b) { uint32_t d; asm("mul.rn.bf16x2 %0, %1, %2;" : "=r"(d) : "r"(a), "r"(b)); return d; }
__device__ __forceinline__ float ex2(float x) { float y; asm("ex2.approx.ftz.f32 %0, %1;" : "=f"(y) : "f"(x)); return y; }
__device__ __forceinline__ float rcp(float x) { float y; asm("rcp.approx.ftz.f32 %0, %1;" : "=f"(y) : "f"(x)); return y; }
__device__ __forceinline__ void st_relaxed4(const void* p, uint32_t a, uint32_t b, uint32_t c, uint32_t d) {
    asm volatile("{\n.reg .b128 t;\nmov.b128 t, {%1,%2,%3,%4};\nst.relaxed.gpu.global.b128 [%0], t;\n}" ::"l"(p), "r"(a), "r"(b), "r"(c), "r"(d) : "memory");
}
__device__ __forceinline__ void st_relaxed2(const void* p, uint32_t a, uint32_t b) {
    asm volatile("{\n.reg .b64 t;\nmov.b64 t, {%1,%2};\nst.relaxed.gpu.global.b64 [%0], t;\n}" ::"l"(p), "r"(a), "r"(b) : "memory");
}
__device__ __forceinline__ void ld_relaxed2_if(uint32_t& a, uint32_t& b, const void* p, bool on) {
    asm volatile("{\n.reg .pred P;\n.reg .b64 t;\nsetp.ne.u32 P, %3, 0;\nmov.b64 t, {%0,%1};\n@P ld.relaxed.gpu.global.b64 t, [%2];\nmov.b64 {%0,%1}, t;\n}" : "+r"(a), "+r"(b) : "l"(p), "r"((uint32_t)on) : "memory");
}
__device__ __forceinline__ uint32_t ld_relaxed1(const void* p) { uint32_t v; asm volatile("ld.relaxed.gpu.global.u32 %0, [%1];" : "=r"(v) : "l"(p) : "memory"); return v; }
__device__ __forceinline__ void st_relaxed1(const void* p, uint32_t v) { asm volatile("st.relaxed.gpu.global.u32 [%0], %1;" ::"l"(p), "r"(v) : "memory"); }
__device__ __forceinline__ uint32_t ld_acquire(const void* p) { uint32_t v; asm volatile("ld.acquire.gpu.global.u32 %0, [%1];" : "=r"(v) : "l"(p) : "memory"); return v; }
__device__ __forceinline__ void red_release(void* p) { asm volatile("red.release.gpu.global.add.u32 [%0], 1;" ::"l"(p) : "memory"); }
__device__ __forceinline__ void st_stream2(float* p, float a, float b) { asm volatile("st.global.cs.v2.f32 [%0], {%1, %2};" ::"l"(p), "f"(a), "f"(b) : "memory"); }
__device__ __forceinline__ void fence_acquire() { asm volatile("fence.acquire.gpu;" ::: "memory"); }
__device__ __forceinline__ void fence_release() { asm volatile("fence.release.gpu;" ::: "memory"); }
__device__ __forceinline__ void fence_async() {  asm volatile("fence.proxy.async.global;" ::: "memory"); }
__device__ __forceinline__ void fence_async_smem() { asm volatile("fence.proxy.async.shared::cta;" ::: "memory"); }
__device__ __forceinline__ void wait_count(const uint32_t* p, uint32_t target) {
    int n = 0;
    while ((int32_t)(ld_acquire(p) - target) < 0) { __nanosleep(POLL); if (++n > SPIN_LIMIT) spin_fault(); }
}
__device__ __forceinline__ void bar_sync(int id, int n) { asm volatile("bar.sync %0, %1;" ::"r"(id), "r"(n) : "memory"); }
__device__ __forceinline__ void bar_arrive(int id, int n) { asm volatile("bar.arrive %0, %1;" ::"r"(id), "r"(n) : "memory"); }
__device__ __forceinline__ bool bar_and(int id, bool v) {
    uint32_t r;
    asm volatile("{\n.reg .pred P, Q;\nsetp.ne.u32 Q, %2, 0;\nbar.red.and.pred P, %1, 128, Q;\nselp.u32 %0, 1, 0, P;\n}" : "=r"(r) : "r"(id), "r"((uint32_t)v) : "memory");
    return r;
}
__device__ __forceinline__ void lds128(uint32_t* v, uint32_t a) { asm volatile("ld.shared.v4.b32 {%0,%1,%2,%3}, [%4];" : "=r"(v[0]), "=r"(v[1]), "=r"(v[2]), "=r"(v[3]) : "r"(a) : "memory"); }
__device__ __forceinline__ uint32_t lds32(uint32_t a) { uint32_t v; asm volatile("ld.shared.b32 %0, [%1];" : "=r"(v) : "r"(a) : "memory"); return v; }
__device__ __forceinline__ void lds64f(float* v, uint32_t a) { asm volatile("ld.shared.v2.f32 {%0,%1}, [%2];" : "=f"(v[0]), "=f"(v[1]) : "r"(a) : "memory"); }
__device__ __forceinline__ void sts128(uint32_t a, const uint32_t* v) { asm volatile("st.shared.v4.b32 [%0], {%1,%2,%3,%4};" ::"r"(a), "r"(v[0]), "r"(v[1]), "r"(v[2]), "r"(v[3]) : "memory"); }
__device__ __forceinline__ void sts64(uint32_t a, uint32_t x, uint32_t y) { asm volatile("st.shared.v2.b32 [%0], {%1,%2};" ::"r"(a), "r"(x), "r"(y) : "memory"); }
__device__ __forceinline__ void sts32(uint32_t a, uint32_t x) { asm volatile("st.shared.b32 [%0], %1;" ::"r"(a), "r"(x) : "memory"); }
__device__ __forceinline__ bool mbar_try(uint32_t b, uint32_t par) {
    uint32_t ok;
    asm volatile("{\n.reg .pred P;\nmbarrier.try_wait.parity.shared::cta.b64 P, [%1], %2;\nselp.u32 %0, 1, 0, P;\n}" : "=r"(ok) : "r"(b), "r"(par) : "memory");
    return ok;
}
__device__ __forceinline__ bool mbar_test(uint32_t b, uint32_t par) {
    uint32_t ok;
    asm volatile("{\n.reg .pred P;\nmbarrier.test_wait.parity.shared::cta.b64 P, [%1], %2;\nselp.u32 %0, 1, 0, P;\n}" : "=r"(ok) : "r"(b), "r"(par) : "memory");
    return ok;
}
__device__ __forceinline__ void mbar_wait(uint32_t b, uint32_t par) { int n = 0; while (!mbar_try(b, par)) { if (++n > SPIN_LIMIT) spin_fault(); } }
__device__ __forceinline__ void mbar_init(uint32_t b, uint32_t n) { asm volatile("mbarrier.init.shared::cta.b64 [%0], %1;" ::"r"(b), "r"(n) : "memory"); }
__device__ __forceinline__ void mbar_expect(uint32_t b, uint32_t bytes) { asm volatile("mbarrier.arrive.expect_tx.shared::cta.b64 _, [%0], %1;" ::"r"(b), "r"(bytes) : "memory"); }
__device__ __forceinline__ void mbar_arrive(uint32_t b) { asm volatile("mbarrier.arrive.shared::cta.b64 _, [%0];" ::"r"(b) : "memory"); }
__device__ __forceinline__ void mbar_arrive_cluster(uint32_t b) { asm volatile("mbarrier.arrive.shared::cluster.b64 _, [%0];" ::"r"(b) : "memory"); }
__device__ __forceinline__ void st_async1(uint32_t a, uint32_t x, uint32_t bar) {
    asm volatile("st.async.weak.shared::cluster.mbarrier::complete_tx::bytes.b32 [%0], %1, [%2];" ::"r"(a), "r"(x), "r"(bar) : "memory");
}
__device__ __forceinline__ void st_async2(uint32_t a, uint32_t x, uint32_t y, uint32_t bar) {
    asm volatile("st.async.weak.shared::cluster.mbarrier::complete_tx::bytes.v2.b32 [%0], {%1,%2}, [%3];" ::"r"(a), "r"(x), "r"(y), "r"(bar) : "memory");
}
__device__ __forceinline__ void cluster_sync() { asm volatile("barrier.cluster.arrive.aligned;\nbarrier.cluster.wait.aligned;" ::: "memory"); }
__device__ __forceinline__ void tma2d(uint32_t dst, const CUtensorMap* m, int c0, int c1, uint32_t bar) {
    asm volatile("cp.async.bulk.tensor.2d.shared::cluster.global.mbarrier::complete_tx::bytes [%0], [%1, {%2, %3}], [%4];" ::"r"(dst), "l"(m), "r"(c0), "r"(c1), "r"(bar) : "memory");
}
__device__ __forceinline__ void tma2d_mc(uint32_t dst, const CUtensorMap* m, int c0, int c1, uint32_t bar) {
    asm volatile("cp.async.bulk.tensor.2d.shared::cluster.global.mbarrier::complete_tx::bytes.multicast::cluster [%0], [%1, {%2, %3}], [%4], %5;" ::"r"(dst), "l"(m), "r"(c0), "r"(c1), "r"(bar), "h"(pair_mask()) : "memory");
}
__device__ __forceinline__ void tma3d(uint32_t dst, const CUtensorMap* m, int c0, int c1, int c2, uint32_t bar) {
    asm volatile("cp.async.bulk.tensor.3d.shared::cluster.global.mbarrier::complete_tx::bytes [%0], [%1, {%2, %3, %4}], [%5];" ::"r"(dst), "l"(m), "r"(c0), "r"(c1), "r"(c2), "r"(bar) : "memory");
}
__device__ __forceinline__ void tma3d_mc(uint32_t dst, const CUtensorMap* m, int c0, int c1, int c2, uint32_t bar) {
    asm volatile("cp.async.bulk.tensor.3d.shared::cluster.global.mbarrier::complete_tx::bytes.multicast::cluster [%0], [%1, {%2, %3, %4}], [%5], %6;" ::"r"(dst), "l"(m), "r"(c0), "r"(c1), "r"(c2), "r"(bar), "h"(pair_mask()) : "memory");
}
__device__ __forceinline__ void tma4d(uint32_t dst, const CUtensorMap* m, int c0, int c3, uint32_t bar) {
    asm volatile("cp.async.bulk.tensor.4d.shared::cluster.global.mbarrier::complete_tx::bytes [%0], [%1, {%2, 0, 0, %3}], [%4];" ::"r"(dst), "l"(m), "r"(c0), "r"(c3), "r"(bar) : "memory");
}
__device__ __forceinline__ void tma4d_mc(uint32_t dst, const CUtensorMap* m, int c0, int c3, uint32_t bar) {
    asm volatile("cp.async.bulk.tensor.4d.shared::cluster.global.mbarrier::complete_tx::bytes.multicast::cluster [%0], [%1, {%2, 0, 0, %3}], [%4], %5;" ::"r"(dst), "l"(m), "r"(c0), "r"(c3), "r"(bar), "h"(pair_mask()) : "memory");
}
__device__ __forceinline__ void tma_prefetch2d(const CUtensorMap* m, int c0, int c1) {
    asm volatile("cp.async.bulk.prefetch.tensor.2d.L2.global [%0, {%1, %2}];" ::"l"(m), "r"(c0), "r"(c1) : "memory");
}
__device__ __forceinline__ void map_prefetch(const CUtensorMap* m) { asm volatile("prefetch.tensormap [%0];" ::"l"(m) : "memory"); }
__device__ __forceinline__ void l2_prefetch(const void* src, uint32_t bytes) { asm volatile("cp.async.bulk.prefetch.L2.global [%0], %1;" ::"l"(src), "r"(bytes) : "memory"); }
__device__ __forceinline__ void bulk_g2s(uint32_t dst, const void* src, uint32_t bytes, uint32_t bar) {
    asm volatile("cp.async.bulk.shared::cluster.global.mbarrier::complete_tx::bytes [%0], [%1], %2, [%3];" ::"r"(dst), "l"(src), "r"(bytes), "r"(bar) : "memory");
}
__device__ __forceinline__ void tma_store2d(const CUtensorMap* m, int c0, int c1, uint32_t src) {
    asm volatile("cp.async.bulk.tensor.2d.global.shared::cta.bulk_group [%0, {%1, %2}], [%3];" ::"l"(m), "r"(c0), "r"(c1), "r"(src) : "memory");
}
__device__ __forceinline__ void bulk_commit() { asm volatile("cp.async.bulk.commit_group;" ::: "memory"); }
__device__ __forceinline__ void bulk_wait_read() { asm volatile("cp.async.bulk.wait_group.read 0;" ::: "memory"); }
__device__ __forceinline__ void bulk_wait_all() { asm volatile("cp.async.bulk.wait_group 0;" ::: "memory"); }
__device__ __forceinline__ uint64_t mkdesc(uint32_t addr, uint32_t lbo, uint32_t sbo, uint32_t swz) {
    return (uint64_t)((addr & 0x3FFFF) >> 4) | ((uint64_t)(lbo >> 4) << 16) | ((uint64_t)(sbo >> 4) << 32) | ((uint64_t)swz << 62);
}
__device__ __forceinline__ void wg_fence() { asm volatile("wgmma.fence.sync.aligned;" ::: "memory"); }
__device__ __forceinline__ void wg_commit() { asm volatile("wgmma.commit_group.sync.aligned;" ::: "memory"); }
template <int N> __device__ __forceinline__ void wg_wait() { asm volatile("wgmma.wait_group.sync.aligned %0;" ::"n"(N) : "memory"); }
template <typename T> __device__ __forceinline__ void pin_ptr(T*& p) { asm volatile("" : "+l"(p)); }
template <int N> __device__ __forceinline__ void pin(uint32_t* d) {
#pragma unroll
    for (int i = 0; i < N; i++) asm volatile("" : "+r"(d[i])::"memory");
}
template <int N> __device__ __forceinline__ void pin(float* d) {
#pragma unroll
    for (int i = 0; i < N; i++) asm volatile("" : "+f"(d[i])::"memory");
}

template <int TA, int TB>
__device__ __forceinline__ void wgmma_ss256(float* d, uint64_t da, uint64_t db) {
    asm volatile("wgmma.mma_async.sync.aligned.m64n256k16.f32.bf16.bf16 "
        "{%0, %1, %2, %3, %4, %5, %6, %7, %8, %9, %10, %11, %12, %13, %14, %15, %16, %17, %18, %19, %20, %21, %22, %23, %24, %25, %26, %27, %28, %29, %30, %31, %32, %33, %34, %35, %36, %37, %38, %39, %40, %41, %42, %43, %44, %45, %46, %47, %48, %49, %50, %51, %52, %53, %54, %55, %56, %57, %58, %59, %60, %61, %62, %63, %64, %65, %66, %67, %68, %69, %70, %71, %72, %73, %74, %75, %76, %77, %78, %79, %80, %81, %82, %83, %84, %85, %86, %87, %88, %89, %90, %91, %92, %93, %94, %95, %96, %97, %98, %99, %100, %101, %102, %103, %104, %105, %106, %107, %108, %109, %110, %111, %112, %113, %114, %115, %116, %117, %118, %119, %120, %121, %122, %123, %124, %125, %126, %127}, %128, %129, 1, 1, 1, %130, %131;"
        : "+f"(d[0]), "+f"(d[1]), "+f"(d[2]), "+f"(d[3]), "+f"(d[4]), "+f"(d[5]), "+f"(d[6]), "+f"(d[7]), "+f"(d[8]), "+f"(d[9]), "+f"(d[10]), "+f"(d[11]), "+f"(d[12]), "+f"(d[13]), "+f"(d[14]), "+f"(d[15]), "+f"(d[16]), "+f"(d[17]), "+f"(d[18]), "+f"(d[19]), "+f"(d[20]), "+f"(d[21]), "+f"(d[22]), "+f"(d[23]), "+f"(d[24]), "+f"(d[25]), "+f"(d[26]), "+f"(d[27]), "+f"(d[28]), "+f"(d[29]), "+f"(d[30]), "+f"(d[31]), "+f"(d[32]), "+f"(d[33]), "+f"(d[34]), "+f"(d[35]), "+f"(d[36]), "+f"(d[37]), "+f"(d[38]), "+f"(d[39]), "+f"(d[40]), "+f"(d[41]), "+f"(d[42]), "+f"(d[43]), "+f"(d[44]), "+f"(d[45]), "+f"(d[46]), "+f"(d[47]), "+f"(d[48]), "+f"(d[49]), "+f"(d[50]), "+f"(d[51]), "+f"(d[52]), "+f"(d[53]), "+f"(d[54]), "+f"(d[55]), "+f"(d[56]), "+f"(d[57]), "+f"(d[58]), "+f"(d[59]), "+f"(d[60]), "+f"(d[61]), "+f"(d[62]), "+f"(d[63]), "+f"(d[64]), "+f"(d[65]), "+f"(d[66]), "+f"(d[67]), "+f"(d[68]), "+f"(d[69]), "+f"(d[70]), "+f"(d[71]), "+f"(d[72]), "+f"(d[73]), "+f"(d[74]), "+f"(d[75]), "+f"(d[76]), "+f"(d[77]), "+f"(d[78]), "+f"(d[79]), "+f"(d[80]), "+f"(d[81]), "+f"(d[82]), "+f"(d[83]), "+f"(d[84]), "+f"(d[85]), "+f"(d[86]), "+f"(d[87]), "+f"(d[88]), "+f"(d[89]), "+f"(d[90]), "+f"(d[91]), "+f"(d[92]), "+f"(d[93]), "+f"(d[94]), "+f"(d[95]), "+f"(d[96]), "+f"(d[97]), "+f"(d[98]), "+f"(d[99]), "+f"(d[100]), "+f"(d[101]), "+f"(d[102]), "+f"(d[103]), "+f"(d[104]), "+f"(d[105]), "+f"(d[106]), "+f"(d[107]), "+f"(d[108]), "+f"(d[109]), "+f"(d[110]), "+f"(d[111]), "+f"(d[112]), "+f"(d[113]), "+f"(d[114]), "+f"(d[115]), "+f"(d[116]), "+f"(d[117]), "+f"(d[118]), "+f"(d[119]), "+f"(d[120]), "+f"(d[121]), "+f"(d[122]), "+f"(d[123]), "+f"(d[124]), "+f"(d[125]), "+f"(d[126]), "+f"(d[127])
        : "l"(da), "l"(db), "n"(TA), "n"(TB));
}
template <int TA, int TB>
__device__ __forceinline__ void wgmma_ss256_first(float* d, uint64_t da, uint64_t db) {
    asm volatile("wgmma.mma_async.sync.aligned.m64n256k16.f32.bf16.bf16 "
        "{%0, %1, %2, %3, %4, %5, %6, %7, %8, %9, %10, %11, %12, %13, %14, %15, %16, %17, %18, %19, %20, %21, %22, %23, %24, %25, %26, %27, %28, %29, %30, %31, %32, %33, %34, %35, %36, %37, %38, %39, %40, %41, %42, %43, %44, %45, %46, %47, %48, %49, %50, %51, %52, %53, %54, %55, %56, %57, %58, %59, %60, %61, %62, %63, %64, %65, %66, %67, %68, %69, %70, %71, %72, %73, %74, %75, %76, %77, %78, %79, %80, %81, %82, %83, %84, %85, %86, %87, %88, %89, %90, %91, %92, %93, %94, %95, %96, %97, %98, %99, %100, %101, %102, %103, %104, %105, %106, %107, %108, %109, %110, %111, %112, %113, %114, %115, %116, %117, %118, %119, %120, %121, %122, %123, %124, %125, %126, %127}, %128, %129, 0, 1, 1, %130, %131;"
        : "=f"(d[0]), "=f"(d[1]), "=f"(d[2]), "=f"(d[3]), "=f"(d[4]), "=f"(d[5]), "=f"(d[6]), "=f"(d[7]), "=f"(d[8]), "=f"(d[9]), "=f"(d[10]), "=f"(d[11]), "=f"(d[12]), "=f"(d[13]), "=f"(d[14]), "=f"(d[15]), "=f"(d[16]), "=f"(d[17]), "=f"(d[18]), "=f"(d[19]), "=f"(d[20]), "=f"(d[21]), "=f"(d[22]), "=f"(d[23]), "=f"(d[24]), "=f"(d[25]), "=f"(d[26]), "=f"(d[27]), "=f"(d[28]), "=f"(d[29]), "=f"(d[30]), "=f"(d[31]), "=f"(d[32]), "=f"(d[33]), "=f"(d[34]), "=f"(d[35]), "=f"(d[36]), "=f"(d[37]), "=f"(d[38]), "=f"(d[39]), "=f"(d[40]), "=f"(d[41]), "=f"(d[42]), "=f"(d[43]), "=f"(d[44]), "=f"(d[45]), "=f"(d[46]), "=f"(d[47]), "=f"(d[48]), "=f"(d[49]), "=f"(d[50]), "=f"(d[51]), "=f"(d[52]), "=f"(d[53]), "=f"(d[54]), "=f"(d[55]), "=f"(d[56]), "=f"(d[57]), "=f"(d[58]), "=f"(d[59]), "=f"(d[60]), "=f"(d[61]), "=f"(d[62]), "=f"(d[63]), "=f"(d[64]), "=f"(d[65]), "=f"(d[66]), "=f"(d[67]), "=f"(d[68]), "=f"(d[69]), "=f"(d[70]), "=f"(d[71]), "=f"(d[72]), "=f"(d[73]), "=f"(d[74]), "=f"(d[75]), "=f"(d[76]), "=f"(d[77]), "=f"(d[78]), "=f"(d[79]), "=f"(d[80]), "=f"(d[81]), "=f"(d[82]), "=f"(d[83]), "=f"(d[84]), "=f"(d[85]), "=f"(d[86]), "=f"(d[87]), "=f"(d[88]), "=f"(d[89]), "=f"(d[90]), "=f"(d[91]), "=f"(d[92]), "=f"(d[93]), "=f"(d[94]), "=f"(d[95]), "=f"(d[96]), "=f"(d[97]), "=f"(d[98]), "=f"(d[99]), "=f"(d[100]), "=f"(d[101]), "=f"(d[102]), "=f"(d[103]), "=f"(d[104]), "=f"(d[105]), "=f"(d[106]), "=f"(d[107]), "=f"(d[108]), "=f"(d[109]), "=f"(d[110]), "=f"(d[111]), "=f"(d[112]), "=f"(d[113]), "=f"(d[114]), "=f"(d[115]), "=f"(d[116]), "=f"(d[117]), "=f"(d[118]), "=f"(d[119]), "=f"(d[120]), "=f"(d[121]), "=f"(d[122]), "=f"(d[123]), "=f"(d[124]), "=f"(d[125]), "=f"(d[126]), "=f"(d[127])
        : "l"(da), "l"(db), "n"(TA), "n"(TB));
}
template <int TA, int TB>
__device__ __forceinline__ void wgmma_ss128(float* d, uint64_t da, uint64_t db) {
    asm volatile("wgmma.mma_async.sync.aligned.m64n128k16.f32.bf16.bf16 "
        "{%0, %1, %2, %3, %4, %5, %6, %7, %8, %9, %10, %11, %12, %13, %14, %15, %16, %17, %18, %19, %20, %21, %22, %23, %24, %25, %26, %27, %28, %29, %30, %31, %32, %33, %34, %35, %36, %37, %38, %39, %40, %41, %42, %43, %44, %45, %46, %47, %48, %49, %50, %51, %52, %53, %54, %55, %56, %57, %58, %59, %60, %61, %62, %63}, %64, %65, 1, 1, 1, %66, %67;"
        : "+f"(d[0]), "+f"(d[1]), "+f"(d[2]), "+f"(d[3]), "+f"(d[4]), "+f"(d[5]), "+f"(d[6]), "+f"(d[7]), "+f"(d[8]), "+f"(d[9]), "+f"(d[10]), "+f"(d[11]), "+f"(d[12]), "+f"(d[13]), "+f"(d[14]), "+f"(d[15]), "+f"(d[16]), "+f"(d[17]), "+f"(d[18]), "+f"(d[19]), "+f"(d[20]), "+f"(d[21]), "+f"(d[22]), "+f"(d[23]), "+f"(d[24]), "+f"(d[25]), "+f"(d[26]), "+f"(d[27]), "+f"(d[28]), "+f"(d[29]), "+f"(d[30]), "+f"(d[31]), "+f"(d[32]), "+f"(d[33]), "+f"(d[34]), "+f"(d[35]), "+f"(d[36]), "+f"(d[37]), "+f"(d[38]), "+f"(d[39]), "+f"(d[40]), "+f"(d[41]), "+f"(d[42]), "+f"(d[43]), "+f"(d[44]), "+f"(d[45]), "+f"(d[46]), "+f"(d[47]), "+f"(d[48]), "+f"(d[49]), "+f"(d[50]), "+f"(d[51]), "+f"(d[52]), "+f"(d[53]), "+f"(d[54]), "+f"(d[55]), "+f"(d[56]), "+f"(d[57]), "+f"(d[58]), "+f"(d[59]), "+f"(d[60]), "+f"(d[61]), "+f"(d[62]), "+f"(d[63])
        : "l"(da), "l"(db), "n"(TA), "n"(TB));
}
template <int TA, int TB>
__device__ __forceinline__ void wgmma_ss128_first(float* d, uint64_t da, uint64_t db) {
    asm volatile("wgmma.mma_async.sync.aligned.m64n128k16.f32.bf16.bf16 "
        "{%0, %1, %2, %3, %4, %5, %6, %7, %8, %9, %10, %11, %12, %13, %14, %15, %16, %17, %18, %19, %20, %21, %22, %23, %24, %25, %26, %27, %28, %29, %30, %31, %32, %33, %34, %35, %36, %37, %38, %39, %40, %41, %42, %43, %44, %45, %46, %47, %48, %49, %50, %51, %52, %53, %54, %55, %56, %57, %58, %59, %60, %61, %62, %63}, %64, %65, 0, 1, 1, %66, %67;"
        : "=f"(d[0]), "=f"(d[1]), "=f"(d[2]), "=f"(d[3]), "=f"(d[4]), "=f"(d[5]), "=f"(d[6]), "=f"(d[7]), "=f"(d[8]), "=f"(d[9]), "=f"(d[10]), "=f"(d[11]), "=f"(d[12]), "=f"(d[13]), "=f"(d[14]), "=f"(d[15]), "=f"(d[16]), "=f"(d[17]), "=f"(d[18]), "=f"(d[19]), "=f"(d[20]), "=f"(d[21]), "=f"(d[22]), "=f"(d[23]), "=f"(d[24]), "=f"(d[25]), "=f"(d[26]), "=f"(d[27]), "=f"(d[28]), "=f"(d[29]), "=f"(d[30]), "=f"(d[31]), "=f"(d[32]), "=f"(d[33]), "=f"(d[34]), "=f"(d[35]), "=f"(d[36]), "=f"(d[37]), "=f"(d[38]), "=f"(d[39]), "=f"(d[40]), "=f"(d[41]), "=f"(d[42]), "=f"(d[43]), "=f"(d[44]), "=f"(d[45]), "=f"(d[46]), "=f"(d[47]), "=f"(d[48]), "=f"(d[49]), "=f"(d[50]), "=f"(d[51]), "=f"(d[52]), "=f"(d[53]), "=f"(d[54]), "=f"(d[55]), "=f"(d[56]), "=f"(d[57]), "=f"(d[58]), "=f"(d[59]), "=f"(d[60]), "=f"(d[61]), "=f"(d[62]), "=f"(d[63])
        : "l"(da), "l"(db), "n"(TA), "n"(TB));
}
template <int TB>
__device__ __forceinline__ void wgmma_rs128(float* d, const uint32_t* a, uint64_t db, uint32_t acc) {
    asm volatile("{\n.reg .pred P;\nsetp.ne.u32 P, %69, 0;\nwgmma.mma_async.sync.aligned.m64n128k16.f32.bf16.bf16 "
        "{%0, %1, %2, %3, %4, %5, %6, %7, %8, %9, %10, %11, %12, %13, %14, %15, %16, %17, %18, %19, %20, %21, %22, %23, %24, %25, %26, %27, %28, %29, %30, %31, %32, %33, %34, %35, %36, %37, %38, %39, %40, %41, %42, %43, %44, %45, %46, %47, %48, %49, %50, %51, %52, %53, %54, %55, %56, %57, %58, %59, %60, %61, %62, %63}, {%64, %65, %66, %67}, %68, P, 1, 1, %70;\n}"
        : "+f"(d[0]), "+f"(d[1]), "+f"(d[2]), "+f"(d[3]), "+f"(d[4]), "+f"(d[5]), "+f"(d[6]), "+f"(d[7]), "+f"(d[8]), "+f"(d[9]), "+f"(d[10]), "+f"(d[11]), "+f"(d[12]), "+f"(d[13]), "+f"(d[14]), "+f"(d[15]), "+f"(d[16]), "+f"(d[17]), "+f"(d[18]), "+f"(d[19]), "+f"(d[20]), "+f"(d[21]), "+f"(d[22]), "+f"(d[23]), "+f"(d[24]), "+f"(d[25]), "+f"(d[26]), "+f"(d[27]), "+f"(d[28]), "+f"(d[29]), "+f"(d[30]), "+f"(d[31]), "+f"(d[32]), "+f"(d[33]), "+f"(d[34]), "+f"(d[35]), "+f"(d[36]), "+f"(d[37]), "+f"(d[38]), "+f"(d[39]), "+f"(d[40]), "+f"(d[41]), "+f"(d[42]), "+f"(d[43]), "+f"(d[44]), "+f"(d[45]), "+f"(d[46]), "+f"(d[47]), "+f"(d[48]), "+f"(d[49]), "+f"(d[50]), "+f"(d[51]), "+f"(d[52]), "+f"(d[53]), "+f"(d[54]), "+f"(d[55]), "+f"(d[56]), "+f"(d[57]), "+f"(d[58]), "+f"(d[59]), "+f"(d[60]), "+f"(d[61]), "+f"(d[62]), "+f"(d[63])
        : "r"(a[0]), "r"(a[1]), "r"(a[2]), "r"(a[3]), "l"(db), "r"(acc), "n"(TB));
}
template <int TB>
__device__ __forceinline__ void wgmma_rs64(float* d, const uint32_t* a, uint64_t db, uint32_t acc) {
    asm volatile("{\n.reg .pred P;\nsetp.ne.u32 P, %37, 0;\nwgmma.mma_async.sync.aligned.m64n64k16.f32.bf16.bf16 "
        "{%0, %1, %2, %3, %4, %5, %6, %7, %8, %9, %10, %11, %12, %13, %14, %15, %16, %17, %18, %19, %20, %21, %22, %23, %24, %25, %26, %27, %28, %29, %30, %31}, {%32, %33, %34, %35}, %36, P, 1, 1, %38;\n}"
        : "+f"(d[0]), "+f"(d[1]), "+f"(d[2]), "+f"(d[3]), "+f"(d[4]), "+f"(d[5]), "+f"(d[6]), "+f"(d[7]), "+f"(d[8]), "+f"(d[9]), "+f"(d[10]), "+f"(d[11]), "+f"(d[12]), "+f"(d[13]), "+f"(d[14]), "+f"(d[15]), "+f"(d[16]), "+f"(d[17]), "+f"(d[18]), "+f"(d[19]), "+f"(d[20]), "+f"(d[21]), "+f"(d[22]), "+f"(d[23]), "+f"(d[24]), "+f"(d[25]), "+f"(d[26]), "+f"(d[27]), "+f"(d[28]), "+f"(d[29]), "+f"(d[30]), "+f"(d[31])
        : "r"(a[0]), "r"(a[1]), "r"(a[2]), "r"(a[3]), "l"(db), "r"(acc), "n"(TB));
}
template <int TB>
__device__ __forceinline__ void wgmma_rs16(float* d, const uint32_t* a, uint64_t db, uint32_t acc) {
    asm volatile("{\n.reg .pred P;\nsetp.ne.u32 P, %13, 0;\nwgmma.mma_async.sync.aligned.m64n16k16.f32.bf16.bf16 "
        "{%0, %1, %2, %3, %4, %5, %6, %7}, {%8, %9, %10, %11}, %12, P, 1, 1, %14;\n}"
        : "+f"(d[0]), "+f"(d[1]), "+f"(d[2]), "+f"(d[3]), "+f"(d[4]), "+f"(d[5]), "+f"(d[6]), "+f"(d[7])
        : "r"(a[0]), "r"(a[1]), "r"(a[2]), "r"(a[3]), "l"(db), "r"(acc), "n"(TB));
}

__device__ __forceinline__ uint32_t delay_loop(int n, uint32_t x0) {
    uint32_t z;
    asm volatile("{\n.reg .pred P;\n.reg .u32 c, x;\nmov.u32 c, %1;\nmov.u32 x, %2;\nDL: mad.lo.u32 x, x, 1664525, 1013904223;\nadd.u32 c, c, -1;\nsetp.gt.s32 P, c, 0;\n@P bra DL;\n"
                 "setp.eq.u32 P, x, 0x7fffffff;\nselp.u32 %0, 16, 0, P;\n}" : "=r"(z) : "r"(n), "r"(x0) : "memory");
    return z;
}
__device__ __forceinline__ uint32_t gtime() { uint32_t t; asm volatile("mov.u32 %0, %%globaltimer_lo;" : "=r"(t)); return t; }
__device__ __forceinline__ void wait_time(uint32_t t, uint32_t sb) { while ((int32_t)(gtime() - t) < (int32_t)delay_loop(2, sb)) {} }
__device__ __forceinline__ uint32_t latest_stamp(const uint32_t* p, uint32_t seq, uint32_t ref, int backoff, uint32_t sb) {
    for (int n = 0;; n++) {
        uint32_t bad = 0; int32_t m = INT32_MIN;
#pragma unroll
        for (int i = 0; i < 3; i++) { const uint32_t v = ld_relaxed1(p + i * 256); bad |= (v ^ seq) & 31u; m = max(m, (int32_t)(v - (ref << 5)) >> 5); }
        if (__all_sync(0xffffffffu, bad == 0)) return ref + __reduce_max_sync(0xffffffffu, m);
        wait_time(gtime() + backoff, sb);
        if (n > SPIN_LIMIT) spin_fault();
    }
}
__device__ __forceinline__ void release_at(uint32_t t, uint32_t sb, uint32_t bar, int lane) {
    wait_time(t, sb);
    if (lane == 0) mbar_arrive(sb + bar);
}
__host__ __device__ constexpr int frag_word(int u, int f) { return (u == 0 ? 0 : u < 3 ? 3 * u - 1 : u == 3 ? 14 : 3 * u - 4) + f; }
__host__ __device__ constexpr int word_col(int e) { return ((0x32FED987CBA65410ull >> (4 * e)) & 14) * 64 + ((0x32FED987CBA65410ull >> (4 * e)) & 1) * 8; }

constexpr uint32_t CLEAR_LO = 0xFE000000u, CLEAR_HI = 0x5A7FEFEFu;
__device__ __forceinline__ void clear_slot(const Params& P, int slot, int cta, int lane) {
    const int i = cta * 2 + (lane >> 3), x = i & 63;
    if (lane < 16) st_relaxed4(P.gm + slot * M_SLOT + (x >> 1) * 1024 + (x & 1) * 256 + (i >> 7) * 512 + ((i >> 6) & 1) * 128 + (lane & 7) * 16, CLEAR_LO, CLEAR_HI, CLEAR_LO, CLEAR_HI);
    st_relaxed4(g_f + slot * F_SLOT + cta * 512 + lane * 16, 0, 0, 0, 0);
}
__device__ __forceinline__ void mem0_max(const Params& P, uint32_t sb, int tid) {
    uint32_t m = 0;
#pragma unroll
    for (int i = 0; i < 4; i++) {
        const uint4 x = __ldg((const uint4*)P.mem0 + i * 256 + tid);
        m = __vmaxu2(__vmaxu2(__vmaxu2(x.x & 0x7fff7fffu, x.y & 0x7fff7fffu), __vmaxu2(x.z & 0x7fff7fffu, x.w & 0x7fff7fffu)), m);
    }
    sts32(sb + S_COEF + (tid >> 5) * 4, __reduce_max_sync(0xffffffffu, max(m >> 16, m & 0xffffu)));
    bar_arrive(7, 288);
}
__device__ __forceinline__ uint32_t pack_mem0(const Params& P, uint32_t sb, int cta, int lane) {
    bar_sync(7, 288);
    const uint32_t e = __reduce_max_sync(0xffffffffu, lds32(sb + S_COEF + (lane & 7) * 4)) >> 7;
    if (e < 64 || e > 192) return 0x3F803F80u;
    const int i = cta * 2 + (lane >> 4), u = (i >> 5), x = i & 63, L = (i & 3) * 8 + ((lane & 15) >> 1);
    uint64_t w = 32;
#pragma unroll
    for (int f = 0; f < 3; f++) if (f < 2 || u % 3) {
        const float v = __bfloat162float(P.mem0[(L >> 2) * 1024 + word_col(frag_word(u, f)) + ((i >> 2) & 7) * 16 + (L & 3) * 2 + (lane & 1)]);
        w += (uint64_t)(int64_t)__float2int_rn(v * __uint_as_float((271 - e) << 23)) << (45 - 19 * f);
    }
    st_relaxed2(P.gm + 7 * M_SLOT + (x >> 1) * 1024 + (x & 1) * 256 + (i >> 7) * 512 + ((i >> 6) & 1) * 128 + (lane & 15) * 8, (uint32_t)w, (uint32_t)(w >> 32));
    return (e - 30) * 0x00800080u;
}
__device__ __forceinline__ void pacer(const Params& P, const uint32_t sb, const int lane) {
    constexpr uint32_t base = 2;
    int cta = lds32(sb + S_CTA);
#pragma unroll 1
    for (int i = 0; i < 8; i++) clear_slot(P, i, cta, lane);
    __syncwarp();
    if (lane == 0) { uint32_t smid; asm("mov.u32 %0, %%smid;" : "=r"(smid)); st_relaxed1(g_hint + 6144 + cta, smid >> 1); }
    sts32(sb + S_EPOCH + 4, pack_mem0(P, sb, cta, lane));
    SSTAMP(0, lane == 0)
    fence_release();
    __syncwarp();
    float rate = 0.58f;
    uint32_t c0 = 0;
#pragma unroll 1
    for (int s = -1; s < 63; s++) {
        cta = lds32(sb + S_CTA);
        const int pair = cta >> 1;
        const uint32_t ahead = s > 0 ? (uint32_t)(rate * (float)(pair >= 32 ? P.dc - P.dv : P.dc)) : 0;
        mbar_wait(sb + B_GO, s & 1);
        SSTAMP(10, lane == 0 && s == 0)
        const uint32_t t0 = gtime();
        if (lane < 4) st_relaxed1(g_hint + ((s & 1) * 4 + lane) * 768 + (cta >> 5) * 256 + (cta & 31), (t0 + ahead + (lds32(sb + S_REDO) == s ? P.extra : 0)) << 5 | ((base + s) & 31u));
        wait_time(t0 + (s < 0 ? 2000 : s == 0 && pair >= 16 ? P.ds0 : P.ds), sb);
        const uint32_t t = latest_stamp(g_hint + ((s & 1) * 4 + (pair & 3)) * 768 + lane, base + s, t0, P.back, sb);
        if (s < 0) {
            SSTAMP(2, lane == 0)
            fence_acquire();
            const uint32_t tpc = ld_relaxed1(g_hint + 6144 + (lane & 15) * 2), g = tpc < 32 ? tpc & 7 : tpc < 60 ? (tpc - 32) % 7 + 1 : (tpc - 54) & 7;
            const uint32_t key = (__popc(__match_any_sync(0xffffffffu, g)) > 4 ? 0 : g + 1) * 16 + (lane & 15);
            const uint32_t tail = (pair & 48) + __popc(__ballot_sync(0xffffffffu, key < __shfl_sync(0xffffffffu, key, pair & 15))) / 2;
            mbar_wait(sb + B_INIT, 0);
            SSTAMP(4, lane == 0)
            sts32(sb + S_TAIL, tail);
            if (lane < 8) sts32(sb + S_SC + lane * 4, lds32(sb + S_EPOCH + 4));
            __syncwarp();
        }
        release_at(t + P.da, sb, B_RELA, lane);
        SSTAMP(11, lane == 0 && s == 0)
        release_at(t + P.db, sb, B_RELB, lane);
        {
            const uint32_t c1 = clock(), g1 = gtime();
            if (s > 1) rate += P.alpha * (__fdividef((float)(g1 - lds32(sb + S_EPOCH + 4)), (float)(c1 - c0)) - rate);
            __syncwarp();
            c0 = c1; sts32(sb + S_EPOCH + 4, g1);
        }
        if (!DBGF(16) && s >= 0) fence_release();
        __syncwarp();
        wait_time(t + P.db + 320, sb);
        clear_slot(P, (s + 6) & 7, cta, lane);
        if (s == 61) {
            sts32(sb + S_COEF, ITEM(ITEM_OFF(lds32(sb + S_TAIL)) + NPRE + 1) + (uint32_t)(uintptr_t)P.out);
            if (lane < M_CQ) map_prefetch(&P.tm[lane]);
        }
    }
}
__device__ __forceinline__ uint32_t xor_or(uint32_t a, uint32_t b, uint32_t t) { uint32_t d; asm("lop3.b32 %0, %1, %2, %3, 0x7E;" : "=r"(d) : "r"(a), "r"(b), "r"(t)); return d; }
__device__ __forceinline__ bool tags_ok(uint32_t bad) { return __all_sync(0xffffffffu, (bad & 1) == 0); }
#define RETRY(k)
#define RETRY_STAT(a, b)
#define UNIT_STAT(u0)
#define SFENCE() asm volatile("pmevent 1;" ::: "memory")
#define PF1 10
static_assert(NS == 24, "fragment residency");
__host__ __device__ constexpr bool in_smem(int n) { return n < 4 || n == 13 || n == 15; }
__host__ __device__ constexpr int unit_pos(int n) { return n < 4 ? n : n < 13 ? n - 4 : n == 13 ? 4 : n == 14 ? 9 : 5; }

__host__ __device__ constexpr int fill_unit(int q) { return q < 4 ? q : q < 6 ? q * 2 + 5 : q < 15 ? q - 2 : 14; }
__host__ __device__ constexpr int frag_off(int q) { return (q >> 2) * 16384 + ((q >> 1) & 1) * 8192 + (q & 1) * 512; }

constexpr uint32_t QBITS = 0x4B002000u;
constexpr uint64_t W_BIAS = ((uint64_t)QBITS << 45) + ((uint64_t)QBITS << 26) + (uint32_t)(QBITS << 7), W_CLEAR = 0 - 32 * W_BIAS;
static_assert(W_CLEAR == ((uint64_t)CLEAR_HI << 32 | CLEAR_LO), "clear value");
__host__ __device__ constexpr int unit_off(int u) { return (u & 1) * 16384 + (u >> 2) * 512 + ((u >> 1) & 1) * 128; }
__device__ __forceinline__ void red_add64(const uint8_t* p, uint64_t v) { asm volatile("red.relaxed.gpu.global.add.u64 [%0], %1;" ::"l"(p), "l"(v) : "memory"); }
template <int NF>
__device__ __forceinline__ uint64_t encode(const float* x, float S, uint32_t two26, uint32_t& bad) {
    uint32_t b[3];
#pragma unroll
    for (int i = 0; i < 3; i++) b[i] = i < NF ? __float_as_uint(fmaf(x[i], S, 8396800.f)) : QBITS;
    bad = xor_or(b[0], b[1], 0x4B000000u) | (NF == 3 ? b[2] ^ 0x4B000000u : 0);
    uint64_t w;
    asm("{\n.reg .b64 t;\nmov.b64 t, {%2, %3};\nmad.wide.u32 %0, %1, %4, t;\n}" : "=l"(w) : "r"(b[1]), "r"(b[2] << 7), "r"(b[0] << 13), "r"(two26));
    return w;
}
template <int NF>
__device__ __forceinline__ void emit(uint64_t* w, const float (*x)[3], const float* S, uint32_t two26, uint32_t lim, const uint8_t* p) {
    uint32_t bad[2];
    w[0] = encode<NF>(x[0], S[0], two26, bad[0]); w[1] = encode<NF>(x[1], S[1], two26, bad[1]);
    const bool ok = (bad[0] | bad[1]) < lim;
    w[0] |= ok; w[1] |= ok;
    red_add64(p, w[0]); red_add64(p + 1024, w[1]);
}
template <int NF>
__device__ __forceinline__ void repair(const uint64_t* w, const float (*x)[3], const float* S, const uint8_t* p, const uint8_t* pf) {
    if (!(w[0] & 1)) {
#pragma unroll
        for (int j = 0; j < 2; j++) {
            const float T = S[j] * 8192.f;
            asm volatile("red.relaxed.gpu.global.add.v4.f32 [%0], {%1,%2,%3,%4};" ::"l"(pf + j * 512), "f"(x[j][0] * T), "f"(x[j][1] * T), "f"(NF == 3 ? x[j][2] * T : 0.f), "f"(0.f) : "memory");
        }
        fence_release();
#pragma unroll
        for (int j = 0; j < 2; j++) {
            asm volatile("red.relaxed.gpu.global.or.b64 [%0], 64;" ::"l"(p + j * 1024) : "memory");
            red_add64(p + j * 1024, W_BIAS + 1 - w[j]);
        }
    }
    __syncwarp();
}
__device__ __forceinline__ void ld_words(uint32_t* v, const uint8_t* p) {
    asm volatile("{\n.reg .b64 a, b;\nld.relaxed.gpu.global.L1::no_allocate.v2.b64 {a, b}, [%4];\nmov.b64 {%0,%1}, a;\nmov.b64 {%2,%3}, b;\n}" : "=r"(v[0]), "=r"(v[1]), "=r"(v[2]), "=r"(v[3]) : "l"(p) : "memory");
}
__device__ __forceinline__ float field(const uint32_t* w, int f) { return __int2float_rn((int)(f == 0 ? w[1] : f == 1 ? __funnelshift_l(w[0], w[1], 19) : w[0] << 6)); }
template <int U>
__device__ __forceinline__ void decode(uint32_t* b, const uint32_t* v) {
#pragma unroll
    for (int f = 0; f < (U % 3 ? 3 : 2); f++) b[frag_word(U, f)] = pack2(field(v, f), field(v + 2, f));
}
__device__ __forceinline__ uint32_t status(const uint32_t (*v)[4], uint32_t c32) { return xor_or(v[0][0], v[0][2], c32) | xor_or(v[1][0], v[1][2], c32) | xor_or(v[2][0], v[2][2], c32); }
__device__ __forceinline__ void gather_slow(const Params& P, uint32_t* b, const uint8_t* pm, int s, int warp, uint32_t ln, uint32_t u2) {
    if (s == 0 && u2 == 0x3F803F80u) {
#pragma unroll
        for (int i = 0; i < 16; i++) b[i] = __ldg((const uint32_t*)(P.mem0 + (ln >> 2) * 1024 + word_col(i) + warp * 16 + (ln & 3) * 2));
        return;
    }
    uint32_t v[6][4], st;
    for (int n = 0;; n++) {
#pragma unroll
        for (int u = 0; u < 6; u++) ld_words(v[u], pm + unit_off(u));
        st = status(v, 32) | status(v + 3, 32);
        if (!__any_sync(0xffffffffu, st & 32)) break;
        __nanosleep(200);
        if (n > SPIN_LIMIT) spin_fault();
    }
    const bool side = __any_sync(0xffffffffu, st & 64);
    if (side) fence_acquire();
    const uint8_t* pf = g_f + ((s + 7) & 7) * F_SLOT + warp * 1024 + ln * 32;
#pragma unroll
    for (int u = 0; u < 6; u++) {
        float x[2][4] = {};
#pragma unroll
        for (int k = 0; k < 2; k++)
            asm volatile("{\n.reg .pred P;\nsetp.ne.u32 P, %5, 0;\n@P ld.relaxed.gpu.global.v4.f32 {%0,%1,%2,%3}, [%4];\n}"
                         : "+f"(x[k][0]), "+f"(x[k][1]), "+f"(x[k][2]), "+f"(x[k][3]) : "l"(pf + u * 8192 + k * 16), "r"((uint32_t)side) : "memory");
#pragma unroll
        for (int f = 0; f < (u % 3 ? 3 : 2); f++) b[frag_word(u, f)] = pack2(field(v[u], f) + x[0][f], field(v[u] + 2, f) + x[1][f]);
    }
}
__device__ __forceinline__ uint32_t max_abs2(uint32_t a, uint32_t b) { uint32_t d; asm("max.NaN.xorsign.abs.bf16x2 %0, %1, %2;" : "=r"(d) : "r"(a), "r"(b)); return d; }
__device__ __forceinline__ uint32_t max6(const uint32_t* b) {
    const uint32_t m = max_abs2(max_abs2(max_abs2(b[0], b[1]), max_abs2(b[2], b[3])), max_abs2(b[4], b[5]));
    return max(m & 0x7fff0000u, (m << 16) & 0x7fff0000u);
}

template <bool TR>
__device__ __forceinline__ void put_partials(uint32_t a, const float* x, const float* y) {
    if (TR) stsm4t(a, pack2(x[0], x[1]), pack2(x[2], x[3]), pack2(y[0], y[1]), pack2(y[2], y[3]));
    else stsm4(a, pack2(x[0], x[1]), pack2(x[2], x[3]), pack2(y[0], y[1]), pack2(y[2], y[3]));
}
__device__ __forceinline__ void reduce_load(uint32_t (*x)[4], uint32_t a) { ldsm4t(x[0], a); ldsm4t(x[1], a + 512); }
__device__ __forceinline__ uint32_t reduce8(const uint32_t (*x)[4], uint32_t l8, uint32_t u2) {
    uint32_t p[2];
#pragma unroll
    for (int i = 0; i < 2; i++) {
        float d[4] = {};
        mma16816(d, x[i][0], x[i][1], x[i][2], x[i][3], (l8 & 32) ? 0u : u2, (l8 & 32) ? u2 : 0u);
        p[i] = pack2((l8 & 8) ? d[2] : d[0], (l8 & 8) ? d[3] : d[1]);
    }
    return (l8 & 16) ? p[1] : p[0];
}
__device__ __forceinline__ void score_half(float (*a)[4], const uint32_t (*qa)[4], const uint32_t (*kf)[4]) {
#pragma unroll
    for (int w = 0; w < 2; w++) {
        mma16816(a[w], qa[w][0], qa[w][1], qa[w][2], qa[w][3], kf[w][0], kf[w][1]);
        mma16816(a[2 + w], qa[w][0], qa[w][1], qa[w][2], qa[w][3], kf[w][2], kf[w][3]);
    }
}
__device__ __forceinline__ void score_sum(float* S, const float (*a)[4]) {
    S[0] = (a[0][0] + a[1][0]) + (a[2][2] + a[3][2]);
    S[1] = (a[0][1] + a[1][1]) + (a[2][3] + a[3][3]);
}
__device__ __forceinline__ float quad_max(float m) {
    m = fmaxf(m, __shfl_xor_sync(0xffffffffu, m, 1));
    return fmaxf(m, __shfl_xor_sync(0xffffffffu, m, 2));
}

#define ISTAMP(i)
__device__ __forceinline__ float next_scale(uint32_t sb, int slot, int warp, uint32_t u2) {
    uint32_t x[2][4];
    lds128(x[0], sb + S_MX + slot * 32); lds128(x[1], sb + S_MX + slot * 32 + 16);
    const uint32_t mx = max(max(max(x[0][0], x[0][1]), max(x[0][2], x[0][3])), max(max(x[1][0], x[1][1]), max(x[1][2], x[1][3])));
    const float top = fminf(fmaxf(__uint_as_float(mx) * bf_hi(u2), 0x1p-40f), 0x1p40f) * (1.f / (12288.f * 8192.f));
    const uint32_t un = pack2(top, top);
    sts32(sb + S_SC + warp * 4, un);
    return rcp(bf_hi(un) * 8192.f);
}
#define NEARLY 1
#define U3POS 1
#define VPOS 1
#define ROT 0
#define BPOS 1
#define ONLINE 0
#define NBAR 1
#define RPOS 1
#define AF 0
#define AFENCE(i) if ((AF >> (i)) & 1) SFENCE();
#define FPOS 99
#define PACE 1
#define PF2 12
__host__ __device__ constexpr int w2_t(int i) { return i < 16 ? i & 1 : 2; }
__host__ __device__ constexpr int w2_k(int i) { return i < 16 ? i >> 1 : i - 16; }
template <int ROLE>
__device__ __forceinline__ void chain_role(const Params& P, const uint32_t sb, const int h, const int warp, const int lane) {
    constexpr int NU = ROLE == 0 ? 2 : 3;
    const bool att = ROLE == 0 && warp < 4;
    uint32_t wr[NR][4];
    {
        const uint32_t frag = sb + warp * 1024 + (lane >> 4) * 8192 + (lane & 7) * 128 + ((((lane >> 3) & 1) ^ (lane & 7)) << 4);
        const uint32_t rel = mapa(sb + B_EMPTY, cluster_rank() ^ (lane & 1));
#define RELEASE(st) { fence_async_smem(); __syncwarp(); if (lane < 2) mbar_arrive_cluster(rel + (st) * 8); }
        mbar_wait(sb + B_FULL, 0); mbar_wait(sb + B_FULL + 8, 0);
        RELEASE(0) RELEASE(1)
#pragma unroll
        for (int st = 2; st < 4; st++) {
            mbar_wait(sb + B_FULL + st * 8, 0);
            ISTAMP(st - 2)
#pragma unroll
            for (int f = 0; f < 12; f++) ldsm4t(wr[st * 12 - 24 + f], (frag ^ ((f & 3) << 5)) + st * STAGE + (f >> 2) * 16384);
            RELEASE(st)
        }
#pragma unroll 2
        for (int u = 0; u < 6; u++) {
            uint32_t x[4][4];
#pragma unroll
            for (int i = 0; i < 4; i++) lds128(x[i], (frag ^ (i << 5)) + u * 16384);
            __syncwarp();
#pragma unroll
            for (int i = 0; i < 4; i++) sts128(sb + warp * 1024 + lane * 16 + u * 16384 + frag_off(i), x[i]);
        }
        mbar_wait(sb + B_FULL, 1); mbar_wait(sb + B_FULL + 8, 1);
        RELEASE(0) RELEASE(1)
#pragma unroll
        for (int st = 2; st < 4; st++) {
            mbar_wait(sb + B_FULL + st * 8, 1);
#pragma unroll
            for (int f = 0; f < (st == 2 ? 12 : 4); f++) ldsm4t(wr[st * 12 + f], (frag ^ ((f & 3) << 5)) + st * STAGE + (f >> 2) * 16384);
            RELEASE(st)
        }
        ISTAMP(2)
        bar_sync(1, 256);
        if (warp == 7 && lane < 3) mbar_arrive_cluster(mapa(sb + B_INIT, (cluster_rank() & 1) + lane * 2));
    }
    uint32_t l8 = opq(sb + lane * 8, lane);
    const uint8_t* persu = (const uint8_t*)((ROLE == 1 ? g_km : g_vmt) + h * 512 + warp * 32) - (sb >> 1);
#define PERS_STORE() { uint32_t* pp = (uint32_t*)(persu + s * 65536 + (l8 >> 1)); pp[0] = r0; pp[256] = r1; }
    const uint32_t rdelta = __shfl_sync(0xffffffffu, mapa(sb, (cluster_rank() + (ROLE == 1 ? 4 : 2)) % 6) - sb, 0);
    const uint32_t vdelta = ROLE ? 0 : __shfl_sync(0xffffffffu, mapa(sb, (cluster_rank() + 4) % 6) - sb, 0);
    ISTAMP(3)
    __syncwarp();
#define GATHER_OFF(s) ((((s) + 7) & 7) * M_SLOT + warp * 2048 + (l8 & 56) * 2 + (l8 & 64) * 4 + (l8 & 128) * 8)
    uint32_t mo = GATHER_OFF(0);
    if (ROT) mbar_wait(sb + B_RELA, 0);
    for (int s = 0; s < (ROLE == 0 ? 63 : 64);) {
        const int slot = s & 1;
        l8 += s & P.zero;
        const uint32_t w1a = l8 * 2 + (S_W1 + warp * 1024 - sb);
        PROF(9)
        uint32_t u2, r0, r1, pld, pub, pbar, x[2][4];
        {
#define pm (P.gm + mo)
            uint32_t as[24][4], b[16], v[6][4];
            float acc[8][4];
#define W1LD(n) _Pragma("unroll") for (int i_ = 0; i_ < 4; i_++) ldsm4t(as[unit_pos(n) * 4 + i_], w1a + frag_off(unit_pos(n) * 4 + i_));
#define W1MMA(n) _Pragma("unroll") for (int i_ = 0; i_ < 4; i_++) { const uint32_t* a_ = in_smem(n) ? as[unit_pos(n) * 4 + i_] : wr[unit_pos(n) * 4 + i_]; \
                                                                   mma16816(acc[((n) & 1) * 4 + i_], a_[0], a_[1], a_[2], a_[3], b[(n) & 14], b[(n) | 1]); }
#pragma unroll
            for (int T = 0; T < 8; T++) { acc[T][0] = acc[T][1] = acc[T][2] = acc[T][3] = 0.f; }
            if (!ROT) mbar_wait(sb + B_RELA, slot);
            PROF(12)
#pragma unroll
            for (int u = 0; u < 3; u++) ld_words(v[u], pm + unit_off(u));
            __syncwarp();
#pragma unroll
            for (int i = 0; i < PF1; i++) ldsm4t(as[i], w1a + frag_off(i));
            __syncwarp();
            mo += mbar_try(sb + B_RELB, slot) & P.zero;
            PROF(13)
#pragma unroll
            for (int u = 3; u < 6; u++) ld_words(v[u], pm + unit_off(u));
            uint32_t st = status(v, ((uint32_t)((uintptr_t)pm >> 32) & P.zero) + 32);
            pin<1>(&st);
            SFENCE();
            UNIT_STAT(0)
            PROF(0)
            decode<0>(b, v[0]); decode<1>(b, v[1]); decode<2>(b, v[2]);
#pragma unroll
            for (int i = PF1; i < 12; i++) ldsm4t(as[i], w1a + frag_off(i));
            W1MMA(0) W1MMA(1) W1MMA(2)
            W1LD(3)
            SFENCE();
            W1MMA(5) W1MMA(4) W1MMA(7) W1MMA(6)
            if (U3POS == 0) W1MMA(3)
            uint32_t mx = max6(b);
            pin<1>(&mx);
            SFENCE();
            PROF(10)
            if (U3POS == 1) W1MMA(3)
            const uint32_t mxa = sb + S_MX + slot * 32 + warp * 4;
            sts32(mxa, __reduce_max_sync(0xffffffffu, mx));
            UNIT_STAT(3)
            st |= status(v + 3, 32);
            const bool redo = __any_sync(0xffffffffu, st & 96);
            const bool kvok = ROLE || mbar_test(sb + B_KVFULL + slot * 8, (s >> 1) & 1);
            decode<4>(b, v[4]); decode<5>(b, v[5]); decode<3>(b, v[3]);
            u2 = lds32(sb + S_SC + warp * 4);
            W1MMA(8) W1MMA(10) W1MMA(12) W1MMA(14)
            W1LD(13)
            if (__builtin_expect(redo || !kvok, 0)) {
                if (redo) {
                    RETRY(3)
                    sts32(sb + S_REDO, s);
                    gather_slow(P, b, pm, s, warp, (l8 - sb) >> 3, u2);
                    sts32(mxa, __reduce_max_sync(0xffffffffu, max6(b)));
#pragma unroll
                    for (int T = 0; T < 8; T++) { acc[T][0] = acc[T][1] = acc[T][2] = acc[T][3] = 0.f; }
#pragma unroll
                    for (int n = 0; n < 15; n += n < 8 ? 1 : 2) {
                        if (in_smem(n)) { W1LD(n) }
                        W1MMA(n)
                    }
                    W1LD(13)
                }
                if (ROLE == 0) mbar_wait(sb + B_KVFULL + slot * 8, (s >> 1) & 1);
            }
#undef pm
            SSTAMP(7, threadIdx.x == 0 && s == 0)
            PROF(14)
            const uint32_t pst = (l8 - sb) * 16 + ((warp * 16) ^ ((l8 * 2) & 112)) + (sb + S_P1);
            put_partials<ROLE == 2>(pst, acc[0], acc[1]); put_partials<ROLE == 2>(pst + 4096, acc[2], acc[3]);
            W1MMA(9)
            SFENCE();
            W1LD(15)
            pld = (l8 & 64) * 4 + (l8 & 128) + (l8 & 56) * 2 + (sb + S_P1 + warp * 1024);
            const uint32_t rd = s == 63 ? 0 : rdelta;
            pub = ((l8 - sb) >> 1) + (ROLE ? sb + rd + (ROLE == 1 ? S_KL : S_VL) + warp * 128 : sb + S_QX + (warp & 4) * 128 + (warp & 1) * 256 + (warp & 2) * 64);
            pbar = sb + rd + (ROLE == 1 && s != 63 ? B_K : B_V);
#define PUBLISH0() { r0 = reduce8(x, l8, u2); if (ROLE) st_async1(pub, r0, pbar); else sts32(pub, r0); }
            if (RPOS == 0) { bar_sync(1, 256); reduce_load(x, pld); SFENCE(); }
            W1MMA(13)
            if (RPOS == 1) { bar_sync(1, 256); reduce_load(x, pld); }
            SFENCE();
            W1MMA(11)
            if (RPOS == 0) PUBLISH0()
            if (RPOS == 2) { bar_sync(1, 256); reduce_load(x, pld); }
            SFENCE();
            W1MMA(15)
            if (RPOS == 1) PUBLISH0()
            put_partials<ROLE == 2>(pst + 8192, acc[4], acc[5]); put_partials<ROLE == 2>(pst + 12288, acc[6], acc[7]);
            if (RPOS == 2) PUBLISH0()
        }
        SSTAMP(8, threadIdx.x == 0 && s == 0)
        PROF(1)
        if (ROLE) {
            bar_sync(1, 256);
            reduce_load(x, pld + 8192);
            r1 = reduce8(x, l8, u2);
            st_async1(pub + 1024, r1, pbar);
            if (s == 63) {
                PERS_STORE()
                mbar_wait(sb + B_V, 0);
                __syncwarp();
                if (l8 == sb) mbar_arrive(sb + B_PERS);
                break;
            }
            PROF(2)
        }
        uint32_t ln, w2a, ro;
#define W2ADDR(late) { l8 += pub & P.zero; ln = (l8 - sb) >> 3; \
        w2a = sb + S_W2 + (ROLE ? (warp >> 2) * 16384 : late * 32768) + ((((ln & 7) + (ln >> 4) * 8) * 128 + ((((ln >> 3) & 1) ^ (ln & 7)) << 4)) ^ ((warp & 3) << 5)); \
        ro = (s & 7) * M_SLOT + (ROLE ? warp * 2048 + unit_off(ROLE) : (warp & 3) * 2048 + late * unit_off(3)) + (ln & 2) * 128 + (ln & 1) * 64 + (ln >> 2) * 8; }
        constexpr int RO2 = ROLE ? unit_off(ROLE + 3) - unit_off(ROLE) : 8192;
        float Sj[2];
        uint32_t w[24][4], ob[4][4];
        float S;
#define W2LD(i) ldsm4t(w[i], w2a + w2_t(i) * (ROLE ? 32768 : 16384) + (w2_k(i) & 1) * 8192 + (w2_k(i) >> 1) * 2048)
#define W2MMA(d, i) mma16816(d, w[i][0], w[i][1], w[i][2], w[i][3], ob[w2_k(i) >> 1][(w2_k(i) & 1) * 2], ob[w2_k(i) >> 1][(w2_k(i) & 1) * 2 + 1])
#define LEADER(wp) (l8 == sb + ((wp) - warp) * 256)
        if (att) {
            const float cs = 0.08838834764831845f * 1.4426950408889634f;
            uint32_t qa[4][4], kf[4][4], vf[4][4], vv[4];
            float T[5][2], sa[4][4] = {};
            const uint32_t l16 = l8 * 2 - sb;
            const uint32_t kaddr = (l8 & 56) * 16 + (((l8 >> 2) ^ (l8 * 2)) & 48) + ((l8 * 2) & 64) + (sb + S_KV + warp * 1024 + slot * 16384);
            bar_sync(1, 256);
            reduce_load(x, pld + 8192);
            __syncwarp();
#pragma unroll
            for (int i = 0; i < 2; i++) { ldsm4(qa[i], l16 + S_QX + i * 512); ldsm4(kf[i], kaddr ^ (i * 64)); }
            AFENCE(0)
            sts32(pub + 1024, reduce8(x, l8, u2));
            __syncwarp();
#pragma unroll
            for (int i = 2; i < 4; i++) ldsm4(kf[i], (kaddr ^ ((i & 1) * 64)) + 4096);
            score_half(sa, qa, kf);
            bar_sync(2, 256);
            PROF(2)
#pragma unroll
            for (int i = 2; i < 4; i++) ldsm4(qa[i], l16 + S_QX + i * 512);
            float sm[4][4] = {};
            score_half(sa, qa + 2, kf + 2);
            score_sum(T[0], sa);
            sts64(l8 + S_SX + warp * 256, __float_as_uint(T[0][0]), __float_as_uint(T[0][1]));
            PROF(4)
            if (BPOS == 0) bar_sync(4, 128);
            mbar_wait(sb + B_K, slot);
            PROF(11)
#pragma unroll
            for (int i = 0; i < 4; i++) ldsm4(kf[i], l16 + S_KL + i * 512);
            if (BPOS == 1) bar_sync(4, 128); else __syncwarp();
#pragma unroll
            for (int n = 0; n < 4; n++) lds64f(T[n], l8 + S_SX + n * 256);
            score_half(sm, qa, kf);
            score_half(sm, qa + 2, kf + 2);
            const uint32_t vaddr = (l8 & 56) * 16 + (l8 & 128) * 8 + (((warp & 1) * 64 + ((l8 >> 2) & 16)) ^ ((l8 * 2) & 112)) + (sb + S_KV + 8192 + (warp >> 1) * 4096 + slot * 16384);
            float mx = fmaxf(fmaxf(fmaxf(T[0][0], T[0][1]), fmaxf(T[1][0], T[1][1])), fmaxf(fmaxf(T[2][0], T[2][1]), fmaxf(T[3][0], T[3][1])));
            score_sum(T[4], sm);
            float m = quad_max(fmaxf(mx, fmaxf(T[4][0], T[4][1])));
            if (VPOS == 0) {
#pragma unroll
                for (int i = 0; i < 4; i++) ldsm4t(vf[i], (vaddr ^ ((i & 1) << 5)) + (i >> 1) * 2048);
            }
            mbar_wait(sb + B_V, slot);
            if (VPOS == 1) {
#pragma unroll
                for (int i = 0; i < 4; i++) ldsm4t(vf[i], (vaddr ^ ((i & 1) << 5)) + (i >> 1) * 2048);
            }
            ldsm4(vv, l16 + S_VL + warp * 512);
            uint32_t pa[5];
            m *= cs;
#pragma unroll
            for (int n = 0; n < 5; n++) { T[n][0] = ex2(fmaf(T[n][0], cs, -m)); T[n][1] = ex2(fmaf(T[n][1], cs, -m)); pa[n] = pack2(T[n][0], T[n][1]); }
            float sum = (((T[0][0] + T[0][1]) + (T[1][0] + T[1][1])) + ((T[2][0] + T[2][1]) + (T[3][0] + T[3][1]))) + (T[4][0] + T[4][1]);
            PROF(3)
            W2ADDR(1)
            const uint32_t lo = sb + S_O + warp * 512 + (ln & 3) * 64 + (ln >> 2) * 8, ls = sb + S_SUM + (ln & 3) * 32 + (ln & 4) * 4 + (ln >> 3) * 4;
            const uint32_t sdelta = warp < 2 ? rdelta : vdelta;
            sum += __shfl_xor_sync(0xffffffffu, sum, 1);
            sum += __shfl_xor_sync(0xffffffffu, sum, 2);
            float O[2][4];
#pragma unroll
            for (int i = 0; i < 2; i++) { O[i][0] = O[i][1] = O[i][2] = O[i][3] = 0.f; }
#pragma unroll
            for (int i = 0; i < 2; i++) {
                mma16816(O[0], vf[2 * i][0], vf[2 * i][1], vf[2 * i][2], vf[2 * i][3], pa[2 * i], pa[2 * i + 1]);
                mma16816(O[1], vf[2 * i + 1][0], vf[2 * i + 1][1], vf[2 * i + 1][2], vf[2 * i + 1][3], pa[2 * i], pa[2 * i + 1]);
            }
            mma1688(O[0], vv[0], vv[1], pa[4]);
            mma1688(O[1], vv[2], vv[3], pa[4]);
            uint32_t o[2][2];
#pragma unroll
            for (int j = 0; j < 2; j++) { o[j][0] = pack2(O[0][j], O[0][2 + j]); o[j][1] = pack2(O[1][j], O[1][2 + j]); }
#pragma unroll
            for (int j = 0; j < 2; j++) st_async2(lo + rdelta + j * 256, o[j][0], o[j][1], sb + rdelta + B_K);
            st_async1(ls + sdelta + (warp & 1) * 128, __float_as_uint(sum), sb + sdelta + B_K);
#pragma unroll
            for (int j = 0; j < 2; j++) st_async2(lo + vdelta + j * 256, o[j][0], o[j][1], sb + vdelta + B_K);
#pragma unroll
            for (int j = 0; j < 2; j++) sts64(lo + j * 256, o[j][0], o[j][1]);
            sts32(ls + warp * 128, __float_as_uint(sum));
            PROF(5)
            bar_sync(3, 256);
            if (LEADER(0)) { mbar_expect(sb + B_K, 2048); mbar_expect(sb + B_V, 2048); mbar_arrive(sb + B_KVGO + slot * 8); }
            S = next_scale(sb, slot, warp, u2);
            if (s == 0) mbar_wait(sb + B_WO, 0);
            pin<1>(&S);
            SFENCE();
#pragma unroll
            for (int j = 0; j < 4; j++) lds128(ob[j], l8 * 2 - sb + S_O + j * 512);
            lds64f(Sj, sb + S_SUM + (l8 & 24));
#pragma unroll
            for (int i = 0; i < PF2; i++) W2LD(i);
        } else {
            if (ROLE == 0) { bar_sync(1, 256); reduce_load(x, pld + 8192); sts32(pub + 1024, reduce8(x, l8, u2)); bar_arrive(2, 256); }
            if (LEADER(7)) { if (s) mbar_arrive(sb + B_GO); if (ROLE) mbar_expect(sb + B_K, 2304); }
            if (ROLE != 0 && (s & 3) == 0 && s > 0 && l8 == sb) mbar_arrive(sb + B_PERS);
            S = next_scale(sb, slot, warp, u2);
            if (s == 0) mbar_wait(sb + B_WO, 0);
            if (ROLE != 0) { l8 += delay_loop(40, l8); if (!DBGF(4)) PERS_STORE() }
            W2ADDR(0)
#pragma unroll
            for (int i = 0; i < PF2; i++) {
                W2LD(i);
                if (ROLE == 0 && (i & PACE) == PACE) w2a += w[i][0] & P.zero;
            }
            ro = opq(ro, ln);
            const uint32_t sa = opq(sb + S_SUM + (l8 & 24), ln), oa = opq(l8 * 2 - sb + S_O, ln);
            if (ROLE == 0) bar_sync(3, 256); else mbar_wait(sb + B_K, slot);
            lds64f(Sj, sa);
#pragma unroll
            for (int j = 0; j < 4; j++) lds128(ob[j], oa + j * 512);
        }
        SSTAMP(9, threadIdx.x == 224 && s == 0)
        SFENCE();
        PROF(6)
        {
            const uint8_t* pr = P.gm + ro;
            float c[4][4];
            uint32_t lim = 0;
#pragma unroll
            for (int i = 0; i < 4; i++) { c[i][0] = c[i][1] = c[i][2] = c[i][3] = 0.f; }
#pragma unroll
            for (int i = 0; i < 16; i++) {
                W2MMA(c[i & (ROLE ? 1 : 3)], i);
                if (i + PF2 < (ROLE ? 16 + NEARLY : 16)) W2LD(i + PF2);
                if (i == 5) {
                    const uint32_t z = __float_as_uint(c[1][0]) & P.zero;
                    Sj[0] = S * rcp(__uint_as_float(__float_as_uint(Sj[0]) | z)); Sj[1] = S * rcp(__uint_as_float(__float_as_uint(Sj[1]) | z));
                }
                if (i == 5) lim = __any_sync(0xffffffffu, fmaxf(fmaxf(fabsf(c[0][0]), fabsf(c[0][2])), fmaxf(fabsf(c[1][0]), fabsf(c[1][2]))) * Sj[0] >= (ROLE ? 24.f : 20.f)) ? 16384 : 0;
                if (i == FPOS) { pin<1>(&lim); pin<2>(Sj); pin_ptr(pr); SFENCE(); }
            }
            if (ROLE == 0) {
#pragma unroll
                for (int i = 0; i < 8; i++) c[i >> 2][i & 3] += c[2 + (i >> 2)][i & 3];
            }
            const float xa[2][3] = {{c[0][0], c[0][2], c[1][0]}, {c[0][1], c[0][3], c[1][1]}};
            uint64_t wa[2], wb[2];
            emit<NU>(wa, xa, Sj, P.two26, lim, pr);
            PROF(7)
            mo = GATHER_OFF(s + 1);
            pin<1>(&mo);
            if (ROLE) {
                SFENCE();
#pragma unroll
                for (int i = 16 + NEARLY; i < 24; i++) { if (i == 16 + NBAR) bar_sync(2, 256); W2LD(i); __syncwarp(); }
                SFENCE();
#pragma unroll
                for (int i = 16; i < 24; i++) W2MMA(c[2 + (i & 1)], i);
#pragma unroll
                for (int i = 0; i < 4; i++) c[2][i] += c[3][i];
            }
            const float y[2][3] = {{ROLE ? c[1][2] : c[1][0], ROLE ? c[2][0] : c[1][2], c[2][2]}, {ROLE ? c[1][3] : c[1][1], ROLE ? c[2][1] : c[1][3], c[2][3]}};
            const bool released = !ROT || mbar_test(sb + B_RELA, slot ^ 1);
            emit<NU>(wb, y, Sj, P.two26, lim, pr + RO2);
            PROF(8)
            if (!__all_sync(0xffffffffu, (wa[0] & wb[0] & 1) && released && s)) {
                if (__builtin_expect(!__all_sync(0xffffffffu, wa[0] & wb[0] & 1), 0)) {
                    RETRY(5)
                    const uint8_t* pf = g_f + (s & 7) * F_SLOT + (ROLE ? ROLE * 8192 + warp * 1024 : (warp & 3) * 1024 + (att ? 24576 : 0)) + (ln & 3) * 128 + (ln >> 2) * 16;
                    repair<NU>(wa, xa, Sj, pr, pf);
                    repair<NU>(wb, y, Sj, pr + RO2, pf + (ROLE ? 24576 : 4096));
                }
                if (s == 0) { bar_sync(1, 256); if (LEADER(7)) mbar_arrive(sb + B_GO); }
                if (ROT) mbar_wait(sb + B_RELA, slot ^ 1);
            }
        }
        s++;
    }
}
struct Pipe { uint32_t stage, phase; };
struct Cons {
    uint32_t sb, rel;
    int wg, wq, lane, rank, pair;
    uint32_t atag, nst;
    Pipe p;
};
__device__ __forceinline__ void pipe_next(Pipe& p) { p.stage = (p.stage + 1) & (NSTAGE - 1); p.phase ^= (p.stage == 0); }
__device__ __forceinline__ void release(const Cons& c, uint32_t stage) { if (c.lane < 2) mbar_arrive_cluster(c.rel + stage * 8); }

enum { PEND_NONE = 0, PEND_KVO = 1, PEND_HT = 2, PEND_OUT = 3, PEND_OUTH = 4 };
struct Pend { uint32_t pk[64]; int kind, row, col, cnt; };

__device__ __forceinline__ void staging_wait(const Cons& c) { if (c.nst) mbar_wait(c.sb + B_SFREE + c.wg * 8, (c.nst - 1) & 1); }
__device__ __forceinline__ void staging_post(Cons& c, int kind, int row, int col, int cnt) {
    __syncwarp();
    if (c.lane == 0) {
        if (c.wq == 0) { const uint32_t x[4] = {(uint32_t)kind, (uint32_t)row, (uint32_t)col, (uint32_t)cnt}; sts128(c.sb + S_DESC + c.wg * 16, x); }
        mbar_arrive(c.sb + B_SFULL + c.wg * 8);
    }
    c.nst++;
}
template <int HF, bool KVONLY = false>
__device__ __forceinline__ void drain(const Params& P, Cons& c, const Pend& d) {
    const uint32_t* pk = d.pk + HF * 32;
    if (!KVONLY && d.kind >= PEND_OUT) {
        if (HF == 1 && d.kind == PEND_OUTH) return;
        float* o = P.out + (size_t)(d.row + c.wq * 16 + (c.lane >> 2)) * 2048 + d.col + HF * 128 + (c.lane & 3) * 2;
#pragma unroll
        for (int j = 0; j < 16; j++) {
            st_stream2(o + j * 8, bf_lo(pk[j * 2]), bf_hi(pk[j * 2]));
            st_stream2(o + 8 * 2048 + j * 8, bf_lo(pk[j * 2 + 1]), bf_hi(pk[j * 2 + 1]));
        }
    } else if (d.kind != PEND_NONE) {
        const bool ht = !KVONLY && d.kind == PEND_HT;
        const int hi = (c.lane >> 3) & 1;
        const uint32_t base = c.sb + S_STG + c.wg * 16384 + ((ht ? hi * 32 + c.wq * 8 : c.wq * 16 + hi * 8) + (c.lane & 7)) * 128;
        staging_wait(c);
#pragma unroll
        for (int j = 0; j < 8; j++) {
            const int ch = (j & 3) * 2 + (c.lane >> 4);
            stsm4(base + (j >> 2) * 8192 + ((ch ^ (c.lane & 7)) << 4), pk[j * 4], pk[j * 4 + 1], pk[j * 4 + 2], pk[j * 4 + 3]);
        }
        fence_async_smem();
        staging_post(c, d.kind, d.row, d.col + HF * 128, HF ? d.cnt : -1);
    }
}
__device__ __forceinline__ void drain_all(const Params& P, Cons& c, Pend& d) { drain<0>(P, c, d); drain<1>(P, c, d); d.kind = PEND_NONE; }

__device__ __forceinline__ void store_warp(const Params& P, uint32_t sb, int wg) {
    const uint32_t stg = sb + S_STG + wg * 16384;
#pragma unroll 1
    for (uint32_t n = 0;; n++) {
        mbar_wait(sb + B_SFULL + wg * 8, n & 1);
        uint32_t x[4];
        lds128(x, sb + S_DESC + wg * 16);
        if (x[0] == PEND_NONE) break;
        const bool ht = x[0] == PEND_HT;
        const CUtensorMap* m = &P.tm[ht ? M_HTS : M_KVO];
#pragma unroll 1
        for (int i = 0; i < 4; i++) if (!(DBGF(128) && gridDim.x != 96)) tma_store2d(m, x[2] + (i >> 1) * 64, x[1] + (i & 1) * (ht ? 1024 : 32), stg + i * 4096);
        bulk_commit();
        bulk_wait_read();
        mbar_arrive(sb + B_SFREE + wg * 8);
        if ((int)x[3] >= 0) { bulk_wait_all(); fence_async(); red_release(&g_cnt(x[3])); }
    }
}

template <int N, int TA, int TB, bool FIRST>
__device__ __forceinline__ void issue_ktile(float* acc, const Cons& c) {
    mbar_wait(c.sb + B_FULL + c.p.stage * 8, c.p.phase);
    const uint32_t a = c.sb + c.p.stage * STAGE + c.wg * 8192, b = c.sb + c.p.stage * STAGE + 16384;
    const uint64_t da = mkdesc(a, TA ? 8192 : 16, 1024, 1), db = mkdesc(b, TB ? 8192 : 16, 1024, 1);
    wg_fence();
#pragma unroll
    for (int k = 0; k < 4; k++) {
        const uint64_t x = da + (TA ? 128 : 2) * k, y = db + (TB ? 128 : 2) * k;
        if (N == 256) { if (FIRST && k == 0) wgmma_ss256_first<TA, TB>(acc, x, y); else wgmma_ss256<TA, TB>(acc, x, y); }
        else { if (FIRST && k == 0) wgmma_ss128_first<TA, TB>(acc, x, y); else wgmma_ss128<TA, TB>(acc, x, y); }
    }
    wg_commit();
}
template <int N, bool FIRST>
__device__ __forceinline__ void issue_any(float* acc, const Cons& c, int type) {
    if (N == 256 && type == T_A1) issue_ktile<N, 0, 0, FIRST>(acc, c);
    else if (type == (N == 256 ? T_A2 : T_A2H)) issue_ktile<N, 1, 0, FIRST>(acc, c);
    else issue_ktile<N, 0, 1, FIRST>(acc, c);
}
template <int N, bool KVONLY = false>
__device__ __forceinline__ void mainloop(float* acc, const Params& P, Cons& c, Pend& d, int type) {
    const int nk = (type == T_OP || type == T_OPH) ? 64 : (type == T_A2 || type == T_A2H) ? 32 : 16;
    issue_any<N, true>(acc, c, type);
    drain<0, KVONLY>(P, c, d);
    uint32_t prev = c.p.stage;
    pipe_next(c.p);
    for (int kt = 1; kt < nk; kt++) {
        issue_any<N, false>(acc, c, type);
        wg_wait<1>();
        release(c, prev);
        if (kt == 2) drain<1, KVONLY>(P, c, d);
        prev = c.p.stage;
        pipe_next(c.p);
    }
    d.kind = PEND_NONE;
    wg_wait<0>();
    pin<N / 2>(acc);
    release(c, prev);
}
__device__ __forceinline__ void pack_half(uint32_t* pk, const float* a) {
#pragma unroll
    for (int i = 0; i < 32; i++) pk[i] = pack2(a[2 * i], a[2 * i + 1]);
}

__device__ __forceinline__ void epi_kv(const float* acc, const Cons& c, Pend& d, int mb, int nb) {
    pack_half(d.pk, acc); pack_half(d.pk + 32, acc + 64);
    d.kind = PEND_KVO; d.row = (nb >> 4) * 2048 + mb * 256 + c.rank * 128 + c.wg * 64; d.col = (nb & 15) * 256; d.cnt = C_KV + mb;
}

__device__ __forceinline__ void epi_qa(const float* acc, Cons& c, Pend& d, int mb, int nb) {
    uint32_t q[64];
    pack_half(q, acc);
    pack_half(q + 32, acc + 64);
#pragma unroll
    for (int i = 0; i < 32; i++) d.pk[32 + i] = 0;
    const int g = c.lane >> 2, t = c.lane & 3;
    const bool sg = c.wq >= 2;
    const int i0 = (c.wq & 1) * 16 + g;
#pragma unroll 1
    for (int hh = 0; hh < 2; hh++) {
        uint32_t pa[5][4];
        {
            float S[32] = {}, Sm[8] = {};
            mbar_wait(c.sb + B_FULL + c.p.stage * 8, c.p.phase);
            const uint32_t st = c.sb + c.p.stage * STAGE;
            const uint64_t dk = mkdesc(st + c.wg * 8192, 16, 1024, 1), dm = mkdesc(st + 32768 + c.wg * 4096, 128, 2048, 0);
            pin<32>(q); pin<32>(S); pin<8>(Sm);
            wg_fence();
#pragma unroll
            for (int i = 0; i < 8; i++) wgmma_rs64<0>(S, q + i * 4, dk + (i >> 2) * 1024 + (i & 3) * 2, i != 0);
#pragma unroll
            for (int i = 0; i < 8; i++) wgmma_rs16<0>(Sm, q + i * 4, dm + i * 16, i != 0);
            wg_commit();
            wg_wait<0>();
            pin<32>(S); pin<8>(Sm);
            release(c, c.p.stage);
            pipe_next(c.p);
            const float scale = 0.08838834764831845f, l2e = 1.4426950408889634f;
            float x[2][10];
#pragma unroll
            for (int r = 0; r < 2; r++) {
#pragma unroll
                for (int j = 0; j < 4; j++)
#pragma unroll
                    for (int e = 0; e < 2; e++) {
                        const float v = sg ? S[16 + j * 4 + r * 2 + e] : S[j * 4 + r * 2 + e];
                        x[r][j * 2 + e] = (j * 8 + 2 * t + e > i0 + r * 8) ? -1e9f : v * scale;
                    }
                x[r][8] = (sg ? Sm[4 + r * 2] : Sm[r * 2]) * scale;
                x[r][9] = (sg ? Sm[5 + r * 2] : Sm[1 + r * 2]) * scale;
                float m = x[r][0];
#pragma unroll
                for (int i = 1; i < 10; i++) m = fmaxf(m, x[r][i]);
                m = fmaxf(m, __shfl_xor_sync(0xffffffffu, m, 1));
                m = fmaxf(m, __shfl_xor_sync(0xffffffffu, m, 2));
                float sum = 0.f;
#pragma unroll
                for (int i = 0; i < 10; i++) { x[r][i] = ex2((x[r][i] - m) * l2e); sum += x[r][i]; }
                sum += __shfl_xor_sync(0xffffffffu, sum, 1);
                sum += __shfl_xor_sync(0xffffffffu, sum, 2);
                const float inv = rcp(sum);
#pragma unroll
                for (int i = 0; i < 10; i++) x[r][i] *= inv;
            }
#pragma unroll
            for (int ks = 0; ks < 2; ks++)
#pragma unroll
                for (int i = 0; i < 4; i++) {
                    const uint32_t p = pack2(x[i & 1][ks * 4 + (i >> 1) * 2], x[i & 1][ks * 4 + (i >> 1) * 2 + 1]);
                    pa[ks][i] = sg ? 0u : p;
                    pa[2 + ks][i] = sg ? p : 0u;
                }
#pragma unroll
            for (int r = 0; r < 2; r++) {
                const uint32_t p = pack2(x[r][8], x[r][9]);
                pa[4][r] = sg ? 0u : p;
                pa[4][2 + r] = sg ? p : 0u;
            }
        }
        float O[64] = {};
        mbar_wait(c.sb + B_FULL + c.p.stage * 8, c.p.phase);
        const uint32_t st = c.sb + c.p.stage * STAGE;
        const uint64_t dv = mkdesc(st + c.wg * 8192, 16384, 1024, 1), dm = mkdesc(st + 32768 + c.wg * 4096, 2048, 128, 0);
        pin<20>(&pa[0][0]); pin<64>(O);
        wg_fence();
#pragma unroll
        for (int ks = 0; ks < 4; ks++) wgmma_rs128<1>(O, pa[ks], dv + ks * 128, ks != 0);
        wgmma_rs128<0>(O, pa[4], dm, 1);
        wg_commit();
        wg_wait<0>();
        pin<64>(O);
        release(c, c.p.stage);
        pipe_next(c.p);
#pragma unroll
        for (int i = 0; i < 32; i++) { q[i] = q[32 + i]; q[32 + i] = d.pk[32 + i]; }
        pack_half(d.pk + 32, O);
    }
#pragma unroll
    for (int i = 0; i < 32; i++) d.pk[i] = q[32 + i];
    d.kind = PEND_KVO; d.row = 4096 + mb * 256 + c.rank * 128 + c.wg * 64; d.col = nb * 256; d.cnt = C_O + mb * 4 + (nb >> 2);
}

__device__ __forceinline__ void epi_op(const float* acc, const Cons& c, Pend& d, int mb, int nb) {
    pack_half(d.pk, acc); pack_half(d.pk + 32, acc + 64);
    d.kind = PEND_OUT; d.row = mb * 256 + c.rank * 128 + c.wg * 64; d.col = 1024 + nb * 256;
}

__device__ __forceinline__ void epi_oph(const float* acc, const Cons& c, Pend& d, int mb, int nb) {
    pack_half(d.pk, acc);
    d.kind = PEND_OUTH; d.row = mb * 256 + c.rank * 128 + c.wg * 64; d.col = 1024 + nb * 128;
}

template <int HF>
__device__ __forceinline__ void epi_a2_half(const float* acc, const Params& P, Cons& c, int mb, int col0) {
    const int g = c.lane >> 2, t = c.lane & 3;
    const int row = mb * 256 + (g >> 1) * 64 + (c.rank * 16 + c.wg * 8 + c.wq * 2) * 2 + (g & 1);
    float* o = P.out + (size_t)row * 2048 + col0 + HF * 128 + t * 2;
    mbar_wait(c.sb + B_FULL + c.p.stage * 8, c.p.phase);
    const uint32_t st = c.sb + c.p.stage * STAGE, da = st + 32768 + (c.lane >> 3) * 16;
    const uint32_t xa = st + (c.wg * 64 + c.wq * 16 + (c.lane & 15)) * 128 + (((c.lane >> 4) ^ (c.lane & 7)) << 4);
#pragma unroll
    for (int j4 = 0; j4 < 4; j4++) {
        uint32_t x[8], dv[4];
        ldsm4(dv, da + j4 * 64);
        ldsm4(x, (xa ^ ((j4 & 1) << 6)) + (j4 >> 1) * 16384);
        ldsm4(x + 4, (xa ^ ((j4 & 1) << 6) ^ 32) + (j4 >> 1) * 16384);
#pragma unroll
        for (int i = 0; i < 4; i++) {
            const int j = j4 * 4 + i;
            const float* a = acc + HF * 64 + j * 4;
            const uint32_t u0 = hmul2(x[2 * i], dv[i]), u1 = hmul2(x[2 * i + 1], dv[i]);
            st_stream2(o + j * 8, a[0] + bf_lo(u0), a[1] + bf_hi(u0));
            st_stream2(o + 2 * 2048 + j * 8, a[2] + bf_lo(u1), a[3] + bf_hi(u1));
        }
    }
    __syncwarp();
    release(c, c.p.stage);
    pipe_next(c.p);
}

#define TSTAMP(i)
__device__ __forceinline__ float2 cmul(float2 a, float2 b) { return make_float2(fmaf(a.x, b.x, -a.y * b.y), fmaf(a.x, b.y, a.y * b.x)); }
__device__ __forceinline__ float2 cfma(float2 a, float2 b, float2 u) { return make_float2(fmaf(a.x, b.x, fmaf(-a.y, b.y, u.x)), fmaf(a.x, b.y, fmaf(a.y, b.x, u.y))); }
__device__ __forceinline__ float4 ssm_coef(float lre, float lim, float logdt) {
    const float dt = __bfloat162float(__float2bfloat16(expf(logdt)));
    const float ea = expf(dt * lre);
    float sn, cn;
    sincosf(dt * lim, &sn, &cn);
    const float br = ea * cn, bi = ea * sn, nr = br - 1.f;
    float cr, ci;
    if (fabsf(lre) >= fabsf(lim)) { const float r = lim / lre, dn = lre + lim * r; cr = (nr + bi * r) / dn; ci = (bi - nr * r) / dn; }
    else { const float r = lre / lim, dn = lre * r + lim; cr = (nr * r + bi) / dn; ci = (bi * r - nr) / dn; }
    return make_float4(br, bi, cr, ci);
}
__device__ __forceinline__ void epi_a1(const float* acc, const Params& P, const Cons& c, Pend& d, int mb, int nb, uint32_t atag) {
    const int t = c.lane & 3;
    const int p = nb * 128 + c.rank * 64 + c.wg * 32 + c.wq * 8 + (c.lane >> 2);
    uint32_t cw[4];
    lds128(cw, c.sb + S_COEF + (p & 63) * 16);
    const float4 cf = make_float4(__uint_as_float(cw[0]), __uint_as_float(cw[1]), __uint_as_float(cw[2]), __uint_as_float(cw[3]));
    TSTAMP(1)
    const float2 lam = make_float2(cf.x, P.swap_ri ? -cf.y : cf.y);
    const float a0 = P.swap_ri ? -2.f * cf.w : 2.f * cf.z, a1 = P.swap_ri ? 2.f * cf.z : -2.f * cf.w;
    const float b0 = P.swap_ri ? -2.f * cf.z : -2.f * cf.w, b1 = P.swap_ri ? -2.f * cf.w : -2.f * cf.z;
    float2 h = make_float2(0.f, 0.f);
#pragma unroll
    for (int round = 0; round < 2; round++) {
#pragma unroll
        for (int j = 0; j < 32; j++) {
            h = cfma(lam, h, make_float2(acc[j * 4], acc[j * 4 + 2]));
            const float r0 = fmaf(a0, h.x, a1 * h.y), m0 = fmaf(b0, h.x, b1 * h.y);
            h = cfma(lam, h, make_float2(acc[j * 4 + 1], acc[j * 4 + 3]));
            d.pk[j * 2] = pack2(r0, fmaf(a0, h.x, a1 * h.y));
            d.pk[j * 2 + 1] = pack2(m0, fmaf(b0, h.x, b1 * h.y));
        }
        if (round) break;
        float2 l64 = lam;
#pragma unroll
        for (int i = 0; i < 6; i++) l64 = cmul(l64, l64);
        const float2 l128 = cmul(l64, l64), l256 = cmul(l128, l128);
        float2 o = make_float2(__shfl_up_sync(0xffffffffu, h.x, 1), __shfl_up_sync(0xffffffffu, h.y, 1));
        if (t >= 1) h = cfma(l64, o, h);
        o = make_float2(__shfl_up_sync(0xffffffffu, h.x, 2), __shfl_up_sync(0xffffffffu, h.y, 2));
        if (t >= 2) h = cfma(l128, o, h);
        TSTAMP(2)
        if (t == 3) st_relaxed2(&g_agg[mb * 1024 + p], (__float_as_uint(h.x) & ~1u) | atag, __float_as_uint(h.y));
        h = make_float2(__shfl_up_sync(0xffffffffu, h.x, 1), __shfl_up_sync(0xffffffffu, h.y, 1));
        if (t == 0) h = make_float2(0.f, 0.f);
        uint32_t ax[7], ay[7];
        int n = 0;
        while (true) {
            uint32_t bad = 0;
#pragma unroll
            for (int j = 0; j < 7; j++) { ax[j] = atag; ay[j] = 0; ld_relaxed2_if(ax[j], ay[j], &g_agg[j * 1024 + p], j < mb); }
#pragma unroll
            for (int j = 0; j < 7; j++) bad |= ax[j] ^ atag;
            if (tags_ok(bad)) break;
            __nanosleep(400);
            if (++n > SPIN_LIMIT) spin_fault();
        }
        float2 carry = make_float2(0.f, 0.f);
#pragma unroll
        for (int j = 0; j < 7; j++) if (j < mb) carry = cfma(l256, carry, make_float2(__uint_as_float(ax[j]), __uint_as_float(ay[j])));
        float2 w = (t & 1) ? l64 : make_float2(1.f, 0.f);
        if (t & 2) w = cmul(w, l128);
        h = cfma(w, carry, h);
        TSTAMP(3)
    }
    TSTAMP(4)
    d.kind = PEND_HT; d.row = nb * 128 + c.rank * 64 + c.wg * 32; d.col = mb * 256; d.cnt = C_HT + mb * 2 + (nb >> 2);
}

__device__ __forceinline__ uint32_t acquire_stage(uint32_t sb, Pipe& p, uint32_t bytes) {
    mbar_wait(sb + B_EMPTY + p.stage * 8, p.phase ^ 1);
    mbar_expect(sb + B_FULL + p.stage * 8, bytes);
    return p.stage;
}
#define AHEAD 1
__device__ __forceinline__ void watcher(const Params& P, const uint32_t sb, const int rank, const int lane) {
    const int pair = lds32(sb + S_TAIL), first = ITEM_OFF(pair) + (pair < NCHAIN ? NPRE + 1 : 0);
    const uint32_t epoch = lds32(sb + S_EPOCH), e1 = epoch + 1;
    uint32_t met = 0;
#pragma unroll 1
    for (int it = first; it < ITEM_OFF(pair + 1); it++) {
        const int item = ITEM(it), type = item >> 8, mb = (item >> 5) & 7, nb = item & 31;
        const int n = (0x24021420 >> (type * 4)) & 7;
        for (int k = 0; it > first && (int)lds32(sb + S_CUR) < it - AHEAD; k++) { __nanosleep(200); if (k > SPIN_LIMIT) spin_fault(); }
#pragma unroll 1
        for (int i = 0; i < n; i++) {
            int idx = n == 4 ? C_O + mb * 4 + i : C_HT + mb * 2 + i;
            uint32_t target = e1 * 16;
            if (type == T_A1) { idx = C_COEF; target = e1 * 4; }
            if (type == T_QA) {
                idx = i ? C_FLAG + (lane & 1) * 32 + nb * 2 + ((lane >> 1) & 1) : C_KV + mb;
                target = i ? epoch * 64 + mb * 8 + rank * 4 + 4 : e1 * 128;
            }
            if (lane < 4) { wait_count(&g_cnt(idx), target); fence_async(); }
            __syncwarp();
            if (lane == 0) asm volatile("st.release.cta.shared.u32 [%0], %1;" ::"r"(sb + S_DEP), "r"(++met) : "memory");
        }
    }
}
__device__ __forceinline__ bool dep_met(uint32_t sb, uint32_t n) { uint32_t v; asm volatile("ld.acquire.cta.shared.u32 %0, [%1];" : "=r"(v) : "r"(sb + S_DEP) : "memory"); return v >= n; }
__device__ __forceinline__ void dep_wait(uint32_t sb, uint32_t n) { for (int k = 0; !dep_met(sb, n); k++) { __nanosleep(32); if (k > SPIN_LIMIT * 8) spin_fault(); } }
__device__ __forceinline__ void producer(const Params& P, const uint32_t sb, int pair, const int rank, const uint32_t epoch) {
    Pipe p = {0, 0};
    const uint32_t e1 = epoch + 1;
    uint32_t dep = 0;
    for (int it = ITEM_OFF(pair); it < ITEM_OFF(pair + 1); it++) {
        const int item = ITEM(it), type = item >> 8, mb = (item >> 5) & 7, nb = item & 31;
        if (type == T_CHAIN) {
            sts32(sb + S_CUR, 0);
            const int role = pair >> 4, h = (pair & 15) * 2 + rank;
#pragma unroll 1
            for (int i = 0, q = 0; i < 8; i++) {
                const int n = (0x13003333 >> (i * 4)) & 3;
                const uint32_t st = acquire_stage(sb, p, n * 16384);
#pragma unroll 1
                for (int k = 0; k < 2 * n; k++, q++)
                    tma3d(sb + st * STAGE + k * 8192, &P.tm[M_CQ + role], h * 128 + (fill_unit(q >> 1) & 1) * 64, word_col((fill_unit(q >> 1) & 14) + (q & 1)) & 8, word_col((fill_unit(q >> 1) & 14) + (q & 1)) >> 4, sb + B_FULL + st * 8);
                pipe_next(p);
            }
            if (role == 0 && !DBGF(1)) { wait_count(&g_cnt(C_KV), e1 * 128); fence_async(); }
            mbar_wait(sb + B_EMPTY + 16, 1); mbar_wait(sb + B_EMPTY + 24, 1);
            mbar_expect(sb + B_WO, role ? 98304 : 65536);
            if (role == 0) { mbar_expect(sb + B_KVFULL, 16384); mbar_expect(sb + B_KVFULL + 8, 16384); }
#pragma unroll 1
            for (int k = role ? 0 : -4; k < 12; k++) {
                const bool kv = role == 0 && (k & 8);
                const int sg = k > 0;
                tma4d(kv ? sb + S_KV + sg * 16384 + (k & 3) * 4096 : sb + S_W2 + k * 8192, &P.tm[kv ? M_KV4 : M_CO + (k & 1)],
                      kv ? h * 128 + (k & 1) * 64 : (role == 0 ? 0 : role == 1 ? 256 : 640) + (k >> 1) * 64, kv ? (k & 2) * 1024 + sg * 32 : h * 8, sb + (kv ? B_KVFULL + sg * 8 : B_WO));
            }
            SSTAMP(5, true)
            if (pair < 16) {
#pragma unroll 1
                for (int s = 2; s < 63; s++) {
                    mbar_wait(sb + B_KVGO + (s & 1) * 8, ((s >> 1) + 1) & 1);
                    wait_time(gtime() + P.dk, sb);
                    SSTAMP(6, s == 2)
                    const uint32_t bar = sb + B_KVFULL + (s & 1) * 8, dst = sb + S_KV + (s & 1) * 16384;
                    if (DBGF(2)) { mbar_arrive(bar); continue; }
                    mbar_expect(bar, 16384);
#pragma unroll 1
                    for (int i = 0; i < 4; i++) tma2d(dst + i * 4096, &P.tm[M_KVO], (pair * 2 + rank) * 128 + (i & 1) * 64, (i >> 1) * 2048 + (DBGF(32 | 512) ? s & 7 : s) * 32, bar);
                    if (s < 62) {
                        if ((s & 7) == 7 && !DBGF(1)) { wait_count(&g_cnt(C_KV + 1 + (s >> 3)), e1 * 128); fence_async(); }
#pragma unroll 1
                        for (int i = 0; i < 4; i++) if (!DBGF(64)) tma_prefetch2d(&P.tm[M_KVO], (pair * 2 + rank) * 128 + (i & 1) * 64, (i >> 1) * 2048 + s * 32 + 32);
                    }
                }
            } else {
                uint32_t* flag = &g_cnt(C_FLAG + pair * 2 + rank - 32);
#pragma unroll 1
                for (int s = 0; s < 16; s++) {
                    mbar_wait(sb + B_PERS, s & 1);
                    if (!DBGF(8)) asm volatile("st.release.gpu.global.u32 [%0], %1;" ::"l"(flag), "r"(epoch * 64 + s * 4 + 4) : "memory");
                }
            }
            mbar_wait(sb + B_RESUME, 0);
            pair = lds32(sb + S_TAIL);
            it = ITEM_OFF(pair) + NPRE;
            continue;
        }
        sts32(sb + S_CUR, it);
        const int m0 = mb * 256 + rank * 128;
        if (type <= T_OP) {
            const CUtensorMap* ma = &P.tm[type == T_OP ? M_OA : M_BX];
            const CUtensorMap* mw = &P.tm[type == T_OP ? M_WO : type == T_QA ? M_WQ : nb < 16 ? M_WK : M_WV];
            const int nk = type == T_OP ? 64 : 16, nc = (nb & 15) * 4 + rank * 2, ma0 = type == T_OP ? 4096 + m0 : m0;
#pragma unroll 1
            for (int kt = 0; kt < nk; kt++) {
                if (type == T_OP && (kt & 15) == 0) dep_wait(sb, ++dep);
                if (DBGF(256) && pair >= NCHAIN) { acquire_stage(sb, p, 0); pipe_next(p); continue; }
                const uint32_t st = acquire_stage(sb, p, STAGE), bar = sb + B_FULL + st * 8;
                tma2d(sb + st * STAGE, ma, kt * 64, ma0, bar);
                tma3d_mc(sb + st * STAGE + 16384 + rank * 16384, mw, 0, kt * 64, nc, bar);
                if (type == T_QA && kt < 12 && dep_met(sb, dep + 1 + (kt >> 3))) {
                    if (kt < 8) tma_prefetch2d(&P.tm[M_OA], nb * 256 + (kt & 3) * 64, (kt >> 2) * 2048 + m0);
                    else {
                        const int o = ((mb * 8 + rank * 4 + (kt & 3)) * 32 + nb * 2) * 512;
                        l2_prefetch(g_km + o, 4096); l2_prefetch(g_vmt + o, 4096);
                    }
                }
                pipe_next(p);
            }
            if (type == T_QA) {
                dep += 2;
                dep_wait(sb, dep);
#pragma unroll 1
                for (int e = 0; e < 4; e++) {
                    const uint32_t st = acquire_stage(sb, p, 40960), bar = sb + B_FULL + st * 8, dst = sb + st * STAGE;
                    tma2d(dst, &P.tm[M_OA], nb * 256 + (e >> 1) * 128, (e & 1) * 2048 + m0, bar);
                    tma2d(dst + 16384, &P.tm[M_OA], nb * 256 + (e >> 1) * 128 + 64, (e & 1) * 2048 + m0, bar);
                    const uint32_t* src = ((e & 1) ? g_vmt : g_km) + ((mb * 8 + rank * 4) * 32 + nb * 2 + (e >> 1)) * 512;
#pragma unroll 1
                    for (int i = 0; i < 4; i++) bulk_g2s(dst + 32768 + i * 2048, src + i * 32 * 512, 2048, bar);
                    pipe_next(p);
                }
            }
        } else if (type == T_OPH) {
#pragma unroll 1
            for (int kt = 0; kt < 64; kt++) {
                if ((kt & 15) == 0) dep_wait(sb, ++dep);
                const uint32_t st = acquire_stage(sb, p, 32768), bar = sb + B_FULL + st * 8;
                tma2d(sb + st * STAGE, &P.tm[M_OA], kt * 64, 4096 + m0, bar);
                tma2d_mc(sb + st * STAGE + 16384 + rank * 8192, &P.tm[M_WOH], nb * 128 + rank * 64, kt * 64, bar);
                pipe_next(p);
            }
        } else if (type == T_A1) {
#pragma unroll 1
            for (int kt = 0; kt < 16; kt++) {
                if (kt == 15) dep_wait(sb, ++dep);
                const uint32_t st = acquire_stage(sb, p, kt == 15 ? STAGE + 1024 : STAGE), bar = sb + B_FULL + st * 8;
                if (kt == 15) bulk_g2s(sb + S_COEF, g_coef + nb * 128 + rank * 64, 1024, bar);
                tma4d(sb + st * STAGE, &P.tm[M_AB], kt * 64, nb * 16 + rank * 8, bar);
                tma4d_mc(sb + st * STAGE + 16384 + rank * 16384, &P.tm[M_AX], kt * 64, mb * 128 + rank * 16, bar);
                pipe_next(p);
            }
        } else {
            const int hw = type == T_A2H ? 64 : 128;
            const CUtensorMap* mc = &P.tm[type == T_A2H ? M_CREH : M_CRE];
#pragma unroll 1
            for (int kt = 0; kt < 32; kt++) {
                if ((kt & 15) == 0) dep_wait(sb, ++dep);
                const uint32_t st = acquire_stage(sb, p, 16384 + hw * 256), bar = sb + B_FULL + st * 8;
                tma3d(sb + st * STAGE, &P.tm[M_HT], 0, (kt & 1) * 1024 + (kt >> 1) * 64, mb * 4 + rank * 2, bar);
                tma2d_mc(sb + st * STAGE + 16384 + rank * hw * 128, mc + (kt & 1), (kt >> 1) * 64, (nb * 2 + rank) * hw, bar);
                pipe_next(p);
            }
#pragma unroll 1
            for (int col = nb * 2 * hw; col < (nb + 1) * 2 * hw; col += 128) {
                const uint32_t st = acquire_stage(sb, p, 32768 + 256), bar = sb + B_FULL + st * 8;
                tma4d(sb + st * STAGE, &P.tm[M_AX], col, mb * 128 + rank * 16, bar);
                tma4d(sb + st * STAGE + 16384, &P.tm[M_AX], col + 64, mb * 128 + rank * 16, bar);
                bulk_g2s(sb + st * STAGE + 32768, P.Dskip + col, 256, bar);
                pipe_next(p);
            }
        }
    }
}

__device__ __forceinline__ uint32_t fresh_tid() { uint32_t t; asm volatile("mov.u32 %0, %%tid.x;" : "=r"(t)); return t; }
__device__ __forceinline__ uint32_t fresh_ctaid() { uint32_t t; asm volatile("mov.u32 %0, %%ctaid.x;" : "=r"(t)); return logical_cta(t); }
__device__ __forceinline__ void reset_state(Cons& c, Pend& d, uint32_t sb, bool resumed) {
    const uint32_t t = fresh_tid(), b = fresh_ctaid();
    const int w = __shfl_sync(0xffffffffu, t >> 5, 0);
    c.sb = sb; c.wg = w >> 2; c.wq = w & 3; c.lane = t & 31;
    c.rank = __shfl_sync(0xffffffffu, b & 1, 0); c.pair = __shfl_sync(0xffffffffu, lds32(sb + S_TAIL), 0);
    c.rel = mapa(sb + B_EMPTY, cluster_rank() ^ (c.lane & 1));
    c.atag = (lds32(sb + S_EPOCH) + 1) & 1;
    c.p.stage = 0; c.p.phase = 0;
    c.nst = resumed && c.pair < NCHAIN ? 2 * NPRE : 0;
    d = Pend{};
}
#define PROF_ITEM(i)
#define PROF_MAIN(i)

__global__ void __launch_bounds__(384, 1) fused_kernel(const __grid_constant__ Params P) {
    extern __shared__ __align__(1024) uint8_t smem[];
    const uint32_t sb = smem_u32(smem);
    asm volatile("griddepcontrol.launch_dependents;");
    const int tid = threadIdx.x, lane = tid & 31;
    const int warp = __shfl_sync(0xffffffffu, tid >> 5, 0);
    const int pair = __shfl_sync(0xffffffffu, logical_cta(blockIdx.x) >> 1, 0), rank = __shfl_sync(0xffffffffu, blockIdx.x & 1, 0);
    if (tid == 0) {
        if (sb & 1023) spin_fault();
        sts32(sb + S_EPOCH, ld_relaxed1(&g_cnt(C_EPOCH)));
        sts32(sb + S_DEP, 0); sts32(sb + S_CUR, 0); sts32(sb + S_TAIL, pair); sts32(sb + S_CTA, pair * 2 + rank);
        for (int i = 0; i < NSTAGE; i++) { mbar_init(sb + B_FULL + i * 8, 1); mbar_init(sb + B_EMPTY + i * 8, 16); }
        mbar_init(sb + B_RESUME, 2);
        mbar_init(sb + B_KVFULL, 1); mbar_init(sb + B_KVFULL + 8, 1);
        mbar_init(sb + B_GO, 1); mbar_init(sb + B_KVGO, 1); mbar_init(sb + B_KVGO + 8, 1); mbar_init(sb + B_K, 1); mbar_init(sb + B_V, 1); mbar_init(sb + B_PERS, 8); mbar_init(sb + B_INIT, 3);
        mbar_init(sb + B_WO, 1);
        for (int i = 0; i < 2; i++) { mbar_init(sb + B_SFULL + i * 8, 4); mbar_init(sb + B_SFREE + i * 8, 1); }
        mbar_init(sb + B_RELA, 1); mbar_init(sb + B_RELB, 1);
        asm volatile("fence.mbarrier_init.release.cluster;" ::: "memory");
        if (pair < 16) mbar_expect(sb + B_K, 2048);
        mbar_expect(sb + B_V, 2048);
    }
    cluster_sync();
    if (warp >= 8) {
        asm volatile("setmaxnreg.dec.sync.aligned.u32 24;");
        if (warp == 10 && lane < M_COUNT) map_prefetch(&P.tm[lane]);
        if (warp == 11 && lane == 0 && pair < 64) {
            const uint32_t t0 = gtime();
#pragma unroll 1
            for (int i = 0; i < 32; i++) {
                wait_time(t0 + P.pf0 + i * P.pf1, sb);
                l2_prefetch((const char*)(i < 16 ? P.Wq : P.Wo) + (size_t)((i & 15) * 128 + pair * 2 + rank) * 4096, 4096);
            }
        }
        if (warp == 9 && pair < NCHAIN) pacer(P, sb, lane);
        if (warp == 9) watcher(P, sb, rank, lane);
        if (warp >= 10 && lane == 0) store_warp(P, sb, warp - 10);
        if (warp == 8) {
            if (lane == 0) producer(P, sb, lds32(sb + S_TAIL), rank, lds32(sb + S_EPOCH));
            __syncwarp();
            asm volatile("barrier.cluster.arrive.relaxed.aligned;\nbarrier.cluster.wait.aligned;" ::: "memory");
        }
    } else {
        asm volatile("setmaxnreg.inc.sync.aligned.u32 240;");
        Cons c;
        Pend d;
        if (pair < NCHAIN) {
            mem0_max(P, sb, tid);
            reset_state(c, d, sb, false);
#pragma unroll 1
            for (int i = 0; i < NPRE; i++) {
                PROF_ITEM(i)
                const int item = ITEM(ITEM_OFF(pair) + i);
                float acc[128];
                mainloop<256, true>(acc, P, c, d, T_KV);
                epi_kv(acc, c, d, (item >> 5) & 7, item & 31);
            }
            ISTAMP(4)
            drain<0, true>(P, c, d);
            drain<1, true>(P, c, d);
            staging_wait(c);
            PROF_ITEM(NPRE)
            const int h = (pair & 15) * 2 + rank;
            if (pair < 16) chain_role<0>(P, sb, h, warp, lane);
            else if (pair < 32) chain_role<1>(P, sb, h, warp, lane);
            else chain_role<2>(P, sb, h, warp, lane);
            fence_async_smem();
            bar_sync(1, 256);
            const uint32_t t2 = fresh_tid();
            if (t2 < 2) mbar_arrive_cluster(mapa(sb + B_RESUME, cluster_rank() ^ t2));
        } else if (pair >= NPAIR - 2) {
            const int ch = (pair - (NPAIR - 2)) * 512 + rank * 256 + tid;
            g_coef[ch] = ssm_coef(__bfloat162float(P.Lre[ch]), __bfloat162float(P.Lim[ch]), __bfloat162float(P.logdt[ch]));
            bar_sync(1, 256);
            if (tid == 0) red_release(&g_cnt(C_COEF));
        }
        reset_state(c, d, sb, true);
        for (int it = ITEM_OFF(c.pair) + (c.pair < NCHAIN ? NPRE + 1 : 0);; it++) {
            const bool last = it == ITEM_OFF(c.pair + 1);
            if (d.kind != PEND_NONE && (last || !bar_and(5 + c.wg, mbar_test(sb + B_FULL + c.p.stage * 8, c.p.phase)))) drain_all(P, c, d);
            if (last) break;
            const int item = ITEM(it), type = item >> 8, mb = (item >> 5) & 7, nb = item & 31;
            PROF_ITEM(it - ITEM_OFF(c.pair))
            if (type >= T_OPH) {
                float acc[64];
                mainloop<128>(acc, P, c, d, type);
                PROF_MAIN(it - ITEM_OFF(c.pair))
                if (type == T_OPH) epi_oph(acc, c, d, mb, nb);
                else epi_a2_half<0>(acc, P, c, mb, nb * 128);
            } else {
                float acc[128];
                mainloop<256>(acc, P, c, d, type);
                PROF_MAIN(it - ITEM_OFF(c.pair))
                if (type == T_KV) epi_kv(acc, c, d, mb, nb);
                else if (type == T_QA) epi_qa(acc, c, d, mb, nb);
                else if (type == T_OP) epi_op(acc, c, d, mb, nb);
                else if (type == T_A1) epi_a1(acc, P, c, d, mb, nb, c.atag);
                else { epi_a2_half<0>(acc, P, c, mb, nb * 256); epi_a2_half<1>(acc, P, c, mb, nb * 256); }
            }
        }
        staging_wait(c);
        staging_post(c, PEND_NONE, 0, 0, 0);
        cluster_sync();
        if (c.wg == 0 && c.wq == 0 && c.lane == 0 && atomicInc(&g_cnt(C_DONE), DBGF(32) ? 95 : NPAIR * 2 - 1) == (DBGF(32) ? 95 : NPAIR * 2 - 1)) atomicAdd(&g_cnt(C_EPOCH), 1);
    }
}

typedef CUresult (*EncodeFn)(CUtensorMap*, CUtensorMapDataType, cuuint32_t, void*, const cuuint64_t*, const cuuint64_t*, const cuuint32_t*, const cuuint32_t*,
                             CUtensorMapInterleave, CUtensorMapSwizzle, CUtensorMapL2promotion, CUtensorMapFloatOOBfill);
void encode(EncodeFn fn, CUtensorMap* m, const void* base, int rank, const uint64_t* dims, const uint64_t* strides, const uint32_t* box, CUtensorMapSwizzle swz = CU_TENSOR_MAP_SWIZZLE_128B) {
    cuuint64_t d[5], s[5]; cuuint32_t b[5], e[5];
    for (int i = 0; i < rank; i++) { d[i] = dims[i]; b[i] = box[i]; e[i] = 1; if (i) s[i - 1] = strides[i - 1]; }
    fn(m, CU_TENSOR_MAP_DATA_TYPE_BFLOAT16, rank, (void*)base, d, s, b, e, CU_TENSOR_MAP_INTERLEAVE_NONE, swz,
       CU_TENSOR_MAP_L2_PROMOTION_L2_256B, CU_TENSOR_MAP_FLOAT_OOB_FILL_NONE);
}
void map_kmajor(EncodeFn fn, CUtensorMap* m, const void* base, uint64_t rows, uint64_t cols, uint32_t box_rows) {
    const uint64_t d[2] = {cols, rows}, s[1] = {cols * 2}; const uint32_t b[2] = {64, box_rows};
    encode(fn, m, base, 2, d, s, b);
}
void map_mnmajor(EncodeFn fn, CUtensorMap* m, const void* base, uint64_t krows, uint64_t cols) {
    const uint64_t d[3] = {64, krows, cols / 64}, s[2] = {cols * 2, 128}; const uint32_t b[3] = {64, 64, 2};
    encode(fn, m, base, 3, d, s, b);
}

}

extern "C" void kernel_launch(void* const* d_in, const int* in_sizes, int n_in, void* d_out, int out_size) {
    static Params P;
    static EncodeFn fn = nullptr;
    if (!fn) {
        cudaDriverEntryPointQueryResult q;
        cudaGetDriverEntryPoint("cuTensorMapEncodeTiled", (void**)&fn, cudaEnableDefault, &q);
        cudaFuncSetAttribute(fused_kernel, cudaFuncAttributeMaxDynamicSharedMemorySize, S_TOTAL);
    }
    const bf16* in[15];
    for (int i = 0; i < 15; i++) in[i] = (const bf16*)d_in[i];
    void *kvo, *ht, *gm;
    cudaGetSymbolAddress(&gm, g_m);
    P.gm = (uint8_t*)(((uintptr_t)gm + 32767) & ~(uintptr_t)32767);
    cudaGetSymbolAddress(&kvo, g_kvo);
    cudaGetSymbolAddress(&ht, g_ht);
    map_kmajor(fn, &P.tm[M_BX], in[9], 2048, 1024, 128);
    map_mnmajor(fn, &P.tm[M_WQ], in[11], 1024, 4096);
    map_mnmajor(fn, &P.tm[M_WK], in[12], 1024, 4096);
    map_mnmajor(fn, &P.tm[M_WV], in[13], 1024, 4096);
    map_mnmajor(fn, &P.tm[M_WO], in[14], 4096, 1024);
    map_kmajor(fn, &P.tm[M_OA], kvo, 3 * 2048, 4096, 128);
    P.swap_ri = in[4] < in[3];
    {
        const bf16* lo = P.swap_ri ? in[4] : in[3];
        const uint64_t diff = (uint64_t)((const char*)(P.swap_ri ? in[3] : in[4]) - (const char*)lo);
        const uint64_t d[4] = {1024, 8, 2, 128}, s[3] = {2048, diff, 16384}; const uint32_t b[4] = {64, 8, 2, 8};
        encode(fn, &P.tm[M_AB], lo, 4, d, s, b);
    }
    {
        const uint64_t d[4] = {1024, 2, 4, 1024}, s[3] = {2048, 64 * 2048, 4096}; const uint32_t b[4] = {64, 2, 4, 16};
        encode(fn, &P.tm[M_AX], in[0], 4, d, s, b);
    }
    map_mnmajor(fn, &P.tm[M_HT], ht, 2048, 2048);
    map_kmajor(fn, &P.tm[M_CRE], in[5], 1024, 1024, 128);
    map_kmajor(fn, &P.tm[M_CIM], in[6], 1024, 1024, 128);
    map_kmajor(fn, &P.tm[M_KVO], kvo, 3 * 2048, 4096, 32);
    map_kmajor(fn, &P.tm[M_HTS], ht, 2048, 2048, 32);
    map_kmajor(fn, &P.tm[M_WOH], in[14], 4096, 1024, 64);
    map_kmajor(fn, &P.tm[M_CREH], in[5], 1024, 1024, 64);
    map_kmajor(fn, &P.tm[M_CIMH], in[6], 1024, 1024, 64);
    for (int i = 0; i < 3; i++) {
        const uint64_t d[3] = {4096, 16, 64}, s[2] = {8192, 16 * 8192}; const uint32_t b[3] = {64, 8, 8};
        encode(fn, &P.tm[M_CQ + i], in[11 + i], 3, d, s, b);
    }
    {
        const uint64_t d[4] = {4096, 1, 1, 4096}, s[3] = {8192, 8192, 8192}; const uint32_t b[4] = {64, 1, 1, 32};
        encode(fn, &P.tm[M_KV4], kvo, 4, d, s, b);
    }
    for (int e = 0; e < 2; e++) {
        const uint64_t d[4] = {1024, 2, 4, 256}, s[3] = {8 * 2048, 2 * 2048, 16 * 2048}; const uint32_t b[4] = {64, 2, 4, 8};
        encode(fn, &P.tm[M_CO + e], in[14] + e * 1024, 4, d, s, b);
    }
    P.Wq = in[11]; P.Wk = in[12]; P.Wv = in[13]; P.Wo = in[14]; P.mem0 = in[10];
    P.Lre = in[1]; P.Lim = in[2]; P.logdt = in[7]; P.Dskip = in[8];
    P.out = (float*)d_out;
    P.two26 = 1u << 26;
    P.ds = 400; P.dc = 1600; P.alpha = 0.3f; P.extra = 200; P.da = 160; P.db = 400; P.dk = 600; P.dv = 60; P.pf0 = 1500; P.pf1 = 350; P.back = 150; P.ds0 = 950;
    for (int i = 0; i < (DBGF(32) ? 1 : 2); i++) {
        cudaLaunchConfig_t cfg = {};
        cfg.gridDim = dim3(i ? 36 : 96); cfg.blockDim = dim3(384); cfg.dynamicSmemBytes = S_TOTAL; cfg.stream = cudaStreamPerThread;
        cudaLaunchAttribute at[2];
        at[0].id = cudaLaunchAttributeClusterDimension; at[0].val.clusterDim.x = i ? 2 : 6; at[0].val.clusterDim.y = at[0].val.clusterDim.z = 1;
        at[1].id = cudaLaunchAttributeProgrammaticStreamSerialization; at[1].val.programmaticStreamSerializationAllowed = 1;
        cfg.attrs = at; cfg.numAttrs = 1 + i;
        cudaLaunchKernelEx(&cfg, fused_kernel, P);
    }
}
```

```cpp
#include <cuda_runtime.h>
#include <cuda_bf16.h>
#include <cuda.h>
#include <stdint.h>
#include <string.h>

typedef __nv_bfloat16 bf16;

namespace {

#define POLL 200
constexpr int SPIN_LIMIT = 1 << 22;
constexpr int NPAIR = 66;
constexpr int NCHAIN = 48;
enum { T_KV = 0, T_QA = 1, T_OP = 2, T_A1 = 3, T_A2 = 4, T_CHAIN = 5, T_OPH = 6, T_A2H = 7 };
enum { M_BX = 0, M_WQ, M_WK, M_WV, M_WO, M_OA, M_AB, M_AX, M_HT, M_CRE, M_CIM, M_KVO, M_HTS, M_WOH, M_CREH, M_CIMH, M_CQ, M_CK, M_CV, M_CO, M_CO1, M_KV4, M_COUNT };
enum { C_KV = 0, C_HT = 8, C_DONE = 24, C_EPOCH = 25, C_COEF = 26, C_FLAG = 32, C_O = 96 };

struct Params {
    CUtensorMap tm[M_COUNT];
    const bf16 *Wq, *Wk, *Wv, *Wo, *mem0, *Lre, *Lim, *logdt, *Dskip;
    float* out;
    uint8_t* gm;
    int swap_ri, zero;
    uint32_t two26;
    int ds, da, db, dk, dv, back, ds0, pf0, pf1, pf2, dc, extra, dp;
    float alpha;
#define DBGF(x) false
};

constexpr int NPRE = 1;
__constant__ uint16_t c_off[67] = {0, 4, 9, 15, 21, 25, 29, 33, 39, 44, 48, 53, 57, 63, 69, 74, 79, 83, 88, 92, 97, 101, 105, 109, 113, 117, 121, 126, 130, 134, 139, 144, 148, 152, 156, 161, 166, 170, 175, 179, 185, 190, 195, 199, 204, 208, 212, 217, 221, 241, 259, 279, 297, 317, 336, 356, 374, 394, 414, 432, 451, 469, 488, 507, 526, 545, 562};
__constant__ uint16_t c_items[640] = {
    32, 1280, 269, 737, 49, 1280, 364, 459, 1248, 34, 1280, 268, 488, 492, 1959, 51, 1280, 299, 399, 366, 1861, 36, 1280, 491,
    577, 53, 1280, 482, 579, 38, 1280, 453, 576, 55, 1280, 421, 361, 463, 1958, 40, 1280, 864, 931, 1250, 57, 1280, 869, 547,
    42, 1280, 928, 963, 1056, 59, 1280, 930, 611, 44, 1280, 486, 303, 367, 1088, 61, 1280, 480, 335, 271, 1091, 46, 1280, 933,
    929, 1184, 63, 1280, 934, 997, 1217, 0, 1280, 392, 739, 1, 1280, 396, 457, 1219, 2, 1280, 328, 609, 3, 1280, 462, 996,
    1154, 4, 1280, 902, 641, 5, 1280, 871, 643, 6, 1280, 333, 578, 7, 1280, 326, 672, 8, 1280, 832, 704, 9, 1280, 837,
    707, 10, 1280, 966, 992, 1121, 11, 1280, 962, 608, 12, 1280, 267, 673, 13, 1280, 363, 994, 1024, 14, 1280, 866, 961, 1186,
    15, 1280, 897, 642, 16, 1280, 391, 738, 17, 1280, 332, 610, 18, 1280, 327, 489, 1216, 19, 1280, 398, 932, 1152, 20, 1280,
    870, 675, 21, 1280, 903, 993, 1059, 22, 1280, 454, 674, 23, 1280, 461, 494, 493, 1860, 24, 1280, 901, 998, 1251, 25, 1280,
    896, 995, 1218, 26, 1280, 834, 544, 27, 1280, 838, 960, 1057, 28, 1280, 360, 513, 29, 1280, 264, 545, 30, 1280, 865, 965,
    1185, 31, 1280, 898, 546, 33, 66, 84, 102, 120, 138, 156, 174, 219, 220, 198, 229, 300, 419, 801, 451, 452, 899, 999,
    1122, 35, 67, 85, 103, 121, 139, 157, 175, 250, 202, 770, 245, 263, 359, 806, 455, 425, 706, 37, 68, 86, 104, 122,
    140, 158, 176, 204, 217, 252, 195, 386, 355, 802, 301, 389, 292, 460, 1120, 39, 69, 87, 105, 123, 141, 159, 177, 203,
    197, 218, 385, 233, 418, 357, 431, 420, 515, 41, 70, 88, 106, 124, 142, 160, 178, 221, 207, 234, 225, 254, 775, 836,
    416, 291, 967, 365, 1026, 43, 71, 89, 107, 125, 143, 161, 179, 200, 213, 257, 232, 804, 320, 295, 427, 325, 495, 1058,
    45, 72, 90, 108, 126, 144, 162, 180, 211, 212, 209, 205, 224, 356, 262, 773, 449, 422, 900, 1155, 47, 73, 91, 109,
    127, 145, 163, 181, 246, 194, 236, 241, 387, 297, 298, 256, 323, 640, 48, 74, 92, 110, 128, 146, 164, 182, 239, 251,
    235, 215, 247, 390, 334, 322, 481, 296, 426, 1153, 50, 75, 93, 111, 129, 147, 165, 183, 196, 210, 222, 248, 255, 321,
    769, 294, 487, 362, 490, 1089, 52, 76, 94, 112, 130, 148, 166, 184, 192, 216, 772, 768, 242, 353, 397, 448, 423, 512,
    54, 77, 95, 113, 131, 149, 167, 185, 240, 253, 214, 244, 226, 237, 289, 800, 805, 261, 514, 56, 78, 96, 114, 132,
    150, 168, 186, 231, 230, 223, 206, 249, 259, 833, 868, 430, 736, 58, 79, 97, 115, 133, 151, 169, 187, 238, 227, 771,
    228, 266, 424, 839, 450, 835, 964, 1027, 60, 80, 98, 116, 134, 152, 170, 188, 288, 193, 330, 803, 774, 417, 395, 484,
    935, 458, 1249, 62, 81, 99, 117, 135, 153, 171, 189, 290, 199, 302, 393, 394, 384, 354, 485, 867, 429, 1025, 64, 82,
    100, 118, 136, 154, 172, 190, 331, 208, 258, 243, 293, 352, 428, 324, 456, 265, 1123, 65, 83, 101, 119, 137, 155, 173,
    191, 270, 201, 329, 388, 807, 358, 483, 260, 705,
};
#define ITEM_OFF(p) c_off[p]
#define ITEM(i) c_items[i]

__device__ __align__(1024) bf16 g_kvo[3 * 2048 * 4096];
__device__ __align__(1024) bf16 g_ht[2048 * 2048];
__device__ __align__(1024) uint8_t g_m[9 * 32768];
__device__ __align__(1024) uint8_t g_f[8 * 49152];
__device__ __align__(1024) uint32_t g_km[64 * 32 * 512];
__device__ __align__(1024) uint32_t g_vmt[64 * 32 * 512];
__device__ __align__(1024) float2 g_agg[8 * 1024];
__device__ __align__(1024) float4 g_coef[1024];
__device__ __align__(1024) uint32_t g_cntl[128 * 32];
#define g_cnt(i) g_cntl[(i) * 32]
__device__ __align__(1024) uint32_t g_hint[6144 + 160];
#define SSTAMP(i, cond)
#define PROF(i)
#define GT_EDGE(o)
constexpr int M_SLOT = 32768, F_SLOT = 49152;

constexpr int STAGE = 49152, NSTAGE = 4;
constexpr int S_STG = NSTAGE * STAGE;
constexpr int S_BAR = S_STG + 32768;
constexpr int B_FULL = S_BAR, B_EMPTY = S_BAR + 32, B_RESUME = S_BAR + 64, B_KVFULL = S_BAR + 72, B_GO = S_BAR + 88, B_K = S_BAR + 96, B_PERS = S_BAR + 104, B_INIT = S_BAR + 112, B_RELA = S_BAR + 120, B_V = S_BAR + 128, B_WO = S_BAR + 136,
              B_SFULL = S_BAR + 144, B_SFREE = S_BAR + 160, S_DESC = S_BAR + 176, S_REDO = S_BAR + 256 + 512 + 64, S_EPOCH = S_BAR + 208, B_RELB = S_BAR + 216, B_KVGO = S_BAR + 224, S_DEP = S_BAR + 240, S_CUR = S_BAR + 244, S_TAIL = S_BAR + 248, S_CTA = S_BAR + 252;
constexpr int S_COEF = S_BAR + 256 + 512, S_TOTAL = S_COEF + 1024;
constexpr int S_W1 = 0;
constexpr int S_O = 24 * 4096, S_VL = S_O + 2048, S_MX = 25 * 4096, S_SC = S_MX + 64, S_SUM = S_MX + 128;
constexpr int S_KL = 26 * 4096;
constexpr int S_W2 = 27 * 4096;
constexpr int S_KV = S_W2 + 65536;
constexpr int S_P1 = S_W2 + 98304;
constexpr int S_QX = S_P1 + 16384;
constexpr int S_SX = S_QX + 2048;
static_assert(S_SX + 1280 <= S_BAR, "chain smem overlaps barriers");
constexpr int NR = 40, NS = 64 - NR;

__device__ __forceinline__ uint32_t logical_cta(uint32_t b) {
    const uint32_t c = b / 6, r = b - c * 6;
    return gridDim.x != 96 ? 96 + b : ((r >> 1) + (c >= 8) + (c >= 15)) % 3 * 32 + c * 2 + (r & 1);
}
__device__ __forceinline__ uint32_t cluster_rank() { uint32_t r; asm("mov.u32 %0, %%cluster_ctarank;" : "=r"(r)); return r; }
__device__ __forceinline__ uint16_t pair_mask() { return (uint16_t)(3u << (cluster_rank() & 6)); }
__device__ __forceinline__ void spin_fault() { asm volatile("st.global.u32 [%0], 0;" ::"l"(0ull) : "memory"); }
__device__ __forceinline__ uint32_t smem_u32(const void* p) { return (uint32_t)__cvta_generic_to_shared(p); }
__device__ __forceinline__ uint32_t opq(uint32_t x, int lane) { return __shfl_sync(0xffffffffu, x, lane); }
__device__ __forceinline__ uint32_t mapa(uint32_t a, uint32_t r) { uint32_t d; asm volatile("mapa.shared::cluster.u32 %0, %1, %2;" : "=r"(d) : "r"(a), "r"(r)); return d; }
__device__ __forceinline__ void mma16816(float* d, uint32_t a0, uint32_t a1, uint32_t a2, uint32_t a3, uint32_t b0, uint32_t b1) {
    asm("mma.sync.aligned.m16n8k16.row.col.f32.bf16.bf16.f32 {%0,%1,%2,%3}, {%4,%5,%6,%7}, {%8,%9}, {%0,%1,%2,%3};"
        : "+f"(d[0]), "+f"(d[1]), "+f"(d[2]), "+f"(d[3]) : "r"(a0), "r"(a1), "r"(a2), "r"(a3), "r"(b0), "r"(b1));
}
__device__ __forceinline__ void mma1688(float* d, uint32_t a0, uint32_t a1, uint32_t b0) {
    asm("mma.sync.aligned.m16n8k8.row.col.f32.bf16.bf16.f32 {%0,%1,%2,%3}, {%4,%5}, {%6}, {%0,%1,%2,%3};"
        : "+f"(d[0]), "+f"(d[1]), "+f"(d[2]), "+f"(d[3]) : "r"(a0), "r"(a1), "r"(b0));
}
__device__ __forceinline__ void ldsm4(uint32_t* r, uint32_t a) {
    asm volatile("ldmatrix.sync.aligned.m8n8.x4.shared.b16 {%0,%1,%2,%3}, [%4];" : "=r"(r[0]), "=r"(r[1]), "=r"(r[2]), "=r"(r[3]) : "r"(a));
}
__device__ __forceinline__ void ldsm4t(uint32_t* r, uint32_t a) {
    asm volatile("ldmatrix.sync.aligned.m8n8.x4.trans.shared.b16 {%0,%1,%2,%3}, [%4];" : "=r"(r[0]), "=r"(r[1]), "=r"(r[2]), "=r"(r[3]) : "r"(a));
}
__device__ __forceinline__ void stsm4(uint32_t a, uint32_t r0, uint32_t r1, uint32_t r2, uint32_t r3) {
    asm volatile("stmatrix.sync.aligned.m8n8.x4.shared.b16 [%0], {%1,%2,%3,%4};" ::"r"(a), "r"(r0), "r"(r1), "r"(r2), "r"(r3) : "memory");
}
__device__ __forceinline__ void stsm4t(uint32_t a, uint32_t r0, uint32_t r1, uint32_t r2, uint32_t r3) {
    asm volatile("stmatrix.sync.aligned.m8n8.x4.trans.shared.b16 [%0], {%1,%2,%3,%4};" ::"r"(a), "r"(r0), "r"(r1), "r"(r2), "r"(r3) : "memory");
}
__device__ __forceinline__ uint32_t pack2(float lo, float hi) { uint32_t d; asm("cvt.rn.bf16x2.f32 %0, %1, %2;" : "=r"(d) : "f"(hi), "f"(lo)); return d; }
__device__ __forceinline__ float bf_lo(uint32_t u) { return __uint_as_float(u << 16); }
__device__ __forceinline__ float bf_hi(uint32_t u) { return __uint_as_float(u & 0xffff0000u); }
__device__ __forceinline__ uint32_t hmul2(uint32_t a, uint32_t b) { uint32_t d; asm("mul.rn.bf16x2 %0, %1, %2;" : "=r"(d) : "r"(a), "r"(b)); return d; }
__device__ __forceinline__ float ex2(float x) { float y; asm("ex2.approx.ftz.f32 %0, %1;" : "=f"(y) : "f"(x)); return y; }
__device__ __forceinline__ float rcp(float x) { float y; asm("rcp.approx.ftz.f32 %0, %1;" : "=f"(y) : "f"(x)); return y; }
__device__ __forceinline__ void st_relaxed4(const void* p, uint32_t a, uint32_t b, uint32_t c, uint32_t d) {
    asm volatile("{\n.reg .b128 t;\nmov.b128 t, {%1,%2,%3,%4};\nst.relaxed.gpu.global.b128 [%0], t;\n}" ::"l"(p), "r"(a), "r"(b), "r"(c), "r"(d) : "memory");
}
__device__ __forceinline__ void st_relaxed2(const void* p, uint32_t a, uint32_t b) {
    asm volatile("{\n.reg .b64 t;\nmov.b64 t, {%1,%2};\nst.relaxed.gpu.global.b64 [%0], t;\n}" ::"l"(p), "r"(a), "r"(b) : "memory");
}
__device__ __forceinline__ void ld_relaxed2_if(uint32_t& a, uint32_t& b, const void* p, bool on) {
    asm volatile("{\n.reg .pred P;\n.reg .b64 t;\nsetp.ne.u32 P, %3, 0;\nmov.b64 t, {%0,%1};\n@P ld.relaxed.gpu.global.b64 t, [%2];\nmov.b64 {%0,%1}, t;\n}" : "+r"(a), "+r"(b) : "l"(p), "r"((uint32_t)on) : "memory");
}
__device__ __forceinline__ uint32_t ld_relaxed1(const void* p) { uint32_t v; asm volatile("ld.relaxed.gpu.global.u32 %0, [%1];" : "=r"(v) : "l"(p) : "memory"); return v; }
__device__ __forceinline__ void st_relaxed1(const void* p, uint32_t v) { asm volatile("st.relaxed.gpu.global.u32 [%0], %1;" ::"l"(p), "r"(v) : "memory"); }
__device__ __forceinline__ uint32_t ld_acquire(const void* p) { uint32_t v; asm volatile("ld.acquire.gpu.global.u32 %0, [%1];" : "=r"(v) : "l"(p) : "memory"); return v; }
__device__ __forceinline__ void red_release(void* p) { asm volatile("red.release.gpu.global.add.u32 [%0], 1;" ::"l"(p) : "memory"); }
__device__ __forceinline__ void st_stream2(float* p, float a, float b) { asm volatile("st.global.cs.v2.f32 [%0], {%1, %2};" ::"l"(p), "f"(a), "f"(b) : "memory"); }
__device__ __forceinline__ void fence_acquire() { asm volatile("fence.acquire.gpu;" ::: "memory"); }
__device__ __forceinline__ void fence_release() { asm volatile("fence.release.gpu;" ::: "memory"); }
__device__ __forceinline__ void fence_async() {  asm volatile("fence.proxy.async.global;" ::: "memory"); }
__device__ __forceinline__ void fence_async_smem() { asm volatile("fence.proxy.async.shared::cta;" ::: "memory"); }
__device__ __forceinline__ void wait_count(const uint32_t* p, uint32_t target) {
    int n = 0;
    while ((int32_t)(ld_acquire(p) - target) < 0) { __nanosleep(POLL); if (++n > SPIN_LIMIT) spin_fault(); }
}
__device__ __forceinline__ void bar_sync(int id, int n) { asm volatile("bar.sync %0, %1;" ::"r"(id), "r"(n) : "memory"); }
__device__ __forceinline__ void bar_arrive(int id, int n) { asm volatile("bar.arrive %0, %1;" ::"r"(id), "r"(n) : "memory"); }
__device__ __forceinline__ bool bar_and(int id, bool v) {
    uint32_t r;
    asm volatile("{\n.reg .pred P, Q;\nsetp.ne.u32 Q, %2, 0;\nbar.red.and.pred P, %1, 128, Q;\nselp.u32 %0, 1, 0, P;\n}" : "=r"(r) : "r"(id), "r"((uint32_t)v) : "memory");
    return r;
}
__device__ __forceinline__ void lds128(uint32_t* v, uint32_t a) { asm volatile("ld.shared.v4.b32 {%0,%1,%2,%3}, [%4];" : "=r"(v[0]), "=r"(v[1]), "=r"(v[2]), "=r"(v[3]) : "r"(a) : "memory"); }
__device__ __forceinline__ uint32_t lds32(uint32_t a) { uint32_t v; asm volatile("ld.shared.b32 %0, [%1];" : "=r"(v) : "r"(a) : "memory"); return v; }
__device__ __forceinline__ void lds64f(float* v, uint32_t a) { asm volatile("ld.shared.v2.f32 {%0,%1}, [%2];" : "=f"(v[0]), "=f"(v[1]) : "r"(a) : "memory"); }
__device__ __forceinline__ void sts128(uint32_t a, const uint32_t* v) { asm volatile("st.shared.v4.b32 [%0], {%1,%2,%3,%4};" ::"r"(a), "r"(v[0]), "r"(v[1]), "r"(v[2]), "r"(v[3]) : "memory"); }
__device__ __forceinline__ void sts64(uint32_t a, uint32_t x, uint32_t y) { asm volatile("st.shared.v2.b32 [%0], {%1,%2};" ::"r"(a), "r"(x), "r"(y) : "memory"); }
__device__ __forceinline__ void sts32(uint32_t a, uint32_t x) { asm volatile("st.shared.b32 [%0], %1;" ::"r"(a), "r"(x) : "memory"); }
__device__ __forceinline__ bool mbar_try(uint32_t b, uint32_t par) {
    uint32_t ok;
    asm volatile("{\n.reg .pred P;\nmbarrier.try_wait.parity.shared::cta.b64 P, [%1], %2;\nselp.u32 %0, 1, 0, P;\n}" : "=r"(ok) : "r"(b), "r"(par) : "memory");
    return ok;
}
__device__ __forceinline__ bool mbar_test(uint32_t b, uint32_t par) {
    uint32_t ok;
    asm volatile("{\n.reg .pred P;\nmbarrier.test_wait.parity.shared::cta.b64 P, [%1], %2;\nselp.u32 %0, 1, 0, P;\n}" : "=r"(ok) : "r"(b), "r"(par) : "memory");
    return ok;
}
__device__ __forceinline__ void mbar_wait(uint32_t b, uint32_t par) { int n = 0; while (!mbar_try(b, par)) { if (++n > SPIN_LIMIT) spin_fault(); } }
__device__ __forceinline__ void mbar_init(uint32_t b, uint32_t n) { asm volatile("mbarrier.init.shared::cta.b64 [%0], %1;" ::"r"(b), "r"(n) : "memory"); }
__device__ __forceinline__ void mbar_expect(uint32_t b, uint32_t bytes) { asm volatile("mbarrier.arrive.expect_tx.shared::cta.b64 _, [%0], %1;" ::"r"(b), "r"(bytes) : "memory"); }
__device__ __forceinline__ void mbar_arrive(uint32_t b) { asm volatile("mbarrier.arrive.shared::cta.b64 _, [%0];" ::"r"(b) : "memory"); }
__device__ __forceinline__ void mbar_arrive_cluster(uint32_t b) { asm volatile("mbarrier.arrive.shared::cluster.b64 _, [%0];" ::"r"(b) : "memory"); }
__device__ __forceinline__ void st_async1(uint32_t a, uint32_t x, uint32_t bar) {
    asm volatile("st.async.weak.shared::cluster.mbarrier::complete_tx::bytes.b32 [%0], %1, [%2];" ::"r"(a), "r"(x), "r"(bar) : "memory");
}
__device__ __forceinline__ void st_async2(uint32_t a, uint32_t x, uint32_t y, uint32_t bar) {
    asm volatile("st.async.weak.shared::cluster.mbarrier::complete_tx::bytes.v2.b32 [%0], {%1,%2}, [%3];" ::"r"(a), "r"(x), "r"(y), "r"(bar) : "memory");
}
__device__ __forceinline__ void cluster_sync() { asm volatile("barrier.cluster.arrive.aligned;\nbarrier.cluster.wait.aligned;" ::: "memory"); }
__device__ __forceinline__ void tma2d(uint32_t dst, const CUtensorMap* m, int c0, int c1, uint32_t bar) {
    asm volatile("cp.async.bulk.tensor.2d.shared::cluster.global.mbarrier::complete_tx::bytes [%0], [%1, {%2, %3}], [%4];" ::"r"(dst), "l"(m), "r"(c0), "r"(c1), "r"(bar) : "memory");
}
__device__ __forceinline__ void tma2d_mc(uint32_t dst, const CUtensorMap* m, int c0, int c1, uint32_t bar) {
    asm volatile("cp.async.bulk.tensor.2d.shared::cluster.global.mbarrier::complete_tx::bytes.multicast::cluster [%0], [%1, {%2, %3}], [%4], %5;" ::"r"(dst), "l"(m), "r"(c0), "r"(c1), "r"(bar), "h"(pair_mask()) : "memory");
}
__device__ __forceinline__ void tma3d(uint32_t dst, const CUtensorMap* m, int c0, int c1, int c2, uint32_t bar) {
    asm volatile("cp.async.bulk.tensor.3d.shared::cluster.global.mbarrier::complete_tx::bytes [%0], [%1, {%2, %3, %4}], [%5];" ::"r"(dst), "l"(m), "r"(c0), "r"(c1), "r"(c2), "r"(bar) : "memory");
}
__device__ __forceinline__ void tma3d_mc(uint32_t dst, const CUtensorMap* m, int c0, int c1, int c2, uint32_t bar) {
    asm volatile("cp.async.bulk.tensor.3d.shared::cluster.global.mbarrier::complete_tx::bytes.multicast::cluster [%0], [%1, {%2, %3, %4}], [%5], %6;" ::"r"(dst), "l"(m), "r"(c0), "r"(c1), "r"(c2), "r"(bar), "h"(pair_mask()) : "memory");
}
__device__ __forceinline__ void tma4d(uint32_t dst, const CUtensorMap* m, int c0, int c3, uint32_t bar) {
    asm volatile("cp.async.bulk.tensor.4d.shared::cluster.global.mbarrier::complete_tx::bytes [%0], [%1, {%2, 0, 0, %3}], [%4];" ::"r"(dst), "l"(m), "r"(c0), "r"(c3), "r"(bar) : "memory");
}
__device__ __forceinline__ void tma4d_mc(uint32_t dst, const CUtensorMap* m, int c0, int c3, uint32_t bar) {
    asm volatile("cp.async.bulk.tensor.4d.shared::cluster.global.mbarrier::complete_tx::bytes.multicast::cluster [%0], [%1, {%2, 0, 0, %3}], [%4], %5;" ::"r"(dst), "l"(m), "r"(c0), "r"(c3), "r"(bar), "h"(pair_mask()) : "memory");
}
__device__ __forceinline__ void tma_prefetch2d(const CUtensorMap* m, int c0, int c1) {
    asm volatile("cp.async.bulk.prefetch.tensor.2d.L2.global [%0, {%1, %2}];" ::"l"(m), "r"(c0), "r"(c1) : "memory");
}
__device__ __forceinline__ void map_prefetch(const CUtensorMap* m) { asm volatile("prefetch.tensormap [%0];" ::"l"(m) : "memory"); }
__device__ __forceinline__ void l2_prefetch(const void* src, uint32_t bytes) { asm volatile("cp.async.bulk.prefetch.L2.global [%0], %1;" ::"l"(src), "r"(bytes) : "memory"); }
__device__ __forceinline__ void bulk_g2s(uint32_t dst, const void* src, uint32_t bytes, uint32_t bar) {
    asm volatile("cp.async.bulk.shared::cluster.global.mbarrier::complete_tx::bytes [%0], [%1], %2, [%3];" ::"r"(dst), "l"(src), "r"(bytes), "r"(bar) : "memory");
}
__device__ __forceinline__ void bulk_s2g(void* dst, uint32_t src, uint32_t bytes) {
    asm volatile("cp.async.bulk.global.shared::cta.bulk_group [%0], [%1], %2;" ::"l"(dst), "r"(src), "r"(bytes) : "memory");
}
__device__ __forceinline__ void tma_store2d(const CUtensorMap* m, int c0, int c1, uint32_t src) {
    asm volatile("cp.async.bulk.tensor.2d.global.shared::cta.bulk_group [%0, {%1, %2}], [%3];" ::"l"(m), "r"(c0), "r"(c1), "r"(src) : "memory");
}
__device__ __forceinline__ void bulk_commit() { asm volatile("cp.async.bulk.commit_group;" ::: "memory"); }
__device__ __forceinline__ void bulk_wait_read() { asm volatile("cp.async.bulk.wait_group.read 0;" ::: "memory"); }
__device__ __forceinline__ void bulk_wait_all() { asm volatile("cp.async.bulk.wait_group 0;" ::: "memory"); }
__device__ __forceinline__ uint64_t mkdesc(uint32_t addr, uint32_t lbo, uint32_t sbo, uint32_t swz) {
    return (uint64_t)((addr & 0x3FFFF) >> 4) | ((uint64_t)(lbo >> 4) << 16) | ((uint64_t)(sbo >> 4) << 32) | ((uint64_t)swz << 62);
}
__device__ __forceinline__ void wg_fence() { asm volatile("wgmma.fence.sync.aligned;" ::: "memory"); }
__device__ __forceinline__ void wg_commit() { asm volatile("wgmma.commit_group.sync.aligned;" ::: "memory"); }
template <int N> __device__ __forceinline__ void wg_wait() { asm volatile("wgmma.wait_group.sync.aligned %0;" ::"n"(N) : "memory"); }
template <typename T> __device__ __forceinline__ void pin_ptr(T*& p) { asm volatile("" : "+l"(p)); }
template <int N> __device__ __forceinline__ void pin(uint32_t* d) {
#pragma unroll
    for (int i = 0; i < N; i++) asm volatile("" : "+r"(d[i])::"memory");
}
template <int N> __device__ __forceinline__ void pin(float* d) {
#pragma unroll
    for (int i = 0; i < N; i++) asm volatile("" : "+f"(d[i])::"memory");
}

template <int TA, int TB>
__device__ __forceinline__ void wgmma_ss256(float* d, uint64_t da, uint64_t db) {
    asm volatile("wgmma.mma_async.sync.aligned.m64n256k16.f32.bf16.bf16 "
        "{%0, %1, %2, %3, %4, %5, %6, %7, %8, %9, %10, %11, %12, %13, %14, %15, %16, %17, %18, %19, %20, %21, %22, %23, %24, %25, %26, %27, %28, %29, %30, %31, %32, %33, %34, %35, %36, %37, %38, %39, %40, %41, %42, %43, %44, %45, %46, %47, %48, %49, %50, %51, %52, %53, %54, %55, %56, %57, %58, %59, %60, %61, %62, %63, %64, %65, %66, %67, %68, %69, %70, %71, %72, %73, %74, %75, %76, %77, %78, %79, %80, %81, %82, %83, %84, %85, %86, %87, %88, %89, %90, %91, %92, %93, %94, %95, %96, %97, %98, %99, %100, %101, %102, %103, %104, %105, %106, %107, %108, %109, %110, %111, %112, %113, %114, %115, %116, %117, %118, %119, %120, %121, %122, %123, %124, %125, %126, %127}, %128, %129, 1, 1, 1, %130, %131;"
        : "+f"(d[0]), "+f"(d[1]), "+f"(d[2]), "+f"(d[3]), "+f"(d[4]), "+f"(d[5]), "+f"(d[6]), "+f"(d[7]), "+f"(d[8]), "+f"(d[9]), "+f"(d[10]), "+f"(d[11]), "+f"(d[12]), "+f"(d[13]), "+f"(d[14]), "+f"(d[15]), "+f"(d[16]), "+f"(d[17]), "+f"(d[18]), "+f"(d[19]), "+f"(d[20]), "+f"(d[21]), "+f"(d[22]), "+f"(d[23]), "+f"(d[24]), "+f"(d[25]), "+f"(d[26]), "+f"(d[27]), "+f"(d[28]), "+f"(d[29]), "+f"(d[30]), "+f"(d[31]), "+f"(d[32]), "+f"(d[33]), "+f"(d[34]), "+f"(d[35]), "+f"(d[36]), "+f"(d[37]), "+f"(d[38]), "+f"(d[39]), "+f"(d[40]), "+f"(d[41]), "+f"(d[42]), "+f"(d[43]), "+f"(d[44]), "+f"(d[45]), "+f"(d[46]), "+f"(d[47]), "+f"(d[48]), "+f"(d[49]), "+f"(d[50]), "+f"(d[51]), "+f"(d[52]), "+f"(d[53]), "+f"(d[54]), "+f"(d[55]), "+f"(d[56]), "+f"(d[57]), "+f"(d[58]), "+f"(d[59]), "+f"(d[60]), "+f"(d[61]), "+f"(d[62]), "+f"(d[63]), "+f"(d[64]), "+f"(d[65]), "+f"(d[66]), "+f"(d[67]), "+f"(d[68]), "+f"(d[69]), "+f"(d[70]), "+f"(d[71]), "+f"(d[72]), "+f"(d[73]), "+f"(d[74]), "+f"(d[75]), "+f"(d[76]), "+f"(d[77]), "+f"(d[78]), "+f"(d[79]), "+f"(d[80]), "+f"(d[81]), "+f"(d[82]), "+f"(d[83]), "+f"(d[84]), "+f"(d[85]), "+f"(d[86]), "+f"(d[87]), "+f"(d[88]), "+f"(d[89]), "+f"(d[90]), "+f"(d[91]), "+f"(d[92]), "+f"(d[93]), "+f"(d[94]), "+f"(d[95]), "+f"(d[96]), "+f"(d[97]), "+f"(d[98]), "+f"(d[99]), "+f"(d[100]), "+f"(d[101]), "+f"(d[102]), "+f"(d[103]), "+f"(d[104]), "+f"(d[105]), "+f"(d[106]), "+f"(d[107]), "+f"(d[108]), "+f"(d[109]), "+f"(d[110]), "+f"(d[111]), "+f"(d[112]), "+f"(d[113]), "+f"(d[114]), "+f"(d[115]), "+f"(d[116]), "+f"(d[117]), "+f"(d[118]), "+f"(d[119]), "+f"(d[120]), "+f"(d[121]), "+f"(d[122]), "+f"(d[123]), "+f"(d[124]), "+f"(d[125]), "+f"(d[126]), "+f"(d[127])
        : "l"(da), "l"(db), "n"(TA), "n"(TB));
}
template <int TA, int TB>
__device__ __forceinline__ void wgmma_ss256_first(float* d, uint64_t da, uint64_t db) {
    asm volatile("wgmma.mma_async.sync.aligned.m64n256k16.f32.bf16.bf16 "
        "{%0, %1, %2, %3, %4, %5, %6, %7, %8, %9, %10, %11, %12, %13, %14, %15, %16, %17, %18, %19, %20, %21, %22, %23, %24, %25, %26, %27, %28, %29, %30, %31, %32, %33, %34, %35, %36, %37, %38, %39, %40, %41, %42, %43, %44, %45, %46, %47, %48, %49, %50, %51, %52, %53, %54, %55, %56, %57, %58, %59, %60, %61, %62, %63, %64, %65, %66, %67, %68, %69, %70, %71, %72, %73, %74, %75, %76, %77, %78, %79, %80, %81, %82, %83, %84, %85, %86, %87, %88, %89, %90, %91, %92, %93, %94, %95, %96, %97, %98, %99, %100, %101, %102, %103, %104, %105, %106, %107, %108, %109, %110, %111, %112, %113, %114, %115, %116, %117, %118, %119, %120, %121, %122, %123, %124, %125, %126, %127}, %128, %129, 0, 1, 1, %130, %131;"
        : "=f"(d[0]), "=f"(d[1]), "=f"(d[2]), "=f"(d[3]), "=f"(d[4]), "=f"(d[5]), "=f"(d[6]), "=f"(d[7]), "=f"(d[8]), "=f"(d[9]), "=f"(d[10]), "=f"(d[11]), "=f"(d[12]), "=f"(d[13]), "=f"(d[14]), "=f"(d[15]), "=f"(d[16]), "=f"(d[17]), "=f"(d[18]), "=f"(d[19]), "=f"(d[20]), "=f"(d[21]), "=f"(d[22]), "=f"(d[23]), "=f"(d[24]), "=f"(d[25]), "=f"(d[26]), "=f"(d[27]), "=f"(d[28]), "=f"(d[29]), "=f"(d[30]), "=f"(d[31]), "=f"(d[32]), "=f"(d[33]), "=f"(d[34]), "=f"(d[35]), "=f"(d[36]), "=f"(d[37]), "=f"(d[38]), "=f"(d[39]), "=f"(d[40]), "=f"(d[41]), "=f"(d[42]), "=f"(d[43]), "=f"(d[44]), "=f"(d[45]), "=f"(d[46]), "=f"(d[47]), "=f"(d[48]), "=f"(d[49]), "=f"(d[50]), "=f"(d[51]), "=f"(d[52]), "=f"(d[53]), "=f"(d[54]), "=f"(d[55]), "=f"(d[56]), "=f"(d[57]), "=f"(d[58]), "=f"(d[59]), "=f"(d[60]), "=f"(d[61]), "=f"(d[62]), "=f"(d[63]), "=f"(d[64]), "=f"(d[65]), "=f"(d[66]), "=f"(d[67]), "=f"(d[68]), "=f"(d[69]), "=f"(d[70]), "=f"(d[71]), "=f"(d[72]), "=f"(d[73]), "=f"(d[74]), "=f"(d[75]), "=f"(d[76]), "=f"(d[77]), "=f"(d[78]), "=f"(d[79]), "=f"(d[80]), "=f"(d[81]), "=f"(d[82]), "=f"(d[83]), "=f"(d[84]), "=f"(d[85]), "=f"(d[86]), "=f"(d[87]), "=f"(d[88]), "=f"(d[89]), "=f"(d[90]), "=f"(d[91]), "=f"(d[92]), "=f"(d[93]), "=f"(d[94]), "=f"(d[95]), "=f"(d[96]), "=f"(d[97]), "=f"(d[98]), "=f"(d[99]), "=f"(d[100]), "=f"(d[101]), "=f"(d[102]), "=f"(d[103]), "=f"(d[104]), "=f"(d[105]), "=f"(d[106]), "=f"(d[107]), "=f"(d[108]), "=f"(d[109]), "=f"(d[110]), "=f"(d[111]), "=f"(d[112]), "=f"(d[113]), "=f"(d[114]), "=f"(d[115]), "=f"(d[116]), "=f"(d[117]), "=f"(d[118]), "=f"(d[119]), "=f"(d[120]), "=f"(d[121]), "=f"(d[122]), "=f"(d[123]), "=f"(d[124]), "=f"(d[125]), "=f"(d[126]), "=f"(d[127])
        : "l"(da), "l"(db), "n"(TA), "n"(TB));
}
template <int TA, int TB>
__device__ __forceinline__ void wgmma_ss128(float* d, uint64_t da, uint64_t db) {
    asm volatile("wgmma.mma_async.sync.aligned.m64n128k16.f32.bf16.bf16 "
        "{%0, %1, %2, %3, %4, %5, %6, %7, %8, %9, %10, %11, %12, %13, %14, %15, %16, %17, %18, %19, %20, %21, %22, %23, %24, %25, %26, %27, %28, %29, %30, %31, %32, %33, %34, %35, %36, %37, %38, %39, %40, %41, %42, %43, %44, %45, %46, %47, %48, %49, %50, %51, %52, %53, %54, %55, %56, %57, %58, %59, %60, %61, %62, %63}, %64, %65, 1, 1, 1, %66, %67;"
        : "+f"(d[0]), "+f"(d[1]), "+f"(d[2]), "+f"(d[3]), "+f"(d[4]), "+f"(d[5]), "+f"(d[6]), "+f"(d[7]), "+f"(d[8]), "+f"(d[9]), "+f"(d[10]), "+f"(d[11]), "+f"(d[12]), "+f"(d[13]), "+f"(d[14]), "+f"(d[15]), "+f"(d[16]), "+f"(d[17]), "+f"(d[18]), "+f"(d[19]), "+f"(d[20]), "+f"(d[21]), "+f"(d[22]), "+f"(d[23]), "+f"(d[24]), "+f"(d[25]), "+f"(d[26]), "+f"(d[27]), "+f"(d[28]), "+f"(d[29]), "+f"(d[30]), "+f"(d[31]), "+f"(d[32]), "+f"(d[33]), "+f"(d[34]), "+f"(d[35]), "+f"(d[36]), "+f"(d[37]), "+f"(d[38]), "+f"(d[39]), "+f"(d[40]), "+f"(d[41]), "+f"(d[42]), "+f"(d[43]), "+f"(d[44]), "+f"(d[45]), "+f"(d[46]), "+f"(d[47]), "+f"(d[48]), "+f"(d[49]), "+f"(d[50]), "+f"(d[51]), "+f"(d[52]), "+f"(d[53]), "+f"(d[54]), "+f"(d[55]), "+f"(d[56]), "+f"(d[57]), "+f"(d[58]), "+f"(d[59]), "+f"(d[60]), "+f"(d[61]), "+f"(d[62]), "+f"(d[63])
        : "l"(da), "l"(db), "n"(TA), "n"(TB));
}
template <int TA, int TB>
__device__ __forceinline__ void wgmma_ss128_first(float* d, uint64_t da, uint64_t db) {
    asm volatile("wgmma.mma_async.sync.aligned.m64n128k16.f32.bf16.bf16 "
        "{%0, %1, %2, %3, %4, %5, %6, %7, %8, %9, %10, %11, %12, %13, %14, %15, %16, %17, %18, %19, %20, %21, %22, %23, %24, %25, %26, %27, %28, %29, %30, %31, %32, %33, %34, %35, %36, %37, %38, %39, %40, %41, %42, %43, %44, %45, %46, %47, %48, %49, %50, %51, %52, %53, %54, %55, %56, %57, %58, %59, %60, %61, %62, %63}, %64, %65, 0, 1, 1, %66, %67;"
        : "=f"(d[0]), "=f"(d[1]), "=f"(d[2]), "=f"(d[3]), "=f"(d[4]), "=f"(d[5]), "=f"(d[6]), "=f"(d[7]), "=f"(d[8]), "=f"(d[9]), "=f"(d[10]), "=f"(d[11]), "=f"(d[12]), "=f"(d[13]), "=f"(d[14]), "=f"(d[15]), "=f"(d[16]), "=f"(d[17]), "=f"(d[18]), "=f"(d[19]), "=f"(d[20]), "=f"(d[21]), "=f"(d[22]), "=f"(d[23]), "=f"(d[24]), "=f"(d[25]), "=f"(d[26]), "=f"(d[27]), "=f"(d[28]), "=f"(d[29]), "=f"(d[30]), "=f"(d[31]), "=f"(d[32]), "=f"(d[33]), "=f"(d[34]), "=f"(d[35]), "=f"(d[36]), "=f"(d[37]), "=f"(d[38]), "=f"(d[39]), "=f"(d[40]), "=f"(d[41]), "=f"(d[42]), "=f"(d[43]), "=f"(d[44]), "=f"(d[45]), "=f"(d[46]), "=f"(d[47]), "=f"(d[48]), "=f"(d[49]), "=f"(d[50]), "=f"(d[51]), "=f"(d[52]), "=f"(d[53]), "=f"(d[54]), "=f"(d[55]), "=f"(d[56]), "=f"(d[57]), "=f"(d[58]), "=f"(d[59]), "=f"(d[60]), "=f"(d[61]), "=f"(d[62]), "=f"(d[63])
        : "l"(da), "l"(db), "n"(TA), "n"(TB));
}
template <int TB>
__device__ __forceinline__ void wgmma_rs128(float* d, const uint32_t* a, uint64_t db, uint32_t acc) {
    asm volatile("{\n.reg .pred P;\nsetp.ne.u32 P, %69, 0;\nwgmma.mma_async.sync.aligned.m64n128k16.f32.bf16.bf16 "
        "{%0, %1, %2, %3, %4, %5, %6, %7, %8, %9, %10, %11, %12, %13, %14, %15, %16, %17, %18, %19, %20, %21, %22, %23, %24, %25, %26, %27, %28, %29, %30, %31, %32, %33, %34, %35, %36, %37, %38, %39, %40, %41, %42, %43, %44, %45, %46, %47, %48, %49, %50, %51, %52, %53, %54, %55, %56, %57, %58, %59, %60, %61, %62, %63}, {%64, %65, %66, %67}, %68, P, 1, 1, %70;\n}"
        : "+f"(d[0]), "+f"(d[1]), "+f"(d[2]), "+f"(d[3]), "+f"(d[4]), "+f"(d[5]), "+f"(d[6]), "+f"(d[7]), "+f"(d[8]), "+f"(d[9]), "+f"(d[10]), "+f"(d[11]), "+f"(d[12]), "+f"(d[13]), "+f"(d[14]), "+f"(d[15]), "+f"(d[16]), "+f"(d[17]), "+f"(d[18]), "+f"(d[19]), "+f"(d[20]), "+f"(d[21]), "+f"(d[22]), "+f"(d[23]), "+f"(d[24]), "+f"(d[25]), "+f"(d[26]), "+f"(d[27]), "+f"(d[28]), "+f"(d[29]), "+f"(d[30]), "+f"(d[31]), "+f"(d[32]), "+f"(d[33]), "+f"(d[34]), "+f"(d[35]), "+f"(d[36]), "+f"(d[37]), "+f"(d[38]), "+f"(d[39]), "+f"(d[40]), "+f"(d[41]), "+f"(d[42]), "+f"(d[43]), "+f"(d[44]), "+f"(d[45]), "+f"(d[46]), "+f"(d[47]), "+f"(d[48]), "+f"(d[49]), "+f"(d[50]), "+f"(d[51]), "+f"(d[52]), "+f"(d[53]), "+f"(d[54]), "+f"(d[55]), "+f"(d[56]), "+f"(d[57]), "+f"(d[58]), "+f"(d[59]), "+f"(d[60]), "+f"(d[61]), "+f"(d[62]), "+f"(d[63])
        : "r"(a[0]), "r"(a[1]), "r"(a[2]), "r"(a[3]), "l"(db), "r"(acc), "n"(TB));
}
template <int TB>
__device__ __forceinline__ void wgmma_rs64(float* d, const uint32_t* a, uint64_t db, uint32_t acc) {
    asm volatile("{\n.reg .pred P;\nsetp.ne.u32 P, %37, 0;\nwgmma.mma_async.sync.aligned.m64n64k16.f32.bf16.bf16 "
        "{%0, %1, %2, %3, %4, %5, %6, %7, %8, %9, %10, %11, %12, %13, %14, %15, %16, %17, %18, %19, %20, %21, %22, %23, %24, %25, %26, %27, %28, %29, %30, %31}, {%32, %33, %34, %35}, %36, P, 1, 1, %38;\n}"
        : "+f"(d[0]), "+f"(d[1]), "+f"(d[2]), "+f"(d[3]), "+f"(d[4]), "+f"(d[5]), "+f"(d[6]), "+f"(d[7]), "+f"(d[8]), "+f"(d[9]), "+f"(d[10]), "+f"(d[11]), "+f"(d[12]), "+f"(d[13]), "+f"(d[14]), "+f"(d[15]), "+f"(d[16]), "+f"(d[17]), "+f"(d[18]), "+f"(d[19]), "+f"(d[20]), "+f"(d[21]), "+f"(d[22]), "+f"(d[23]), "+f"(d[24]), "+f"(d[25]), "+f"(d[26]), "+f"(d[27]), "+f"(d[28]), "+f"(d[29]), "+f"(d[30]), "+f"(d[31])
        : "r"(a[0]), "r"(a[1]), "r"(a[2]), "r"(a[3]), "l"(db), "r"(acc), "n"(TB));
}
template <int TB>
__device__ __forceinline__ void wgmma_rs16(float* d, const uint32_t* a, uint64_t db, uint32_t acc) {
    asm volatile("{\n.reg .pred P;\nsetp.ne.u32 P, %13, 0;\nwgmma.mma_async.sync.aligned.m64n16k16.f32.bf16.bf16 "
        "{%0, %1, %2, %3, %4, %5, %6, %7}, {%8, %9, %10, %11}, %12, P, 1, 1, %14;\n}"
        : "+f"(d[0]), "+f"(d[1]), "+f"(d[2]), "+f"(d[3]), "+f"(d[4]), "+f"(d[5]), "+f"(d[6]), "+f"(d[7])
        : "r"(a[0]), "r"(a[1]), "r"(a[2]), "r"(a[3]), "l"(db), "r"(acc), "n"(TB));
}

__device__ __forceinline__ uint32_t delay_loop(int n, uint32_t x0) {
    uint32_t z;
    asm volatile("{\n.reg .pred P;\n.reg .u32 c, x;\nmov.u32 c, %1;\nmov.u32 x, %2;\nDL: mad.lo.u32 x, x, 1664525, 1013904223;\nadd.u32 c, c, -1;\nsetp.gt.s32 P, c, 0;\n@P bra DL;\n"
                 "setp.eq.u32 P, x, 0x7fffffff;\nselp.u32 %0, 16, 0, P;\n}" : "=r"(z) : "r"(n), "r"(x0) : "memory");
    return z;
}
__device__ __forceinline__ uint32_t gtime() { uint32_t t; asm volatile("mov.u32 %0, %%globaltimer_lo;" : "=r"(t)); return t; }
__device__ __forceinline__ void wait_time(uint32_t t, uint32_t sb) { while ((int32_t)(gtime() - t) < (int32_t)delay_loop(2, sb)) {} }
__device__ __forceinline__ uint32_t tpc_gpc(uint32_t t) { return t < 32 ? t & 7 : t < 60 ? (t - 32) % 7 + 1 : (t - 54) & 7; }
__device__ __forceinline__ uint32_t latest_stamp(const uint32_t* p, uint32_t seq, uint32_t ref, int backoff, uint32_t sb) {
    for (int n = 0;; n++) {
        uint32_t bad = 0; int32_t m = INT32_MIN;
#pragma unroll
        for (int i = 0; i < 3; i++) { const uint32_t v = ld_relaxed1(p + i * 256); bad |= (v ^ seq) & 31u; m = max(m, (int32_t)(v - (ref << 5)) >> 5); }
        if (__all_sync(0xffffffffu, bad == 0)) return ref + __reduce_max_sync(0xffffffffu, m);
        wait_time(gtime() + backoff, sb);
        if (n > SPIN_LIMIT) spin_fault();
    }
}
__device__ __forceinline__ void release_at(uint32_t t, uint32_t sb, uint32_t bar, int lane) {
    wait_time(t, sb);
    if (lane == 0) mbar_arrive(sb + bar);
}
__host__ __device__ constexpr int frag_word(int u, int f) { return (u == 0 ? 0 : u < 3 ? 3 * u - 1 : u == 3 ? 14 : 3 * u - 4) + f; }
__host__ __device__ constexpr int word_col(int e) { return ((0x32FED987CBA65410ull >> (4 * e)) & 14) * 64 + ((0x32FED987CBA65410ull >> (4 * e)) & 1) * 8; }

constexpr uint32_t CLEAR_LO = 0xFE000000u, CLEAR_HI = 0x5A7FEFEFu;
__device__ __forceinline__ void clear_slot(const Params& P, int slot, int cta, int lane) {
    const int i = cta * 2 + (lane >> 3), x = i & 63;
    if (lane < 16) st_relaxed4(P.gm + slot * M_SLOT + (x >> 1) * 1024 + (x & 1) * 256 + (i >> 7) * 512 + ((i >> 6) & 1) * 128 + (lane & 7) * 16, CLEAR_LO, CLEAR_HI, CLEAR_LO, CLEAR_HI);
    st_relaxed4(g_f + slot * F_SLOT + cta * 512 + lane * 16, 0, 0, 0, 0);
}
__device__ __forceinline__ void mem0_max(const Params& P, uint32_t sb, int tid) {
    uint32_t m = 0;
#pragma unroll
    for (int i = 0; i < 4; i++) {
        const uint4 x = __ldg((const uint4*)P.mem0 + i * 256 + tid);
        m = __vmaxu2(__vmaxu2(__vmaxu2(x.x & 0x7fff7fffu, x.y & 0x7fff7fffu), __vmaxu2(x.z & 0x7fff7fffu, x.w & 0x7fff7fffu)), m);
    }
    sts32(sb + S_COEF + (tid >> 5) * 4, __reduce_max_sync(0xffffffffu, max(m >> 16, m & 0xffffu)));
    bar_arrive(7, 288);
}
__device__ __forceinline__ uint32_t pack_mem0(const Params& P, uint32_t sb, int cta, int lane) {
    bar_sync(7, 288);
    const uint32_t e = __reduce_max_sync(0xffffffffu, lds32(sb + S_COEF + (lane & 7) * 4)) >> 7;
    if (e < 64 || e > 192) return 0x3F803F80u;
    const int i = cta * 2 + (lane >> 4), u = (i >> 5), x = i & 63, L = (i & 3) * 8 + ((lane & 15) >> 1);
    uint64_t w = 32;
#pragma unroll
    for (int f = 0; f < 3; f++) if (f < 2 || u % 3) {
        const float v = __bfloat162float(P.mem0[(L >> 2) * 1024 + word_col(frag_word(u, f)) + ((i >> 2) & 7) * 16 + (L & 3) * 2 + (lane & 1)]);
        w += (uint64_t)(int64_t)__float2int_rn(v * __uint_as_float((271 - e) << 23)) << (45 - 19 * f);
    }
    st_relaxed2(P.gm + 7 * M_SLOT + (x >> 1) * 1024 + (x & 1) * 256 + (i >> 7) * 512 + ((i >> 6) & 1) * 128 + (lane & 15) * 8, (uint32_t)w, (uint32_t)(w >> 32));
    return (e - 30) * 0x00800080u;
}
__device__ __forceinline__ void pacer(const Params& P, const uint32_t sb, const int lane) {
    constexpr uint32_t base = 2;
    int cta = lds32(sb + S_CTA);
#pragma unroll 1
    for (int i = 0; i < 8; i++) clear_slot(P, i, cta, lane);
    __syncwarp();
    if (lane == 0) { uint32_t smid; asm("mov.u32 %0, %%smid;" : "=r"(smid)); st_relaxed1(g_hint + 6144 + cta, smid >> 1); }
    sts32(sb + S_EPOCH + 4, pack_mem0(P, sb, cta, lane));
    SSTAMP(0, lane == 0)
    fence_release();
    __syncwarp();
    float rate = 0.58f;
    uint32_t c0 = 0;
#pragma unroll 1
    for (int s = -1; s < 63; s++) {
        cta = lds32(sb + S_CTA);
        const int pair = cta >> 1;
        const uint32_t ahead = s > 0 ? (uint32_t)(rate * (float)(pair >= 32 ? P.dc - P.dv : P.dc)) : 0;
        mbar_wait(sb + B_GO, s & 1);
        SSTAMP(10, lane == 0 && s == 0)
        const uint32_t t0 = gtime();
        if (lane < 4) st_relaxed1(g_hint + ((s & 1) * 4 + lane) * 768 + (cta >> 5) * 256 + (cta & 31), (t0 + ahead + (lds32(sb + S_REDO) == s ? P.extra : 0)) << 5 | ((base + s) & 31u));
        wait_time(t0 + (s < 0 ? 2000 : s == 0 && pair >= 16 ? P.ds0 : P.ds), sb);
        const uint32_t t = latest_stamp(g_hint + ((s & 1) * 4 + (pair & 3)) * 768 + lane, base + s, t0, P.back, sb);
        if (s < 0) {
            SSTAMP(2, lane == 0)
            fence_acquire();
            const uint32_t g = tpc_gpc(ld_relaxed1(g_hint + 6144 + (lane & 15) * 2));
            const uint32_t key = (__popc(__match_any_sync(0xffffffffu, g)) > 4 ? 0 : g + 1) * 16 + (lane & 15);
            const uint32_t tail = (pair & 48) + __popc(__ballot_sync(0xffffffffu, key < __shfl_sync(0xffffffffu, key, pair & 15))) / 2;
            mbar_wait(sb + B_INIT, 0);
            SSTAMP(4, lane == 0)
            sts32(sb + S_TAIL, tail);
            if (lane < 8) sts32(sb + S_SC + lane * 4, lds32(sb + S_EPOCH + 4));
            __syncwarp();
        }
        release_at(t + P.da, sb, B_RELA, lane);
        SSTAMP(11, lane == 0 && s == 0)
        release_at(t + P.db, sb, B_RELB, lane);
        {
            const uint32_t c1 = clock(), g1 = gtime();
            if (s > 1) rate += P.alpha * (__fdividef((float)(g1 - lds32(sb + S_EPOCH + 4)), (float)(c1 - c0)) - rate);
            __syncwarp();
            c0 = c1; sts32(sb + S_EPOCH + 4, g1);
        }
        if (s == 61) {
            sts32(sb + S_COEF, ITEM(ITEM_OFF(lds32(sb + S_TAIL)) + NPRE + 1) + (uint32_t)(uintptr_t)P.out);
            if (lane < M_CQ) map_prefetch(&P.tm[lane]);
        }
    }
}
__device__ __forceinline__ uint32_t xor_or(uint32_t a, uint32_t b, uint32_t t) { uint32_t d; asm("lop3.b32 %0, %1, %2, %3, 0x7E;" : "=r"(d) : "r"(a), "r"(b), "r"(t)); return d; }
__device__ __forceinline__ bool tags_ok(uint32_t bad) { return __all_sync(0xffffffffu, (bad & 1) == 0); }
#define RETRY(k)
#define RETRY_STAT(a, b)
#define UNIT_STAT(u0)
#define SFENCE() asm volatile("pmevent 1;" ::: "memory")
#define PF1 10
static_assert(NS == 24, "fragment residency");
__host__ __device__ constexpr bool in_smem(int n) { return n < 4 || n == 12 || n == 13; }
__host__ __device__ constexpr int unit_pos(int n) { return n < 4 ? n : n < 12 ? n - 4 : n < 14 ? n - 8 : n - 6; }

__host__ __device__ constexpr int fill_unit(int q) { return q < 4 ? q : q < 6 ? q + 8 : q < 14 ? q - 2 : q; }
__host__ __device__ constexpr int frag_off(int q) { return (q >> 2) * 16384 + ((q >> 1) & 1) * 8192 + (q & 1) * 512; }

constexpr uint32_t QBITS = 0x4B002000u;
constexpr uint64_t W_BIAS = ((uint64_t)QBITS << 45) + ((uint64_t)QBITS << 26) + (uint32_t)(QBITS << 7), W_CLEAR = 0 - 32 * W_BIAS;
static_assert(W_CLEAR == ((uint64_t)CLEAR_HI << 32 | CLEAR_LO), "clear value");
__host__ __device__ constexpr int unit_off(int u) { return (u & 1) * 16384 + (u >> 2) * 512 + ((u >> 1) & 1) * 128; }
__device__ __forceinline__ void red_add64(const uint8_t* p, uint64_t v) { asm volatile("red.relaxed.gpu.global.add.u64 [%0], %1;" ::"l"(p), "l"(v) : "memory"); }
template <int NF>
__device__ __forceinline__ uint64_t encode(const float* x, float S, uint32_t two26, uint32_t& bad) {
    uint32_t b[3];
#pragma unroll
    for (int i = 0; i < 3; i++) b[i] = i < NF ? __float_as_uint(fmaf(x[i], S, 8396800.f)) : QBITS;
    bad = xor_or(b[0], b[1], 0x4B000000u) | (NF == 3 ? b[2] ^ 0x4B000000u : 0);
    uint64_t w;
    asm("{\n.reg .b64 t;\nmov.b64 t, {%2, %3};\nmad.wide.u32 %0, %1, %4, t;\n}" : "=l"(w) : "r"(b[1]), "r"(b[2] << 7), "r"(b[0] << 13), "r"(two26));
    return w;
}
template <int NF>
__device__ __forceinline__ void emit(uint64_t* w, const float (*x)[3], const float* S, uint32_t two26, uint32_t lim, const uint8_t* p) {
    uint32_t bad[2];
    w[0] = encode<NF>(x[0], S[0], two26, bad[0]); w[1] = encode<NF>(x[1], S[1], two26, bad[1]);
    const bool ok = (bad[0] | bad[1]) < lim;
    w[0] |= ok; w[1] |= ok;
    red_add64(p, w[0]); red_add64(p + 1024, w[1]);
}
template <int NF>
__device__ __forceinline__ void repair(const uint64_t* w, const float (*x)[3], const float* S, const uint8_t* p, const uint8_t* pf) {
    if (!(w[0] & 1)) {
#pragma unroll
        for (int j = 0; j < 2; j++) {
            const float T = S[j] * 8192.f;
            asm volatile("red.relaxed.gpu.global.add.v4.f32 [%0], {%1,%2,%3,%4};" ::"l"(pf + j * 512), "f"(x[j][0] * T), "f"(x[j][1] * T), "f"(NF == 3 ? x[j][2] * T : 0.f), "f"(0.f) : "memory");
        }
        fence_release();
#pragma unroll
        for (int j = 0; j < 2; j++) {
            asm volatile("red.relaxed.gpu.global.or.b64 [%0], 64;" ::"l"(p + j * 1024) : "memory");
            red_add64(p + j * 1024, W_BIAS + 1 - w[j]);
        }
    }
    __syncwarp();
}
__device__ __forceinline__ void ld_words(uint32_t* v, const uint8_t* p) {
    asm volatile("{\n.reg .b64 a, b;\nld.relaxed.gpu.global.L1::no_allocate.v2.b64 {a, b}, [%4];\nmov.b64 {%0,%1}, a;\nmov.b64 {%2,%3}, b;\n}" : "=r"(v[0]), "=r"(v[1]), "=r"(v[2]), "=r"(v[3]) : "l"(p) : "memory");
}
__device__ __forceinline__ float field(const uint32_t* w, int f) { return __int2float_rn((int)(f == 0 ? w[1] : f == 1 ? __funnelshift_l(w[0], w[1], 19) : w[0] << 6)); }
template <int U>
__device__ __forceinline__ void decode(uint32_t* b, const uint32_t* v) {
#pragma unroll
    for (int f = 0; f < (U % 3 ? 3 : 2); f++) b[frag_word(U, f)] = pack2(field(v, f), field(v + 2, f));
}
__device__ __forceinline__ uint32_t status(const uint32_t (*v)[4], uint32_t c32) { return xor_or(v[0][0], v[0][2], c32) | xor_or(v[1][0], v[1][2], c32) | xor_or(v[2][0], v[2][2], c32); }
__device__ __forceinline__ void gather_slow(const Params& P, uint32_t* b, const uint8_t* pm, int s, int warp, uint32_t ln, uint32_t u2) {
    if (s == 0 && u2 == 0x3F803F80u) {
#pragma unroll
        for (int i = 0; i < 16; i++) b[i] = __ldg((const uint32_t*)(P.mem0 + (ln >> 2) * 1024 + word_col(i) + warp * 16 + (ln & 3) * 2));
        return;
    }
    uint32_t v[6][4], st;
    for (int n = 0;; n++) {
#pragma unroll
        for (int u = 0; u < 6; u++) ld_words(v[u], pm + unit_off(u));
        st = status(v, 32) | status(v + 3, 32);
        if (!__any_sync(0xffffffffu, st & 32)) break;
        __nanosleep(200);
        if (n > SPIN_LIMIT) spin_fault();
    }
    const bool side = __any_sync(0xffffffffu, st & 64);
    if (side) fence_acquire();
    const uint8_t* pf = g_f + ((s + 7) & 7) * F_SLOT + warp * 1024 + ln * 32;
#pragma unroll
    for (int u = 0; u < 6; u++) {
        float x[2][4] = {};
#pragma unroll
        for (int k = 0; k < 2; k++)
            asm volatile("{\n.reg .pred P;\nsetp.ne.u32 P, %5, 0;\n@P ld.relaxed.gpu.global.v4.f32 {%0,%1,%2,%3}, [%4];\n}"
                         : "+f"(x[k][0]), "+f"(x[k][1]), "+f"(x[k][2]), "+f"(x[k][3]) : "l"(pf + u * 8192 + k * 16), "r"((uint32_t)side) : "memory");
#pragma unroll
        for (int f = 0; f < (u % 3 ? 3 : 2); f++) b[frag_word(u, f)] = pack2(field(v[u], f) + x[0][f], field(v[u] + 2, f) + x[1][f]);
    }
}
__device__ __forceinline__ uint32_t max_abs2(uint32_t a, uint32_t b) { uint32_t d; asm("max.NaN.xorsign.abs.bf16x2 %0, %1, %2;" : "=r"(d) : "r"(a), "r"(b)); return d; }
__device__ __forceinline__ uint32_t max6(const uint32_t* b) {
    const uint32_t m = max_abs2(max_abs2(max_abs2(b[0], b[1]), max_abs2(b[2], b[3])), max_abs2(b[4], b[5]));
    return max(m & 0x7fff0000u, (m << 16) & 0x7fff0000u);
}

template <bool TR>
__device__ __forceinline__ void put_partials(uint32_t a, const float* x, const float* y) {
    if (TR) stsm4t(a, pack2(x[0], x[1]), pack2(x[2], x[3]), pack2(y[0], y[1]), pack2(y[2], y[3]));
    else stsm4(a, pack2(x[0], x[1]), pack2(x[2], x[3]), pack2(y[0], y[1]), pack2(y[2], y[3]));
}
__device__ __forceinline__ void reduce_load(uint32_t (*x)[4], uint32_t a) { ldsm4t(x[0], a); ldsm4t(x[1], a + 512); }
__device__ __forceinline__ uint32_t reduce8(const uint32_t (*x)[4], uint32_t l8, uint32_t u2) {
    uint32_t p[2];
#pragma unroll
    for (int i = 0; i < 2; i++) {
        float d[4] = {};
        mma16816(d, x[i][0], x[i][1], x[i][2], x[i][3], (l8 & 32) ? 0u : u2, (l8 & 32) ? u2 : 0u);
        p[i] = pack2((l8 & 8) ? d[2] : d[0], (l8 & 8) ? d[3] : d[1]);
    }
    return (l8 & 16) ? p[1] : p[0];
}
__device__ __forceinline__ void score_half(float (*a)[4], const uint32_t (*qa)[4], const uint32_t (*kf)[4]) {
#pragma unroll
    for (int w = 0; w < 2; w++) {
        mma16816(a[w], qa[w][0], qa[w][1], qa[w][2], qa[w][3], kf[w][0], kf[w][1]);
        mma16816(a[2 + w], qa[w][0], qa[w][1], qa[w][2], qa[w][3], kf[w][2], kf[w][3]);
    }
}
__device__ __forceinline__ void score_sum(float* S, const float (*a)[4]) {
    S[0] = (a[0][0] + a[1][0]) + (a[2][2] + a[3][2]);
    S[1] = (a[0][1] + a[1][1]) + (a[2][3] + a[3][3]);
}
__device__ __forceinline__ float quad_max(float m) {
    m = fmaxf(m, __shfl_xor_sync(0xffffffffu, m, 1));
    return fmaxf(m, __shfl_xor_sync(0xffffffffu, m, 2));
}

#define ISTAMP(i)
__device__ __forceinline__ float next_scale(uint32_t sb, int slot, int warp, uint32_t u2) {
    uint32_t x[2][4];
    lds128(x[0], sb + S_MX + slot * 32); lds128(x[1], sb + S_MX + slot * 32 + 16);
    const uint32_t mx = max(max(max(x[0][0], x[0][1]), max(x[0][2], x[0][3])), max(max(x[1][0], x[1][1]), max(x[1][2], x[1][3])));
    const float top = fminf(fmaxf(__uint_as_float(mx) * bf_hi(u2), 0x1p-40f), 0x1p40f) * (1.f / (12288.f * 8192.f));
    const uint32_t un = pack2(top, top);
    sts32(sb + S_SC + warp * 4, un);
    return rcp(bf_hi(un) * 8192.f);
}
#define NEARLY 1
#define U3POS 1
#define VPOS 1
#define ROT 0
#define BPOS 1
#define ONLINE 0
#define NBAR 1
#define ORD3 0
#define F2 1
#define EARLY 0
#define TK 0
#define RPOS 1
#define AF 0
#define AFENCE(i) if ((AF >> (i)) & 1) SFENCE();
#define FPOS 99
#define PACE 1
#define PF2 12
__host__ __device__ constexpr int w2_t(int i) { return i < 16 ? i & 1 : 2; }
__host__ __device__ constexpr int w2_k(int i) { return i < 16 ? i >> 1 : i - 16; }
template <typename G>
__device__ __forceinline__ void load_weights(uint32_t (*wr)[4], const uint32_t sb, const int warp, const int lane, G stores_read) {
    const uint32_t frag = sb + warp * 1024 + (lane >> 4) * 8192 + (lane & 7) * 128 + ((((lane >> 3) & 1) ^ (lane & 7)) << 4);
    const uint32_t rel = mapa(sb + B_EMPTY, cluster_rank() ^ (lane & 1));
#define RELEASE(st) { fence_async_smem(); __syncwarp(); if (lane < 2) mbar_arrive_cluster(rel + (st) * 8); }
    mbar_wait(sb + B_FULL, 0); mbar_wait(sb + B_FULL + 8, 0);
    RELEASE(0) RELEASE(1)
#pragma unroll
    for (int st = 2; st < 4; st++) {
        mbar_wait(sb + B_FULL + st * 8, 0);
        ISTAMP(st - 2)
#pragma unroll
        for (int f = 0; f < 12; f++) ldsm4t(wr[st * 12 - 24 + f], (frag ^ ((f & 3) << 5)) + st * STAGE + (f >> 2) * 16384);
        RELEASE(st)
    }
#pragma unroll 2
    for (int u = 0; u < 6; u++) {
        uint32_t x[4][4];
#pragma unroll
        for (int i = 0; i < 4; i++) lds128(x[i], (frag ^ (i << 5)) + u * 16384);
        __syncwarp();
#pragma unroll
        for (int i = 0; i < 4; i++) sts128(sb + warp * 1024 + lane * 16 + u * 16384 + frag_off(i), x[i]);
    }
    stores_read();
    mbar_wait(sb + B_FULL, 1); mbar_wait(sb + B_FULL + 8, 1);
    RELEASE(0) RELEASE(1)
#pragma unroll
    for (int st = 2; st < 4; st++) {
        mbar_wait(sb + B_FULL + st * 8, 1);
#pragma unroll
        for (int f = 0; f < (st == 2 ? 12 : 4); f++) ldsm4t(wr[st * 12 + f], (frag ^ ((f & 3) << 5)) + st * STAGE + (f >> 2) * 16384);
        RELEASE(st)
    }
    ISTAMP(2)
    bar_sync(1, 256);
    if (warp == 7 && lane < 3) mbar_arrive_cluster(mapa(sb + B_INIT, (cluster_rank() & 1) + lane * 2));
}
template <int ROLE>
__device__ __forceinline__ void chain_role(const Params& P, const uint32_t (*wr)[4], const uint32_t sb, const int h, const int warp, const int lane) {
    constexpr int NU = ROLE == 0 ? 2 : 3;
    const bool att = ROLE == 0 && warp < 4;
    uint32_t l8 = opq(sb + lane * 8, lane);
#define PERSIST() { mbar_wait(sb + B_KVGO, slot ^ 1); const uint32_t pa_ = ((l8 - sb) >> 1) + (sb + S_QX + warp * 128); sts32(pa_, r0); sts32(pa_ + 1024, r1); \
                    fence_async_smem(); __syncwarp(); if (l8 == sb) mbar_arrive(sb + B_PERS); }
    if (ROLE) sts32(sb + S_SX + warp * 128 + lane * 4, warp >= 2 ? 0 : (lane & 1) ? CLEAR_HI : CLEAR_LO);
    const uint32_t rdelta = __shfl_sync(0xffffffffu, mapa(sb, (cluster_rank() + (ROLE == 1 ? 4 : 2)) % 6) - sb, 0);
    const uint32_t vdelta = ROLE ? 0 : __shfl_sync(0xffffffffu, mapa(sb, (cluster_rank() + 4) % 6) - sb, 0);
    ISTAMP(3)
    __syncwarp();
#define GATHER_OFF(s) ((((s) + 7) & 7) * M_SLOT + warp * 2048 + (l8 & 56) * 2 + (l8 & 64) * 4 + (l8 & 128) * 8)
    uint32_t mo = GATHER_OFF(0);
    if (ROT) mbar_wait(sb + B_RELA, 0);
    for (int s = 0; s < (ROLE == 0 ? 63 : 64);) {
        const int slot = s & 1;
        l8 += s & P.zero;
        const uint32_t w1a = l8 * 2 + (S_W1 + warp * 1024 - sb);
        PROF(9)
        uint32_t u2, r0, r1, pld, pub, pbar, x[2][4];
        {
#define pm (P.gm + mo)
            uint32_t as[24][4], b[16], v[6][4];
            float acc[8][4];
#define W1LD(n) _Pragma("unroll") for (int i_ = 0; i_ < 4; i_++) ldsm4t(as[unit_pos(n) * 4 + i_], w1a + frag_off(unit_pos(n) * 4 + i_));
#define W1LD2(n, p) { const uint32_t wa_ = w1a + (as[unit_pos(p) * 4][0] & as[unit_pos(p) * 4 + 1][0] & as[unit_pos(p) * 4 + 2][0] & as[unit_pos(p) * 4 + 3][0] & P.zero); \
                      _Pragma("unroll") for (int i_ = 0; i_ < 4; i_++) ldsm4t(as[unit_pos(n) * 4 + i_], wa_ + frag_off(unit_pos(n) * 4 + i_)); }
#define W1MMA(n) _Pragma("unroll") for (int i_ = 0; i_ < 4; i_++) { const uint32_t* a_ = in_smem(n) ? as[unit_pos(n) * 4 + i_] : wr[unit_pos(n) * 4 + i_]; \
                                                                   mma16816(acc[((n) & 1) * 4 + i_], a_[0], a_[1], a_[2], a_[3], b[(n) & 14], b[(n) | 1]); }
#pragma unroll
            for (int T = 0; T < 8; T++) { acc[T][0] = acc[T][1] = acc[T][2] = acc[T][3] = 0.f; }
            if (!ROT) mbar_wait(sb + B_RELA, slot);
            PROF(12)
#pragma unroll
            for (int u = 0; u < 3; u++) ld_words(v[u], pm + unit_off(u));
            __syncwarp();
#pragma unroll
            for (int i = 0; i < PF1; i++) ldsm4t(as[i], w1a + frag_off(i));
            __syncwarp();
            mo += mbar_try(sb + B_RELB, slot) & P.zero;
            PROF(13)
#pragma unroll
            for (int u = 3; u < 6; u++) ld_words(v[u], pm + unit_off(u));
            uint32_t st = status(v, ((uint32_t)((uintptr_t)pm >> 32) & P.zero) + 32);
            pin<1>(&st);
            SFENCE();
            UNIT_STAT(0)
            PROF(0)
            decode<0>(b, v[0]); decode<1>(b, v[1]); decode<2>(b, v[2]);
#pragma unroll
            for (int i = PF1; i < 12; i++) ldsm4t(as[i], w1a + frag_off(i));
            W1MMA(0) W1MMA(1) W1MMA(2)
            if (TK & 1) W1LD2(3, 2) else { W1LD(3) }
            SFENCE();
            if (TK & 8) { W1MMA(5) W1MMA(4) W1MMA(3) W1MMA(6) } else { W1MMA(5) W1MMA(4) W1MMA(6) W1MMA(3) }
            if (U3POS == 0) W1MMA(7)
            if (TK & 2) W1LD2(12, 3) else { W1LD(12) }
            uint32_t mx = max6(b);
            pin<1>(&mx);
            SFENCE();
            PROF(10)
            if (U3POS == 1) W1MMA(7)
            const uint32_t mxa = sb + S_MX + slot * 32 + warp * 4;
            sts32(mxa, __reduce_max_sync(0xffffffffu, mx));
            UNIT_STAT(3)
            st |= status(v + 3, 32);
            const bool redo = __any_sync(0xffffffffu, st & 96);
            const bool kvok = ROLE || mbar_test(sb + B_KVFULL + slot * 8, (s >> 1) & 1);
            decode<4>(b, v[4]); decode<5>(b, v[5]); decode<3>(b, v[3]);
            u2 = lds32(sb + S_SC + warp * 4);
            W1MMA(8) W1MMA(10) if (ORD3) { W1MMA(14) W1MMA(12) } else { W1MMA(12) W1MMA(14) }
            if (TK & 4) W1LD2(13, 12) else { W1LD(13) }
            if (__builtin_expect(redo || !kvok, 0)) {
                if (redo) {
                    RETRY(3)
                    sts32(sb + S_REDO, s);
                    gather_slow(P, b, P.gm + GATHER_OFF(s), s, warp, (l8 - sb) >> 3, u2);
                    sts32(mxa, __reduce_max_sync(0xffffffffu, max6(b)));
#pragma unroll
                    for (int T = 0; T < 8; T++) { acc[T][0] = acc[T][1] = acc[T][2] = acc[T][3] = 0.f; }
#pragma unroll
                    for (int n = 0; n < 15; n += n < 8 ? 1 : 2) {
                        if (in_smem(n)) { W1LD(n) }
                        W1MMA(n)
                    }
                    W1LD(13)
                }
                if (ROLE == 0) mbar_wait(sb + B_KVFULL + slot * 8, (s >> 1) & 1);
            }
#undef pm
            SSTAMP(7, threadIdx.x == 0 && s == 0)
            PROF(14)
            const uint32_t pst = (l8 - sb) * 16 + ((warp * 16) ^ ((l8 * 2) & 112)) + (sb + S_P1);
            put_partials<ROLE == 2>(pst, acc[0], acc[1]); put_partials<ROLE == 2>(pst + 4096, acc[2], acc[3]);
            W1MMA(9)
            SFENCE();
            pld = (l8 & 64) * 4 + (l8 & 128) + (l8 & 56) * 2 + (sb + S_P1 + warp * 1024);
            const uint32_t rd = s == 63 ? 0 : rdelta;
            pub = ((l8 - sb) >> 1) + (ROLE ? sb + rd + (ROLE == 1 ? S_KL : S_VL) + warp * 128 : sb + S_QX + (warp & 4) * 128 + (warp & 1) * 256 + (warp & 2) * 64);
            pbar = sb + rd + (ROLE == 1 && s != 63 ? B_K : B_V);
#define PUBLISH0() { r0 = reduce8(x, l8, u2); if (ROLE) st_async1(pub, r0, pbar); else sts32(pub, r0); }
            if (RPOS == 0) { bar_sync(1, 256); reduce_load(x, pld); SFENCE(); }
            W1MMA(11)
            if (RPOS == 1) { bar_sync(1, 256); reduce_load(x, pld); }
            if (RPOS != 2 || F2) SFENCE();
            W1MMA(15)
            if (RPOS == 0) PUBLISH0()
            if (RPOS == 2) { bar_sync(1, 256); reduce_load(x, pld); }
            if (RPOS != 1 || F2) SFENCE();
            W1MMA(13)
            if (RPOS == 1) PUBLISH0()
            put_partials<ROLE == 2>(pst + 8192, acc[4], acc[5]); put_partials<ROLE == 2>(pst + 12288, acc[6], acc[7]);
            if (RPOS == 2) PUBLISH0()
        }
        SSTAMP(8, threadIdx.x == 0 && s == 0)
        PROF(1)
        if (ROLE) {
            bar_sync(1, 256);
            reduce_load(x, pld + 8192);
            r1 = reduce8(x, l8, u2);
            st_async1(pub + 1024, r1, pbar);
            if (s == 63) {
                PERSIST()
                mbar_wait(sb + B_V, 0);
                break;
            }
            PROF(2)
        }
        uint32_t ln, w2a, ro;
#define W2ADDR(late) { l8 += pub & P.zero; ln = (l8 - sb) >> 3; \
        w2a = sb + S_W2 + (ROLE ? (warp >> 2) * 16384 : late * 32768) + ((((ln & 7) + (ln >> 4) * 8) * 128 + ((((ln >> 3) & 1) ^ (ln & 7)) << 4)) ^ ((warp & 3) << 5)); \
        ro = (s & 7) * M_SLOT + (ROLE ? warp * 2048 + unit_off(ROLE) : (warp & 3) * 2048 + late * unit_off(3)) + (ln & 2) * 128 + (ln & 1) * 64 + (ln >> 2) * 8; }
        constexpr int RO2 = ROLE ? unit_off(ROLE + 3) - unit_off(ROLE) : 8192;
        float Sj[2];
        uint32_t w[24][4], ob[4][4];
        float S;
#define W2LD(i) ldsm4t(w[i], w2a + w2_t(i) * (ROLE ? 32768 : 16384) + (w2_k(i) & 1) * 8192 + (w2_k(i) >> 1) * 2048)
#define W2MMA(d, i) mma16816(d, w[i][0], w[i][1], w[i][2], w[i][3], ob[w2_k(i) >> 1][(w2_k(i) & 1) * 2], ob[w2_k(i) >> 1][(w2_k(i) & 1) * 2 + 1])
#define LEADER(wp) (l8 == sb + ((wp) - warp) * 256)
        if (att) {
            const float cs = 0.08838834764831845f * 1.4426950408889634f;
            uint32_t qa[4][4], kf[4][4], vf[4][4], vv[4];
            float T[5][2], sa[4][4] = {};
            const uint32_t l16 = l8 * 2 - sb;
            const uint32_t kaddr = (l8 & 56) * 16 + (((l8 >> 2) ^ (l8 * 2)) & 48) + ((l8 * 2) & 64) + (sb + S_KV + warp * 1024 + slot * 16384);
            bar_sync(1, 256);
            reduce_load(x, pld + 8192);
            __syncwarp();
#pragma unroll
            for (int i = 0; i < 2; i++) { ldsm4(qa[i], l16 + S_QX + i * 512); ldsm4(kf[i], kaddr ^ (i * 64)); }
            AFENCE(0)
            sts32(pub + 1024, reduce8(x, l8, u2));
            __syncwarp();
#pragma unroll
            for (int i = 2; i < 4; i++) ldsm4(kf[i], (kaddr ^ ((i & 1) * 64)) + 4096);
            score_half(sa, qa, kf);
            bar_sync(2, 256);
            PROF(2)
#pragma unroll
            for (int i = 2; i < 4; i++) ldsm4(qa[i], l16 + S_QX + i * 512);
            float sm[4][4] = {};
            score_half(sa, qa + 2, kf + 2);
            score_sum(T[0], sa);
            sts64(l8 + S_SX + warp * 256, __float_as_uint(T[0][0]), __float_as_uint(T[0][1]));
            PROF(4)
            if (BPOS == 0) bar_sync(4, 128);
            mbar_wait(sb + B_K, slot);
            PROF(11)
#pragma unroll
            for (int i = 0; i < 4; i++) ldsm4(kf[i], l16 + S_KL + i * 512);
            if (BPOS == 1) bar_sync(4, 128); else __syncwarp();
#pragma unroll
            for (int n = 0; n < 4; n++) lds64f(T[n], l8 + S_SX + n * 256);
            score_half(sm, qa, kf);
            score_half(sm, qa + 2, kf + 2);
            const uint32_t vaddr = (l8 & 56) * 16 + (l8 & 128) * 8 + (((warp & 1) * 64 + ((l8 >> 2) & 16)) ^ ((l8 * 2) & 112)) + (sb + S_KV + 8192 + (warp >> 1) * 4096 + slot * 16384);
            float mx = fmaxf(fmaxf(fmaxf(T[0][0], T[0][1]), fmaxf(T[1][0], T[1][1])), fmaxf(fmaxf(T[2][0], T[2][1]), fmaxf(T[3][0], T[3][1])));
            score_sum(T[4], sm);
            float m = quad_max(fmaxf(mx, fmaxf(T[4][0], T[4][1])));
            if (VPOS == 0) {
#pragma unroll
                for (int i = 0; i < 4; i++) ldsm4t(vf[i], (vaddr ^ ((i & 1) << 5)) + (i >> 1) * 2048);
            }
            mbar_wait(sb + B_V, slot);
            if (VPOS == 1) {
#pragma unroll
                for (int i = 0; i < 4; i++) ldsm4t(vf[i], (vaddr ^ ((i & 1) << 5)) + (i >> 1) * 2048);
            }
            ldsm4(vv, l16 + S_VL + warp * 512);
            uint32_t pa[5];
            m *= cs;
#pragma unroll
            for (int n = 0; n < 5; n++) { T[n][0] = ex2(fmaf(T[n][0], cs, -m)); T[n][1] = ex2(fmaf(T[n][1], cs, -m)); pa[n] = pack2(T[n][0], T[n][1]); }
            float sum = (((T[0][0] + T[0][1]) + (T[1][0] + T[1][1])) + ((T[2][0] + T[2][1]) + (T[3][0] + T[3][1]))) + (T[4][0] + T[4][1]);
            PROF(3)
            W2ADDR(1)
            const uint32_t lo = sb + S_O + warp * 512 + (ln & 3) * 64 + (ln >> 2) * 8, ls = sb + S_SUM + (ln & 3) * 32 + (ln & 4) * 4 + (ln >> 3) * 4;
            const uint32_t sdelta = warp < 2 ? rdelta : vdelta;
            sum += __shfl_xor_sync(0xffffffffu, sum, 1);
            sum += __shfl_xor_sync(0xffffffffu, sum, 2);
            float O[2][4];
#pragma unroll
            for (int i = 0; i < 2; i++) { O[i][0] = O[i][1] = O[i][2] = O[i][3] = 0.f; }
#pragma unroll
            for (int i = 0; i < 2; i++) {
                mma16816(O[0], vf[2 * i][0], vf[2 * i][1], vf[2 * i][2], vf[2 * i][3], pa[2 * i], pa[2 * i + 1]);
                mma16816(O[1], vf[2 * i + 1][0], vf[2 * i + 1][1], vf[2 * i + 1][2], vf[2 * i + 1][3], pa[2 * i], pa[2 * i + 1]);
            }
            mma1688(O[0], vv[0], vv[1], pa[4]);
            mma1688(O[1], vv[2], vv[3], pa[4]);
            uint32_t o[2][2];
#pragma unroll
            for (int j = 0; j < 2; j++) { o[j][0] = pack2(O[0][j], O[0][2 + j]); o[j][1] = pack2(O[1][j], O[1][2 + j]); }
#pragma unroll
            for (int j = 0; j < 2; j++) st_async2(lo + rdelta + j * 256, o[j][0], o[j][1], sb + rdelta + B_K);
            st_async1(ls + sdelta + (warp & 1) * 128, __float_as_uint(sum), sb + sdelta + B_K);
#pragma unroll
            for (int j = 0; j < 2; j++) st_async2(lo + vdelta + j * 256, o[j][0], o[j][1], sb + vdelta + B_K);
#pragma unroll
            for (int j = 0; j < 2; j++) sts64(lo + j * 256, o[j][0], o[j][1]);
            sts32(ls + warp * 128, __float_as_uint(sum));
            PROF(5)
            bar_sync(3, 256);
            if (LEADER(0)) { mbar_expect(sb + B_K, 2048); mbar_expect(sb + B_V, 2048); mbar_arrive(sb + B_KVGO + slot * 8); }
            S = next_scale(sb, slot, warp, u2);
            if (s == 0) mbar_wait(sb + B_WO, 0);
            pin<1>(&S);
            SFENCE();
#pragma unroll
            for (int j = 0; j < 4; j++) lds128(ob[j], l8 * 2 - sb + S_O + j * 512);
            lds64f(Sj, sb + S_SUM + (l8 & 24));
#pragma unroll
            for (int i = 0; i < PF2; i++) W2LD(i);
        } else {
            if (ROLE == 0) { bar_sync(1, 256); reduce_load(x, pld + 8192); sts32(pub + 1024, reduce8(x, l8, u2)); bar_arrive(2, 256); }
            if (LEADER(7)) { if (s) mbar_arrive(sb + B_GO); if (ROLE) mbar_expect(sb + B_K, 2304); }
            S = next_scale(sb, slot, warp, u2);
            if (s == 0) mbar_wait(sb + B_WO, 0);
            if (ROLE != 0) PERSIST()
            W2ADDR(0)
#pragma unroll
            for (int i = 0; i < PF2; i++) {
                W2LD(i);
                if (ROLE == 0 && (i & PACE) == PACE) w2a += w[i][0] & P.zero;
            }
            ro = opq(ro, ln);
            const uint32_t sa = opq(sb + S_SUM + (l8 & 24), ln), oa = opq(l8 * 2 - sb + S_O, ln);
            if (ROLE == 0) bar_sync(3, 256); else mbar_wait(sb + B_K, slot);
            lds64f(Sj, sa);
#pragma unroll
            for (int j = 0; j < 4; j++) lds128(ob[j], oa + j * 512);
        }
        SSTAMP(9, threadIdx.x == 224 && s == 0)
        SFENCE();
        PROF(6)
        {
            const uint8_t* pr = P.gm + ro;
            float c[4][4];
            uint32_t lim = 0;
#pragma unroll
            for (int i = 0; i < 4; i++) { c[i][0] = c[i][1] = c[i][2] = c[i][3] = 0.f; }
#pragma unroll
            for (int i = 0; i < 16; i++) {
                W2MMA(c[i & (ROLE ? 1 : 3)], i);
                if (i + PF2 < (ROLE ? 16 + NEARLY : 16)) W2LD(i + PF2);
                if (i == 5) {
                    const uint32_t z = __float_as_uint(c[1][0]) & P.zero;
                    Sj[0] = S * rcp(__uint_as_float(__float_as_uint(Sj[0]) | z)); Sj[1] = S * rcp(__uint_as_float(__float_as_uint(Sj[1]) | z));
                }
                if (i == 5) lim = __any_sync(0xffffffffu, fmaxf(fmaxf(fabsf(c[0][0]), fabsf(c[0][2])), fmaxf(fabsf(c[1][0]), fabsf(c[1][2]))) * Sj[0] >= (ROLE ? 24.f : 20.f)) ? 16384 : 0;
                if (i == FPOS) { pin<1>(&lim); pin<2>(Sj); pin_ptr(pr); SFENCE(); }
            }
            if (ROLE == 0) {
#pragma unroll
                for (int i = 0; i < 8; i++) c[i >> 2][i & 3] += c[2 + (i >> 2)][i & 3];
            }
            const float xa[2][3] = {{c[0][0], c[0][2], c[1][0]}, {c[0][1], c[0][3], c[1][1]}};
            uint64_t wa[2], wb[2];
            emit<NU>(wa, xa, Sj, P.two26, lim, pr);
            PROF(7)
            mo = GATHER_OFF(s + 1);
            pin<1>(&mo);
            if (ROLE) {
                SFENCE();
#pragma unroll
                for (int i = 16 + NEARLY; i < 24; i++) { if (i == 16 + NBAR) bar_sync(2, 256); W2LD(i); __syncwarp(); }
                SFENCE();
#pragma unroll
                for (int i = 16; i < 24; i++) W2MMA(c[2 + (i & 1)], i);
#pragma unroll
                for (int i = 0; i < 4; i++) c[2][i] += c[3][i];
            }
            const float y[2][3] = {{ROLE ? c[1][2] : c[1][0], ROLE ? c[2][0] : c[1][2], c[2][2]}, {ROLE ? c[1][3] : c[1][1], ROLE ? c[2][1] : c[1][3], c[2][3]}};
            const bool released = !ROT || mbar_test(sb + B_RELA, slot ^ 1);
            emit<NU>(wb, y, Sj, P.two26, lim, pr + RO2);
            PROF(8)
            if (!__all_sync(0xffffffffu, (wa[0] & wb[0] & 1) && released && s)) {
                if (__builtin_expect(!__all_sync(0xffffffffu, wa[0] & wb[0] & 1), 0)) {
                    RETRY(5)
                    const uint8_t* pf = g_f + (s & 7) * F_SLOT + (ROLE ? ROLE * 8192 + warp * 1024 : (warp & 3) * 1024 + (att ? 24576 : 0)) + (ln & 3) * 128 + (ln >> 2) * 16;
                    repair<NU>(wa, xa, Sj, pr, pf);
                    repair<NU>(wb, y, Sj, pr + RO2, pf + (ROLE ? 24576 : 4096));
                }
                if (s == 0) { bar_sync(1, 256); if (LEADER(7)) mbar_arrive(sb + B_GO); }
                if (ROT) mbar_wait(sb + B_RELA, slot ^ 1);
            }
        }
        s++;
    }
}
struct Pipe { uint32_t stage, phase; };
struct Cons {
    uint32_t sb, rel;
    int wg, wq, lane, rank, pair;
    uint32_t nst;
    Pipe p;
};
__device__ __forceinline__ void pipe_next(Pipe& p) { p.stage = (p.stage + 1) & (NSTAGE - 1); p.phase ^= (p.stage == 0); }
__device__ __forceinline__ void release(const Cons& c, uint32_t stage) { if (c.lane < 2) mbar_arrive_cluster(c.rel + stage * 8); }

enum { PEND_NONE = 0, PEND_KVO = 1, PEND_HT = 2, PEND_OUT = 3, PEND_OUTH = 4 };
struct Pend { uint32_t pk[64]; int kind, row, col, cnt; };

__device__ __forceinline__ void staging_wait(const Cons& c) { if (c.nst) mbar_wait(c.sb + B_SFREE + c.wg * 8, (c.nst - 1) & 1); }
__device__ __forceinline__ void staging_post(Cons& c, int kind, int row, int col, int cnt) {
    __syncwarp();
    if (c.lane == 0) {
        if (c.wq == 0) { const uint32_t x[4] = {(uint32_t)kind, (uint32_t)row, (uint32_t)col, (uint32_t)cnt}; sts128(c.sb + S_DESC + c.wg * 16, x); }
        mbar_arrive(c.sb + B_SFULL + c.wg * 8);
    }
    c.nst++;
}
template <int HF, bool KVONLY = false>
__device__ __forceinline__ void drain(const Params& P, Cons& c, const Pend& d) {
    const uint32_t* pk = d.pk + HF * 32;
    if (!KVONLY && d.kind >= PEND_OUT) {
        if (HF == 1 && d.kind == PEND_OUTH) return;
        float* o = P.out + (size_t)(d.row + c.wq * 16 + (c.lane >> 2)) * 2048 + d.col + HF * 128 + (c.lane & 3) * 2;
#pragma unroll
        for (int j = 0; j < 16; j++) {
            st_stream2(o + j * 8, bf_lo(pk[j * 2]), bf_hi(pk[j * 2]));
            st_stream2(o + 8 * 2048 + j * 8, bf_lo(pk[j * 2 + 1]), bf_hi(pk[j * 2 + 1]));
        }
    } else if (d.kind != PEND_NONE) {
        const bool ht = !KVONLY && d.kind == PEND_HT;
        const int hi = (c.lane >> 3) & 1;
        const uint32_t base = c.sb + S_STG + c.wg * 16384 + ((ht ? hi * 32 + c.wq * 8 : c.wq * 16 + hi * 8) + (c.lane & 7)) * 128;
        staging_wait(c);
#pragma unroll
        for (int j = 0; j < 8; j++) {
            const int ch = (j & 3) * 2 + (c.lane >> 4);
            stsm4(base + (j >> 2) * 8192 + ((ch ^ (c.lane & 7)) << 4), pk[j * 4], pk[j * 4 + 1], pk[j * 4 + 2], pk[j * 4 + 3]);
        }
        fence_async_smem();
        staging_post(c, d.kind, d.row, d.col + HF * 128, HF ? d.cnt : -1);
    }
}
__device__ __forceinline__ void drain_all(const Params& P, Cons& c, Pend& d) { drain<0>(P, c, d); drain<1>(P, c, d); d.kind = PEND_NONE; }

__device__ __forceinline__ void store_warp(const Params& P, uint32_t sb, int wg) {
    const uint32_t stg = sb + S_STG + wg * 16384;
#pragma unroll 1
    for (uint32_t n = 0;; n++) {
        mbar_wait(sb + B_SFULL + wg * 8, n & 1);
        uint32_t x[4];
        lds128(x, sb + S_DESC + wg * 16);
        if (x[0] == PEND_NONE) break;
        const bool ht = x[0] == PEND_HT;
        const CUtensorMap* m = &P.tm[ht ? M_HTS : M_KVO];
#pragma unroll 1
        for (int i = 0; i < 4; i++) if (!(DBGF(128) && gridDim.x != 96)) tma_store2d(m, x[2] + (i >> 1) * 64, x[1] + (i & 1) * (ht ? 1024 : 32), stg + i * 4096);
        bulk_commit();
        bulk_wait_read();
        mbar_arrive(sb + B_SFREE + wg * 8);
        if ((int)x[3] >= 0) {
            bulk_wait_all(); fence_async();
            asm volatile("red.relaxed.gpu.global.add.u32 [%0], 1;" ::"l"(&g_cnt(x[3])) : "memory");
        }
    }
}

template <int N, int TA, int TB, bool FIRST>
__device__ __forceinline__ void issue_ktile(float* acc, const Cons& c) {
    mbar_wait(c.sb + B_FULL + c.p.stage * 8, c.p.phase);
    const uint32_t a = c.sb + c.p.stage * STAGE + c.wg * 8192, b = c.sb + c.p.stage * STAGE + 16384;
    const uint64_t da = mkdesc(a, TA ? 8192 : 16, 1024, 1), db = mkdesc(b, TB ? 8192 : 16, 1024, 1);
    wg_fence();
#pragma unroll
    for (int k = 0; k < 4; k++) {
        const uint64_t x = da + (TA ? 128 : 2) * k, y = db + (TB ? 128 : 2) * k;
        if (N == 256) { if (FIRST && k == 0) wgmma_ss256_first<TA, TB>(acc, x, y); else wgmma_ss256<TA, TB>(acc, x, y); }
        else { if (FIRST && k == 0) wgmma_ss128_first<TA, TB>(acc, x, y); else wgmma_ss128<TA, TB>(acc, x, y); }
    }
    wg_commit();
}
template <int N, bool FIRST>
__device__ __forceinline__ void issue_any(float* acc, const Cons& c, int type) {
    if (N == 256 && type == T_A1) issue_ktile<N, 0, 0, FIRST>(acc, c);
    else if (type == (N == 256 ? T_A2 : T_A2H)) issue_ktile<N, 1, 0, FIRST>(acc, c);
    else issue_ktile<N, 0, 1, FIRST>(acc, c);
}
template <int N, bool KVONLY = false>
__device__ __forceinline__ void mainloop(float* acc, const Params& P, Cons& c, Pend& d, int type) {
    const int nk = (type == T_OP || type == T_OPH) ? 64 : (type == T_A2 || type == T_A2H) ? 32 : 16;
    issue_any<N, true>(acc, c, type);
    drain<0, KVONLY>(P, c, d);
    uint32_t prev = c.p.stage;
    pipe_next(c.p);
    for (int kt = 1; kt < nk; kt++) {
        issue_any<N, false>(acc, c, type);
        wg_wait<1>();
        release(c, prev);
        if (kt == 2) drain<1, KVONLY>(P, c, d);
        prev = c.p.stage;
        pipe_next(c.p);
    }
    d.kind = PEND_NONE;
    wg_wait<0>();
    pin<N / 2>(acc);
    release(c, prev);
}
__device__ __forceinline__ void pack_half(uint32_t* pk, const float* a) {
#pragma unroll
    for (int i = 0; i < 32; i++) pk[i] = pack2(a[2 * i], a[2 * i + 1]);
}

__device__ __forceinline__ void epi_kv(const float* acc, const Cons& c, Pend& d, int mb, int nb) {
    pack_half(d.pk, acc); pack_half(d.pk + 32, acc + 64);
    d.kind = PEND_KVO; d.row = (nb >> 4) * 2048 + mb * 256 + c.rank * 128 + c.wg * 64; d.col = (nb & 15) * 256; d.cnt = C_KV + mb;
}

__device__ __forceinline__ void epi_qa(const float* acc, Cons& c, Pend& d, int mb, int nb) {
    uint32_t q[64];
    pack_half(q, acc);
    pack_half(q + 32, acc + 64);
#pragma unroll
    for (int i = 0; i < 32; i++) d.pk[32 + i] = 0;
    const int g = c.lane >> 2, t = c.lane & 3;
    const bool sg = c.wq >= 2;
    const int i0 = (c.wq & 1) * 16 + g;
#pragma unroll 1
    for (int hh = 0; hh < 2; hh++) {
        uint32_t pa[5][4];
        {
            float S[32] = {}, Sm[8] = {};
            mbar_wait(c.sb + B_FULL + c.p.stage * 8, c.p.phase);
            const uint32_t st = c.sb + c.p.stage * STAGE;
            const uint64_t dk = mkdesc(st + c.wg * 8192, 16, 1024, 1), dm = mkdesc(st + 32768 + c.wg * 4096, 128, 2048, 0);
            pin<32>(q); pin<32>(S); pin<8>(Sm);
            wg_fence();
#pragma unroll
            for (int i = 0; i < 8; i++) wgmma_rs64<0>(S, q + i * 4, dk + (i >> 2) * 1024 + (i & 3) * 2, i != 0);
#pragma unroll
            for (int i = 0; i < 8; i++) wgmma_rs16<0>(Sm, q + i * 4, dm + i * 16, i != 0);
            wg_commit();
            wg_wait<0>();
            pin<32>(S); pin<8>(Sm);
            release(c, c.p.stage);
            pipe_next(c.p);
            const float scale = 0.08838834764831845f, l2e = 1.4426950408889634f;
            float x[2][10];
#pragma unroll
            for (int r = 0; r < 2; r++) {
#pragma unroll
                for (int j = 0; j < 4; j++)
#pragma unroll
                    for (int e = 0; e < 2; e++) {
                        const float v = sg ? S[16 + j * 4 + r * 2 + e] : S[j * 4 + r * 2 + e];
                        x[r][j * 2 + e] = (j * 8 + 2 * t + e > i0 + r * 8) ? -1e9f : v * scale;
                    }
                x[r][8] = (sg ? Sm[4 + r * 2] : Sm[r * 2]) * scale;
                x[r][9] = (sg ? Sm[5 + r * 2] : Sm[1 + r * 2]) * scale;
                float m = x[r][0];
#pragma unroll
                for (int i = 1; i < 10; i++) m = fmaxf(m, x[r][i]);
                m = fmaxf(m, __shfl_xor_sync(0xffffffffu, m, 1));
                m = fmaxf(m, __shfl_xor_sync(0xffffffffu, m, 2));
                float sum = 0.f;
#pragma unroll
                for (int i = 0; i < 10; i++) { x[r][i] = ex2((x[r][i] - m) * l2e); sum += x[r][i]; }
                sum += __shfl_xor_sync(0xffffffffu, sum, 1);
                sum += __shfl_xor_sync(0xffffffffu, sum, 2);
                const float inv = rcp(sum);
#pragma unroll
                for (int i = 0; i < 10; i++) x[r][i] *= inv;
            }
#pragma unroll
            for (int ks = 0; ks < 2; ks++)
#pragma unroll
                for (int i = 0; i < 4; i++) {
                    const uint32_t p = pack2(x[i & 1][ks * 4 + (i >> 1) * 2], x[i & 1][ks * 4 + (i >> 1) * 2 + 1]);
                    pa[ks][i] = sg ? 0u : p;
                    pa[2 + ks][i] = sg ? p : 0u;
                }
#pragma unroll
            for (int r = 0; r < 2; r++) {
                const uint32_t p = pack2(x[r][8], x[r][9]);
                pa[4][r] = sg ? 0u : p;
                pa[4][2 + r] = sg ? p : 0u;
            }
        }
        float O[64] = {};
        mbar_wait(c.sb + B_FULL + c.p.stage * 8, c.p.phase);
        const uint32_t st = c.sb + c.p.stage * STAGE;
        const uint64_t dv = mkdesc(st + c.wg * 8192, 16384, 1024, 1), dm = mkdesc(st + 32768 + c.wg * 4096, 2048, 128, 0);
        pin<20>(&pa[0][0]); pin<64>(O);
        wg_fence();
#pragma unroll
        for (int ks = 0; ks < 4; ks++) wgmma_rs128<1>(O, pa[ks], dv + ks * 128, ks != 0);
        wgmma_rs128<0>(O, pa[4], dm, 1);
        wg_commit();
        wg_wait<0>();
        pin<64>(O);
        release(c, c.p.stage);
        pipe_next(c.p);
#pragma unroll
        for (int i = 0; i < 32; i++) { q[i] = q[32 + i]; q[32 + i] = d.pk[32 + i]; }
        pack_half(d.pk + 32, O);
    }
#pragma unroll
    for (int i = 0; i < 32; i++) d.pk[i] = q[32 + i];
    d.kind = PEND_KVO; d.row = 4096 + mb * 256 + c.rank * 128 + c.wg * 64; d.col = nb * 256; d.cnt = C_O + mb * 4 + (nb >> 2);
}

__device__ __forceinline__ void epi_op(const float* acc, const Cons& c, Pend& d, int mb, int nb) {
    pack_half(d.pk, acc); pack_half(d.pk + 32, acc + 64);
    d.kind = PEND_OUT; d.row = mb * 256 + c.rank * 128 + c.wg * 64; d.col = 1024 + nb * 256;
}

__device__ __forceinline__ void epi_oph(const float* acc, const Cons& c, Pend& d, int mb, int nb) {
    pack_half(d.pk, acc);
    d.kind = PEND_OUTH; d.row = mb * 256 + c.rank * 128 + c.wg * 64; d.col = 1024 + nb * 128;
}

template <int HF>
__device__ __forceinline__ void epi_a2_half(const float* acc, const Params& P, Cons& c, int mb, int col0) {
    const int g = c.lane >> 2, t = c.lane & 3;
    const int row = mb * 256 + (g >> 1) * 64 + (c.rank * 16 + c.wg * 8 + c.wq * 2) * 2 + (g & 1);
    float* o = P.out + (size_t)row * 2048 + col0 + HF * 128 + t * 2;
    mbar_wait(c.sb + B_FULL + c.p.stage * 8, c.p.phase);
    const uint32_t st = c.sb + c.p.stage * STAGE, da = st + 32768 + (c.lane >> 3) * 16;
    const uint32_t xa = st + (c.wg * 64 + c.wq * 16 + (c.lane & 15)) * 128 + (((c.lane >> 4) ^ (c.lane & 7)) << 4);
#pragma unroll
    for (int j4 = 0; j4 < 4; j4++) {
        uint32_t x[8], dv[4];
        ldsm4(dv, da + j4 * 64);
        ldsm4(x, (xa ^ ((j4 & 1) << 6)) + (j4 >> 1) * 16384);
        ldsm4(x + 4, (xa ^ ((j4 & 1) << 6) ^ 32) + (j4 >> 1) * 16384);
#pragma unroll
        for (int i = 0; i < 4; i++) {
            const int j = j4 * 4 + i;
            const float* a = acc + HF * 64 + j * 4;
            const uint32_t u0 = hmul2(x[2 * i], dv[i]), u1 = hmul2(x[2 * i + 1], dv[i]);
            st_stream2(o + j * 8, a[0] + bf_lo(u0), a[1] + bf_hi(u0));
            st_stream2(o + 2 * 2048 + j * 8, a[2] + bf_lo(u1), a[3] + bf_hi(u1));
        }
    }
    __syncwarp();
    release(c, c.p.stage);
    pipe_next(c.p);
}

#define TSTAMP(i)
__device__ __forceinline__ float2 cmul(float2 a, float2 b) { return make_float2(fmaf(a.x, b.x, -a.y * b.y), fmaf(a.x, b.y, a.y * b.x)); }
__device__ __forceinline__ float2 cfma(float2 a, float2 b, float2 u) { return make_float2(fmaf(a.x, b.x, fmaf(-a.y, b.y, u.x)), fmaf(a.x, b.y, fmaf(a.y, b.x, u.y))); }
__device__ __forceinline__ float4 ssm_coef(float lre, float lim, float logdt) {
    const float dt = __bfloat162float(__float2bfloat16(expf(logdt)));
    const float ea = expf(dt * lre);
    float sn, cn;
    sincosf(dt * lim, &sn, &cn);
    const float br = ea * cn, bi = ea * sn, nr = br - 1.f;
    float cr, ci;
    if (fabsf(lre) >= fabsf(lim)) { const float r = lim / lre, dn = lre + lim * r; cr = (nr + bi * r) / dn; ci = (bi - nr * r) / dn; }
    else { const float r = lre / lim, dn = lre * r + lim; cr = (nr * r + bi) / dn; ci = (bi * r - nr) / dn; }
    return make_float4(br, bi, cr, ci);
}
__device__ __forceinline__ void epi_a1(const float* acc, const Params& P, const Cons& c, Pend& d, int mb, int nb, uint32_t atag) {
    const int t = c.lane & 3;
    const int p = nb * 128 + c.rank * 64 + c.wg * 32 + c.wq * 8 + (c.lane >> 2);
    uint32_t cw[4];
    lds128(cw, c.sb + S_COEF + (p & 63) * 16);
    const float4 cf = make_float4(__uint_as_float(cw[0]), __uint_as_float(cw[1]), __uint_as_float(cw[2]), __uint_as_float(cw[3]));
    TSTAMP(1)
    const float2 lam = make_float2(cf.x, P.swap_ri ? -cf.y : cf.y);
    const float a0 = P.swap_ri ? -2.f * cf.w : 2.f * cf.z, a1 = P.swap_ri ? 2.f * cf.z : -2.f * cf.w;
    const float b0 = P.swap_ri ? -2.f * cf.z : -2.f * cf.w, b1 = P.swap_ri ? -2.f * cf.w : -2.f * cf.z;
    float2 h = make_float2(0.f, 0.f);
#pragma unroll
    for (int round = 0; round < 2; round++) {
#pragma unroll
        for (int j = 0; j < 32; j++) {
            h = cfma(lam, h, make_float2(acc[j * 4], acc[j * 4 + 2]));
            const float r0 = fmaf(a0, h.x, a1 * h.y), m0 = fmaf(b0, h.x, b1 * h.y);
            h = cfma(lam, h, make_float2(acc[j * 4 + 1], acc[j * 4 + 3]));
            d.pk[j * 2] = pack2(r0, fmaf(a0, h.x, a1 * h.y));
            d.pk[j * 2 + 1] = pack2(m0, fmaf(b0, h.x, b1 * h.y));
        }
        if (round) break;
        float2 l64 = lam;
#pragma unroll
        for (int i = 0; i < 6; i++) l64 = cmul(l64, l64);
        const float2 l128 = cmul(l64, l64), l256 = cmul(l128, l128);
        float2 o = make_float2(__shfl_up_sync(0xffffffffu, h.x, 1), __shfl_up_sync(0xffffffffu, h.y, 1));
        if (t >= 1) h = cfma(l64, o, h);
        o = make_float2(__shfl_up_sync(0xffffffffu, h.x, 2), __shfl_up_sync(0xffffffffu, h.y, 2));
        if (t >= 2) h = cfma(l128, o, h);
        TSTAMP(2)
        if (t == 3) st_relaxed2(&g_agg[mb * 1024 + p], (__float_as_uint(h.x) & ~1u) | atag, __float_as_uint(h.y));
        h = make_float2(__shfl_up_sync(0xffffffffu, h.x, 1), __shfl_up_sync(0xffffffffu, h.y, 1));
        if (t == 0) h = make_float2(0.f, 0.f);
        uint32_t ax[7], ay[7];
        int n = 0;
        while (true) {
            uint32_t bad = 0;
#pragma unroll
            for (int j = 0; j < 7; j++) { ax[j] = atag; ay[j] = 0; ld_relaxed2_if(ax[j], ay[j], &g_agg[j * 1024 + p], j < mb); }
#pragma unroll
            for (int j = 0; j < 7; j++) bad |= ax[j] ^ atag;
            if (tags_ok(bad)) break;
            __nanosleep(400);
            if (++n > SPIN_LIMIT) spin_fault();
        }
        float2 carry = make_float2(0.f, 0.f);
#pragma unroll
        for (int j = 0; j < 7; j++) if (j < mb) carry = cfma(l256, carry, make_float2(__uint_as_float(ax[j]), __uint_as_float(ay[j])));
        float2 w = (t & 1) ? l64 : make_float2(1.f, 0.f);
        if (t & 2) w = cmul(w, l128);
        h = cfma(w, carry, h);
        TSTAMP(3)
    }
    TSTAMP(4)
    d.kind = PEND_HT; d.row = nb * 128 + c.rank * 64 + c.wg * 32; d.col = mb * 256; d.cnt = C_HT + mb * 2 + (nb >> 2);
}

__device__ __forceinline__ uint32_t acquire_stage(uint32_t sb, Pipe& p, uint32_t bytes) {
    mbar_wait(sb + B_EMPTY + p.stage * 8, p.phase ^ 1);
    mbar_expect(sb + B_FULL + p.stage * 8, bytes);
    return p.stage;
}
#define AHEAD 1
__device__ __forceinline__ void watcher(const Params& P, const uint32_t sb, const int rank, const int lane) {
    const uint32_t epoch = ld_relaxed1(&g_cnt(C_EPOCH)), e1 = epoch + 1;
    sts32(sb + S_EPOCH, epoch);
    if (gridDim.x != 96) {
        uint32_t v;
        asm("mov.u32 %0, %%smid;" : "=r"(v));
        if (lane == 0 && rank == 0) st_relaxed1(g_hint + 6272 + (blockIdx.x >> 1), e1 << 8 | v >> 1);
        for (int k = 0;; k++) {
            __nanosleep(1000);
            v = ld_relaxed1(g_hint + 6272 + min(lane, 17));
            if (__all_sync(0xffffffffu, (v ^ e1 << 8) < 256)) break;
            if (k > SPIN_LIMIT) spin_fault();
        }
        const uint32_t key = ((v & 255) >= 62 ? 0 : tpc_gpc(v & 255)) * 32 + lane;
        sts32(sb + S_TAIL, 48 + __popc(__ballot_sync(0xffffffffu, key < __shfl_sync(0xffffffffu, key, blockIdx.x >> 1)) & 0x3ffff));
        __syncwarp();
    }
    uint32_t met = 1;
    if (lane == 0) asm volatile("st.release.cta.shared.u32 [%0], 1;" ::"r"(sb + S_DEP) : "memory");
    const int pair = lds32(sb + S_TAIL), first = ITEM_OFF(pair) + (pair < NCHAIN ? NPRE + 1 : 1);
#pragma unroll 1
    for (int it = first; it < ITEM_OFF(pair + 1); it++) {
        const int item = ITEM(it), type = item >> 8, mb = (item >> 5) & 7, nb = item & 31;
        const int n = (0x24021420 >> (type * 4)) & 7;
        for (int k = 0; it > first && (int)lds32(sb + S_CUR) < it - AHEAD; k++) { __nanosleep(200); if (k > SPIN_LIMIT) spin_fault(); }
#pragma unroll 1
        for (int i = 0; i < n; i++) {
            int idx = n == 4 ? C_O + mb * 4 + i : C_HT + mb * 2 + i;
            uint32_t target = e1 * 16;
            if (type == T_A1) { idx = C_COEF; target = e1 * 4; }
            if (type == T_QA) {
                idx = i ? C_FLAG + (lane & 1) * 32 + nb * 2 + ((lane >> 1) & 1) : C_KV + mb;
                target = i ? epoch * 64 + mb * 8 + rank * 4 + 4 : e1 * 128;
            }
            if (lane < 4) { wait_count(&g_cnt(idx), target); fence_async(); }
            __syncwarp();
            if (lane == 0) asm volatile("st.release.cta.shared.u32 [%0], %1;" ::"r"(sb + S_DEP), "r"(++met) : "memory");
        }
    }
}
__device__ __forceinline__ bool dep_met(uint32_t sb, uint32_t n) { uint32_t v; asm volatile("ld.acquire.cta.shared.u32 %0, [%1];" : "=r"(v) : "r"(sb + S_DEP) : "memory"); return v >= n; }
__device__ __forceinline__ void dep_wait(uint32_t sb, uint32_t n) { for (int k = 0; !dep_met(sb, n); k++) { __nanosleep(32); if (k > SPIN_LIMIT * 8) spin_fault(); } }
__device__ __forceinline__ void producer(const Params& P, const uint32_t sb, int pair, const int rank) {
    Pipe p = {0, 0};
    uint32_t dep = 1;
    for (int it = ITEM_OFF(pair); it < ITEM_OFF(pair + 1); it++) {
        const int item = ITEM(it), type = item >> 8, mb = (item >> 5) & 7, nb = item & 31;
        if (type == T_CHAIN) {
            sts32(sb + S_CUR, 0);
            const uint32_t epoch = ld_relaxed1(&g_cnt(C_EPOCH)), e1 = epoch + 1;
            const int role = pair >> 4, h = (pair & 15) * 2 + rank;
#pragma unroll 1
            for (int i = 0, q = 0; i < 8; i++) {
                const int n = (0x13003333 >> (i * 4)) & 3;
                const uint32_t st = acquire_stage(sb, p, n * 16384);
                SSTAMP(1, i == 0) SSTAMP(3, i == 3)
#pragma unroll 1
                for (int k = 0; k < 2 * n; k++, q++)
                    tma3d(sb + st * STAGE + k * 8192, &P.tm[M_CQ + role], h * 128 + (fill_unit(q >> 1) & 1) * 64, word_col((fill_unit(q >> 1) & 14) + (q & 1)) & 8, word_col((fill_unit(q >> 1) & 14) + (q & 1)) >> 4, sb + B_FULL + st * 8);
                pipe_next(p);
            }
            if (role == 0 && !DBGF(1)) { wait_count(&g_cnt(C_KV), e1 * 128); fence_async(); }
            mbar_wait(sb + B_EMPTY + 16, 1); mbar_wait(sb + B_EMPTY + 24, 1);
            mbar_expect(sb + B_WO, role ? 98304 : 65536);
            if (role == 0) { mbar_expect(sb + B_KVFULL, 16384); mbar_expect(sb + B_KVFULL + 8, 16384); }
#pragma unroll 1
            for (int k = role ? 0 : -4; k < 12; k++) {
                const bool kv = role == 0 && (k & 8);
                const int sg = k > 0;
                tma4d(kv ? sb + S_KV + sg * 16384 + (k & 3) * 4096 : sb + S_W2 + k * 8192, &P.tm[kv ? M_KV4 : M_CO + (k & 1)],
                      kv ? h * 128 + (k & 1) * 64 : (role == 0 ? 0 : role == 1 ? 256 : 640) + (k >> 1) * 64, kv ? (k & 2) * 1024 + sg * 32 : h * 8, sb + (kv ? B_KVFULL + sg * 8 : B_WO));
            }
            SSTAMP(5, true)
            if (pair < 16) {
#pragma unroll 1
                for (int s = 2; s < 63; s++) {
                    mbar_wait(sb + B_KVGO + (s & 1) * 8, ((s >> 1) + 1) & 1);
                    wait_time(gtime() + P.dk, sb);
                    SSTAMP(6, s == 2)
                    const uint32_t bar = sb + B_KVFULL + (s & 1) * 8, dst = sb + S_KV + (s & 1) * 16384;
                    if (DBGF(2)) { mbar_arrive(bar); continue; }
                    mbar_expect(bar, 16384);
#pragma unroll 1
                    for (int i = 0; i < 4; i++) tma2d(dst + i * 4096, &P.tm[M_KVO], (pair * 2 + rank) * 128 + (i & 1) * 64, (i >> 1) * 2048 + (DBGF(32 | 512) ? s & 7 : s) * 32, bar);
                    if ((s & 7) == 7 && !DBGF(1)) { wait_count(&g_cnt(C_KV + 1 + (s >> 3)), e1 * 128); fence_async(); }
                }
            } else {
                uint32_t* flag = &g_cnt(C_FLAG + pair * 2 + rank - 32);
                const int x = pair * 2 + rank - 32;
#pragma unroll 1
                for (int s = 0; s < 64; s++) {
                    mbar_wait(sb + B_PERS, s & 1);
                    if (s < 63) wait_time(gtime() + P.dp, sb);
                    if (!DBGF(4)) bulk_s2g((role == 1 ? g_km : g_vmt) + (s * 32 + h) * 512, sb + S_QX, 2048);
                    if (s < 57) {
                        uint8_t* m = P.gm + ((s + 6) & 7) * M_SLOT + (x >> 1) * 1024 + (x & 1) * 256;
                        bulk_s2g(m, sb + S_SX, 256); bulk_s2g(m + 512, sb + S_SX, 128);
                        bulk_s2g(g_f + ((s + 6) & 7) * F_SLOT + x * 768, sb + S_SX + 256, 768);
                    }
                    bulk_commit();
                    bulk_wait_read();
                    mbar_arrive(sb + B_KVGO);
                    bulk_wait_all();
                    fence_async();
                    if ((s & 3) == 3) st_relaxed1(flag, epoch * 64 + s + 1);
                }
            }
            mbar_wait(sb + B_RESUME, 0);
            pair = lds32(sb + S_TAIL);
            it = ITEM_OFF(pair) + NPRE;
            continue;
        }
        if (it == ITEM_OFF(pair) && pair >= NCHAIN) it = -1; else sts32(sb + S_CUR, it);
        const int m0 = mb * 256 + rank * 128;
        if (type <= T_OP) {
            const CUtensorMap* ma = &P.tm[type == T_OP ? M_OA : M_BX];
            const CUtensorMap* mw = &P.tm[type == T_OP ? M_WO : type == T_QA ? M_WQ : nb < 16 ? M_WK : M_WV];
            const int nk = type == T_OP ? 64 : 16, nc = (nb & 15) * 4 + rank * 2, ma0 = type == T_OP ? 4096 + m0 : m0;
#pragma unroll 1
            for (int kt = 0; kt < nk; kt++) {
                if (type == T_OP && (kt & 15) == 0) dep_wait(sb, ++dep);
                if (DBGF(256) && pair >= NCHAIN) { acquire_stage(sb, p, 0); pipe_next(p); continue; }
                const uint32_t st = acquire_stage(sb, p, STAGE), bar = sb + B_FULL + st * 8;
                tma2d(sb + st * STAGE, ma, kt * 64, ma0, bar);
                tma3d_mc(sb + st * STAGE + 16384 + rank * 16384, mw, 0, kt * 64, nc, bar);
                if (type == T_QA && kt < 12 && dep_met(sb, dep + 1 + (kt >> 3))) {
                    if (kt < 8) tma_prefetch2d(&P.tm[M_OA], nb * 256 + (kt & 3) * 64, (kt >> 2) * 2048 + m0);
                    else {
                        const int o = ((mb * 8 + rank * 4 + (kt & 3)) * 32 + nb * 2) * 512;
                        l2_prefetch(g_km + o, 4096); l2_prefetch(g_vmt + o, 4096);
                    }
                }
                pipe_next(p);
            }
            if (type == T_QA) {
                dep += 2;
                dep_wait(sb, dep);
#pragma unroll 1
                for (int e = 0; e < 4; e++) {
                    const uint32_t st = acquire_stage(sb, p, 40960), bar = sb + B_FULL + st * 8, dst = sb + st * STAGE;
                    tma2d(dst, &P.tm[M_OA], nb * 256 + (e >> 1) * 128, (e & 1) * 2048 + m0, bar);
                    tma2d(dst + 16384, &P.tm[M_OA], nb * 256 + (e >> 1) * 128 + 64, (e & 1) * 2048 + m0, bar);
                    const uint32_t* src = ((e & 1) ? g_vmt : g_km) + ((mb * 8 + rank * 4) * 32 + nb * 2 + (e >> 1)) * 512;
#pragma unroll 1
                    for (int i = 0; i < 4; i++) bulk_g2s(dst + 32768 + i * 2048, src + i * 32 * 512, 2048, bar);
                    pipe_next(p);
                }
            }
        } else if (type == T_OPH) {
#pragma unroll 1
            for (int kt = 0; kt < 64; kt++) {
                if ((kt & 15) == 0) dep_wait(sb, ++dep);
                const uint32_t st = acquire_stage(sb, p, 32768), bar = sb + B_FULL + st * 8;
                tma2d(sb + st * STAGE, &P.tm[M_OA], kt * 64, 4096 + m0, bar);
                tma2d_mc(sb + st * STAGE + 16384 + rank * 8192, &P.tm[M_WOH], nb * 128 + rank * 64, kt * 64, bar);
                pipe_next(p);
            }
        } else if (type == T_A1) {
#pragma unroll 1
            for (int kt = 0; kt < 16; kt++) {
                if (kt == 15) dep_wait(sb, ++dep);
                const uint32_t st = acquire_stage(sb, p, kt == 15 ? STAGE + 1024 : STAGE), bar = sb + B_FULL + st * 8;
                if (kt == 15) bulk_g2s(sb + S_COEF, g_coef + nb * 128 + rank * 64, 1024, bar);
                tma4d(sb + st * STAGE, &P.tm[M_AB], kt * 64, nb * 16 + rank * 8, bar);
                tma4d_mc(sb + st * STAGE + 16384 + rank * 16384, &P.tm[M_AX], kt * 64, mb * 128 + rank * 16, bar);
                pipe_next(p);
            }
        } else {
            const int hw = type == T_A2H ? 64 : 128;
            const CUtensorMap* mc = &P.tm[type == T_A2H ? M_CREH : M_CRE];
#pragma unroll 1
            for (int kt = 0; kt < 32; kt++) {
                if ((kt & 15) == 0) dep_wait(sb, ++dep);
                const uint32_t st = acquire_stage(sb, p, 16384 + hw * 256), bar = sb + B_FULL + st * 8;
                tma3d(sb + st * STAGE, &P.tm[M_HT], 0, (kt & 1) * 1024 + (kt >> 1) * 64, mb * 4 + rank * 2, bar);
                tma2d_mc(sb + st * STAGE + 16384 + rank * hw * 128, mc + (kt & 1), (kt >> 1) * 64, (nb * 2 + rank) * hw, bar);
                pipe_next(p);
            }
#pragma unroll 1
            for (int col = nb * 2 * hw; col < (nb + 1) * 2 * hw; col += 128) {
                const uint32_t st = acquire_stage(sb, p, 32768 + 256), bar = sb + B_FULL + st * 8;
                tma4d(sb + st * STAGE, &P.tm[M_AX], col, mb * 128 + rank * 16, bar);
                tma4d(sb + st * STAGE + 16384, &P.tm[M_AX], col + 64, mb * 128 + rank * 16, bar);
                bulk_g2s(sb + st * STAGE + 32768, P.Dskip + col, 256, bar);
                pipe_next(p);
            }
        }
        if (it < 0) { dep_wait(sb, 1); pair = lds32(sb + S_TAIL); it = ITEM_OFF(pair); }
    }
}

__device__ __forceinline__ uint32_t fresh_tid() { uint32_t t; asm volatile("mov.u32 %0, %%tid.x;" : "=r"(t)); return t; }
__device__ __forceinline__ uint32_t fresh_ctaid() { uint32_t t; asm volatile("mov.u32 %0, %%ctaid.x;" : "=r"(t)); return logical_cta(t); }
__device__ __forceinline__ void reset_state(Cons& c, Pend& d, uint32_t sb, bool resumed) {
    const uint32_t t = fresh_tid(), b = fresh_ctaid();
    const int w = __shfl_sync(0xffffffffu, t >> 5, 0);
    c.sb = sb; c.wg = w >> 2; c.wq = w & 3; c.lane = t & 31;
    c.rank = __shfl_sync(0xffffffffu, b & 1, 0); c.pair = __shfl_sync(0xffffffffu, resumed && b < NCHAIN * 2 ? lds32(sb + S_TAIL) : b >> 1, 0);
    c.rel = mapa(sb + B_EMPTY, cluster_rank() ^ (c.lane & 1));
    c.p.stage = 0; c.p.phase = 0;
    c.nst = resumed && c.pair < NCHAIN ? 2 * NPRE : 0;
    d = Pend{};
}
#define PROF_ITEM(i)
#define PROF_MAIN(i)

__global__ void __launch_bounds__(384, 1) fused_kernel(const __grid_constant__ Params P) {
    extern __shared__ __align__(1024) uint8_t smem[];
    const uint32_t sb = smem_u32(smem);
    asm volatile("griddepcontrol.launch_dependents;");
    const int tid = threadIdx.x, lane = tid & 31;
    const int warp = __shfl_sync(0xffffffffu, tid >> 5, 0);
    const int pair = __shfl_sync(0xffffffffu, logical_cta(blockIdx.x) >> 1, 0), rank = __shfl_sync(0xffffffffu, blockIdx.x & 1, 0);
    if (tid == 0) {
        if (sb & 1023) spin_fault();
        sts32(sb + S_DEP, 0); sts32(sb + S_CUR, 0); sts32(sb + S_TAIL, pair); sts32(sb + S_CTA, pair * 2 + rank);
        for (int i = 0; i < NSTAGE; i++) { mbar_init(sb + B_FULL + i * 8, 1); mbar_init(sb + B_EMPTY + i * 8, 16); }
        mbar_init(sb + B_RESUME, 2);
        mbar_init(sb + B_KVFULL, 1); mbar_init(sb + B_KVFULL + 8, 1);
        mbar_init(sb + B_GO, 1); mbar_init(sb + B_KVGO, 1); mbar_init(sb + B_KVGO + 8, 1); mbar_init(sb + B_K, 1); mbar_init(sb + B_V, 1); mbar_init(sb + B_PERS, 8); mbar_init(sb + B_INIT, 3);
        mbar_init(sb + B_WO, 1);
        for (int i = 0; i < 2; i++) { mbar_init(sb + B_SFULL + i * 8, 4); mbar_init(sb + B_SFREE + i * 8, 1); }
        mbar_init(sb + B_RELA, 1); mbar_init(sb + B_RELB, 1);
        asm volatile("fence.mbarrier_init.release.cluster;" ::: "memory");
        if (pair < 16) mbar_expect(sb + B_K, 2048);
        mbar_expect(sb + B_V, 2048);
    }
    cluster_sync();
    if (warp >= 8) {
        asm volatile("setmaxnreg.dec.sync.aligned.u32 24;");
        if (warp == 10 && lane < M_COUNT) map_prefetch(&P.tm[lane]);
        if (warp == 11 && lane == 0 && pair < NCHAIN) {
            const uint32_t t0 = gtime();
            const int role = pair >> 4, h = (pair & 15) * 2 + rank;
#pragma unroll 1
            for (int i = role ? 32 : 0; i < (role ? 44 : 40); i++) {
                wait_time(t0 + P.pf0 + min(i, 32) * P.pf1 + max(i - 32, 0) * P.pf2, sb);
                if (i < 32) asm volatile("cp.async.bulk.prefetch.tensor.3d.L2.global [%0, {%1, %2, %3}];" ::"l"(&P.tm[M_CQ]), "r"(h * 128 + (i & 1) * 64), "r"((i & 2) * 4), "r"((i >> 2) * 8) : "memory");
                else asm volatile("cp.async.bulk.prefetch.tensor.4d.L2.global [%0, {%1, 0, 0, %2}];" ::"l"(&P.tm[M_CO + (i & 1)]), "r"((role == 0 ? 0 : role == 1 ? 256 : 640) + ((i - 32) >> 1) * 64), "r"(h * 8) : "memory");
            }
        }
        if (warp == 9 && pair < NCHAIN) pacer(P, sb, lane);
        if (warp == 9) watcher(P, sb, rank, lane);
        if (warp >= 10 && lane == 0) store_warp(P, sb, warp - 10);
        if (warp == 8) {
            if (lane == 0) producer(P, sb, lds32(sb + S_CTA) >> 1, rank);
            __syncwarp();
            asm volatile("barrier.cluster.arrive.relaxed.aligned;\nbarrier.cluster.wait.aligned;" ::: "memory");
        }
    } else {
        asm volatile("setmaxnreg.inc.sync.aligned.u32 240;");
        Cons c;
        Pend d;
        if (pair < NCHAIN) {
            mem0_max(P, sb, tid);
            reset_state(c, d, sb, false);
#pragma unroll 1
            for (int i = 0; i < NPRE; i++) {
                PROF_ITEM(i)
                const int item = ITEM(ITEM_OFF(pair) + i);
                float acc[128];
                mainloop<256, true>(acc, P, c, d, T_KV);
                epi_kv(acc, c, d, (item >> 5) & 7, item & 31);
            }
            ISTAMP(4)
            drain<0, true>(P, c, d);
            drain<1, true>(P, c, d);
            PROF_ITEM(NPRE)
            uint32_t wr[NR][4];
            load_weights(wr, sb, warp, lane, [&]() { staging_wait(c); });
            const int h = (pair & 15) * 2 + rank;
            if (pair < 16) chain_role<0>(P, wr, sb, h, warp, lane);
            else if (pair < 32) chain_role<1>(P, wr, sb, h, warp, lane);
            else chain_role<2>(P, wr, sb, h, warp, lane);
            fence_async_smem();
            bar_sync(1, 256);
            const uint32_t t2 = fresh_tid();
            if (t2 < 2) mbar_arrive_cluster(mapa(sb + B_RESUME, cluster_rank() ^ t2));
        } else if (pair >= NPAIR - 2) {
            const int ch = (pair - (NPAIR - 2)) * 512 + rank * 256 + tid;
            g_coef[ch] = ssm_coef(__bfloat162float(P.Lre[ch]), __bfloat162float(P.Lim[ch]), __bfloat162float(P.logdt[ch]));
            bar_sync(1, 256);
            if (tid == 0) red_release(&g_cnt(C_COEF));
        }
        reset_state(c, d, sb, true);
        for (int it = ITEM_OFF(c.pair) + (c.pair < NCHAIN ? NPRE + 1 : 0);; it++) {
            const bool last = it == ITEM_OFF(c.pair + 1);
            if (d.kind != PEND_NONE && (last || !bar_and(5 + c.wg, mbar_test(sb + B_FULL + c.p.stage * 8, c.p.phase)))) drain_all(P, c, d);
            if (last) break;
            const int item = ITEM(it), type = item >> 8, mb = (item >> 5) & 7, nb = item & 31;
            PROF_ITEM(it - ITEM_OFF(c.pair))
            if (type >= T_OPH) {
                float acc[64];
                mainloop<128>(acc, P, c, d, type);
                PROF_MAIN(it - ITEM_OFF(c.pair))
                if (type == T_OPH) epi_oph(acc, c, d, mb, nb);
                else epi_a2_half<0>(acc, P, c, mb, nb * 128);
            } else {
                float acc[128];
                mainloop<256>(acc, P, c, d, type);
                PROF_MAIN(it - ITEM_OFF(c.pair))
                if (type == T_KV) epi_kv(acc, c, d, mb, nb);
                else if (type == T_QA) epi_qa(acc, c, d, mb, nb);
                else if (type == T_OP) epi_op(acc, c, d, mb, nb);
                else if (type == T_A1) epi_a1(acc, P, c, d, mb, nb, (lds32(sb + S_EPOCH) + 1) & 1);
                else { epi_a2_half<0>(acc, P, c, mb, nb * 256); epi_a2_half<1>(acc, P, c, mb, nb * 256); }
            }
            if (it == ITEM_OFF(c.pair)) { dep_wait(sb, 1); c.pair = __shfl_sync(0xffffffffu, lds32(sb + S_TAIL), 0); it = ITEM_OFF(c.pair); }
        }
        staging_wait(c);
        staging_post(c, PEND_NONE, 0, 0, 0);
        cluster_sync();
        if (c.wg == 0 && c.wq == 0 && c.lane == 0 && atomicInc(&g_cnt(C_DONE), DBGF(32) ? 95 : NPAIR * 2 - 1) == (DBGF(32) ? 95 : NPAIR * 2 - 1)) atomicAdd(&g_cnt(C_EPOCH), 1);
    }
}

typedef CUresult (*EncodeFn)(CUtensorMap*, CUtensorMapDataType, cuuint32_t, void*, const cuuint64_t*, const cuuint64_t*, const cuuint32_t*, const cuuint32_t*,
                             CUtensorMapInterleave, CUtensorMapSwizzle, CUtensorMapL2promotion, CUtensorMapFloatOOBfill);
void encode(EncodeFn fn, CUtensorMap* m, const void* base, int rank, const uint64_t* dims, const uint64_t* strides, const uint32_t* box, CUtensorMapSwizzle swz = CU_TENSOR_MAP_SWIZZLE_128B) {
    cuuint64_t d[5], s[5]; cuuint32_t b[5], e[5];
    for (int i = 0; i < rank; i++) { d[i] = dims[i]; b[i] = box[i]; e[i] = 1; if (i) s[i - 1] = strides[i - 1]; }
    fn(m, CU_TENSOR_MAP_DATA_TYPE_BFLOAT16, rank, (void*)base, d, s, b, e, CU_TENSOR_MAP_INTERLEAVE_NONE, swz,
       CU_TENSOR_MAP_L2_PROMOTION_L2_256B, CU_TENSOR_MAP_FLOAT_OOB_FILL_NONE);
}
void map_kmajor(EncodeFn fn, CUtensorMap* m, const void* base, uint64_t rows, uint64_t cols, uint32_t box_rows) {
    const uint64_t d[2] = {cols, rows}, s[1] = {cols * 2}; const uint32_t b[2] = {64, box_rows};
    encode(fn, m, base, 2, d, s, b);
}
void map_mnmajor(EncodeFn fn, CUtensorMap* m, const void* base, uint64_t krows, uint64_t cols) {
    const uint64_t d[3] = {64, krows, cols / 64}, s[2] = {cols * 2, 128}; const uint32_t b[3] = {64, 64, 2};
    encode(fn, m, base, 3, d, s, b);
}

}

extern "C" void kernel_launch(void* const* d_in, const int* in_sizes, int n_in, void* d_out, int out_size) {
    static Params P;
    static EncodeFn fn = nullptr;
    if (!fn) {
        cudaDriverEntryPointQueryResult q;
        cudaGetDriverEntryPoint("cuTensorMapEncodeTiled", (void**)&fn, cudaEnableDefault, &q);
        cudaFuncSetAttribute(fused_kernel, cudaFuncAttributeMaxDynamicSharedMemorySize, S_TOTAL);
    }
    const bf16* in[15];
    for (int i = 0; i < 15; i++) in[i] = (const bf16*)d_in[i];
    void *kvo, *ht, *gm;
    cudaGetSymbolAddress(&gm, g_m);
    P.gm = (uint8_t*)(((uintptr_t)gm + 32767) & ~(uintptr_t)32767);
    cudaGetSymbolAddress(&kvo, g_kvo);
    cudaGetSymbolAddress(&ht, g_ht);
    map_kmajor(fn, &P.tm[M_BX], in[9], 2048, 1024, 128);
    map_mnmajor(fn, &P.tm[M_WQ], in[11], 1024, 4096);
    map_mnmajor(fn, &P.tm[M_WK], in[12], 1024, 4096);
    map_mnmajor(fn, &P.tm[M_WV], in[13], 1024, 4096);
    map_mnmajor(fn, &P.tm[M_WO], in[14], 4096, 1024);
    map_kmajor(fn, &P.tm[M_OA], kvo, 3 * 2048, 4096, 128);
    P.swap_ri = in[4] < in[3];
    {
        const bf16* lo = P.swap_ri ? in[4] : in[3];
        const uint64_t diff = (uint64_t)((const char*)(P.swap_ri ? in[3] : in[4]) - (const char*)lo);
        const uint64_t d[4] = {1024, 8, 2, 128}, s[3] = {2048, diff, 16384}; const uint32_t b[4] = {64, 8, 2, 8};
        encode(fn, &P.tm[M_AB], lo, 4, d, s, b);
    }
    {
        const uint64_t d[4] = {1024, 2, 4, 1024}, s[3] = {2048, 64 * 2048, 4096}; const uint32_t b[4] = {64, 2, 4, 16};
        encode(fn, &P.tm[M_AX], in[0], 4, d, s, b);
    }
    map_mnmajor(fn, &P.tm[M_HT], ht, 2048, 2048);
    map_kmajor(fn, &P.tm[M_CRE], in[5], 1024, 1024, 128);
    map_kmajor(fn, &P.tm[M_CIM], in[6], 1024, 1024, 128);
    map_kmajor(fn, &P.tm[M_KVO], kvo, 3 * 2048, 4096, 32);
    map_kmajor(fn, &P.tm[M_HTS], ht, 2048, 2048, 32);
    map_kmajor(fn, &P.tm[M_WOH], in[14], 4096, 1024, 64);
    map_kmajor(fn, &P.tm[M_CREH], in[5], 1024, 1024, 64);
    map_kmajor(fn, &P.tm[M_CIMH], in[6], 1024, 1024, 64);
    for (int i = 0; i < 3; i++) {
        const uint64_t d[3] = {4096, 16, 64}, s[2] = {8192, 16 * 8192}; const uint32_t b[3] = {64, 8, 8};
        encode(fn, &P.tm[M_CQ + i], in[11 + i], 3, d, s, b);
    }
    {
        const uint64_t d[4] = {4096, 1, 1, 4096}, s[3] = {8192, 8192, 8192}; const uint32_t b[4] = {64, 1, 1, 32};
        encode(fn, &P.tm[M_KV4], kvo, 4, d, s, b);
    }
    for (int e = 0; e < 2; e++) {
        const uint64_t d[4] = {1024, 2, 4, 256}, s[3] = {8 * 2048, 2 * 2048, 16 * 2048}; const uint32_t b[4] = {64, 2, 4, 8};
        encode(fn, &P.tm[M_CO + e], in[14] + e * 1024, 4, d, s, b);
    }
    P.Wq = in[11]; P.Wk = in[12]; P.Wv = in[13]; P.Wo = in[14]; P.mem0 = in[10];
    P.Lre = in[1]; P.Lim = in[2]; P.logdt = in[7]; P.Dskip = in[8];
    P.out = (float*)d_out;
    P.two26 = 1u << 26;
    P.ds = 400; P.dc = 1600; P.alpha = 0.3f; P.extra = 200; P.da = 192; P.db = 432; P.dk = 800; P.dp = 1550; P.dv = 60; P.pf0 = 1500; P.pf1 = 175; P.pf2 = 450; P.back = 150; P.ds0 = 950;
    for (int i = 0; i < (DBGF(32) ? 1 : 2); i++) {
        cudaLaunchConfig_t cfg = {};
        cfg.gridDim = dim3(i ? 36 : 96); cfg.blockDim = dim3(384); cfg.dynamicSmemBytes = S_TOTAL; cfg.stream = cudaStreamPerThread;
        cudaLaunchAttribute at[2];
        at[0].id = cudaLaunchAttributeClusterDimension; at[0].val.clusterDim.x = i ? 2 : 6; at[0].val.clusterDim.y = at[0].val.clusterDim.z = 1;
        at[1].id = cudaLaunchAttributeProgrammaticStreamSerialization; at[1].val.programmaticStreamSerializationAllowed = 1;
        cfg.attrs = at; cfg.numAttrs = 1 + i;
        cudaLaunchKernelEx(&cfg, fused_kernel, P);
    }
}
```

```cpp
#include <cuda_runtime.h>
#include <cuda_bf16.h>
#include <cuda.h>
#include <stdint.h>
#include <string.h>

typedef __nv_bfloat16 bf16;

namespace {

#define POLL 200
constexpr int SPIN_LIMIT = 1 << 22;
constexpr int NPAIR = 66;
constexpr int NCHAIN = 48;
enum { T_KV = 0, T_QA = 1, T_OP = 2, T_A1 = 3, T_A2 = 4, T_CHAIN = 5, T_OPH = 6, T_A2H = 7 };
enum { M_BX = 0, M_WQ, M_WK, M_WV, M_WO, M_OA, M_AB, M_AX, M_HT, M_CRE, M_CIM, M_KVO, M_HTS, M_WOH, M_CREH, M_CIMH, M_CQ, M_CK, M_CV, M_CO, M_CO1, M_KV4, M_COUNT };
enum { C_KV = 0, C_HT = 8, C_DONE = 24, C_EPOCH = 25, C_COEF = 26, C_FLAG = 32, C_O = 96 };

struct Params {
    CUtensorMap tm[M_COUNT];
    const bf16 *Wq, *Wk, *Wv, *Wo, *mem0, *Lre, *Lim, *logdt, *Dskip;
    float* out;
    uint8_t* gm;
    int swap_ri, zero;
    uint32_t two26;
    int ds, da, db, dk, dv, back, ds0, pf0, pf1, pf2, dc, extra, dp;
    float alpha;
#define DBGF(x) false
};

constexpr int NPRE = 1;
__constant__ uint16_t c_off[67] = {0, 5, 10, 15, 19, 23, 27, 31, 35, 39, 43, 48, 52, 56, 60, 64, 68, 73, 78, 83, 87, 91, 95, 101, 106, 110, 114, 118, 122, 127, 132, 136, 140, 145, 150, 155, 159, 163, 167, 173, 179, 183, 187, 191, 195, 199, 204, 208, 212, 232, 252, 271, 291, 311, 331, 350, 370, 390, 409, 429, 449, 468, 488, 505, 524, 543, 562};
__constant__ uint16_t c_items[640] = {
    32, 1280, 423, 495, 1122, 49, 1280, 455, 333, 1057, 34, 1280, 428, 302, 1056, 51, 1280, 422, 642, 36, 1280, 326, 641, 53,
    1280, 330, 545, 38, 1280, 869, 547, 55, 1280, 867, 546, 40, 1280, 931, 608, 57, 1280, 899, 609, 42, 1280, 452, 297, 1185,
    59, 1280, 454, 513, 44, 1280, 836, 675, 61, 1280, 804, 672, 46, 1280, 389, 544, 63, 1280, 388, 576, 0, 1280, 292, 491,
    1250, 1, 1280, 484, 493, 1120, 2, 1280, 492, 334, 1058, 3, 1280, 457, 512, 4, 1280, 490, 673, 5, 1280, 458, 610, 6,
    1280, 425, 301, 460, 1862, 7, 1280, 424, 299, 1025, 8, 1280, 871, 707, 9, 1280, 839, 704, 10, 1280, 963, 736, 11, 1280,
    995, 705, 12, 1280, 992, 902, 1218, 13, 1280, 961, 966, 1249, 14, 1280, 928, 739, 15, 1280, 929, 578, 16, 1280, 356, 494,
    1121, 17, 1280, 364, 335, 1153, 18, 1280, 300, 331, 1248, 19, 1280, 453, 514, 20, 1280, 488, 674, 21, 1280, 486, 737, 22,
    1280, 393, 429, 461, 1857, 23, 1280, 392, 427, 463, 1863, 24, 1280, 903, 611, 25, 1280, 866, 515, 26, 1280, 901, 706, 27,
    1280, 898, 738, 28, 1280, 960, 643, 29, 1280, 993, 934, 1217, 30, 1280, 896, 579, 31, 1280, 897, 577, 33, 66, 84, 102,
    120, 138, 156, 174, 210, 246, 204, 201, 224, 323, 365, 259, 835, 962, 329, 1027, 35, 67, 85, 103, 121, 139, 157, 175,
    221, 223, 213, 220, 354, 229, 419, 367, 384, 261, 964, 1152, 37, 68, 86, 104, 122, 140, 158, 176, 239, 196, 263, 225,
    360, 264, 832, 837, 994, 996, 1059, 39, 69, 87, 105, 123, 141, 159, 177, 207, 199, 195, 237, 396, 296, 322, 390, 489,
    395, 967, 1251, 41, 70, 88, 106, 124, 142, 160, 178, 253, 245, 192, 197, 235, 386, 362, 352, 262, 487, 269, 1216, 43,
    71, 89, 107, 125, 143, 161, 179, 241, 249, 233, 219, 353, 321, 387, 834, 256, 459, 933, 1187, 45, 72, 90, 108, 126,
    144, 162, 180, 203, 250, 226, 358, 327, 805, 324, 449, 900, 332, 1154, 47, 73, 91, 109, 127, 145, 163, 181, 240, 200,
    244, 212, 227, 385, 357, 448, 483, 868, 271, 1026, 48, 74, 92, 110, 128, 146, 164, 182, 206, 248, 218, 216, 247, 238,
    397, 768, 838, 361, 935, 1090, 50, 75, 93, 111, 129, 147, 165, 183, 231, 222, 211, 363, 773, 801, 431, 420, 394, 430,
    1024, 52, 76, 94, 112, 130, 148, 166, 184, 193, 228, 214, 215, 355, 803, 288, 295, 864, 359, 998, 1219, 54, 77, 95,
    113, 131, 149, 167, 185, 243, 198, 194, 205, 325, 417, 303, 294, 481, 456, 366, 1186, 56, 78, 96, 114, 132, 150, 168,
    186, 234, 202, 242, 328, 775, 833, 800, 421, 485, 932, 1089, 58, 79, 97, 115, 133, 151, 169, 187, 217, 208, 209, 290,
    398, 416, 265, 865, 480, 462, 997, 1184, 60, 80, 98, 116, 134, 152, 170, 188, 291, 254, 298, 255, 771, 806, 450, 807,
    640, 62, 81, 99, 117, 135, 153, 171, 189, 257, 251, 232, 769, 772, 289, 451, 870, 426, 999, 1856, 64, 82, 100, 118,
    136, 154, 172, 190, 260, 230, 293, 252, 774, 770, 266, 418, 930, 270, 1123, 65, 83, 101, 119, 137, 155, 173, 191, 267,
    236, 320, 258, 399, 391, 802, 482, 268, 965, 1155,
};
#define ITEM_OFF(p) c_off[p]
#define ITEM(i) c_items[i]

__device__ __align__(1024) bf16 g_kvo[3 * 2048 * 4096];
__device__ __align__(1024) bf16 g_ht[2048 * 2048];
__device__ __align__(1024) uint8_t g_m[9 * 32768];
__device__ __align__(1024) uint8_t g_f[8 * 49152];
__device__ __align__(1024) uint32_t g_km[64 * 32 * 512];
__device__ __align__(1024) uint32_t g_vmt[64 * 32 * 512];
__device__ __align__(1024) float2 g_agg[8 * 1024];
__device__ __align__(1024) float4 g_coef[1024];
__device__ __align__(1024) uint32_t g_cntl[128 * 32];
#define g_cnt(i) g_cntl[(i) * 32]
__device__ __align__(1024) uint32_t g_hint[6144 + 160];
#define SSTAMP(i, cond)
#define PROF(i)
#define GT_EDGE(o)
constexpr int M_SLOT = 32768, F_SLOT = 49152;

constexpr int STAGE = 49152, NSTAGE = 4;
constexpr int S_STG = NSTAGE * STAGE;
constexpr int S_BAR = S_STG + 32768;
constexpr int B_FULL = S_BAR, B_EMPTY = S_BAR + 32, B_RESUME = S_BAR + 64, B_KVFULL = S_BAR + 72, B_GO = S_BAR + 88, B_K = S_BAR + 96, B_PERS = S_BAR + 104, B_INIT = S_BAR + 112, B_RELA = S_BAR + 120, B_V = S_BAR + 128, B_WO = S_BAR + 136,
              B_SFULL = S_BAR + 144, B_SFREE = S_BAR + 160, S_DESC = S_BAR + 176, S_REDO = S_BAR + 256 + 512 + 64, S_EPOCH = S_BAR + 208, B_RELB = S_BAR + 216, B_KVGO = S_BAR + 224, S_DEP = S_BAR + 240, S_CUR = S_BAR + 244, S_TAIL = S_BAR + 248, S_CTA = S_BAR + 252;
constexpr int S_COEF = S_BAR + 256 + 512, S_TOTAL = S_COEF + 1024;
constexpr int S_W1 = 0;
constexpr int S_O = 24 * 4096, S_VL = S_O + 2048, S_MX = 25 * 4096, S_SC = S_MX + 64, S_SUM = S_MX + 128;
constexpr int S_KL = 26 * 4096;
constexpr int S_W2 = 27 * 4096;
constexpr int S_KV = S_W2 + 65536;
constexpr int S_P1 = S_W2 + 98304;
constexpr int S_QX = S_P1 + 16384;
constexpr int S_SX = S_QX + 2048;
static_assert(S_SX + 1280 <= S_BAR, "chain smem overlaps barriers");
constexpr int NR = 40, NS = 64 - NR;

__device__ __forceinline__ uint32_t logical_cta(uint32_t b) {
    const uint32_t c = b / 6, r = b - c * 6;
    return gridDim.x != 96 ? 96 + b : ((r >> 1) + (c >= 8) + (c >= 15)) % 3 * 32 + c * 2 + (r & 1);
}
__device__ __forceinline__ uint32_t cluster_rank() { uint32_t r; asm("mov.u32 %0, %%cluster_ctarank;" : "=r"(r)); return r; }
__device__ __forceinline__ uint16_t pair_mask() { return (uint16_t)(3u << (cluster_rank() & 6)); }
__device__ __forceinline__ void spin_fault() { asm volatile("st.global.u32 [%0], 0;" ::"l"(0ull) : "memory"); }
__device__ __forceinline__ uint32_t smem_u32(const void* p) { return (uint32_t)__cvta_generic_to_shared(p); }
__device__ __forceinline__ uint32_t opq(uint32_t x, int lane) { return __shfl_sync(0xffffffffu, x, lane); }
__device__ __forceinline__ uint32_t mapa(uint32_t a, uint32_t r) { uint32_t d; asm volatile("mapa.shared::cluster.u32 %0, %1, %2;" : "=r"(d) : "r"(a), "r"(r)); return d; }
__device__ __forceinline__ void mma16816(float* d, uint32_t a0, uint32_t a1, uint32_t a2, uint32_t a3, uint32_t b0, uint32_t b1) {
    asm("mma.sync.aligned.m16n8k16.row.col.f32.bf16.bf16.f32 {%0,%1,%2,%3}, {%4,%5,%6,%7}, {%8,%9}, {%0,%1,%2,%3};"
        : "+f"(d[0]), "+f"(d[1]), "+f"(d[2]), "+f"(d[3]) : "r"(a0), "r"(a1), "r"(a2), "r"(a3), "r"(b0), "r"(b1));
}
__device__ __forceinline__ void mma1688(float* d, uint32_t a0, uint32_t a1, uint32_t b0) {
    asm("mma.sync.aligned.m16n8k8.row.col.f32.bf16.bf16.f32 {%0,%1,%2,%3}, {%4,%5}, {%6}, {%0,%1,%2,%3};"
        : "+f"(d[0]), "+f"(d[1]), "+f"(d[2]), "+f"(d[3]) : "r"(a0), "r"(a1), "r"(b0));
}
__device__ __forceinline__ void ldsm4(uint32_t* r, uint32_t a) {
    asm volatile("ldmatrix.sync.aligned.m8n8.x4.shared.b16 {%0,%1,%2,%3}, [%4];" : "=r"(r[0]), "=r"(r[1]), "=r"(r[2]), "=r"(r[3]) : "r"(a));
}
__device__ __forceinline__ void ldsm4t(uint32_t* r, uint32_t a) {
    asm volatile("ldmatrix.sync.aligned.m8n8.x4.trans.shared.b16 {%0,%1,%2,%3}, [%4];" : "=r"(r[0]), "=r"(r[1]), "=r"(r[2]), "=r"(r[3]) : "r"(a));
}
__device__ __forceinline__ void stsm4(uint32_t a, uint32_t r0, uint32_t r1, uint32_t r2, uint32_t r3) {
    asm volatile("stmatrix.sync.aligned.m8n8.x4.shared.b16 [%0], {%1,%2,%3,%4};" ::"r"(a), "r"(r0), "r"(r1), "r"(r2), "r"(r3) : "memory");
}
__device__ __forceinline__ void stsm4t(uint32_t a, uint32_t r0, uint32_t r1, uint32_t r2, uint32_t r3) {
    asm volatile("stmatrix.sync.aligned.m8n8.x4.trans.shared.b16 [%0], {%1,%2,%3,%4};" ::"r"(a), "r"(r0), "r"(r1), "r"(r2), "r"(r3) : "memory");
}
__device__ __forceinline__ uint32_t pack2(float lo, float hi) { uint32_t d; asm("cvt.rn.bf16x2.f32 %0, %1, %2;" : "=r"(d) : "f"(hi), "f"(lo)); return d; }
__device__ __forceinline__ float bf_lo(uint32_t u) { return __uint_as_float(u << 16); }
__device__ __forceinline__ float bf_hi(uint32_t u) { return __uint_as_float(u & 0xffff0000u); }
__device__ __forceinline__ uint32_t hmul2(uint32_t a, uint32_t b) { uint32_t d; asm("mul.rn.bf16x2 %0, %1, %2;" : "=r"(d) : "r"(a), "r"(b)); return d; }
__device__ __forceinline__ float ex2(float x) { float y; asm("ex2.approx.ftz.f32 %0, %1;" : "=f"(y) : "f"(x)); return y; }
__device__ __forceinline__ float rcp(float x) { float y; asm("rcp.approx.ftz.f32 %0, %1;" : "=f"(y) : "f"(x)); return y; }
__device__ __forceinline__ void st_relaxed4(const void* p, uint32_t a, uint32_t b, uint32_t c, uint32_t d) {
    asm volatile("{\n.reg .b128 t;\nmov.b128 t, {%1,%2,%3,%4};\nst.relaxed.gpu.global.b128 [%0], t;\n}" ::"l"(p), "r"(a), "r"(b), "r"(c), "r"(d) : "memory");
}
__device__ __forceinline__ void st_relaxed2(const void* p, uint32_t a, uint32_t b) {
    asm volatile("{\n.reg .b64 t;\nmov.b64 t, {%1,%2};\nst.relaxed.gpu.global.b64 [%0], t;\n}" ::"l"(p), "r"(a), "r"(b) : "memory");
}
__device__ __forceinline__ void ld_relaxed2_if(uint32_t& a, uint32_t& b, const void* p, bool on) {
    asm volatile("{\n.reg .pred P;\n.reg .b64 t;\nsetp.ne.u32 P, %3, 0;\nmov.b64 t, {%0,%1};\n@P ld.relaxed.gpu.global.b64 t, [%2];\nmov.b64 {%0,%1}, t;\n}" : "+r"(a), "+r"(b) : "l"(p), "r"((uint32_t)on) : "memory");
}
__device__ __forceinline__ uint32_t ld_relaxed1(const void* p) { uint32_t v; asm volatile("ld.relaxed.gpu.global.u32 %0, [%1];" : "=r"(v) : "l"(p) : "memory"); return v; }
__device__ __forceinline__ void st_relaxed1(const void* p, uint32_t v) { asm volatile("st.relaxed.gpu.global.u32 [%0], %1;" ::"l"(p), "r"(v) : "memory"); }
__device__ __forceinline__ uint32_t ld_acquire(const void* p) { uint32_t v; asm volatile("ld.acquire.gpu.global.u32 %0, [%1];" : "=r"(v) : "l"(p) : "memory"); return v; }
__device__ __forceinline__ void red_release(void* p) { asm volatile("red.release.gpu.global.add.u32 [%0], 1;" ::"l"(p) : "memory"); }
__device__ __forceinline__ void st_stream2(float* p, float a, float b) { asm volatile("st.global.cs.v2.f32 [%0], {%1, %2};" ::"l"(p), "f"(a), "f"(b) : "memory"); }
__device__ __forceinline__ void fence_acquire() { asm volatile("fence.acquire.gpu;" ::: "memory"); }
__device__ __forceinline__ void fence_release() { asm volatile("fence.release.gpu;" ::: "memory"); }
__device__ __forceinline__ void fence_async() {  asm volatile("fence.proxy.async.global;" ::: "memory"); }
__device__ __forceinline__ void fence_async_smem() { asm volatile("fence.proxy.async.shared::cta;" ::: "memory"); }
__device__ __forceinline__ void wait_count(const uint32_t* p, uint32_t target) {
    int n = 0;
    while ((int32_t)(ld_acquire(p) - target) < 0) { __nanosleep(POLL); if (++n > SPIN_LIMIT) spin_fault(); }
}
__device__ __forceinline__ void bar_sync(int id, int n) { asm volatile("bar.sync %0, %1;" ::"r"(id), "r"(n) : "memory"); }
__device__ __forceinline__ void bar_arrive(int id, int n) { asm volatile("bar.arrive %0, %1;" ::"r"(id), "r"(n) : "memory"); }
__device__ __forceinline__ bool bar_and(int id, bool v) {
    uint32_t r;
    asm volatile("{\n.reg .pred P, Q;\nsetp.ne.u32 Q, %2, 0;\nbar.red.and.pred P, %1, 128, Q;\nselp.u32 %0, 1, 0, P;\n}" : "=r"(r) : "r"(id), "r"((uint32_t)v) : "memory");
    return r;
}
__device__ __forceinline__ void lds128(uint32_t* v, uint32_t a) { asm volatile("ld.shared.v4.b32 {%0,%1,%2,%3}, [%4];" : "=r"(v[0]), "=r"(v[1]), "=r"(v[2]), "=r"(v[3]) : "r"(a) : "memory"); }
__device__ __forceinline__ uint32_t lds32(uint32_t a) { uint32_t v; asm volatile("ld.shared.b32 %0, [%1];" : "=r"(v) : "r"(a) : "memory"); return v; }
__device__ __forceinline__ void lds64f(float* v, uint32_t a) { asm volatile("ld.shared.v2.f32 {%0,%1}, [%2];" : "=f"(v[0]), "=f"(v[1]) : "r"(a) : "memory"); }
__device__ __forceinline__ void sts128(uint32_t a, const uint32_t* v) { asm volatile("st.shared.v4.b32 [%0], {%1,%2,%3,%4};" ::"r"(a), "r"(v[0]), "r"(v[1]), "r"(v[2]), "r"(v[3]) : "memory"); }
__device__ __forceinline__ void sts64(uint32_t a, uint32_t x, uint32_t y) { asm volatile("st.shared.v2.b32 [%0], {%1,%2};" ::"r"(a), "r"(x), "r"(y) : "memory"); }
__device__ __forceinline__ void sts32(uint32_t a, uint32_t x) { asm volatile("st.shared.b32 [%0], %1;" ::"r"(a), "r"(x) : "memory"); }
__device__ __forceinline__ bool mbar_try(uint32_t b, uint32_t par) {
    uint32_t ok;
    asm volatile("{\n.reg .pred P;\nmbarrier.try_wait.parity.shared::cta.b64 P, [%1], %2;\nselp.u32 %0, 1, 0, P;\n}" : "=r"(ok) : "r"(b), "r"(par) : "memory");
    return ok;
}
__device__ __forceinline__ bool mbar_test(uint32_t b, uint32_t par) {
    uint32_t ok;
    asm volatile("{\n.reg .pred P;\nmbarrier.test_wait.parity.shared::cta.b64 P, [%1], %2;\nselp.u32 %0, 1, 0, P;\n}" : "=r"(ok) : "r"(b), "r"(par) : "memory");
    return ok;
}
__device__ __forceinline__ void mbar_wait(uint32_t b, uint32_t par) { int n = 0; while (!mbar_try(b, par)) { if (++n > SPIN_LIMIT) spin_fault(); } }
__device__ __forceinline__ void mbar_init(uint32_t b, uint32_t n) { asm volatile("mbarrier.init.shared::cta.b64 [%0], %1;" ::"r"(b), "r"(n) : "memory"); }
__device__ __forceinline__ void mbar_expect(uint32_t b, uint32_t bytes) { asm volatile("mbarrier.arrive.expect_tx.shared::cta.b64 _, [%0], %1;" ::"r"(b), "r"(bytes) : "memory"); }
__device__ __forceinline__ void mbar_arrive(uint32_t b) { asm volatile("mbarrier.arrive.shared::cta.b64 _, [%0];" ::"r"(b) : "memory"); }
__device__ __forceinline__ void mbar_arrive_cluster(uint32_t b) { asm volatile("mbarrier.arrive.shared::cluster.b64 _, [%0];" ::"r"(b) : "memory"); }
__device__ __forceinline__ void st_async1(uint32_t a, uint32_t x, uint32_t bar) {
    asm volatile("st.async.weak.shared::cluster.mbarrier::complete_tx::bytes.b32 [%0], %1, [%2];" ::"r"(a), "r"(x), "r"(bar) : "memory");
}
__device__ __forceinline__ void st_async2(uint32_t a, uint32_t x, uint32_t y, uint32_t bar) {
    asm volatile("st.async.weak.shared::cluster.mbarrier::complete_tx::bytes.v2.b32 [%0], {%1,%2}, [%3];" ::"r"(a), "r"(x), "r"(y), "r"(bar) : "memory");
}
__device__ __forceinline__ void cluster_sync() { asm volatile("barrier.cluster.arrive.aligned;\nbarrier.cluster.wait.aligned;" ::: "memory"); }
__device__ __forceinline__ void tma2d(uint32_t dst, const CUtensorMap* m, int c0, int c1, uint32_t bar) {
    asm volatile("cp.async.bulk.tensor.2d.shared::cluster.global.mbarrier::complete_tx::bytes [%0], [%1, {%2, %3}], [%4];" ::"r"(dst), "l"(m), "r"(c0), "r"(c1), "r"(bar) : "memory");
}
__device__ __forceinline__ void tma2d_mc(uint32_t dst, const CUtensorMap* m, int c0, int c1, uint32_t bar) {
    asm volatile("cp.async.bulk.tensor.2d.shared::cluster.global.mbarrier::complete_tx::bytes.multicast::cluster [%0], [%1, {%2, %3}], [%4], %5;" ::"r"(dst), "l"(m), "r"(c0), "r"(c1), "r"(bar), "h"(pair_mask()) : "memory");
}
__device__ __forceinline__ void tma3d(uint32_t dst, const CUtensorMap* m, int c0, int c1, int c2, uint32_t bar) {
    asm volatile("cp.async.bulk.tensor.3d.shared::cluster.global.mbarrier::complete_tx::bytes [%0], [%1, {%2, %3, %4}], [%5];" ::"r"(dst), "l"(m), "r"(c0), "r"(c1), "r"(c2), "r"(bar) : "memory");
}
__device__ __forceinline__ void tma3d_mc(uint32_t dst, const CUtensorMap* m, int c0, int c1, int c2, uint32_t bar) {
    asm volatile("cp.async.bulk.tensor.3d.shared::cluster.global.mbarrier::complete_tx::bytes.multicast::cluster [%0], [%1, {%2, %3, %4}], [%5], %6;" ::"r"(dst), "l"(m), "r"(c0), "r"(c1), "r"(c2), "r"(bar), "h"(pair_mask()) : "memory");
}
__device__ __forceinline__ void tma4d(uint32_t dst, const CUtensorMap* m, int c0, int c3, uint32_t bar) {
    asm volatile("cp.async.bulk.tensor.4d.shared::cluster.global.mbarrier::complete_tx::bytes [%0], [%1, {%2, 0, 0, %3}], [%4];" ::"r"(dst), "l"(m), "r"(c0), "r"(c3), "r"(bar) : "memory");
}
__device__ __forceinline__ void tma4d_mc(uint32_t dst, const CUtensorMap* m, int c0, int c3, uint32_t bar) {
    asm volatile("cp.async.bulk.tensor.4d.shared::cluster.global.mbarrier::complete_tx::bytes.multicast::cluster [%0], [%1, {%2, 0, 0, %3}], [%4], %5;" ::"r"(dst), "l"(m), "r"(c0), "r"(c3), "r"(bar), "h"(pair_mask()) : "memory");
}
__device__ __forceinline__ void tma_prefetch2d(const CUtensorMap* m, int c0, int c1) {
    asm volatile("cp.async.bulk.prefetch.tensor.2d.L2.global [%0, {%1, %2}];" ::"l"(m), "r"(c0), "r"(c1) : "memory");
}
__device__ __forceinline__ void map_prefetch(const CUtensorMap* m) { asm volatile("prefetch.tensormap [%0];" ::"l"(m) : "memory"); }
__device__ __forceinline__ void l2_prefetch(const void* src, uint32_t bytes) { asm volatile("cp.async.bulk.prefetch.L2.global [%0], %1;" ::"l"(src), "r"(bytes) : "memory"); }
__device__ __forceinline__ void bulk_g2s(uint32_t dst, const void* src, uint32_t bytes, uint32_t bar) {
    asm volatile("cp.async.bulk.shared::cluster.global.mbarrier::complete_tx::bytes [%0], [%1], %2, [%3];" ::"r"(dst), "l"(src), "r"(bytes), "r"(bar) : "memory");
}
__device__ __forceinline__ void bulk_s2g(void* dst, uint32_t src, uint32_t bytes) {
    asm volatile("cp.async.bulk.global.shared::cta.bulk_group [%0], [%1], %2;" ::"l"(dst), "r"(src), "r"(bytes) : "memory");
}
__device__ __forceinline__ void tma_store2d(const CUtensorMap* m, int c0, int c1, uint32_t src) {
    asm volatile("cp.async.bulk.tensor.2d.global.shared::cta.bulk_group [%0, {%1, %2}], [%3];" ::"l"(m), "r"(c0), "r"(c1), "r"(src) : "memory");
}
__device__ __forceinline__ void bulk_commit() { asm volatile("cp.async.bulk.commit_group;" ::: "memory"); }
__device__ __forceinline__ void bulk_wait_read() { asm volatile("cp.async.bulk.wait_group.read 0;" ::: "memory"); }
__device__ __forceinline__ void bulk_wait_all() { asm volatile("cp.async.bulk.wait_group 0;" ::: "memory"); }
__device__ __forceinline__ uint64_t mkdesc(uint32_t addr, uint32_t lbo, uint32_t sbo, uint32_t swz) {
    return (uint64_t)((addr & 0x3FFFF) >> 4) | ((uint64_t)(lbo >> 4) << 16) | ((uint64_t)(sbo >> 4) << 32) | ((uint64_t)swz << 62);
}
__device__ __forceinline__ void wg_fence() { asm volatile("wgmma.fence.sync.aligned;" ::: "memory"); }
__device__ __forceinline__ void wg_commit() { asm volatile("wgmma.commit_group.sync.aligned;" ::: "memory"); }
template <int N> __device__ __forceinline__ void wg_wait() { asm volatile("wgmma.wait_group.sync.aligned %0;" ::"n"(N) : "memory"); }
template <typename T> __device__ __forceinline__ void pin_ptr(T*& p) { asm volatile("" : "+l"(p)); }
template <int N> __device__ __forceinline__ void pin(uint32_t* d) {
#pragma unroll
    for (int i = 0; i < N; i++) asm volatile("" : "+r"(d[i])::"memory");
}
template <int N> __device__ __forceinline__ void pin(float* d) {
#pragma unroll
    for (int i = 0; i < N; i++) asm volatile("" : "+f"(d[i])::"memory");
}

template <int TA, int TB>
__device__ __forceinline__ void wgmma_ss256(float* d, uint64_t da, uint64_t db) {
    asm volatile("wgmma.mma_async.sync.aligned.m64n256k16.f32.bf16.bf16 "
        "{%0, %1, %2, %3, %4, %5, %6, %7, %8, %9, %10, %11, %12, %13, %14, %15, %16, %17, %18, %19, %20, %21, %22, %23, %24, %25, %26, %27, %28, %29, %30, %31, %32, %33, %34, %35, %36, %37, %38, %39, %40, %41, %42, %43, %44, %45, %46, %47, %48, %49, %50, %51, %52, %53, %54, %55, %56, %57, %58, %59, %60, %61, %62, %63, %64, %65, %66, %67, %68, %69, %70, %71, %72, %73, %74, %75, %76, %77, %78, %79, %80, %81, %82, %83, %84, %85, %86, %87, %88, %89, %90, %91, %92, %93, %94, %95, %96, %97, %98, %99, %100, %101, %102, %103, %104, %105, %106, %107, %108, %109, %110, %111, %112, %113, %114, %115, %116, %117, %118, %119, %120, %121, %122, %123, %124, %125, %126, %127}, %128, %129, 1, 1, 1, %130, %131;"
        : "+f"(d[0]), "+f"(d[1]), "+f"(d[2]), "+f"(d[3]), "+f"(d[4]), "+f"(d[5]), "+f"(d[6]), "+f"(d[7]), "+f"(d[8]), "+f"(d[9]), "+f"(d[10]), "+f"(d[11]), "+f"(d[12]), "+f"(d[13]), "+f"(d[14]), "+f"(d[15]), "+f"(d[16]), "+f"(d[17]), "+f"(d[18]), "+f"(d[19]), "+f"(d[20]), "+f"(d[21]), "+f"(d[22]), "+f"(d[23]), "+f"(d[24]), "+f"(d[25]), "+f"(d[26]), "+f"(d[27]), "+f"(d[28]), "+f"(d[29]), "+f"(d[30]), "+f"(d[31]), "+f"(d[32]), "+f"(d[33]), "+f"(d[34]), "+f"(d[35]), "+f"(d[36]), "+f"(d[37]), "+f"(d[38]), "+f"(d[39]), "+f"(d[40]), "+f"(d[41]), "+f"(d[42]), "+f"(d[43]), "+f"(d[44]), "+f"(d[45]), "+f"(d[46]), "+f"(d[47]), "+f"(d[48]), "+f"(d[49]), "+f"(d[50]), "+f"(d[51]), "+f"(d[52]), "+f"(d[53]), "+f"(d[54]), "+f"(d[55]), "+f"(d[56]), "+f"(d[57]), "+f"(d[58]), "+f"(d[59]), "+f"(d[60]), "+f"(d[61]), "+f"(d[62]), "+f"(d[63]), "+f"(d[64]), "+f"(d[65]), "+f"(d[66]), "+f"(d[67]), "+f"(d[68]), "+f"(d[69]), "+f"(d[70]), "+f"(d[71]), "+f"(d[72]), "+f"(d[73]), "+f"(d[74]), "+f"(d[75]), "+f"(d[76]), "+f"(d[77]), "+f"(d[78]), "+f"(d[79]), "+f"(d[80]), "+f"(d[81]), "+f"(d[82]), "+f"(d[83]), "+f"(d[84]), "+f"(d[85]), "+f"(d[86]), "+f"(d[87]), "+f"(d[88]), "+f"(d[89]), "+f"(d[90]), "+f"(d[91]), "+f"(d[92]), "+f"(d[93]), "+f"(d[94]), "+f"(d[95]), "+f"(d[96]), "+f"(d[97]), "+f"(d[98]), "+f"(d[99]), "+f"(d[100]), "+f"(d[101]), "+f"(d[102]), "+f"(d[103]), "+f"(d[104]), "+f"(d[105]), "+f"(d[106]), "+f"(d[107]), "+f"(d[108]), "+f"(d[109]), "+f"(d[110]), "+f"(d[111]), "+f"(d[112]), "+f"(d[113]), "+f"(d[114]), "+f"(d[115]), "+f"(d[116]), "+f"(d[117]), "+f"(d[118]), "+f"(d[119]), "+f"(d[120]), "+f"(d[121]), "+f"(d[122]), "+f"(d[123]), "+f"(d[124]), "+f"(d[125]), "+f"(d[126]), "+f"(d[127])
        : "l"(da), "l"(db), "n"(TA), "n"(TB));
}
template <int TA, int TB>
__device__ __forceinline__ void wgmma_ss256_first(float* d, uint64_t da, uint64_t db) {
    asm volatile("wgmma.mma_async.sync.aligned.m64n256k16.f32.bf16.bf16 "
        "{%0, %1, %2, %3, %4, %5, %6, %7, %8, %9, %10, %11, %12, %13, %14, %15, %16, %17, %18, %19, %20, %21, %22, %23, %24, %25, %26, %27, %28, %29, %30, %31, %32, %33, %34, %35, %36, %37, %38, %39, %40, %41, %42, %43, %44, %45, %46, %47, %48, %49, %50, %51, %52, %53, %54, %55, %56, %57, %58, %59, %60, %61, %62, %63, %64, %65, %66, %67, %68, %69, %70, %71, %72, %73, %74, %75, %76, %77, %78, %79, %80, %81, %82, %83, %84, %85, %86, %87, %88, %89, %90, %91, %92, %93, %94, %95, %96, %97, %98, %99, %100, %101, %102, %103, %104, %105, %106, %107, %108, %109, %110, %111, %112, %113, %114, %115, %116, %117, %118, %119, %120, %121, %122, %123, %124, %125, %126, %127}, %128, %129, 0, 1, 1, %130, %131;"
        : "=f"(d[0]), "=f"(d[1]), "=f"(d[2]), "=f"(d[3]), "=f"(d[4]), "=f"(d[5]), "=f"(d[6]), "=f"(d[7]), "=f"(d[8]), "=f"(d[9]), "=f"(d[10]), "=f"(d[11]), "=f"(d[12]), "=f"(d[13]), "=f"(d[14]), "=f"(d[15]), "=f"(d[16]), "=f"(d[17]), "=f"(d[18]), "=f"(d[19]), "=f"(d[20]), "=f"(d[21]), "=f"(d[22]), "=f"(d[23]), "=f"(d[24]), "=f"(d[25]), "=f"(d[26]), "=f"(d[27]), "=f"(d[28]), "=f"(d[29]), "=f"(d[30]), "=f"(d[31]), "=f"(d[32]), "=f"(d[33]), "=f"(d[34]), "=f"(d[35]), "=f"(d[36]), "=f"(d[37]), "=f"(d[38]), "=f"(d[39]), "=f"(d[40]), "=f"(d[41]), "=f"(d[42]), "=f"(d[43]), "=f"(d[44]), "=f"(d[45]), "=f"(d[46]), "=f"(d[47]), "=f"(d[48]), "=f"(d[49]), "=f"(d[50]), "=f"(d[51]), "=f"(d[52]), "=f"(d[53]), "=f"(d[54]), "=f"(d[55]), "=f"(d[56]), "=f"(d[57]), "=f"(d[58]), "=f"(d[59]), "=f"(d[60]), "=f"(d[61]), "=f"(d[62]), "=f"(d[63]), "=f"(d[64]), "=f"(d[65]), "=f"(d[66]), "=f"(d[67]), "=f"(d[68]), "=f"(d[69]), "=f"(d[70]), "=f"(d[71]), "=f"(d[72]), "=f"(d[73]), "=f"(d[74]), "=f"(d[75]), "=f"(d[76]), "=f"(d[77]), "=f"(d[78]), "=f"(d[79]), "=f"(d[80]), "=f"(d[81]), "=f"(d[82]), "=f"(d[83]), "=f"(d[84]), "=f"(d[85]), "=f"(d[86]), "=f"(d[87]), "=f"(d[88]), "=f"(d[89]), "=f"(d[90]), "=f"(d[91]), "=f"(d[92]), "=f"(d[93]), "=f"(d[94]), "=f"(d[95]), "=f"(d[96]), "=f"(d[97]), "=f"(d[98]), "=f"(d[99]), "=f"(d[100]), "=f"(d[101]), "=f"(d[102]), "=f"(d[103]), "=f"(d[104]), "=f"(d[105]), "=f"(d[106]), "=f"(d[107]), "=f"(d[108]), "=f"(d[109]), "=f"(d[110]), "=f"(d[111]), "=f"(d[112]), "=f"(d[113]), "=f"(d[114]), "=f"(d[115]), "=f"(d[116]), "=f"(d[117]), "=f"(d[118]), "=f"(d[119]), "=f"(d[120]), "=f"(d[121]), "=f"(d[122]), "=f"(d[123]), "=f"(d[124]), "=f"(d[125]), "=f"(d[126]), "=f"(d[127])
        : "l"(da), "l"(db), "n"(TA), "n"(TB));
}
template <int TA, int TB>
__device__ __forceinline__ void wgmma_ss128(float* d, uint64_t da, uint64_t db) {
    asm volatile("wgmma.mma_async.sync.aligned.m64n128k16.f32.bf16.bf16 "
        "{%0, %1, %2, %3, %4, %5, %6, %7, %8, %9, %10, %11, %12, %13, %14, %15, %16, %17, %18, %19, %20, %21, %22, %23, %24, %25, %26, %27, %28, %29, %30, %31, %32, %33, %34, %35, %36, %37, %38, %39, %40, %41, %42, %43, %44, %45, %46, %47, %48, %49, %50, %51, %52, %53, %54, %55, %56, %57, %58, %59, %60, %61, %62, %63}, %64, %65, 1, 1, 1, %66, %67;"
        : "+f"(d[0]), "+f"(d[1]), "+f"(d[2]), "+f"(d[3]), "+f"(d[4]), "+f"(d[5]), "+f"(d[6]), "+f"(d[7]), "+f"(d[8]), "+f"(d[9]), "+f"(d[10]), "+f"(d[11]), "+f"(d[12]), "+f"(d[13]), "+f"(d[14]), "+f"(d[15]), "+f"(d[16]), "+f"(d[17]), "+f"(d[18]), "+f"(d[19]), "+f"(d[20]), "+f"(d[21]), "+f"(d[22]), "+f"(d[23]), "+f"(d[24]), "+f"(d[25]), "+f"(d[26]), "+f"(d[27]), "+f"(d[28]), "+f"(d[29]), "+f"(d[30]), "+f"(d[31]), "+f"(d[32]), "+f"(d[33]), "+f"(d[34]), "+f"(d[35]), "+f"(d[36]), "+f"(d[37]), "+f"(d[38]), "+f"(d[39]), "+f"(d[40]), "+f"(d[41]), "+f"(d[42]), "+f"(d[43]), "+f"(d[44]), "+f"(d[45]), "+f"(d[46]), "+f"(d[47]), "+f"(d[48]), "+f"(d[49]), "+f"(d[50]), "+f"(d[51]), "+f"(d[52]), "+f"(d[53]), "+f"(d[54]), "+f"(d[55]), "+f"(d[56]), "+f"(d[57]), "+f"(d[58]), "+f"(d[59]), "+f"(d[60]), "+f"(d[61]), "+f"(d[62]), "+f"(d[63])
        : "l"(da), "l"(db), "n"(TA), "n"(TB));
}
template <int TA, int TB>
__device__ __forceinline__ void wgmma_ss128_first(float* d, uint64_t da, uint64_t db) {
    asm volatile("wgmma.mma_async.sync.aligned.m64n128k16.f32.bf16.bf16 "
        "{%0, %1, %2, %3, %4, %5, %6, %7, %8, %9, %10, %11, %12, %13, %14, %15, %16, %17, %18, %19, %20, %21, %22, %23, %24, %25, %26, %27, %28, %29, %30, %31, %32, %33, %34, %35, %36, %37, %38, %39, %40, %41, %42, %43, %44, %45, %46, %47, %48, %49, %50, %51, %52, %53, %54, %55, %56, %57, %58, %59, %60, %61, %62, %63}, %64, %65, 0, 1, 1, %66, %67;"
        : "=f"(d[0]), "=f"(d[1]), "=f"(d[2]), "=f"(d[3]), "=f"(d[4]), "=f"(d[5]), "=f"(d[6]), "=f"(d[7]), "=f"(d[8]), "=f"(d[9]), "=f"(d[10]), "=f"(d[11]), "=f"(d[12]), "=f"(d[13]), "=f"(d[14]), "=f"(d[15]), "=f"(d[16]), "=f"(d[17]), "=f"(d[18]), "=f"(d[19]), "=f"(d[20]), "=f"(d[21]), "=f"(d[22]), "=f"(d[23]), "=f"(d[24]), "=f"(d[25]), "=f"(d[26]), "=f"(d[27]), "=f"(d[28]), "=f"(d[29]), "=f"(d[30]), "=f"(d[31]), "=f"(d[32]), "=f"(d[33]), "=f"(d[34]), "=f"(d[35]), "=f"(d[36]), "=f"(d[37]), "=f"(d[38]), "=f"(d[39]), "=f"(d[40]), "=f"(d[41]), "=f"(d[42]), "=f"(d[43]), "=f"(d[44]), "=f"(d[45]), "=f"(d[46]), "=f"(d[47]), "=f"(d[48]), "=f"(d[49]), "=f"(d[50]), "=f"(d[51]), "=f"(d[52]), "=f"(d[53]), "=f"(d[54]), "=f"(d[55]), "=f"(d[56]), "=f"(d[57]), "=f"(d[58]), "=f"(d[59]), "=f"(d[60]), "=f"(d[61]), "=f"(d[62]), "=f"(d[63])
        : "l"(da), "l"(db), "n"(TA), "n"(TB));
}
template <int TB>
__device__ __forceinline__ void wgmma_rs128(float* d, const uint32_t* a, uint64_t db, uint32_t acc) {
    asm volatile("{\n.reg .pred P;\nsetp.ne.u32 P, %69, 0;\nwgmma.mma_async.sync.aligned.m64n128k16.f32.bf16.bf16 "
        "{%0, %1, %2, %3, %4, %5, %6, %7, %8, %9, %10, %11, %12, %13, %14, %15, %16, %17, %18, %19, %20, %21, %22, %23, %24, %25, %26, %27, %28, %29, %30, %31, %32, %33, %34, %35, %36, %37, %38, %39, %40, %41, %42, %43, %44, %45, %46, %47, %48, %49, %50, %51, %52, %53, %54, %55, %56, %57, %58, %59, %60, %61, %62, %63}, {%64, %65, %66, %67}, %68, P, 1, 1, %70;\n}"
        : "+f"(d[0]), "+f"(d[1]), "+f"(d[2]), "+f"(d[3]), "+f"(d[4]), "+f"(d[5]), "+f"(d[6]), "+f"(d[7]), "+f"(d[8]), "+f"(d[9]), "+f"(d[10]), "+f"(d[11]), "+f"(d[12]), "+f"(d[13]), "+f"(d[14]), "+f"(d[15]), "+f"(d[16]), "+f"(d[17]), "+f"(d[18]), "+f"(d[19]), "+f"(d[20]), "+f"(d[21]), "+f"(d[22]), "+f"(d[23]), "+f"(d[24]), "+f"(d[25]), "+f"(d[26]), "+f"(d[27]), "+f"(d[28]), "+f"(d[29]), "+f"(d[30]), "+f"(d[31]), "+f"(d[32]), "+f"(d[33]), "+f"(d[34]), "+f"(d[35]), "+f"(d[36]), "+f"(d[37]), "+f"(d[38]), "+f"(d[39]), "+f"(d[40]), "+f"(d[41]), "+f"(d[42]), "+f"(d[43]), "+f"(d[44]), "+f"(d[45]), "+f"(d[46]), "+f"(d[47]), "+f"(d[48]), "+f"(d[49]), "+f"(d[50]), "+f"(d[51]), "+f"(d[52]), "+f"(d[53]), "+f"(d[54]), "+f"(d[55]), "+f"(d[56]), "+f"(d[57]), "+f"(d[58]), "+f"(d[59]), "+f"(d[60]), "+f"(d[61]), "+f"(d[62]), "+f"(d[63])
        : "r"(a[0]), "r"(a[1]), "r"(a[2]), "r"(a[3]), "l"(db), "r"(acc), "n"(TB));
}
template <int TB>
__device__ __forceinline__ void wgmma_rs64(float* d, const uint32_t* a, uint64_t db, uint32_t acc) {
    asm volatile("{\n.reg .pred P;\nsetp.ne.u32 P, %37, 0;\nwgmma.mma_async.sync.aligned.m64n64k16.f32.bf16.bf16 "
        "{%0, %1, %2, %3, %4, %5, %6, %7, %8, %9, %10, %11, %12, %13, %14, %15, %16, %17, %18, %19, %20, %21, %22, %23, %24, %25, %26, %27, %28, %29, %30, %31}, {%32, %33, %34, %35}, %36, P, 1, 1, %38;\n}"
        : "+f"(d[0]), "+f"(d[1]), "+f"(d[2]), "+f"(d[3]), "+f"(d[4]), "+f"(d[5]), "+f"(d[6]), "+f"(d[7]), "+f"(d[8]), "+f"(d[9]), "+f"(d[10]), "+f"(d[11]), "+f"(d[12]), "+f"(d[13]), "+f"(d[14]), "+f"(d[15]), "+f"(d[16]), "+f"(d[17]), "+f"(d[18]), "+f"(d[19]), "+f"(d[20]), "+f"(d[21]), "+f"(d[22]), "+f"(d[23]), "+f"(d[24]), "+f"(d[25]), "+f"(d[26]), "+f"(d[27]), "+f"(d[28]), "+f"(d[29]), "+f"(d[30]), "+f"(d[31])
        : "r"(a[0]), "r"(a[1]), "r"(a[2]), "r"(a[3]), "l"(db), "r"(acc), "n"(TB));
}
template <int TB>
__device__ __forceinline__ void wgmma_rs16(float* d, const uint32_t* a, uint64_t db, uint32_t acc) {
    asm volatile("{\n.reg .pred P;\nsetp.ne.u32 P, %13, 0;\nwgmma.mma_async.sync.aligned.m64n16k16.f32.bf16.bf16 "
        "{%0, %1, %2, %3, %4, %5, %6, %7}, {%8, %9, %10, %11}, %12, P, 1, 1, %14;\n}"
        : "+f"(d[0]), "+f"(d[1]), "+f"(d[2]), "+f"(d[3]), "+f"(d[4]), "+f"(d[5]), "+f"(d[6]), "+f"(d[7])
        : "r"(a[0]), "r"(a[1]), "r"(a[2]), "r"(a[3]), "l"(db), "r"(acc), "n"(TB));
}

__device__ __forceinline__ uint32_t delay_loop(int n, uint32_t x0) {
    uint32_t z;
    asm volatile("{\n.reg .pred P;\n.reg .u32 c, x;\nmov.u32 c, %1;\nmov.u32 x, %2;\nDL: mad.lo.u32 x, x, 1664525, 1013904223;\nadd.u32 c, c, -1;\nsetp.gt.s32 P, c, 0;\n@P bra DL;\n"
                 "setp.eq.u32 P, x, 0x7fffffff;\nselp.u32 %0, 16, 0, P;\n}" : "=r"(z) : "r"(n), "r"(x0) : "memory");
    return z;
}
__device__ __forceinline__ uint32_t gtime() { uint32_t t; asm volatile("mov.u32 %0, %%globaltimer_lo;" : "=r"(t)); return t; }
__device__ __forceinline__ void wait_time(uint32_t t, uint32_t sb) { while ((int32_t)(gtime() - t) < (int32_t)delay_loop(2, sb)) {} }
__device__ __forceinline__ uint32_t tpc_gpc(uint32_t t) { return t < 32 ? t & 7 : t < 60 ? (t - 32) % 7 + 1 : (t - 54) & 7; }
__device__ __forceinline__ uint32_t latest_stamp(const uint32_t* p, uint32_t seq, uint32_t ref, int backoff, uint32_t sb) {
    for (int n = 0;; n++) {
        uint32_t bad = 0; int32_t m = INT32_MIN;
#pragma unroll
        for (int i = 0; i < 3; i++) { const uint32_t v = ld_relaxed1(p + i * 256); bad |= (v ^ seq) & 31u; m = max(m, (int32_t)(v - (ref << 5)) >> 5); }
        if (__all_sync(0xffffffffu, bad == 0)) return ref + __reduce_max_sync(0xffffffffu, m);
        wait_time(gtime() + backoff, sb);
        if (n > SPIN_LIMIT) spin_fault();
    }
}
__device__ __forceinline__ void release_at(uint32_t t, uint32_t sb, uint32_t bar, int lane) {
    wait_time(t, sb);
    if (lane == 0) mbar_arrive(sb + bar);
}
__host__ __device__ constexpr int frag_word(int u, int f) { return (u == 0 ? 0 : u < 3 ? 3 * u - 1 : u == 3 ? 14 : 3 * u - 4) + f; }
__host__ __device__ constexpr int word_col(int e) { return ((0x32FED987CBA65410ull >> (4 * e)) & 14) * 64 + ((0x32FED987CBA65410ull >> (4 * e)) & 1) * 8; }

constexpr uint32_t CLEAR_LO = 0xFE000000u, CLEAR_HI = 0x5A7FEFEFu;
__device__ __forceinline__ void clear_slot(const Params& P, int slot, int cta, int lane) {
    const int i = cta * 2 + (lane >> 3), x = i & 63;
    if (lane < 16) st_relaxed4(P.gm + slot * M_SLOT + (x >> 1) * 1024 + (x & 1) * 256 + (i >> 7) * 512 + ((i >> 6) & 1) * 128 + (lane & 7) * 16, CLEAR_LO, CLEAR_HI, CLEAR_LO, CLEAR_HI);
    st_relaxed4(g_f + slot * F_SLOT + cta * 512 + lane * 16, 0, 0, 0, 0);
}
__device__ __forceinline__ void mem0_max(const Params& P, uint32_t sb, int tid) {
    uint32_t m = 0;
#pragma unroll
    for (int i = 0; i < 4; i++) {
        const uint4 x = __ldg((const uint4*)P.mem0 + i * 256 + tid);
        m = __vmaxu2(__vmaxu2(__vmaxu2(x.x & 0x7fff7fffu, x.y & 0x7fff7fffu), __vmaxu2(x.z & 0x7fff7fffu, x.w & 0x7fff7fffu)), m);
    }
    sts32(sb + S_COEF + (tid >> 5) * 4, __reduce_max_sync(0xffffffffu, max(m >> 16, m & 0xffffu)));
    bar_arrive(7, 288);
}
__device__ __forceinline__ uint32_t pack_mem0(const Params& P, uint32_t sb, int cta, int lane) {
    bar_sync(7, 288);
    const uint32_t e = __reduce_max_sync(0xffffffffu, lds32(sb + S_COEF + (lane & 7) * 4)) >> 7;
    if (e < 64 || e > 192) return 0x3F803F80u;
    const int i = cta * 2 + (lane >> 4), u = (i >> 5), x = i & 63, L = (i & 3) * 8 + ((lane & 15) >> 1);
    uint64_t w = 32;
#pragma unroll
    for (int f = 0; f < 3; f++) if (f < 2 || u % 3) {
        const float v = __bfloat162float(P.mem0[(L >> 2) * 1024 + word_col(frag_word(u, f)) + ((i >> 2) & 7) * 16 + (L & 3) * 2 + (lane & 1)]);
        w += (uint64_t)(int64_t)__float2int_rn(v * __uint_as_float((271 - e) << 23)) << (45 - 19 * f);
    }
    st_relaxed2(P.gm + 7 * M_SLOT + (x >> 1) * 1024 + (x & 1) * 256 + (i >> 7) * 512 + ((i >> 6) & 1) * 128 + (lane & 15) * 8, (uint32_t)w, (uint32_t)(w >> 32));
    return (e - 30) * 0x00800080u;
}
__device__ __forceinline__ void pacer(const Params& P, const uint32_t sb, const int lane) {
    constexpr uint32_t base = 2;
    int cta = lds32(sb + S_CTA);
#pragma unroll 1
    for (int i = 0; i < 8; i++) clear_slot(P, i, cta, lane);
    __syncwarp();
    if (lane == 0) { uint32_t smid; asm("mov.u32 %0, %%smid;" : "=r"(smid)); st_relaxed1(g_hint + 6144 + cta, smid >> 1); }
    sts32(sb + S_EPOCH + 4, pack_mem0(P, sb, cta, lane));
    SSTAMP(0, lane == 0)
    fence_release();
    __syncwarp();
    float rate = 0.58f;
    uint32_t c0 = 0;
#pragma unroll 1
    for (int s = -1; s < 63; s++) {
        cta = lds32(sb + S_CTA);
        const int pair = cta >> 1;
        const uint32_t ahead = s > 0 ? (uint32_t)(rate * (float)(pair >= 32 ? P.dc - P.dv : P.dc)) : 0;
        mbar_wait(sb + B_GO, s & 1);
        SSTAMP(10, lane == 0 && s == 0)
        const uint32_t t0 = gtime();
        if (lane < 4) st_relaxed1(g_hint + ((s & 1) * 4 + lane) * 768 + (cta >> 5) * 256 + (cta & 31), (t0 + ahead + (lds32(sb + S_REDO) == s ? P.extra : 0)) << 5 | ((base + s) & 31u));
        wait_time(t0 + (s < 0 ? 2000 : s == 0 && pair >= 16 ? P.ds0 : P.ds), sb);
        const uint32_t t = latest_stamp(g_hint + ((s & 1) * 4 + (pair & 3)) * 768 + lane, base + s, t0, P.back, sb);
        if (s < 0) {
            SSTAMP(2, lane == 0)
            fence_acquire();
            const uint32_t g = tpc_gpc(ld_relaxed1(g_hint + 6144 + (lane & 15) * 2));
            const uint32_t key = (__popc(__match_any_sync(0xffffffffu, g)) > 4 ? 0 : g + 1) * 16 + (lane & 15);
            const uint32_t tail = (pair & 48) + __popc(__ballot_sync(0xffffffffu, key < __shfl_sync(0xffffffffu, key, pair & 15))) / 2;
            mbar_wait(sb + B_INIT, 0);
            SSTAMP(4, lane == 0)
            sts32(sb + S_TAIL, tail);
            if (lane < 8) sts32(sb + S_SC + lane * 4, lds32(sb + S_EPOCH + 4));
            __syncwarp();
        }
        release_at(t + P.da, sb, B_RELA, lane);
        SSTAMP(11, lane == 0 && s == 0)
        release_at(t + P.db, sb, B_RELB, lane);
        {
            const uint32_t c1 = clock(), g1 = gtime();
            if (s > 1) rate += P.alpha * (__fdividef((float)(g1 - lds32(sb + S_EPOCH + 4)), (float)(c1 - c0)) - rate);
            __syncwarp();
            c0 = c1; sts32(sb + S_EPOCH + 4, g1);
        }
        if (s == 61) {
            sts32(sb + S_COEF, ITEM(ITEM_OFF(lds32(sb + S_TAIL)) + NPRE + 1) + (uint32_t)(uintptr_t)P.out);
            if (lane < M_CQ) map_prefetch(&P.tm[lane]);
        }
    }
}
__device__ __forceinline__ uint32_t xor_or(uint32_t a, uint32_t b, uint32_t t) { uint32_t d; asm("lop3.b32 %0, %1, %2, %3, 0x7E;" : "=r"(d) : "r"(a), "r"(b), "r"(t)); return d; }
__device__ __forceinline__ bool tags_ok(uint32_t bad) { return __all_sync(0xffffffffu, (bad & 1) == 0); }
#define RETRY(k)
#define RETRY_STAT(a, b)
#define UNIT_STAT(u0)
#define SFENCE() asm volatile("pmevent 1;" ::: "memory")
#define PF1 10
static_assert(NS == 24, "fragment residency");
__host__ __device__ constexpr bool in_smem(int n) { return n < 4 || n == 12 || n == 13; }
__host__ __device__ constexpr int unit_pos(int n) { return n < 4 ? n : n < 12 ? n - 4 : n < 14 ? n - 8 : n - 6; }

__host__ __device__ constexpr int fill_unit(int q) { return q < 4 ? q : q < 6 ? q + 8 : q < 14 ? q - 2 : q; }
__host__ __device__ constexpr int frag_off(int q) { return (q >> 2) * 16384 + ((q >> 1) & 1) * 8192 + (q & 1) * 512; }

constexpr uint32_t QBITS = 0x4B002000u;
constexpr uint64_t W_BIAS = ((uint64_t)QBITS << 45) + ((uint64_t)QBITS << 26) + (uint32_t)(QBITS << 7), W_CLEAR = 0 - 32 * W_BIAS;
static_assert(W_CLEAR == ((uint64_t)CLEAR_HI << 32 | CLEAR_LO), "clear value");
__host__ __device__ constexpr int unit_off(int u) { return (u & 1) * 16384 + (u >> 2) * 512 + ((u >> 1) & 1) * 128; }
__device__ __forceinline__ void red_add64(const uint8_t* p, uint64_t v) { asm volatile("red.relaxed.gpu.global.add.u64 [%0], %1;" ::"l"(p), "l"(v) : "memory"); }
template <int NF>
__device__ __forceinline__ uint64_t encode(const float* x, float S, uint32_t two26, uint32_t& bad) {
    uint32_t b[3];
#pragma unroll
    for (int i = 0; i < 3; i++) b[i] = i < NF ? __float_as_uint(fmaf(x[i], S, 8396800.f)) : QBITS;
    bad = xor_or(b[0], b[1], 0x4B000000u) | (NF == 3 ? b[2] ^ 0x4B000000u : 0);
    uint64_t w;
    asm("{\n.reg .b64 t;\nmov.b64 t, {%2, %3};\nmad.wide.u32 %0, %1, %4, t;\n}" : "=l"(w) : "r"(b[1]), "r"(b[2] << 7), "r"(b[0] << 13), "r"(two26));
    return w;
}
template <int NF>
__device__ __forceinline__ void emit(uint64_t* w, const float (*x)[3], const float* S, uint32_t two26, uint32_t lim, const uint8_t* p) {
    uint32_t bad[2];
    w[0] = encode<NF>(x[0], S[0], two26, bad[0]); w[1] = encode<NF>(x[1], S[1], two26, bad[1]);
    const bool ok = (bad[0] | bad[1]) < lim;
    w[0] |= ok; w[1] |= ok;
    red_add64(p, w[0]); red_add64(p + 1024, w[1]);
}
template <int NF>
__device__ __forceinline__ void repair(const uint64_t* w, const float (*x)[3], const float* S, const uint8_t* p, const uint8_t* pf) {
    if (!(w[0] & 1)) {
#pragma unroll
        for (int j = 0; j < 2; j++) {
            const float T = S[j] * 8192.f;
            asm volatile("red.relaxed.gpu.global.add.v4.f32 [%0], {%1,%2,%3,%4};" ::"l"(pf + j * 512), "f"(x[j][0] * T), "f"(x[j][1] * T), "f"(NF == 3 ? x[j][2] * T : 0.f), "f"(0.f) : "memory");
        }
        fence_release();
#pragma unroll
        for (int j = 0; j < 2; j++) {
            asm volatile("red.relaxed.gpu.global.or.b64 [%0], 64;" ::"l"(p + j * 1024) : "memory");
            red_add64(p + j * 1024, W_BIAS + 1 - w[j]);
        }
    }
    __syncwarp();
}
__device__ __forceinline__ void ld_words(uint32_t* v, const uint8_t* p) {
    asm volatile("{\n.reg .b64 a, b;\nld.relaxed.gpu.global.L1::no_allocate.v2.b64 {a, b}, [%4];\nmov.b64 {%0,%1}, a;\nmov.b64 {%2,%3}, b;\n}" : "=r"(v[0]), "=r"(v[1]), "=r"(v[2]), "=r"(v[3]) : "l"(p) : "memory");
}
__device__ __forceinline__ float field(const uint32_t* w, int f) { return __int2float_rn((int)(f == 0 ? w[1] : f == 1 ? __funnelshift_l(w[0], w[1], 19) : w[0] << 6)); }
template <int U>
__device__ __forceinline__ void decode(uint32_t* b, const uint32_t* v) {
#pragma unroll
    for (int f = 0; f < (U % 3 ? 3 : 2); f++) b[frag_word(U, f)] = pack2(field(v, f), field(v + 2, f));
}
__device__ __forceinline__ uint32_t status(const uint32_t (*v)[4], uint32_t c32) { return xor_or(v[0][0], v[0][2], c32) | xor_or(v[1][0], v[1][2], c32) | xor_or(v[2][0], v[2][2], c32); }
__device__ __forceinline__ void gather_slow(const Params& P, uint32_t* b, const uint8_t* pm, int s, int warp, uint32_t ln, uint32_t u2) {
    if (s == 0 && u2 == 0x3F803F80u) {
#pragma unroll
        for (int i = 0; i < 16; i++) b[i] = __ldg((const uint32_t*)(P.mem0 + (ln >> 2) * 1024 + word_col(i) + warp * 16 + (ln & 3) * 2));
        return;
    }
    uint32_t v[6][4], st;
    for (int n = 0;; n++) {
#pragma unroll
        for (int u = 0; u < 6; u++) ld_words(v[u], pm + unit_off(u));
        st = status(v, 32) | status(v + 3, 32);
        if (!__any_sync(0xffffffffu, st & 32)) break;
        __nanosleep(200);
        if (n > SPIN_LIMIT) spin_fault();
    }
    const bool side = __any_sync(0xffffffffu, st & 64);
    if (side) fence_acquire();
    const uint8_t* pf = g_f + ((s + 7) & 7) * F_SLOT + warp * 1024 + ln * 32;
#pragma unroll
    for (int u = 0; u < 6; u++) {
        float x[2][4] = {};
#pragma unroll
        for (int k = 0; k < 2; k++)
            asm volatile("{\n.reg .pred P;\nsetp.ne.u32 P, %5, 0;\n@P ld.relaxed.gpu.global.v4.f32 {%0,%1,%2,%3}, [%4];\n}"
                         : "+f"(x[k][0]), "+f"(x[k][1]), "+f"(x[k][2]), "+f"(x[k][3]) : "l"(pf + u * 8192 + k * 16), "r"((uint32_t)side) : "memory");
#pragma unroll
        for (int f = 0; f < (u % 3 ? 3 : 2); f++) b[frag_word(u, f)] = pack2(field(v[u], f) + x[0][f], field(v[u] + 2, f) + x[1][f]);
    }
}
__device__ __forceinline__ uint32_t max_abs2(uint32_t a, uint32_t b) { uint32_t d; asm("max.NaN.xorsign.abs.bf16x2 %0, %1, %2;" : "=r"(d) : "r"(a), "r"(b)); return d; }
__device__ __forceinline__ uint32_t max6(const uint32_t* b) {
    const uint32_t m = max_abs2(max_abs2(max_abs2(b[0], b[1]), max_abs2(b[2], b[3])), max_abs2(b[4], b[5]));
    return max(m & 0x7fff0000u, (m << 16) & 0x7fff0000u);
}

template <bool TR>
__device__ __forceinline__ void put_partials(uint32_t a, const float* x, const float* y) {
    if (TR) stsm4t(a, pack2(x[0], x[1]), pack2(x[2], x[3]), pack2(y[0], y[1]), pack2(y[2], y[3]));
    else stsm4(a, pack2(x[0], x[1]), pack2(x[2], x[3]), pack2(y[0], y[1]), pack2(y[2], y[3]));
}
__device__ __forceinline__ void reduce_load(uint32_t (*x)[4], uint32_t a) { ldsm4t(x[0], a); ldsm4t(x[1], a + 512); }
__device__ __forceinline__ uint32_t reduce8(const uint32_t (*x)[4], uint32_t l8, uint32_t u2) {
    uint32_t p[2];
#pragma unroll
    for (int i = 0; i < 2; i++) {
        float d[4] = {};
        mma16816(d, x[i][0], x[i][1], x[i][2], x[i][3], (l8 & 32) ? 0u : u2, (l8 & 32) ? u2 : 0u);
        p[i] = pack2((l8 & 8) ? d[2] : d[0], (l8 & 8) ? d[3] : d[1]);
    }
    return (l8 & 16) ? p[1] : p[0];
}
__device__ __forceinline__ void score_half(float (*a)[4], const uint32_t (*qa)[4], const uint32_t (*kf)[4]) {
#pragma unroll
    for (int w = 0; w < 2; w++) {
        mma16816(a[w], qa[w][0], qa[w][1], qa[w][2], qa[w][3], kf[w][0], kf[w][1]);
        mma16816(a[2 + w], qa[w][0], qa[w][1], qa[w][2], qa[w][3], kf[w][2], kf[w][3]);
    }
}
__device__ __forceinline__ void score_sum(float* S, const float (*a)[4]) {
    S[0] = (a[0][0] + a[1][0]) + (a[2][2] + a[3][2]);
    S[1] = (a[0][1] + a[1][1]) + (a[2][3] + a[3][3]);
}
__device__ __forceinline__ float quad_max(float m) {
    m = fmaxf(m, __shfl_xor_sync(0xffffffffu, m, 1));
    return fmaxf(m, __shfl_xor_sync(0xffffffffu, m, 2));
}

#define ISTAMP(i)
__device__ __forceinline__ float next_scale(uint32_t sb, int slot, int warp, uint32_t u2) {
    uint32_t x[2][4];
    lds128(x[0], sb + S_MX + slot * 32); lds128(x[1], sb + S_MX + slot * 32 + 16);
    const uint32_t mx = max(max(max(x[0][0], x[0][1]), max(x[0][2], x[0][3])), max(max(x[1][0], x[1][1]), max(x[1][2], x[1][3])));
    const float top = fminf(fmaxf(__uint_as_float(mx) * bf_hi(u2), 0x1p-40f), 0x1p40f) * (1.f / (12288.f * 8192.f));
    const uint32_t un = pack2(top, top);
    sts32(sb + S_SC + warp * 4, un);
    return rcp(bf_hi(un) * 8192.f);
}
#define NEARLY 1
#define U3POS 1
#define VPOS 1
#define ROT 0
#define BPOS 1
#define ONLINE 0
#define NBAR 1
#define ORD3 0
#define F2 1
#define EARLY 0
#define TK 0
#define RPOS 1
#define AF 0
#define AFENCE(i) if ((AF >> (i)) & 1) SFENCE();
#define FPOS 99
#define PACE 1
#define PF2 12
__host__ __device__ constexpr int w2_t(int i) { return i < 16 ? i & 1 : 2; }
__host__ __device__ constexpr int w2_k(int i) { return i < 16 ? i >> 1 : i - 16; }
template <typename G>
__device__ __forceinline__ void load_weights(uint32_t (*wr)[4], const uint32_t sb, const int warp, const int lane, G stores_read) {
    const uint32_t frag = sb + warp * 1024 + (lane >> 4) * 8192 + (lane & 7) * 128 + ((((lane >> 3) & 1) ^ (lane & 7)) << 4);
    const uint32_t rel = mapa(sb + B_EMPTY, cluster_rank() ^ (lane & 1));
#define RELEASE(st) { fence_async_smem(); __syncwarp(); if (lane < 2) mbar_arrive_cluster(rel + (st) * 8); }
    mbar_wait(sb + B_FULL, 0); mbar_wait(sb + B_FULL + 8, 0);
    RELEASE(0) RELEASE(1)
#pragma unroll
    for (int st = 2; st < 4; st++) {
        mbar_wait(sb + B_FULL + st * 8, 0);
        ISTAMP(st - 2)
#pragma unroll
        for (int f = 0; f < 12; f++) ldsm4t(wr[st * 12 - 24 + f], (frag ^ ((f & 3) << 5)) + st * STAGE + (f >> 2) * 16384);
        RELEASE(st)
    }
#pragma unroll 2
    for (int u = 0; u < 6; u++) {
        uint32_t x[4][4];
#pragma unroll
        for (int i = 0; i < 4; i++) lds128(x[i], (frag ^ (i << 5)) + u * 16384);
        __syncwarp();
#pragma unroll
        for (int i = 0; i < 4; i++) sts128(sb + warp * 1024 + lane * 16 + u * 16384 + frag_off(i), x[i]);
    }
    stores_read();
    mbar_wait(sb + B_FULL, 1); mbar_wait(sb + B_FULL + 8, 1);
    RELEASE(0) RELEASE(1)
#pragma unroll
    for (int st = 2; st < 4; st++) {
        mbar_wait(sb + B_FULL + st * 8, 1);
#pragma unroll
        for (int f = 0; f < (st == 2 ? 12 : 4); f++) ldsm4t(wr[st * 12 + f], (frag ^ ((f & 3) << 5)) + st * STAGE + (f >> 2) * 16384);
        RELEASE(st)
    }
    ISTAMP(2)
    bar_sync(1, 256);
    if (warp == 7 && lane < 3) mbar_arrive_cluster(mapa(sb + B_INIT, (cluster_rank() & 1) + lane * 2));
}
template <int ROLE>
__device__ __forceinline__ void chain_role(const Params& P, const uint32_t (*wr)[4], const uint32_t sb, const int h, const int warp, const int lane) {
    constexpr int NU = ROLE == 0 ? 2 : 3;
    const bool att = ROLE == 0 && warp < 4;
    uint32_t l8 = opq(sb + lane * 8, lane);
#define PERSIST() { mbar_wait(sb + B_KVGO, slot ^ 1); const uint32_t pa_ = ((l8 - sb) >> 1) + (sb + S_QX + warp * 128); sts32(pa_, r0); sts32(pa_ + 1024, r1); \
                    fence_async_smem(); __syncwarp(); if (l8 == sb) mbar_arrive(sb + B_PERS); }
    if (ROLE) sts32(sb + S_SX + warp * 128 + lane * 4, warp >= 2 ? 0 : (lane & 1) ? CLEAR_HI : CLEAR_LO);
    const uint32_t rdelta = __shfl_sync(0xffffffffu, mapa(sb, (cluster_rank() + (ROLE == 1 ? 4 : 2)) % 6) - sb, 0);
    const uint32_t vdelta = ROLE ? 0 : __shfl_sync(0xffffffffu, mapa(sb, (cluster_rank() + 4) % 6) - sb, 0);
    ISTAMP(3)
    __syncwarp();
#define GATHER_OFF(s) ((((s) + 7) & 7) * M_SLOT + warp * 2048 + (l8 & 56) * 2 + (l8 & 64) * 4 + (l8 & 128) * 8)
    uint32_t mo = GATHER_OFF(0);
    if (ROT) mbar_wait(sb + B_RELA, 0);
    for (int s = 0; s < (ROLE == 0 ? 63 : 64);) {
        const int slot = s & 1;
        l8 += s & P.zero;
        const uint32_t w1a = l8 * 2 + (S_W1 + warp * 1024 - sb);
        PROF(9)
        uint32_t u2, r0, r1, pld, pub, pbar, x[2][4];
        {
#define pm (P.gm + mo)
            uint32_t as[24][4], b[16], v[6][4];
            float acc[8][4];
#define W1LD(n) _Pragma("unroll") for (int i_ = 0; i_ < 4; i_++) ldsm4t(as[unit_pos(n) * 4 + i_], w1a + frag_off(unit_pos(n) * 4 + i_));
#define W1LD2(n, p) { const uint32_t wa_ = w1a + (as[unit_pos(p) * 4][0] & as[unit_pos(p) * 4 + 1][0] & as[unit_pos(p) * 4 + 2][0] & as[unit_pos(p) * 4 + 3][0] & P.zero); \
                      _Pragma("unroll") for (int i_ = 0; i_ < 4; i_++) ldsm4t(as[unit_pos(n) * 4 + i_], wa_ + frag_off(unit_pos(n) * 4 + i_)); }
#define W1MMA(n) _Pragma("unroll") for (int i_ = 0; i_ < 4; i_++) { const uint32_t* a_ = in_smem(n) ? as[unit_pos(n) * 4 + i_] : wr[unit_pos(n) * 4 + i_]; \
                                                                   mma16816(acc[((n) & 1) * 4 + i_], a_[0], a_[1], a_[2], a_[3], b[(n) & 14], b[(n) | 1]); }
#pragma unroll
            for (int T = 0; T < 8; T++) { acc[T][0] = acc[T][1] = acc[T][2] = acc[T][3] = 0.f; }
            if (!ROT) mbar_wait(sb + B_RELA, slot);
            PROF(12)
#pragma unroll
            for (int u = 0; u < 3; u++) ld_words(v[u], pm + unit_off(u));
            __syncwarp();
#pragma unroll
            for (int i = 0; i < PF1; i++) ldsm4t(as[i], w1a + frag_off(i));
            __syncwarp();
            mo += mbar_try(sb + B_RELB, slot) & P.zero;
            PROF(13)
#pragma unroll
            for (int u = 3; u < 6; u++) ld_words(v[u], pm + unit_off(u));
            uint32_t st = status(v, ((uint32_t)((uintptr_t)pm >> 32) & P.zero) + 32);
            pin<1>(&st);
            SFENCE();
            UNIT_STAT(0)
            PROF(0)
            decode<0>(b, v[0]); decode<1>(b, v[1]); decode<2>(b, v[2]);
#pragma unroll
            for (int i = PF1; i < 12; i++) ldsm4t(as[i], w1a + frag_off(i));
            W1MMA(0) W1MMA(1) W1MMA(2)
            if (TK & 1) W1LD2(3, 2) else { W1LD(3) }
            SFENCE();
            if (TK & 8) { W1MMA(5) W1MMA(4) W1MMA(3) W1MMA(6) } else { W1MMA(5) W1MMA(4) W1MMA(6) W1MMA(3) }
            if (U3POS == 0) W1MMA(7)
            if (TK & 2) W1LD2(12, 3) else { W1LD(12) }
            uint32_t mx = max6(b);
            pin<1>(&mx);
            SFENCE();
            PROF(10)
            if (U3POS == 1) W1MMA(7)
            const uint32_t mxa = sb + S_MX + slot * 32 + warp * 4;
            sts32(mxa, __reduce_max_sync(0xffffffffu, mx));
            UNIT_STAT(3)
            st |= status(v + 3, 32);
            const bool redo = __any_sync(0xffffffffu, st & 96);
            const bool kvok = ROLE || mbar_test(sb + B_KVFULL + slot * 8, (s >> 1) & 1);
            decode<4>(b, v[4]); decode<5>(b, v[5]); decode<3>(b, v[3]);
            u2 = lds32(sb + S_SC + warp * 4);
            W1MMA(8) W1MMA(10) if (ORD3) { W1MMA(14) W1MMA(12) } else { W1MMA(12) W1MMA(14) }
            if (TK & 4) W1LD2(13, 12) else { W1LD(13) }
            if (__builtin_expect(redo || !kvok, 0)) {
                if (redo) {
                    RETRY(3)
                    sts32(sb + S_REDO, s);
                    gather_slow(P, b, P.gm + GATHER_OFF(s), s, warp, (l8 - sb) >> 3, u2);
                    sts32(mxa, __reduce_max_sync(0xffffffffu, max6(b)));
#pragma unroll
                    for (int T = 0; T < 8; T++) { acc[T][0] = acc[T][1] = acc[T][2] = acc[T][3] = 0.f; }
#pragma unroll
                    for (int n = 0; n < 15; n += n < 8 ? 1 : 2) {
                        if (in_smem(n)) { W1LD(n) }
                        W1MMA(n)
                    }
                    W1LD(13)
                }
                if (ROLE == 0) mbar_wait(sb + B_KVFULL + slot * 8, (s >> 1) & 1);
            }
#undef pm
            SSTAMP(7, threadIdx.x == 0 && s == 0)
            PROF(14)
            const uint32_t pst = (l8 - sb) * 16 + ((warp * 16) ^ ((l8 * 2) & 112)) + (sb + S_P1);
            put_partials<ROLE == 2>(pst, acc[0], acc[1]); put_partials<ROLE == 2>(pst + 4096, acc[2], acc[3]);
            W1MMA(9)
            SFENCE();
            pld = (l8 & 64) * 4 + (l8 & 128) + (l8 & 56) * 2 + (sb + S_P1 + warp * 1024);
            const uint32_t rd = s == 63 ? 0 : rdelta;
            pub = ((l8 - sb) >> 1) + (ROLE ? sb + rd + (ROLE == 1 ? S_KL : S_VL) + warp * 128 : sb + S_QX + (warp & 4) * 128 + (warp & 1) * 256 + (warp & 2) * 64);
            pbar = sb + rd + (ROLE == 1 && s != 63 ? B_K : B_V);
#define PUBLISH0() { r0 = reduce8(x, l8, u2); if (ROLE) st_async1(pub, r0, pbar); else sts32(pub, r0); }
            if (RPOS == 0) { bar_sync(1, 256); reduce_load(x, pld); SFENCE(); }
            W1MMA(11)
            if (RPOS == 1) { bar_sync(1, 256); reduce_load(x, pld); }
            if (RPOS != 2 || F2) SFENCE();
            W1MMA(15)
            if (RPOS == 0) PUBLISH0()
            if (RPOS == 2) { bar_sync(1, 256); reduce_load(x, pld); }
            if (RPOS != 1 || F2) SFENCE();
            W1MMA(13)
            if (RPOS == 1) PUBLISH0()
            put_partials<ROLE == 2>(pst + 8192, acc[4], acc[5]); put_partials<ROLE == 2>(pst + 12288, acc[6], acc[7]);
            if (RPOS == 2) PUBLISH0()
        }
        SSTAMP(8, threadIdx.x == 0 && s == 0)
        PROF(1)
        if (ROLE) {
            bar_sync(1, 256);
            reduce_load(x, pld + 8192);
            r1 = reduce8(x, l8, u2);
            st_async1(pub + 1024, r1, pbar);
            if (s == 63) {
                PERSIST()
                mbar_wait(sb + B_V, 0);
                break;
            }
            PROF(2)
        }
        uint32_t ln, w2a, ro;
#define W2ADDR(late) { l8 += pub & P.zero; ln = (l8 - sb) >> 3; \
        w2a = sb + S_W2 + (ROLE ? (warp >> 2) * 16384 : late * 32768) + ((((ln & 7) + (ln >> 4) * 8) * 128 + ((((ln >> 3) & 1) ^ (ln & 7)) << 4)) ^ ((warp & 3) << 5)); \
        ro = (s & 7) * M_SLOT + (ROLE ? warp * 2048 + unit_off(ROLE) : (warp & 3) * 2048 + late * unit_off(3)) + (ln & 2) * 128 + (ln & 1) * 64 + (ln >> 2) * 8; }
        constexpr int RO2 = ROLE ? unit_off(ROLE + 3) - unit_off(ROLE) : 8192;
        float Sj[2];
        uint32_t w[24][4], ob[4][4];
        float S;
#define W2LD(i) ldsm4t(w[i], w2a + w2_t(i) * (ROLE ? 32768 : 16384) + (w2_k(i) & 1) * 8192 + (w2_k(i) >> 1) * 2048)
#define W2MMA(d, i) mma16816(d, w[i][0], w[i][1], w[i][2], w[i][3], ob[w2_k(i) >> 1][(w2_k(i) & 1) * 2], ob[w2_k(i) >> 1][(w2_k(i) & 1) * 2 + 1])
#define LEADER(wp) (l8 == sb + ((wp) - warp) * 256)
        if (att) {
            const float cs = 0.08838834764831845f * 1.4426950408889634f;
            uint32_t qa[4][4], kf[4][4], vf[4][4], vv[4];
            float T[5][2], sa[4][4] = {};
            const uint32_t l16 = l8 * 2 - sb;
            const uint32_t kaddr = (l8 & 56) * 16 + (((l8 >> 2) ^ (l8 * 2)) & 48) + ((l8 * 2) & 64) + (sb + S_KV + warp * 1024 + slot * 16384);
            bar_sync(1, 256);
            reduce_load(x, pld + 8192);
            __syncwarp();
#pragma unroll
            for (int i = 0; i < 2; i++) { ldsm4(qa[i], l16 + S_QX + i * 512); ldsm4(kf[i], kaddr ^ (i * 64)); }
            AFENCE(0)
            sts32(pub + 1024, reduce8(x, l8, u2));
            __syncwarp();
#pragma unroll
            for (int i = 2; i < 4; i++) ldsm4(kf[i], (kaddr ^ ((i & 1) * 64)) + 4096);
            score_half(sa, qa, kf);
            bar_sync(2, 256);
            PROF(2)
#pragma unroll
            for (int i = 2; i < 4; i++) ldsm4(qa[i], l16 + S_QX + i * 512);
            float sm[4][4] = {};
            score_half(sa, qa + 2, kf + 2);
            score_sum(T[0], sa);
            sts64(l8 + S_SX + warp * 256, __float_as_uint(T[0][0]), __float_as_uint(T[0][1]));
            PROF(4)
            if (BPOS == 0) bar_sync(4, 128);
            mbar_wait(sb + B_K, slot);
            PROF(11)
#pragma unroll
            for (int i = 0; i < 4; i++) ldsm4(kf[i], l16 + S_KL + i * 512);
            if (BPOS == 1) bar_sync(4, 128); else __syncwarp();
#pragma unroll
            for (int n = 0; n < 4; n++) lds64f(T[n], l8 + S_SX + n * 256);
            score_half(sm, qa, kf);
            score_half(sm, qa + 2, kf + 2);
            const uint32_t vaddr = (l8 & 56) * 16 + (l8 & 128) * 8 + (((warp & 1) * 64 + ((l8 >> 2) & 16)) ^ ((l8 * 2) & 112)) + (sb + S_KV + 8192 + (warp >> 1) * 4096 + slot * 16384);
            float mx = fmaxf(fmaxf(fmaxf(T[0][0], T[0][1]), fmaxf(T[1][0], T[1][1])), fmaxf(fmaxf(T[2][0], T[2][1]), fmaxf(T[3][0], T[3][1])));
            score_sum(T[4], sm);
            float m = quad_max(fmaxf(mx, fmaxf(T[4][0], T[4][1])));
            if (VPOS == 0) {
#pragma unroll
                for (int i = 0; i < 4; i++) ldsm4t(vf[i], (vaddr ^ ((i & 1) << 5)) + (i >> 1) * 2048);
            }
            mbar_wait(sb + B_V, slot);
            if (VPOS == 1) {
#pragma unroll
                for (int i = 0; i < 4; i++) ldsm4t(vf[i], (vaddr ^ ((i & 1) << 5)) + (i >> 1) * 2048);
            }
            ldsm4(vv, l16 + S_VL + warp * 512);
            uint32_t pa[5];
            m *= cs;
#pragma unroll
            for (int n = 0; n < 5; n++) { T[n][0] = ex2(fmaf(T[n][0], cs, -m)); T[n][1] = ex2(fmaf(T[n][1], cs, -m)); pa[n] = pack2(T[n][0], T[n][1]); }
            float sum = (((T[0][0] + T[0][1]) + (T[1][0] + T[1][1])) + ((T[2][0] + T[2][1]) + (T[3][0] + T[3][1]))) + (T[4][0] + T[4][1]);
            PROF(3)
            W2ADDR(1)
            const uint32_t lo = sb + S_O + warp * 512 + (ln & 3) * 64 + (ln >> 2) * 8, ls = sb + S_SUM + (ln & 3) * 32 + (ln & 4) * 4 + (ln >> 3) * 4;
            const uint32_t sdelta = warp < 2 ? rdelta : vdelta;
            sum += __shfl_xor_sync(0xffffffffu, sum, 1);
            sum += __shfl_xor_sync(0xffffffffu, sum, 2);
            float O[2][4];
#pragma unroll
            for (int i = 0; i < 2; i++) { O[i][0] = O[i][1] = O[i][2] = O[i][3] = 0.f; }
#pragma unroll
            for (int i = 0; i < 2; i++) {
                mma16816(O[0], vf[2 * i][0], vf[2 * i][1], vf[2 * i][2], vf[2 * i][3], pa[2 * i], pa[2 * i + 1]);
                mma16816(O[1], vf[2 * i + 1][0], vf[2 * i + 1][1], vf[2 * i + 1][2], vf[2 * i + 1][3], pa[2 * i], pa[2 * i + 1]);
            }
            mma1688(O[0], vv[0], vv[1], pa[4]);
            mma1688(O[1], vv[2], vv[3], pa[4]);
            uint32_t o[2][2];
#pragma unroll
            for (int j = 0; j < 2; j++) { o[j][0] = pack2(O[0][j], O[0][2 + j]); o[j][1] = pack2(O[1][j], O[1][2 + j]); }
#pragma unroll
            for (int j = 0; j < 2; j++) st_async2(lo + rdelta + j * 256, o[j][0], o[j][1], sb + rdelta + B_K);
            st_async1(ls + sdelta + (warp & 1) * 128, __float_as_uint(sum), sb + sdelta + B_K);
#pragma unroll
            for (int j = 0; j < 2; j++) st_async2(lo + vdelta + j * 256, o[j][0], o[j][1], sb + vdelta + B_K);
#pragma unroll
            for (int j = 0; j < 2; j++) sts64(lo + j * 256, o[j][0], o[j][1]);
            sts32(ls + warp * 128, __float_as_uint(sum));
            PROF(5)
            bar_sync(3, 256);
            if (LEADER(0)) { mbar_expect(sb + B_K, 2048); mbar_expect(sb + B_V, 2048); mbar_arrive(sb + B_KVGO + slot * 8); }
            S = next_scale(sb, slot, warp, u2);
            if (s == 0) mbar_wait(sb + B_WO, 0);
            pin<1>(&S);
            SFENCE();
#pragma unroll
            for (int j = 0; j < 4; j++) lds128(ob[j], l8 * 2 - sb + S_O + j * 512);
            lds64f(Sj, sb + S_SUM + (l8 & 24));
#pragma unroll
            for (int i = 0; i < PF2; i++) W2LD(i);
        } else {
            if (ROLE == 0) { bar_sync(1, 256); reduce_load(x, pld + 8192); sts32(pub + 1024, reduce8(x, l8, u2)); bar_arrive(2, 256); }
            if (LEADER(7)) { if (s) mbar_arrive(sb + B_GO); if (ROLE) mbar_expect(sb + B_K, 2304); }
            S = next_scale(sb, slot, warp, u2);
            if (s == 0) mbar_wait(sb + B_WO, 0);
            if (ROLE != 0) PERSIST()
            W2ADDR(0)
#pragma unroll
            for (int i = 0; i < PF2; i++) {
                W2LD(i);
                if (ROLE == 0 && (i & PACE) == PACE) w2a += w[i][0] & P.zero;
            }
            ro = opq(ro, ln);
            const uint32_t sa = opq(sb + S_SUM + (l8 & 24), ln), oa = opq(l8 * 2 - sb + S_O, ln);
            if (ROLE == 0) bar_sync(3, 256); else mbar_wait(sb + B_K, slot);
            lds64f(Sj, sa);
#pragma unroll
            for (int j = 0; j < 4; j++) lds128(ob[j], oa + j * 512);
        }
        SSTAMP(9, threadIdx.x == 224 && s == 0)
        SFENCE();
        PROF(6)
        {
            const uint8_t* pr = P.gm + ro;
            float c[4][4];
            uint32_t lim = 0;
#pragma unroll
            for (int i = 0; i < 4; i++) { c[i][0] = c[i][1] = c[i][2] = c[i][3] = 0.f; }
#pragma unroll
            for (int i = 0; i < 16; i++) {
                W2MMA(c[i & (ROLE ? 1 : 3)], i);
                if (i + PF2 < (ROLE ? 16 + NEARLY : 16)) W2LD(i + PF2);
                if (i == 5) {
                    const uint32_t z = __float_as_uint(c[1][0]) & P.zero;
                    Sj[0] = S * rcp(__uint_as_float(__float_as_uint(Sj[0]) | z)); Sj[1] = S * rcp(__uint_as_float(__float_as_uint(Sj[1]) | z));
                }
                if (i == 5) lim = __any_sync(0xffffffffu, fmaxf(fmaxf(fabsf(c[0][0]), fabsf(c[0][2])), fmaxf(fabsf(c[1][0]), fabsf(c[1][2]))) * Sj[0] >= (ROLE ? 24.f : 20.f)) ? 16384 : 0;
                if (i == FPOS) { pin<1>(&lim); pin<2>(Sj); pin_ptr(pr); SFENCE(); }
            }
            if (ROLE == 0) {
#pragma unroll
                for (int i = 0; i < 8; i++) c[i >> 2][i & 3] += c[2 + (i >> 2)][i & 3];
            }
            const float xa[2][3] = {{c[0][0], c[0][2], c[1][0]}, {c[0][1], c[0][3], c[1][1]}};
            uint64_t wa[2], wb[2];
            emit<NU>(wa, xa, Sj, P.two26, lim, pr);
            PROF(7)
            mo = GATHER_OFF(s + 1);
            pin<1>(&mo);
            if (ROLE) {
                SFENCE();
#pragma unroll
                for (int i = 16 + NEARLY; i < 24; i++) { if (i == 16 + NBAR) bar_sync(2, 256); W2LD(i); __syncwarp(); }
                SFENCE();
#pragma unroll
                for (int i = 16; i < 24; i++) W2MMA(c[2 + (i & 1)], i);
#pragma unroll
                for (int i = 0; i < 4; i++) c[2][i] += c[3][i];
            }
            const float y[2][3] = {{ROLE ? c[1][2] : c[1][0], ROLE ? c[2][0] : c[1][2], c[2][2]}, {ROLE ? c[1][3] : c[1][1], ROLE ? c[2][1] : c[1][3], c[2][3]}};
            const bool released = !ROT || mbar_test(sb + B_RELA, slot ^ 1);
            emit<NU>(wb, y, Sj, P.two26, lim, pr + RO2);
            PROF(8)
            if (!__all_sync(0xffffffffu, (wa[0] & wb[0] & 1) && released && s)) {
                if (__builtin_expect(!__all_sync(0xffffffffu, wa[0] & wb[0] & 1), 0)) {
                    RETRY(5)
                    const uint8_t* pf = g_f + (s & 7) * F_SLOT + (ROLE ? ROLE * 8192 + warp * 1024 : (warp & 3) * 1024 + (att ? 24576 : 0)) + (ln & 3) * 128 + (ln >> 2) * 16;
                    repair<NU>(wa, xa, Sj, pr, pf);
                    repair<NU>(wb, y, Sj, pr + RO2, pf + (ROLE ? 24576 : 4096));
                }
                if (s == 0) { bar_sync(1, 256); if (LEADER(7)) mbar_arrive(sb + B_GO); }
                if (ROT) mbar_wait(sb + B_RELA, slot ^ 1);
            }
        }
        s++;
    }
}
struct Pipe { uint32_t stage, phase; };
struct Cons {
    uint32_t sb, rel;
    int wg, wq, lane, rank, pair;
    uint32_t nst;
    Pipe p;
};
__device__ __forceinline__ void pipe_next(Pipe& p) { p.stage = (p.stage + 1) & (NSTAGE - 1); p.phase ^= (p.stage == 0); }
__device__ __forceinline__ void release(const Cons& c, uint32_t stage) { if (c.lane < 2) mbar_arrive_cluster(c.rel + stage * 8); }

enum { PEND_NONE = 0, PEND_KVO = 1, PEND_HT = 2, PEND_OUT = 3, PEND_OUTH = 4 };
struct Pend { uint32_t pk[64]; int kind, row, col, cnt; };

__device__ __forceinline__ void staging_wait(const Cons& c) { if (c.nst) mbar_wait(c.sb + B_SFREE + c.wg * 8, (c.nst - 1) & 1); }
__device__ __forceinline__ void staging_post(Cons& c, int kind, int row, int col, int cnt) {
    __syncwarp();
    if (c.lane == 0) {
        if (c.wq == 0) { const uint32_t x[4] = {(uint32_t)kind, (uint32_t)row, (uint32_t)col, (uint32_t)cnt}; sts128(c.sb + S_DESC + c.wg * 16, x); }
        mbar_arrive(c.sb + B_SFULL + c.wg * 8);
    }
    c.nst++;
}
template <int HF, bool KVONLY = false>
__device__ __forceinline__ void drain(const Params& P, Cons& c, const Pend& d) {
    const uint32_t* pk = d.pk + HF * 32;
    if (!KVONLY && d.kind >= PEND_OUT) {
        if (HF == 1 && d.kind == PEND_OUTH) return;
        float* o = P.out + (size_t)(d.row + c.wq * 16 + (c.lane >> 2)) * 2048 + d.col + HF * 128 + (c.lane & 3) * 2;
#pragma unroll
        for (int j = 0; j < 16; j++) {
            st_stream2(o + j * 8, bf_lo(pk[j * 2]), bf_hi(pk[j * 2]));
            st_stream2(o + 8 * 2048 + j * 8, bf_lo(pk[j * 2 + 1]), bf_hi(pk[j * 2 + 1]));
        }
    } else if (d.kind != PEND_NONE) {
        const bool ht = !KVONLY && d.kind == PEND_HT;
        const int hi = (c.lane >> 3) & 1;
        const uint32_t base = c.sb + S_STG + c.wg * 16384 + ((ht ? hi * 32 + c.wq * 8 : c.wq * 16 + hi * 8) + (c.lane & 7)) * 128;
        staging_wait(c);
#pragma unroll
        for (int j = 0; j < 8; j++) {
            const int ch = (j & 3) * 2 + (c.lane >> 4);
            stsm4(base + (j >> 2) * 8192 + ((ch ^ (c.lane & 7)) << 4), pk[j * 4], pk[j * 4 + 1], pk[j * 4 + 2], pk[j * 4 + 3]);
        }
        fence_async_smem();
        staging_post(c, d.kind, d.row, d.col + HF * 128, HF ? d.cnt : -1);
    }
}
__device__ __forceinline__ void drain_all(const Params& P, Cons& c, Pend& d) { drain<0>(P, c, d); drain<1>(P, c, d); d.kind = PEND_NONE; }

__device__ __forceinline__ void store_warp(const Params& P, uint32_t sb, int wg) {
    const uint32_t stg = sb + S_STG + wg * 16384;
#pragma unroll 1
    for (uint32_t n = 0;; n++) {
        mbar_wait(sb + B_SFULL + wg * 8, n & 1);
        uint32_t x[4];
        lds128(x, sb + S_DESC + wg * 16);
        if (x[0] == PEND_NONE) break;
        const bool ht = x[0] == PEND_HT;
        const CUtensorMap* m = &P.tm[ht ? M_HTS : M_KVO];
#pragma unroll 1
        for (int i = 0; i < 4; i++) if (!(DBGF(128) && gridDim.x != 96)) tma_store2d(m, x[2] + (i >> 1) * 64, x[1] + (i & 1) * (ht ? 1024 : 32), stg + i * 4096);
        bulk_commit();
        bulk_wait_read();
        mbar_arrive(sb + B_SFREE + wg * 8);
        if ((int)x[3] >= 0) {
            bulk_wait_all(); fence_async();
            asm volatile("red.relaxed.gpu.global.add.u32 [%0], 1;" ::"l"(&g_cnt(x[3])) : "memory");
        }
    }
}

template <int N, int TA, int TB, bool FIRST>
__device__ __forceinline__ void issue_ktile(float* acc, const Cons& c) {
    mbar_wait(c.sb + B_FULL + c.p.stage * 8, c.p.phase);
    const uint32_t a = c.sb + c.p.stage * STAGE + c.wg * 8192, b = c.sb + c.p.stage * STAGE + 16384;
    const uint64_t da = mkdesc(a, TA ? 8192 : 16, 1024, 1), db = mkdesc(b, TB ? 8192 : 16, 1024, 1);
    wg_fence();
#pragma unroll
    for (int k = 0; k < 4; k++) {
        const uint64_t x = da + (TA ? 128 : 2) * k, y = db + (TB ? 128 : 2) * k;
        if (N == 256) { if (FIRST && k == 0) wgmma_ss256_first<TA, TB>(acc, x, y); else wgmma_ss256<TA, TB>(acc, x, y); }
        else { if (FIRST && k == 0) wgmma_ss128_first<TA, TB>(acc, x, y); else wgmma_ss128<TA, TB>(acc, x, y); }
    }
    wg_commit();
}
template <int N, bool FIRST>
__device__ __forceinline__ void issue_any(float* acc, const Cons& c, int type) {
    if (N == 256 && type == T_A1) issue_ktile<N, 0, 0, FIRST>(acc, c);
    else if (type == (N == 256 ? T_A2 : T_A2H)) issue_ktile<N, 1, 0, FIRST>(acc, c);
    else issue_ktile<N, 0, 1, FIRST>(acc, c);
}
template <int N, bool KVONLY = false>
__device__ __forceinline__ void mainloop(float* acc, const Params& P, Cons& c, Pend& d, int type) {
    const int nk = (type == T_OP || type == T_OPH) ? 64 : (type == T_A2 || type == T_A2H) ? 32 : 16;
    issue_any<N, true>(acc, c, type);
    drain<0, KVONLY>(P, c, d);
    uint32_t prev = c.p.stage;
    pipe_next(c.p);
    for (int kt = 1; kt < nk; kt++) {
        issue_any<N, false>(acc, c, type);
        wg_wait<1>();
        release(c, prev);
        if (kt == 2) drain<1, KVONLY>(P, c, d);
        prev = c.p.stage;
        pipe_next(c.p);
    }
    d.kind = PEND_NONE;
    wg_wait<0>();
    pin<N / 2>(acc);
    release(c, prev);
}
__device__ __forceinline__ void pack_half(uint32_t* pk, const float* a) {
#pragma unroll
    for (int i = 0; i < 32; i++) pk[i] = pack2(a[2 * i], a[2 * i + 1]);
}

__device__ __forceinline__ void epi_kv(const float* acc, const Cons& c, Pend& d, int mb, int nb) {
    pack_half(d.pk, acc); pack_half(d.pk + 32, acc + 64);
    d.kind = PEND_KVO; d.row = (nb >> 4) * 2048 + mb * 256 + c.rank * 128 + c.wg * 64; d.col = (nb & 15) * 256; d.cnt = C_KV + mb;
}

__device__ __forceinline__ void epi_qa(const float* acc, Cons& c, Pend& d, int mb, int nb) {
    uint32_t q[64];
    pack_half(q, acc);
    pack_half(q + 32, acc + 64);
#pragma unroll
    for (int i = 0; i < 32; i++) d.pk[32 + i] = 0;
    const int g = c.lane >> 2, t = c.lane & 3;
    const bool sg = c.wq >= 2;
    const int i0 = (c.wq & 1) * 16 + g;
#pragma unroll 1
    for (int hh = 0; hh < 2; hh++) {
        uint32_t pa[5][4];
        {
            float S[32] = {}, Sm[8] = {};
            mbar_wait(c.sb + B_FULL + c.p.stage * 8, c.p.phase);
            const uint32_t st = c.sb + c.p.stage * STAGE;
            const uint64_t dk = mkdesc(st + c.wg * 8192, 16, 1024, 1), dm = mkdesc(st + 32768 + c.wg * 4096, 128, 2048, 0);
            pin<32>(q); pin<32>(S); pin<8>(Sm);
            wg_fence();
#pragma unroll
            for (int i = 0; i < 8; i++) wgmma_rs64<0>(S, q + i * 4, dk + (i >> 2) * 1024 + (i & 3) * 2, i != 0);
#pragma unroll
            for (int i = 0; i < 8; i++) wgmma_rs16<0>(Sm, q + i * 4, dm + i * 16, i != 0);
            wg_commit();
            wg_wait<0>();
            pin<32>(S); pin<8>(Sm);
            release(c, c.p.stage);
            pipe_next(c.p);
            const float scale = 0.08838834764831845f, l2e = 1.4426950408889634f;
            float x[2][10];
#pragma unroll
            for (int r = 0; r < 2; r++) {
#pragma unroll
                for (int j = 0; j < 4; j++)
#pragma unroll
                    for (int e = 0; e < 2; e++) {
                        const float v = sg ? S[16 + j * 4 + r * 2 + e] : S[j * 4 + r * 2 + e];
                        x[r][j * 2 + e] = (j * 8 + 2 * t + e > i0 + r * 8) ? -1e9f : v * scale;
                    }
                x[r][8] = (sg ? Sm[4 + r * 2] : Sm[r * 2]) * scale;
                x[r][9] = (sg ? Sm[5 + r * 2] : Sm[1 + r * 2]) * scale;
                float m = x[r][0];
#pragma unroll
                for (int i = 1; i < 10; i++) m = fmaxf(m, x[r][i]);
                m = fmaxf(m, __shfl_xor_sync(0xffffffffu, m, 1));
                m = fmaxf(m, __shfl_xor_sync(0xffffffffu, m, 2));
                float sum = 0.f;
#pragma unroll
                for (int i = 0; i < 10; i++) { x[r][i] = ex2((x[r][i] - m) * l2e); sum += x[r][i]; }
                sum += __shfl_xor_sync(0xffffffffu, sum, 1);
                sum += __shfl_xor_sync(0xffffffffu, sum, 2);
                const float inv = rcp(sum);
#pragma unroll
                for (int i = 0; i < 10; i++) x[r][i] *= inv;
            }
#pragma unroll
            for (int ks = 0; ks < 2; ks++)
#pragma unroll
                for (int i = 0; i < 4; i++) {
                    const uint32_t p = pack2(x[i & 1][ks * 4 + (i >> 1) * 2], x[i & 1][ks * 4 + (i >> 1) * 2 + 1]);
                    pa[ks][i] = sg ? 0u : p;
                    pa[2 + ks][i] = sg ? p : 0u;
                }
#pragma unroll
            for (int r = 0; r < 2; r++) {
                const uint32_t p = pack2(x[r][8], x[r][9]);
                pa[4][r] = sg ? 0u : p;
                pa[4][2 + r] = sg ? p : 0u;
            }
        }
        float O[64] = {};
        mbar_wait(c.sb + B_FULL + c.p.stage * 8, c.p.phase);
        const uint32_t st = c.sb + c.p.stage * STAGE;
        const uint64_t dv = mkdesc(st + c.wg * 8192, 16384, 1024, 1), dm = mkdesc(st + 32768 + c.wg * 4096, 2048, 128, 0);
        pin<20>(&pa[0][0]); pin<64>(O);
        wg_fence();
#pragma unroll
        for (int ks = 0; ks < 4; ks++) wgmma_rs128<1>(O, pa[ks], dv + ks * 128, ks != 0);
        wgmma_rs128<0>(O, pa[4], dm, 1);
        wg_commit();
        wg_wait<0>();
        pin<64>(O);
        release(c, c.p.stage);
        pipe_next(c.p);
#pragma unroll
        for (int i = 0; i < 32; i++) { q[i] = q[32 + i]; q[32 + i] = d.pk[32 + i]; }
        pack_half(d.pk + 32, O);
    }
#pragma unroll
    for (int i = 0; i < 32; i++) d.pk[i] = q[32 + i];
    d.kind = PEND_KVO; d.row = 4096 + mb * 256 + c.rank * 128 + c.wg * 64; d.col = nb * 256; d.cnt = C_O + mb * 4 + (nb >> 2);
}

__device__ __forceinline__ void epi_op(const float* acc, const Cons& c, Pend& d, int mb, int nb) {
    pack_half(d.pk, acc); pack_half(d.pk + 32, acc + 64);
    d.kind = PEND_OUT; d.row = mb * 256 + c.rank * 128 + c.wg * 64; d.col = 1024 + nb * 256;
}

__device__ __forceinline__ void epi_oph(const float* acc, const Cons& c, Pend& d, int mb, int nb) {
    pack_half(d.pk, acc);
    d.kind = PEND_OUTH; d.row = mb * 256 + c.rank * 128 + c.wg * 64; d.col = 1024 + nb * 128;
}

template <int HF>
__device__ __forceinline__ void epi_a2_half(const float* acc, const Params& P, Cons& c, int mb, int col0) {
    const int g = c.lane >> 2, t = c.lane & 3;
    const int row = mb * 256 + (g >> 1) * 64 + (c.rank * 16 + c.wg * 8 + c.wq * 2) * 2 + (g & 1);
    float* o = P.out + (size_t)row * 2048 + col0 + HF * 128 + t * 2;
    mbar_wait(c.sb + B_FULL + c.p.stage * 8, c.p.phase);
    const uint32_t st = c.sb + c.p.stage * STAGE, da = st + 32768 + (c.lane >> 3) * 16;
    const uint32_t xa = st + (c.wg * 64 + c.wq * 16 + (c.lane & 15)) * 128 + (((c.lane >> 4) ^ (c.lane & 7)) << 4);
#pragma unroll
    for (int j4 = 0; j4 < 4; j4++) {
        uint32_t x[8], dv[4];
        ldsm4(dv, da + j4 * 64);
        ldsm4(x, (xa ^ ((j4 & 1) << 6)) + (j4 >> 1) * 16384);
        ldsm4(x + 4, (xa ^ ((j4 & 1) << 6) ^ 32) + (j4 >> 1) * 16384);
#pragma unroll
        for (int i = 0; i < 4; i++) {
            const int j = j4 * 4 + i;
            const float* a = acc + HF * 64 + j * 4;
            const uint32_t u0 = hmul2(x[2 * i], dv[i]), u1 = hmul2(x[2 * i + 1], dv[i]);
            st_stream2(o + j * 8, a[0] + bf_lo(u0), a[1] + bf_hi(u0));
            st_stream2(o + 2 * 2048 + j * 8, a[2] + bf_lo(u1), a[3] + bf_hi(u1));
        }
    }
    __syncwarp();
    release(c, c.p.stage);
    pipe_next(c.p);
}

#define TSTAMP(i)
__device__ __forceinline__ float2 cmul(float2 a, float2 b) { return make_float2(fmaf(a.x, b.x, -a.y * b.y), fmaf(a.x, b.y, a.y * b.x)); }
__device__ __forceinline__ float2 cfma(float2 a, float2 b, float2 u) { return make_float2(fmaf(a.x, b.x, fmaf(-a.y, b.y, u.x)), fmaf(a.x, b.y, fmaf(a.y, b.x, u.y))); }
__device__ __forceinline__ float4 ssm_coef(float lre, float lim, float logdt) {
    const float dt = __bfloat162float(__float2bfloat16(expf(logdt)));
    const float ea = expf(dt * lre);
    float sn, cn;
    sincosf(dt * lim, &sn, &cn);
    const float br = ea * cn, bi = ea * sn, nr = br - 1.f;
    float cr, ci;
    if (fabsf(lre) >= fabsf(lim)) { const float r = lim / lre, dn = lre + lim * r; cr = (nr + bi * r) / dn; ci = (bi - nr * r) / dn; }
    else { const float r = lre / lim, dn = lre * r + lim; cr = (nr * r + bi) / dn; ci = (bi * r - nr) / dn; }
    return make_float4(br, bi, cr, ci);
}
__device__ __forceinline__ void epi_a1(const float* acc, const Params& P, const Cons& c, Pend& d, int mb, int nb, uint32_t atag) {
    const int t = c.lane & 3;
    const int p = nb * 128 + c.rank * 64 + c.wg * 32 + c.wq * 8 + (c.lane >> 2);
    uint32_t cw[4];
    lds128(cw, c.sb + S_COEF + (p & 63) * 16);
    const float4 cf = make_float4(__uint_as_float(cw[0]), __uint_as_float(cw[1]), __uint_as_float(cw[2]), __uint_as_float(cw[3]));
    TSTAMP(1)
    const float2 lam = make_float2(cf.x, P.swap_ri ? -cf.y : cf.y);
    const float a0 = P.swap_ri ? -2.f * cf.w : 2.f * cf.z, a1 = P.swap_ri ? 2.f * cf.z : -2.f * cf.w;
    const float b0 = P.swap_ri ? -2.f * cf.z : -2.f * cf.w, b1 = P.swap_ri ? -2.f * cf.w : -2.f * cf.z;
    float2 h = make_float2(0.f, 0.f);
#pragma unroll
    for (int round = 0; round < 2; round++) {
#pragma unroll
        for (int j = 0; j < 32; j++) {
            h = cfma(lam, h, make_float2(acc[j * 4], acc[j * 4 + 2]));
            const float r0 = fmaf(a0, h.x, a1 * h.y), m0 = fmaf(b0, h.x, b1 * h.y);
            h = cfma(lam, h, make_float2(acc[j * 4 + 1], acc[j * 4 + 3]));
            d.pk[j * 2] = pack2(r0, fmaf(a0, h.x, a1 * h.y));
            d.pk[j * 2 + 1] = pack2(m0, fmaf(b0, h.x, b1 * h.y));
        }
        if (round) break;
        float2 l64 = lam;
#pragma unroll
        for (int i = 0; i < 6; i++) l64 = cmul(l64, l64);
        const float2 l128 = cmul(l64, l64), l256 = cmul(l128, l128);
        float2 o = make_float2(__shfl_up_sync(0xffffffffu, h.x, 1), __shfl_up_sync(0xffffffffu, h.y, 1));
        if (t >= 1) h = cfma(l64, o, h);
        o = make_float2(__shfl_up_sync(0xffffffffu, h.x, 2), __shfl_up_sync(0xffffffffu, h.y, 2));
        if (t >= 2) h = cfma(l128, o, h);
        TSTAMP(2)
        if (t == 3) st_relaxed2(&g_agg[mb * 1024 + p], (__float_as_uint(h.x) & ~1u) | atag, __float_as_uint(h.y));
        h = make_float2(__shfl_up_sync(0xffffffffu, h.x, 1), __shfl_up_sync(0xffffffffu, h.y, 1));
        if (t == 0) h = make_float2(0.f, 0.f);
        uint32_t ax[7], ay[7];
        int n = 0;
        while (true) {
            uint32_t bad = 0;
#pragma unroll
            for (int j = 0; j < 7; j++) { ax[j] = atag; ay[j] = 0; ld_relaxed2_if(ax[j], ay[j], &g_agg[j * 1024 + p], j < mb); }
#pragma unroll
            for (int j = 0; j < 7; j++) bad |= ax[j] ^ atag;
            if (tags_ok(bad)) break;
            __nanosleep(400);
            if (++n > SPIN_LIMIT) spin_fault();
        }
        float2 carry = make_float2(0.f, 0.f);
#pragma unroll
        for (int j = 0; j < 7; j++) if (j < mb) carry = cfma(l256, carry, make_float2(__uint_as_float(ax[j]), __uint_as_float(ay[j])));
        float2 w = (t & 1) ? l64 : make_float2(1.f, 0.f);
        if (t & 2) w = cmul(w, l128);
        h = cfma(w, carry, h);
        TSTAMP(3)
    }
    TSTAMP(4)
    d.kind = PEND_HT; d.row = nb * 128 + c.rank * 64 + c.wg * 32; d.col = mb * 256; d.cnt = C_HT + mb * 2 + (nb >> 2);
}

__device__ __forceinline__ uint32_t acquire_stage(uint32_t sb, Pipe& p, uint32_t bytes) {
    mbar_wait(sb + B_EMPTY + p.stage * 8, p.phase ^ 1);
    mbar_expect(sb + B_FULL + p.stage * 8, bytes);
    return p.stage;
}
#define AHEAD 1
__device__ __forceinline__ void watcher(const Params& P, const uint32_t sb, const int rank, const int lane) {
    const uint32_t epoch = ld_relaxed1(&g_cnt(C_EPOCH)), e1 = epoch + 1;
    sts32(sb + S_EPOCH, epoch);
    __syncwarp();
    if (lane == 0 && atomicInc(&g_cnt(C_DONE), (DBGF(32) ? 95 : NPAIR * 2 - 1) + (epoch & P.zero)) == (DBGF(32) ? 95 : NPAIR * 2 - 1)) atomicAdd(&g_cnt(C_EPOCH), 1);
    if (gridDim.x != 96) {
        uint32_t v;
        asm("mov.u32 %0, %%smid;" : "=r"(v));
        if (lane == 0 && rank == 0) st_relaxed1(g_hint + 6272 + (blockIdx.x >> 1), e1 << 8 | v >> 1);
        for (int k = 0;; k++) {
            __nanosleep(1000);
            v = ld_relaxed1(g_hint + 6272 + min(lane, 17));
            if (__all_sync(0xffffffffu, (v ^ e1 << 8) < 256)) break;
            if (k > SPIN_LIMIT) spin_fault();
        }
        const uint32_t key = ((v & 255) >= 62 ? 0 : tpc_gpc(v & 255)) * 32 + lane;
        sts32(sb + S_TAIL, 48 + __popc(__ballot_sync(0xffffffffu, key < __shfl_sync(0xffffffffu, key, blockIdx.x >> 1)) & 0x3ffff));
        __syncwarp();
    }
    uint32_t met = 1;
    if (lane == 0) asm volatile("st.release.cta.shared.u32 [%0], 1;" ::"r"(sb + S_DEP) : "memory");
    const int pair = lds32(sb + S_TAIL), first = ITEM_OFF(pair) + (pair < NCHAIN ? NPRE + 1 : 1);
#pragma unroll 1
    for (int it = first; it < ITEM_OFF(pair + 1); it++) {
        const int item = ITEM(it), type = item >> 8, mb = (item >> 5) & 7, nb = item & 31;
        const int n = (0x24021420 >> (type * 4)) & 7;
        for (int k = 0; it > first && (int)lds32(sb + S_CUR) < it - AHEAD; k++) { __nanosleep(200); if (k > SPIN_LIMIT) spin_fault(); }
#pragma unroll 1
        for (int i = 0; i < n; i++) {
            int idx = n == 4 ? C_O + mb * 4 + i : C_HT + mb * 2 + i;
            uint32_t target = e1 * 16;
            if (type == T_A1) { idx = C_COEF; target = e1 * 4; }
            if (type == T_QA) {
                idx = i ? C_FLAG + (lane & 1) * 32 + nb * 2 + ((lane >> 1) & 1) : C_KV + mb;
                target = i ? epoch * 64 + mb * 8 + rank * 4 + 4 : e1 * 128;
            }
            if (lane < 4) { wait_count(&g_cnt(idx), target); fence_async(); }
            __syncwarp();
            if (lane == 0) asm volatile("st.release.cta.shared.u32 [%0], %1;" ::"r"(sb + S_DEP), "r"(++met) : "memory");
        }
    }
}
__device__ __forceinline__ bool dep_met(uint32_t sb, uint32_t n) { uint32_t v; asm volatile("ld.acquire.cta.shared.u32 %0, [%1];" : "=r"(v) : "r"(sb + S_DEP) : "memory"); return v >= n; }
__device__ __forceinline__ void dep_wait(uint32_t sb, uint32_t n) { for (int k = 0; !dep_met(sb, n); k++) { __nanosleep(32); if (k > SPIN_LIMIT * 8) spin_fault(); } }
__device__ __forceinline__ void producer(const Params& P, const uint32_t sb, int pair, const int rank) {
    Pipe p = {0, 0};
    uint32_t dep = 1;
    for (int it = ITEM_OFF(pair); it < ITEM_OFF(pair + 1); it++) {
        const int item = ITEM(it), type = item >> 8, mb = (item >> 5) & 7, nb = item & 31;
        if (type == T_CHAIN) {
            sts32(sb + S_CUR, 0);
            const uint32_t epoch = ld_relaxed1(&g_cnt(C_EPOCH)), e1 = epoch + 1;
            const int role = pair >> 4, h = (pair & 15) * 2 + rank;
#pragma unroll 1
            for (int i = 0, q = 0; i < 8; i++) {
                const int n = (0x13003333 >> (i * 4)) & 3;
                const uint32_t st = acquire_stage(sb, p, n * 16384);
                SSTAMP(1, i == 0) SSTAMP(3, i == 3)
#pragma unroll 1
                for (int k = 0; k < 2 * n; k++, q++)
                    tma3d(sb + st * STAGE + k * 8192, &P.tm[M_CQ + role], h * 128 + (fill_unit(q >> 1) & 1) * 64, word_col((fill_unit(q >> 1) & 14) + (q & 1)) & 8, word_col((fill_unit(q >> 1) & 14) + (q & 1)) >> 4, sb + B_FULL + st * 8);
                pipe_next(p);
            }
            if (role == 0 && !DBGF(1)) { wait_count(&g_cnt(C_KV), e1 * 128); fence_async(); }
            mbar_wait(sb + B_EMPTY + 16, 1); mbar_wait(sb + B_EMPTY + 24, 1);
            mbar_expect(sb + B_WO, role ? 98304 : 65536);
            if (role == 0) { mbar_expect(sb + B_KVFULL, 16384); mbar_expect(sb + B_KVFULL + 8, 16384); }
#pragma unroll 1
            for (int k = role ? 0 : -4; k < 12; k++) {
                const bool kv = role == 0 && (k & 8);
                const int sg = k > 0;
                tma4d(kv ? sb + S_KV + sg * 16384 + (k & 3) * 4096 : sb + S_W2 + k * 8192, &P.tm[kv ? M_KV4 : M_CO + (k & 1)],
                      kv ? h * 128 + (k & 1) * 64 : (role == 0 ? 0 : role == 1 ? 256 : 640) + (k >> 1) * 64, kv ? (k & 2) * 1024 + sg * 32 : h * 8, sb + (kv ? B_KVFULL + sg * 8 : B_WO));
            }
            SSTAMP(5, true)
            if (pair < 16) {
#pragma unroll 1
                for (int s = 2; s < 63; s++) {
                    mbar_wait(sb + B_KVGO + (s & 1) * 8, ((s >> 1) + 1) & 1);
                    wait_time(gtime() + P.dk, sb);
                    SSTAMP(6, s == 2)
                    const uint32_t bar = sb + B_KVFULL + (s & 1) * 8, dst = sb + S_KV + (s & 1) * 16384;
                    if (DBGF(2)) { mbar_arrive(bar); continue; }
                    mbar_expect(bar, 16384);
#pragma unroll 1
                    for (int i = 0; i < 4; i++) tma2d(dst + i * 4096, &P.tm[M_KVO], (pair * 2 + rank) * 128 + (i & 1) * 64, (i >> 1) * 2048 + (DBGF(32 | 512) ? s & 7 : s) * 32, bar);
                    if ((s & 7) == 7 && !DBGF(1)) { wait_count(&g_cnt(C_KV + 1 + (s >> 3)), e1 * 128); fence_async(); }
                }
            } else {
                uint32_t* flag = &g_cnt(C_FLAG + pair * 2 + rank - 32);
                const int x = pair * 2 + rank - 32;
#pragma unroll 1
                for (int s = 0; s < 64; s++) {
                    mbar_wait(sb + B_PERS, s & 1);
                    if (s < 63) wait_time(gtime() + P.dp, sb);
                    if (!DBGF(4)) bulk_s2g((role == 1 ? g_km : g_vmt) + (s * 32 + h) * 512, sb + S_QX, 2048);
                    if (s < 57) {
                        uint8_t* m = P.gm + ((s + 6) & 7) * M_SLOT + (x >> 1) * 1024 + (x & 1) * 256;
                        bulk_s2g(m, sb + S_SX, 256); bulk_s2g(m + 512, sb + S_SX, 128);
                        bulk_s2g(g_f + ((s + 6) & 7) * F_SLOT + x * 768, sb + S_SX + 256, 768);
                    }
                    bulk_commit();
                    bulk_wait_read();
                    mbar_arrive(sb + B_KVGO);
                    bulk_wait_all();
                    fence_async();
                    if ((s & 3) == 3) st_relaxed1(flag, epoch * 64 + s + 1);
                }
            }
            mbar_wait(sb + B_RESUME, 0);
            pair = lds32(sb + S_TAIL);
            it = ITEM_OFF(pair) + NPRE;
            continue;
        }
        if (it == ITEM_OFF(pair) && pair >= NCHAIN) it = -1; else sts32(sb + S_CUR, it);
        const int m0 = mb * 256 + rank * 128;
        if (type <= T_OP) {
            const CUtensorMap* ma = &P.tm[type == T_OP ? M_OA : M_BX];
            const CUtensorMap* mw = &P.tm[type == T_OP ? M_WO : type == T_QA ? M_WQ : nb < 16 ? M_WK : M_WV];
            const int nk = type == T_OP ? 64 : 16, nc = (nb & 15) * 4 + rank * 2, ma0 = type == T_OP ? 4096 + m0 : m0;
#pragma unroll 1
            for (int kt = 0; kt < nk; kt++) {
                if (type == T_OP && (kt & 15) == 0) dep_wait(sb, ++dep);
                if (DBGF(256) && pair >= NCHAIN) { acquire_stage(sb, p, 0); pipe_next(p); continue; }
                const uint32_t st = acquire_stage(sb, p, STAGE), bar = sb + B_FULL + st * 8;
                tma2d(sb + st * STAGE, ma, kt * 64, ma0, bar);
                tma3d_mc(sb + st * STAGE + 16384 + rank * 16384, mw, 0, kt * 64, nc, bar);
                if (type == T_QA && kt < 12 && dep_met(sb, dep + 1 + (kt >> 3))) {
                    if (kt < 8) tma_prefetch2d(&P.tm[M_OA], nb * 256 + (kt & 3) * 64, (kt >> 2) * 2048 + m0);
                    else {
                        const int o = ((mb * 8 + rank * 4 + (kt & 3)) * 32 + nb * 2) * 512;
                        l2_prefetch(g_km + o, 4096); l2_prefetch(g_vmt + o, 4096);
                    }
                }
                pipe_next(p);
            }
            if (type == T_QA) {
                dep += 2;
                dep_wait(sb, dep);
#pragma unroll 1
                for (int e = 0; e < 4; e++) {
                    const uint32_t st = acquire_stage(sb, p, 40960), bar = sb + B_FULL + st * 8, dst = sb + st * STAGE;
                    tma2d(dst, &P.tm[M_OA], nb * 256 + (e >> 1) * 128, (e & 1) * 2048 + m0, bar);
                    tma2d(dst + 16384, &P.tm[M_OA], nb * 256 + (e >> 1) * 128 + 64, (e & 1) * 2048 + m0, bar);
                    const uint32_t* src = ((e & 1) ? g_vmt : g_km) + ((mb * 8 + rank * 4) * 32 + nb * 2 + (e >> 1)) * 512;
#pragma unroll 1
                    for (int i = 0; i < 4; i++) bulk_g2s(dst + 32768 + i * 2048, src + i * 32 * 512, 2048, bar);
                    pipe_next(p);
                }
            }
        } else if (type == T_OPH) {
#pragma unroll 1
            for (int kt = 0; kt < 64; kt++) {
                if ((kt & 15) == 0) dep_wait(sb, ++dep);
                const uint32_t st = acquire_stage(sb, p, 32768), bar = sb + B_FULL + st * 8;
                tma2d(sb + st * STAGE, &P.tm[M_OA], kt * 64, 4096 + m0, bar);
                tma2d_mc(sb + st * STAGE + 16384 + rank * 8192, &P.tm[M_WOH], nb * 128 + rank * 64, kt * 64, bar);
                pipe_next(p);
            }
        } else if (type == T_A1) {
#pragma unroll 1
            for (int kt = 0; kt < 16; kt++) {
                if (kt == 15) dep_wait(sb, ++dep);
                const uint32_t st = acquire_stage(sb, p, kt == 15 ? STAGE + 1024 : STAGE), bar = sb + B_FULL + st * 8;
                if (kt == 15) bulk_g2s(sb + S_COEF, g_coef + nb * 128 + rank * 64, 1024, bar);
                tma4d(sb + st * STAGE, &P.tm[M_AB], kt * 64, nb * 16 + rank * 8, bar);
                tma4d_mc(sb + st * STAGE + 16384 + rank * 16384, &P.tm[M_AX], kt * 64, mb * 128 + rank * 16, bar);
                pipe_next(p);
            }
        } else {
            const int hw = type == T_A2H ? 64 : 128;
            const CUtensorMap* mc = &P.tm[type == T_A2H ? M_CREH : M_CRE];
#pragma unroll 1
            for (int kt = 0; kt < 32; kt++) {
                if ((kt & 15) == 0) dep_wait(sb, ++dep);
                const uint32_t st = acquire_stage(sb, p, 16384 + hw * 256), bar = sb + B_FULL + st * 8;
                tma3d(sb + st * STAGE, &P.tm[M_HT], 0, (kt & 1) * 1024 + (kt >> 1) * 64, mb * 4 + rank * 2, bar);
                tma2d_mc(sb + st * STAGE + 16384 + rank * hw * 128, mc + (kt & 1), (kt >> 1) * 64, (nb * 2 + rank) * hw, bar);
                pipe_next(p);
            }
#pragma unroll 1
            for (int col = nb * 2 * hw; col < (nb + 1) * 2 * hw; col += 128) {
                const uint32_t st = acquire_stage(sb, p, 32768 + 256), bar = sb + B_FULL + st * 8;
                tma4d(sb + st * STAGE, &P.tm[M_AX], col, mb * 128 + rank * 16, bar);
                tma4d(sb + st * STAGE + 16384, &P.tm[M_AX], col + 64, mb * 128 + rank * 16, bar);
                bulk_g2s(sb + st * STAGE + 32768, P.Dskip + col, 256, bar);
                pipe_next(p);
            }
        }
        if (it < 0) { dep_wait(sb, 1); pair = lds32(sb + S_TAIL); it = ITEM_OFF(pair); }
    }
}

__device__ __forceinline__ uint32_t fresh_tid() { uint32_t t; asm volatile("mov.u32 %0, %%tid.x;" : "=r"(t)); return t; }
__device__ __forceinline__ uint32_t fresh_ctaid() { uint32_t t; asm volatile("mov.u32 %0, %%ctaid.x;" : "=r"(t)); return logical_cta(t); }
__device__ __forceinline__ void reset_state(Cons& c, Pend& d, uint32_t sb, bool resumed) {
    const uint32_t t = fresh_tid(), b = fresh_ctaid();
    const int w = __shfl_sync(0xffffffffu, t >> 5, 0);
    c.sb = sb; c.wg = w >> 2; c.wq = w & 3; c.lane = t & 31;
    c.rank = __shfl_sync(0xffffffffu, b & 1, 0); c.pair = __shfl_sync(0xffffffffu, resumed && b < NCHAIN * 2 ? lds32(sb + S_TAIL) : b >> 1, 0);
    c.rel = mapa(sb + B_EMPTY, cluster_rank() ^ (c.lane & 1));
    c.p.stage = 0; c.p.phase = 0;
    c.nst = resumed && c.pair < NCHAIN ? 2 * NPRE : 0;
    d = Pend{};
}
#define PROF_ITEM(i)
#define PROF_MAIN(i)

__global__ void __launch_bounds__(384, 1) fused_kernel(const __grid_constant__ Params P) {
    extern __shared__ __align__(1024) uint8_t smem[];
    const uint32_t sb = smem_u32(smem);
    asm volatile("griddepcontrol.launch_dependents;");
    const int tid = threadIdx.x, lane = tid & 31;
    const int warp = __shfl_sync(0xffffffffu, tid >> 5, 0);
    const int pair = __shfl_sync(0xffffffffu, logical_cta(blockIdx.x) >> 1, 0), rank = __shfl_sync(0xffffffffu, blockIdx.x & 1, 0);
    if (tid == 0) {
        if (sb & 1023) spin_fault();
        sts32(sb + S_DEP, 0); sts32(sb + S_CUR, 0); sts32(sb + S_TAIL, pair); sts32(sb + S_CTA, pair * 2 + rank);
        for (int i = 0; i < NSTAGE; i++) { mbar_init(sb + B_FULL + i * 8, 1); mbar_init(sb + B_EMPTY + i * 8, 16); }
        mbar_init(sb + B_RESUME, 2);
        mbar_init(sb + B_KVFULL, 1); mbar_init(sb + B_KVFULL + 8, 1);
        mbar_init(sb + B_GO, 1); mbar_init(sb + B_KVGO, 1); mbar_init(sb + B_KVGO + 8, 1); mbar_init(sb + B_K, 1); mbar_init(sb + B_V, 1); mbar_init(sb + B_PERS, 8); mbar_init(sb + B_INIT, 3);
        mbar_init(sb + B_WO, 1);
        for (int i = 0; i < 2; i++) { mbar_init(sb + B_SFULL + i * 8, 4); mbar_init(sb + B_SFREE + i * 8, 1); }
        mbar_init(sb + B_RELA, 1); mbar_init(sb + B_RELB, 1);
        asm volatile("fence.mbarrier_init.release.cluster;" ::: "memory");
        if (pair < 16) mbar_expect(sb + B_K, 2048);
        mbar_expect(sb + B_V, 2048);
    }
    cluster_sync();
    if (warp >= 8) {
        asm volatile("setmaxnreg.dec.sync.aligned.u32 24;");
        if (warp == 10 && lane < M_COUNT) map_prefetch(&P.tm[lane]);
        if (warp == 11 && lane == 0 && pair < NCHAIN) {
            const uint32_t t0 = gtime();
            const int role = pair >> 4, h = (pair & 15) * 2 + rank;
#pragma unroll 1
            for (int i = role ? 32 : 0; i < (role ? 44 : 40); i++) {
                wait_time(t0 + P.pf0 + min(i, 32) * P.pf1 + max(i - 32, 0) * P.pf2, sb);
                if (i < 32) asm volatile("cp.async.bulk.prefetch.tensor.3d.L2.global [%0, {%1, %2, %3}];" ::"l"(&P.tm[M_CQ]), "r"(h * 128 + (i & 1) * 64), "r"((i & 2) * 4), "r"((i >> 2) * 8) : "memory");
                else asm volatile("cp.async.bulk.prefetch.tensor.4d.L2.global [%0, {%1, 0, 0, %2}];" ::"l"(&P.tm[M_CO + (i & 1)]), "r"((role == 0 ? 0 : role == 1 ? 256 : 640) + ((i - 32) >> 1) * 64), "r"(h * 8) : "memory");
            }
        }
        if (warp == 9 && pair < NCHAIN) pacer(P, sb, lane);
        if (warp == 9) watcher(P, sb, rank, lane);
        if (warp >= 10 && lane == 0) store_warp(P, sb, warp - 10);
        if (warp == 8) {
            if (lane == 0) producer(P, sb, lds32(sb + S_CTA) >> 1, rank);
            __syncwarp();
            asm volatile("barrier.cluster.arrive.relaxed.aligned;\nbarrier.cluster.wait.aligned;" ::: "memory");
        }
    } else {
        asm volatile("setmaxnreg.inc.sync.aligned.u32 240;");
        Cons c;
        Pend d;
        if (pair < NCHAIN) {
            mem0_max(P, sb, tid);
            reset_state(c, d, sb, false);
#pragma unroll 1
            for (int i = 0; i < NPRE; i++) {
                PROF_ITEM(i)
                const int item = ITEM(ITEM_OFF(pair) + i);
                float acc[128];
                mainloop<256, true>(acc, P, c, d, T_KV);
                epi_kv(acc, c, d, (item >> 5) & 7, item & 31);
            }
            ISTAMP(4)
            drain<0, true>(P, c, d);
            drain<1, true>(P, c, d);
            PROF_ITEM(NPRE)
            uint32_t wr[NR][4];
            load_weights(wr, sb, warp, lane, [&]() { staging_wait(c); });
            const int h = (pair & 15) * 2 + rank;
            if (pair < 16) chain_role<0>(P, wr, sb, h, warp, lane);
            else if (pair < 32) chain_role<1>(P, wr, sb, h, warp, lane);
            else chain_role<2>(P, wr, sb, h, warp, lane);
            fence_async_smem();
            bar_sync(1, 256);
            const uint32_t t2 = fresh_tid();
            if (t2 < 2) mbar_arrive_cluster(mapa(sb + B_RESUME, cluster_rank() ^ t2));
        } else if (pair >= NPAIR - 2) {
            const int ch = (pair - (NPAIR - 2)) * 512 + rank * 256 + tid;
            g_coef[ch] = ssm_coef(__bfloat162float(P.Lre[ch]), __bfloat162float(P.Lim[ch]), __bfloat162float(P.logdt[ch]));
            bar_sync(1, 256);
            if (tid == 0) red_release(&g_cnt(C_COEF));
        }
        reset_state(c, d, sb, true);
        for (int it = ITEM_OFF(c.pair) + (c.pair < NCHAIN ? NPRE + 1 : 0);; it++) {
            const bool last = it == ITEM_OFF(c.pair + 1);
            if (d.kind != PEND_NONE && (last || !bar_and(5 + c.wg, mbar_test(sb + B_FULL + c.p.stage * 8, c.p.phase)))) drain_all(P, c, d);
            if (last) break;
            const int item = ITEM(it), type = item >> 8, mb = (item >> 5) & 7, nb = item & 31;
            PROF_ITEM(it - ITEM_OFF(c.pair))
            if (type >= T_OPH) {
                float acc[64];
                mainloop<128>(acc, P, c, d, type);
                PROF_MAIN(it - ITEM_OFF(c.pair))
                if (type == T_OPH) epi_oph(acc, c, d, mb, nb);
                else epi_a2_half<0>(acc, P, c, mb, nb * 128);
            } else {
                float acc[128];
                mainloop<256>(acc, P, c, d, type);
                PROF_MAIN(it - ITEM_OFF(c.pair))
                if (type == T_KV) epi_kv(acc, c, d, mb, nb);
                else if (type == T_QA) epi_qa(acc, c, d, mb, nb);
                else if (type == T_OP) epi_op(acc, c, d, mb, nb);
                else if (type == T_A1) epi_a1(acc, P, c, d, mb, nb, (lds32(sb + S_EPOCH) + 1) & 1);
                else { epi_a2_half<0>(acc, P, c, mb, nb * 256); epi_a2_half<1>(acc, P, c, mb, nb * 256); }
            }
            if (it == ITEM_OFF(c.pair)) { dep_wait(sb, 1); c.pair = __shfl_sync(0xffffffffu, lds32(sb + S_TAIL), 0); it = ITEM_OFF(c.pair); }
        }
        staging_wait(c);
        staging_post(c, PEND_NONE, 0, 0, 0);
        asm volatile("barrier.cluster.arrive.relaxed.aligned;\nbarrier.cluster.wait.aligned;" ::: "memory");
    }
}

typedef CUresult (*EncodeFn)(CUtensorMap*, CUtensorMapDataType, cuuint32_t, void*, const cuuint64_t*, const cuuint64_t*, const cuuint32_t*, const cuuint32_t*,
                             CUtensorMapInterleave, CUtensorMapSwizzle, CUtensorMapL2promotion, CUtensorMapFloatOOBfill);
void encode(EncodeFn fn, CUtensorMap* m, const void* base, int rank, const uint64_t* dims, const uint64_t* strides, const uint32_t* box, CUtensorMapSwizzle swz = CU_TENSOR_MAP_SWIZZLE_128B) {
    cuuint64_t d[5], s[5]; cuuint32_t b[5], e[5];
    for (int i = 0; i < rank; i++) { d[i] = dims[i]; b[i] = box[i]; e[i] = 1; if (i) s[i - 1] = strides[i - 1]; }
    fn(m, CU_TENSOR_MAP_DATA_TYPE_BFLOAT16, rank, (void*)base, d, s, b, e, CU_TENSOR_MAP_INTERLEAVE_NONE, swz,
       CU_TENSOR_MAP_L2_PROMOTION_L2_256B, CU_TENSOR_MAP_FLOAT_OOB_FILL_NONE);
}
void map_kmajor(EncodeFn fn, CUtensorMap* m, const void* base, uint64_t rows, uint64_t cols, uint32_t box_rows) {
    const uint64_t d[2] = {cols, rows}, s[1] = {cols * 2}; const uint32_t b[2] = {64, box_rows};
    encode(fn, m, base, 2, d, s, b);
}
void map_mnmajor(EncodeFn fn, CUtensorMap* m, const void* base, uint64_t krows, uint64_t cols) {
    const uint64_t d[3] = {64, krows, cols / 64}, s[2] = {cols * 2, 128}; const uint32_t b[3] = {64, 64, 2};
    encode(fn, m, base, 3, d, s, b);
}

}

extern "C" void kernel_launch(void* const* d_in, const int* in_sizes, int n_in, void* d_out, int out_size) {
    static Params P;
    static EncodeFn fn = nullptr;
    if (!fn) {
        cudaDriverEntryPointQueryResult q;
        cudaGetDriverEntryPoint("cuTensorMapEncodeTiled", (void**)&fn, cudaEnableDefault, &q);
        cudaFuncSetAttribute(fused_kernel, cudaFuncAttributeMaxDynamicSharedMemorySize, S_TOTAL);
    }
    const bf16* in[15];
    for (int i = 0; i < 15; i++) in[i] = (const bf16*)d_in[i];
    void *kvo, *ht, *gm;
    cudaGetSymbolAddress(&gm, g_m);
    P.gm = (uint8_t*)(((uintptr_t)gm + 32767) & ~(uintptr_t)32767);
    cudaGetSymbolAddress(&kvo, g_kvo);
    cudaGetSymbolAddress(&ht, g_ht);
    map_kmajor(fn, &P.tm[M_BX], in[9], 2048, 1024, 128);
    map_mnmajor(fn, &P.tm[M_WQ], in[11], 1024, 4096);
    map_mnmajor(fn, &P.tm[M_WK], in[12], 1024, 4096);
    map_mnmajor(fn, &P.tm[M_WV], in[13], 1024, 4096);
    map_mnmajor(fn, &P.tm[M_WO], in[14], 4096, 1024);
    map_kmajor(fn, &P.tm[M_OA], kvo, 3 * 2048, 4096, 128);
    P.swap_ri = in[4] < in[3];
    {
        const bf16* lo = P.swap_ri ? in[4] : in[3];
        const uint64_t diff = (uint64_t)((const char*)(P.swap_ri ? in[3] : in[4]) - (const char*)lo);
        const uint64_t d[4] = {1024, 8, 2, 128}, s[3] = {2048, diff, 16384}; const uint32_t b[4] = {64, 8, 2, 8};
        encode(fn, &P.tm[M_AB], lo, 4, d, s, b);
    }
    {
        const uint64_t d[4] = {1024, 2, 4, 1024}, s[3] = {2048, 64 * 2048, 4096}; const uint32_t b[4] = {64, 2, 4, 16};
        encode(fn, &P.tm[M_AX], in[0], 4, d, s, b);
    }
    map_mnmajor(fn, &P.tm[M_HT], ht, 2048, 2048);
    map_kmajor(fn, &P.tm[M_CRE], in[5], 1024, 1024, 128);
    map_kmajor(fn, &P.tm[M_CIM], in[6], 1024, 1024, 128);
    map_kmajor(fn, &P.tm[M_KVO], kvo, 3 * 2048, 4096, 32);
    map_kmajor(fn, &P.tm[M_HTS], ht, 2048, 2048, 32);
    map_kmajor(fn, &P.tm[M_WOH], in[14], 4096, 1024, 64);
    map_kmajor(fn, &P.tm[M_CREH], in[5], 1024, 1024, 64);
    map_kmajor(fn, &P.tm[M_CIMH], in[6], 1024, 1024, 64);
    for (int i = 0; i < 3; i++) {
        const uint64_t d[3] = {4096, 16, 64}, s[2] = {8192, 16 * 8192}; const uint32_t b[3] = {64, 8, 8};
        encode(fn, &P.tm[M_CQ + i], in[11 + i], 3, d, s, b);
    }
    {
        const uint64_t d[4] = {4096, 1, 1, 4096}, s[3] = {8192, 8192, 8192}; const uint32_t b[4] = {64, 1, 1, 32};
        encode(fn, &P.tm[M_KV4], kvo, 4, d, s, b);
    }
    for (int e = 0; e < 2; e++) {
        const uint64_t d[4] = {1024, 2, 4, 256}, s[3] = {8 * 2048, 2 * 2048, 16 * 2048}; const uint32_t b[4] = {64, 2, 4, 8};
        encode(fn, &P.tm[M_CO + e], in[14] + e * 1024, 4, d, s, b);
    }
    P.Wq = in[11]; P.Wk = in[12]; P.Wv = in[13]; P.Wo = in[14]; P.mem0 = in[10];
    P.Lre = in[1]; P.Lim = in[2]; P.logdt = in[7]; P.Dskip = in[8];
    P.out = (float*)d_out;
    P.two26 = 1u << 26;
    P.ds = 400; P.dc = 1600; P.alpha = 0.3f; P.extra = 200; P.da = 192; P.db = 432; P.dk = 800; P.dp = 1550; P.dv = 60; P.pf0 = 1500; P.pf1 = 175; P.pf2 = 450; P.back = 150; P.ds0 = 950;
    for (int i = 0; i < (DBGF(32) ? 1 : 2); i++) {
        cudaLaunchConfig_t cfg = {};
        cfg.gridDim = dim3(i ? 36 : 96); cfg.blockDim = dim3(384); cfg.dynamicSmemBytes = S_TOTAL; cfg.stream = cudaStreamPerThread;
        cudaLaunchAttribute at[2];
        at[0].id = cudaLaunchAttributeClusterDimension; at[0].val.clusterDim.x = i ? 2 : 6; at[0].val.clusterDim.y = at[0].val.clusterDim.z = 1;
        at[1].id = cudaLaunchAttributeProgrammaticStreamSerialization; at[1].val.programmaticStreamSerializationAllowed = 1;
        cfg.attrs = at; cfg.numAttrs = 1 + i;
        cudaLaunchKernelEx(&cfg, fused_kernel, P);
    }
}
```

```cpp
#include <cuda_runtime.h>
#include <cuda_bf16.h>
#include <cuda.h>
#include <stdint.h>
#include <string.h>

typedef __nv_bfloat16 bf16;

namespace {

#define POLL 200
constexpr int SPIN_LIMIT = 1 << 22;
constexpr int NPAIR = 66;
constexpr int NCHAIN = 48;
enum { T_KV = 0, T_QA = 1, T_OP = 2, T_A1 = 3, T_A2 = 4, T_CHAIN = 5, T_OPH = 6, T_A2H = 7 };
enum { M_BX = 0, M_WQ, M_WK, M_WV, M_WO, M_OA, M_AB, M_AX, M_HT, M_CRE, M_CIM, M_KVO, M_HTS, M_WOH, M_CREH, M_CIMH, M_CQ, M_CK, M_CV, M_CO, M_CO1, M_KV4, M_COUNT };
enum { C_KV = 0, C_HT = 8, C_DONE = 24, C_EPOCH = 25, C_COEF = 26, C_FLAG = 32, C_O = 96 };

struct Params {
    CUtensorMap tm[M_COUNT];
    const bf16 *Wq, *Wk, *Wv, *Wo, *mem0, *Lre, *Lim, *logdt, *Dskip;
    float* out;
    uint8_t* gm;
    int swap_ri, zero;
    uint32_t two26;
    int ds, da, db, dk, dv, back, ds0, pf0, pf1, pf2, dc, extra, dp;
    float alpha;
#define DBGF(x) false
};

constexpr int NPRE = 1;
__constant__ uint16_t c_off[67] = {0, 5, 10, 15, 19, 23, 27, 31, 35, 39, 43, 48, 52, 56, 60, 64, 68, 73, 78, 83, 87, 91, 95, 101, 106, 110, 114, 118, 122, 127, 132, 136, 140, 145, 150, 155, 159, 163, 167, 173, 179, 183, 187, 191, 195, 199, 204, 208, 212, 232, 252, 271, 291, 311, 331, 350, 370, 390, 409, 429, 449, 468, 488, 505, 524, 543, 562};
__constant__ uint16_t c_items[640] = {
    32, 1280, 423, 495, 1122, 49, 1280, 455, 333, 1057, 34, 1280, 428, 302, 1056, 51, 1280, 422, 642, 36, 1280, 326, 641, 53,
    1280, 330, 545, 38, 1280, 869, 547, 55, 1280, 867, 546, 40, 1280, 931, 608, 57, 1280, 899, 609, 42, 1280, 452, 297, 1185,
    59, 1280, 454, 513, 44, 1280, 836, 675, 61, 1280, 804, 672, 46, 1280, 389, 544, 63, 1280, 388, 576, 0, 1280, 292, 491,
    1250, 1, 1280, 484, 493, 1120, 2, 1280, 492, 334, 1058, 3, 1280, 457, 512, 4, 1280, 490, 673, 5, 1280, 458, 610, 6,
    1280, 425, 301, 460, 1862, 7, 1280, 424, 299, 1025, 8, 1280, 871, 707, 9, 1280, 839, 704, 10, 1280, 963, 736, 11, 1280,
    995, 705, 12, 1280, 992, 902, 1218, 13, 1280, 961, 966, 1249, 14, 1280, 928, 739, 15, 1280, 929, 578, 16, 1280, 356, 494,
    1121, 17, 1280, 364, 335, 1153, 18, 1280, 300, 331, 1248, 19, 1280, 453, 514, 20, 1280, 488, 674, 21, 1280, 486, 737, 22,
    1280, 393, 429, 461, 1857, 23, 1280, 392, 427, 463, 1863, 24, 1280, 903, 611, 25, 1280, 866, 515, 26, 1280, 901, 706, 27,
    1280, 898, 738, 28, 1280, 960, 643, 29, 1280, 993, 934, 1217, 30, 1280, 896, 579, 31, 1280, 897, 577, 33, 66, 84, 102,
    120, 138, 156, 174, 210, 246, 204, 201, 224, 323, 365, 259, 835, 962, 329, 1027, 35, 67, 85, 103, 121, 139, 157, 175,
    221, 223, 213, 220, 354, 229, 419, 367, 384, 261, 964, 1152, 37, 68, 86, 104, 122, 140, 158, 176, 239, 196, 263, 225,
    360, 264, 832, 837, 994, 996, 1059, 39, 69, 87, 105, 123, 141, 159, 177, 207, 199, 195, 237, 396, 296, 322, 390, 489,
    395, 967, 1251, 41, 70, 88, 106, 124, 142, 160, 178, 253, 245, 192, 197, 235, 386, 362, 352, 262, 487, 269, 1216, 43,
    71, 89, 107, 125, 143, 161, 179, 241, 249, 233, 219, 353, 321, 387, 834, 256, 459, 933, 1187, 45, 72, 90, 108, 126,
    144, 162, 180, 203, 250, 226, 358, 327, 805, 324, 449, 900, 332, 1154, 47, 73, 91, 109, 127, 145, 163, 181, 240, 200,
    244, 212, 227, 385, 357, 448, 483, 868, 271, 1026, 48, 74, 92, 110, 128, 146, 164, 182, 206, 248, 218, 216, 247, 238,
    397, 768, 838, 361, 935, 1090, 50, 75, 93, 111, 129, 147, 165, 183, 231, 222, 211, 363, 773, 801, 431, 420, 394, 430,
    1024, 52, 76, 94, 112, 130, 148, 166, 184, 193, 228, 214, 215, 355, 803, 288, 295, 864, 359, 998, 1219, 54, 77, 95,
    113, 131, 149, 167, 185, 243, 198, 194, 205, 325, 417, 303, 294, 481, 456, 366, 1186, 56, 78, 96, 114, 132, 150, 168,
    186, 234, 202, 242, 328, 775, 833, 800, 421, 485, 932, 1089, 58, 79, 97, 115, 133, 151, 169, 187, 217, 208, 209, 290,
    398, 416, 265, 865, 480, 462, 997, 1184, 60, 80, 98, 116, 134, 152, 170, 188, 291, 254, 298, 255, 771, 806, 450, 807,
    640, 62, 81, 99, 117, 135, 153, 171, 189, 257, 251, 232, 769, 772, 289, 451, 870, 426, 999, 1856, 64, 82, 100, 118,
    136, 154, 172, 190, 260, 230, 293, 252, 774, 770, 266, 418, 930, 270, 1123, 65, 83, 101, 119, 137, 155, 173, 191, 267,
    236, 320, 258, 399, 391, 802, 482, 268, 965, 1155,
};
#define ITEM_OFF(p) c_off[p]
#define ITEM(i) c_items[i]

__device__ __align__(1024) bf16 g_kvo[3 * 2048 * 4096];
__device__ __align__(1024) bf16 g_ht[2048 * 2048];
__device__ __align__(1024) uint8_t g_m[9 * 32768];
__device__ __align__(1024) uint8_t g_f[8 * 49152];
__device__ __align__(1024) uint32_t g_km[64 * 32 * 512];
__device__ __align__(1024) uint32_t g_vmt[64 * 32 * 512];
__device__ __align__(1024) float2 g_agg[8 * 1024];
__device__ __align__(1024) float4 g_coef[1024];
__device__ __align__(1024) uint32_t g_cntl[128 * 32];
#define g_cnt(i) g_cntl[(i) * 32]
__device__ __align__(1024) uint32_t g_hint[6144 + 160];
#define SSTAMP(i, cond)
#define PROF(i)
#define GT_EDGE(o)
constexpr int M_SLOT = 32768, F_SLOT = 49152;

constexpr int STAGE = 49152, NSTAGE = 4;
constexpr int S_STG = NSTAGE * STAGE;
constexpr int S_BAR = S_STG + 32768;
constexpr int B_FULL = S_BAR, B_EMPTY = S_BAR + 32, B_RESUME = S_BAR + 64, B_KVFULL = S_BAR + 72, B_GO = S_BAR + 88, B_K = S_BAR + 96, B_PERS = S_BAR + 104, B_INIT = S_BAR + 112, B_RELA = S_BAR + 120, B_V = S_BAR + 128, B_WO = S_BAR + 136,
              B_SFULL = S_BAR + 144, B_SFREE = S_BAR + 160, S_DESC = S_BAR + 176, S_REDO = S_BAR + 256 + 512 + 64, S_EPOCH = S_BAR + 208, B_RELB = S_BAR + 216, B_KVGO = S_BAR + 224, S_DEP = S_BAR + 240, S_CUR = S_BAR + 244, S_TAIL = S_BAR + 248, S_CTA = S_BAR + 252;
constexpr int S_COEF = S_BAR + 256 + 512, S_TOTAL = S_COEF + 1024;
constexpr int S_W1 = 0;
constexpr int S_O = 24 * 4096, S_VL = S_O + 2048, S_MX = 25 * 4096, S_SC = S_MX + 64, S_SUM = S_MX + 128;
constexpr int S_KL = 26 * 4096;
constexpr int S_W2 = 27 * 4096;
constexpr int S_KV = S_W2 + 65536;
constexpr int S_P1 = S_W2 + 98304;
constexpr int S_QX = S_P1 + 16384;
constexpr int S_SX = S_QX + 2048;
static_assert(S_SX + 1280 <= S_BAR, "chain smem overlaps barriers");
constexpr int NR = 40, NS = 64 - NR;

__device__ __forceinline__ uint32_t logical_cta(uint32_t b) {
    const uint32_t c = b / 6, r = b - c * 6;
    return gridDim.x != 96 ? 96 + b : ((r >> 1) + (c >= 8) + (c >= 15)) % 3 * 32 + c * 2 + (r & 1);
}
__device__ __forceinline__ uint32_t cluster_rank() { uint32_t r; asm("mov.u32 %0, %%cluster_ctarank;" : "=r"(r)); return r; }
__device__ __forceinline__ uint16_t pair_mask() { return (uint16_t)(3u << (cluster_rank() & 6)); }
__device__ __forceinline__ void spin_fault() { asm volatile("st.global.u32 [%0], 0;" ::"l"(0ull) : "memory"); }
__device__ __forceinline__ uint32_t smem_u32(const void* p) { return (uint32_t)__cvta_generic_to_shared(p); }
__device__ __forceinline__ uint32_t opq(uint32_t x, int lane) { return __shfl_sync(0xffffffffu, x, lane); }
__device__ __forceinline__ uint32_t mapa(uint32_t a, uint32_t r) { uint32_t d; asm volatile("mapa.shared::cluster.u32 %0, %1, %2;" : "=r"(d) : "r"(a), "r"(r)); return d; }
__device__ __forceinline__ void mma16816(float* d, uint32_t a0, uint32_t a1, uint32_t a2, uint32_t a3, uint32_t b0, uint32_t b1) {
    asm("mma.sync.aligned.m16n8k16.row.col.f32.bf16.bf16.f32 {%0,%1,%2,%3}, {%4,%5,%6,%7}, {%8,%9}, {%0,%1,%2,%3};"
        : "+f"(d[0]), "+f"(d[1]), "+f"(d[2]), "+f"(d[3]) : "r"(a0), "r"(a1), "r"(a2), "r"(a3), "r"(b0), "r"(b1));
}
__device__ __forceinline__ void mma1688(float* d, uint32_t a0, uint32_t a1, uint32_t b0) {
    asm("mma.sync.aligned.m16n8k8.row.col.f32.bf16.bf16.f32 {%0,%1,%2,%3}, {%4,%5}, {%6}, {%0,%1,%2,%3};"
        : "+f"(d[0]), "+f"(d[1]), "+f"(d[2]), "+f"(d[3]) : "r"(a0), "r"(a1), "r"(b0));
}
__device__ __forceinline__ void ldsm4(uint32_t* r, uint32_t a) {
    asm volatile("ldmatrix.sync.aligned.m8n8.x4.shared.b16 {%0,%1,%2,%3}, [%4];" : "=r"(r[0]), "=r"(r[1]), "=r"(r[2]), "=r"(r[3]) : "r"(a));
}
__device__ __forceinline__ void ldsm4t(uint32_t* r, uint32_t a) {
    asm volatile("ldmatrix.sync.aligned.m8n8.x4.trans.shared.b16 {%0,%1,%2,%3}, [%4];" : "=r"(r[0]), "=r"(r[1]), "=r"(r[2]), "=r"(r[3]) : "r"(a));
}
__device__ __forceinline__ void stsm4(uint32_t a, uint32_t r0, uint32_t r1, uint32_t r2, uint32_t r3) {
    asm volatile("stmatrix.sync.aligned.m8n8.x4.shared.b16 [%0], {%1,%2,%3,%4};" ::"r"(a), "r"(r0), "r"(r1), "r"(r2), "r"(r3) : "memory");
}
__device__ __forceinline__ void stsm4t(uint32_t a, uint32_t r0, uint32_t r1, uint32_t r2, uint32_t r3) {
    asm volatile("stmatrix.sync.aligned.m8n8.x4.trans.shared.b16 [%0], {%1,%2,%3,%4};" ::"r"(a), "r"(r0), "r"(r1), "r"(r2), "r"(r3) : "memory");
}
__device__ __forceinline__ uint32_t pack2(float lo, float hi) { uint32_t d; asm("cvt.rn.bf16x2.f32 %0, %1, %2;" : "=r"(d) : "f"(hi), "f"(lo)); return d; }
__device__ __forceinline__ float bf_lo(uint32_t u) { return __uint_as_float(u << 16); }
__device__ __forceinline__ float bf_hi(uint32_t u) { return __uint_as_float(u & 0xffff0000u); }
__device__ __forceinline__ uint32_t hmul2(uint32_t a, uint32_t b) { uint32_t d; asm("mul.rn.bf16x2 %0, %1, %2;" : "=r"(d) : "r"(a), "r"(b)); return d; }
__device__ __forceinline__ float ex2(float x) { float y; asm("ex2.approx.ftz.f32 %0, %1;" : "=f"(y) : "f"(x)); return y; }
__device__ __forceinline__ float rcp(float x) { float y; asm("rcp.approx.ftz.f32 %0, %1;" : "=f"(y) : "f"(x)); return y; }
__device__ __forceinline__ void st_relaxed4(const void* p, uint32_t a, uint32_t b, uint32_t c, uint32_t d) {
    asm volatile("{\n.reg .b128 t;\nmov.b128 t, {%1,%2,%3,%4};\nst.relaxed.gpu.global.b128 [%0], t;\n}" ::"l"(p), "r"(a), "r"(b), "r"(c), "r"(d) : "memory");
}
__device__ __forceinline__ void st_relaxed2(const void* p, uint32_t a, uint32_t b) {
    asm volatile("{\n.reg .b64 t;\nmov.b64 t, {%1,%2};\nst.relaxed.gpu.global.b64 [%0], t;\n}" ::"l"(p), "r"(a), "r"(b) : "memory");
}
__device__ __forceinline__ void ld_relaxed2_if(uint32_t& a, uint32_t& b, const void* p, bool on) {
    asm volatile("{\n.reg .pred P;\n.reg .b64 t;\nsetp.ne.u32 P, %3, 0;\nmov.b64 t, {%0,%1};\n@P ld.relaxed.gpu.global.b64 t, [%2];\nmov.b64 {%0,%1}, t;\n}" : "+r"(a), "+r"(b) : "l"(p), "r"((uint32_t)on) : "memory");
}
__device__ __forceinline__ uint32_t ld_relaxed1(const void* p) { uint32_t v; asm volatile("ld.relaxed.gpu.global.u32 %0, [%1];" : "=r"(v) : "l"(p) : "memory"); return v; }
__device__ __forceinline__ void st_relaxed1(const void* p, uint32_t v) { asm volatile("st.relaxed.gpu.global.u32 [%0], %1;" ::"l"(p), "r"(v) : "memory"); }
__device__ __forceinline__ uint32_t ld_acquire(const void* p) { uint32_t v; asm volatile("ld.acquire.gpu.global.u32 %0, [%1];" : "=r"(v) : "l"(p) : "memory"); return v; }
__device__ __forceinline__ void red_release(void* p) { asm volatile("red.release.gpu.global.add.u32 [%0], 1;" ::"l"(p) : "memory"); }
__device__ __forceinline__ void st_stream2(float* p, float a, float b) { asm volatile("st.global.cs.v2.f32 [%0], {%1, %2};" ::"l"(p), "f"(a), "f"(b) : "memory"); }
__device__ __forceinline__ void fence_acquire() { asm volatile("fence.acquire.gpu;" ::: "memory"); }
__device__ __forceinline__ void fence_release() { asm volatile("fence.release.gpu;" ::: "memory"); }
__device__ __forceinline__ void fence_async() {  asm volatile("fence.proxy.async.global;" ::: "memory"); }
__device__ __forceinline__ void fence_async_smem() { asm volatile("fence.proxy.async.shared::cta;" ::: "memory"); }
__device__ __forceinline__ void wait_count(const uint32_t* p, uint32_t target) {
    int n = 0;
    while ((int32_t)(ld_acquire(p) - target) < 0) { __nanosleep(POLL); if (++n > SPIN_LIMIT) spin_fault(); }
}
__device__ __forceinline__ void bar_sync(int id, int n) { asm volatile("bar.sync %0, %1;" ::"r"(id), "r"(n) : "memory"); }
__device__ __forceinline__ void bar_arrive(int id, int n) { asm volatile("bar.arrive %0, %1;" ::"r"(id), "r"(n) : "memory"); }
__device__ __forceinline__ bool bar_and(int id, bool v) {
    uint32_t r;
    asm volatile("{\n.reg .pred P, Q;\nsetp.ne.u32 Q, %2, 0;\nbar.red.and.pred P, %1, 128, Q;\nselp.u32 %0, 1, 0, P;\n}" : "=r"(r) : "r"(id), "r"((uint32_t)v) : "memory");
    return r;
}
__device__ __forceinline__ void lds128(uint32_t* v, uint32_t a) { asm volatile("ld.shared.v4.b32 {%0,%1,%2,%3}, [%4];" : "=r"(v[0]), "=r"(v[1]), "=r"(v[2]), "=r"(v[3]) : "r"(a) : "memory"); }
__device__ __forceinline__ uint32_t lds32(uint32_t a) { uint32_t v; asm volatile("ld.shared.b32 %0, [%1];" : "=r"(v) : "r"(a) : "memory"); return v; }
__device__ __forceinline__ void lds64f(float* v, uint32_t a) { asm volatile("ld.shared.v2.f32 {%0,%1}, [%2];" : "=f"(v[0]), "=f"(v[1]) : "r"(a) : "memory"); }
__device__ __forceinline__ void sts128(uint32_t a, const uint32_t* v) { asm volatile("st.shared.v4.b32 [%0], {%1,%2,%3,%4};" ::"r"(a), "r"(v[0]), "r"(v[1]), "r"(v[2]), "r"(v[3]) : "memory"); }
__device__ __forceinline__ void sts64(uint32_t a, uint32_t x, uint32_t y) { asm volatile("st.shared.v2.b32 [%0], {%1,%2};" ::"r"(a), "r"(x), "r"(y) : "memory"); }
__device__ __forceinline__ void sts32(uint32_t a, uint32_t x) { asm volatile("st.shared.b32 [%0], %1;" ::"r"(a), "r"(x) : "memory"); }
__device__ __forceinline__ bool mbar_try(uint32_t b, uint32_t par) {
    uint32_t ok;
    asm volatile("{\n.reg .pred P;\nmbarrier.try_wait.parity.shared::cta.b64 P, [%1], %2;\nselp.u32 %0, 1, 0, P;\n}" : "=r"(ok) : "r"(b), "r"(par) : "memory");
    return ok;
}
__device__ __forceinline__ bool mbar_test(uint32_t b, uint32_t par) {
    uint32_t ok;
    asm volatile("{\n.reg .pred P;\nmbarrier.test_wait.parity.shared::cta.b64 P, [%1], %2;\nselp.u32 %0, 1, 0, P;\n}" : "=r"(ok) : "r"(b), "r"(par) : "memory");
    return ok;
}
__device__ __forceinline__ void mbar_wait(uint32_t b, uint32_t par) { int n = 0; while (!mbar_try(b, par)) { if (++n > SPIN_LIMIT) spin_fault(); } }
__device__ __forceinline__ void mbar_init(uint32_t b, uint32_t n) { asm volatile("mbarrier.init.shared::cta.b64 [%0], %1;" ::"r"(b), "r"(n) : "memory"); }
__device__ __forceinline__ void mbar_expect(uint32_t b, uint32_t bytes) { asm volatile("mbarrier.arrive.expect_tx.shared::cta.b64 _, [%0], %1;" ::"r"(b), "r"(bytes) : "memory"); }
__device__ __forceinline__ void mbar_arrive(uint32_t b) { asm volatile("mbarrier.arrive.shared::cta.b64 _, [%0];" ::"r"(b) : "memory"); }
__device__ __forceinline__ void mbar_arrive_cluster(uint32_t b) { asm volatile("mbarrier.arrive.shared::cluster.b64 _, [%0];" ::"r"(b) : "memory"); }
__device__ __forceinline__ void st_async1(uint32_t a, uint32_t x, uint32_t bar) {
    asm volatile("st.async.weak.shared::cluster.mbarrier::complete_tx::bytes.b32 [%0], %1, [%2];" ::"r"(a), "r"(x), "r"(bar) : "memory");
}
__device__ __forceinline__ void st_async2(uint32_t a, uint32_t x, uint32_t y, uint32_t bar) {
    asm volatile("st.async.weak.shared::cluster.mbarrier::complete_tx::bytes.v2.b32 [%0], {%1,%2}, [%3];" ::"r"(a), "r"(x), "r"(y), "r"(bar) : "memory");
}
__device__ __forceinline__ void cluster_sync() { asm volatile("barrier.cluster.arrive.aligned;\nbarrier.cluster.wait.aligned;" ::: "memory"); }
__device__ __forceinline__ void tma2d(uint32_t dst, const CUtensorMap* m, int c0, int c1, uint32_t bar) {
    asm volatile("cp.async.bulk.tensor.2d.shared::cluster.global.mbarrier::complete_tx::bytes [%0], [%1, {%2, %3}], [%4];" ::"r"(dst), "l"(m), "r"(c0), "r"(c1), "r"(bar) : "memory");
}
__device__ __forceinline__ void tma2d_mc(uint32_t dst, const CUtensorMap* m, int c0, int c1, uint32_t bar) {
    asm volatile("cp.async.bulk.tensor.2d.shared::cluster.global.mbarrier::complete_tx::bytes.multicast::cluster [%0], [%1, {%2, %3}], [%4], %5;" ::"r"(dst), "l"(m), "r"(c0), "r"(c1), "r"(bar), "h"(pair_mask()) : "memory");
}
__device__ __forceinline__ void tma3d(uint32_t dst, const CUtensorMap* m, int c0, int c1, int c2, uint32_t bar) {
    asm volatile("cp.async.bulk.tensor.3d.shared::cluster.global.mbarrier::complete_tx::bytes [%0], [%1, {%2, %3, %4}], [%5];" ::"r"(dst), "l"(m), "r"(c0), "r"(c1), "r"(c2), "r"(bar) : "memory");
}
__device__ __forceinline__ void tma3d_mc(uint32_t dst, const CUtensorMap* m, int c0, int c1, int c2, uint32_t bar) {
    asm volatile("cp.async.bulk.tensor.3d.shared::cluster.global.mbarrier::complete_tx::bytes.multicast::cluster [%0], [%1, {%2, %3, %4}], [%5], %6;" ::"r"(dst), "l"(m), "r"(c0), "r"(c1), "r"(c2), "r"(bar), "h"(pair_mask()) : "memory");
}
__device__ __forceinline__ void tma4d(uint32_t dst, const CUtensorMap* m, int c0, int c3, uint32_t bar) {
    asm volatile("cp.async.bulk.tensor.4d.shared::cluster.global.mbarrier::complete_tx::bytes [%0], [%1, {%2, 0, 0, %3}], [%4];" ::"r"(dst), "l"(m), "r"(c0), "r"(c3), "r"(bar) : "memory");
}
__device__ __forceinline__ void tma4d_mc(uint32_t dst, const CUtensorMap* m, int c0, int c3, uint32_t bar) {
    asm volatile("cp.async.bulk.tensor.4d.shared::cluster.global.mbarrier::complete_tx::bytes.multicast::cluster [%0], [%1, {%2, 0, 0, %3}], [%4], %5;" ::"r"(dst), "l"(m), "r"(c0), "r"(c3), "r"(bar), "h"(pair_mask()) : "memory");
}
__device__ __forceinline__ void map_prefetch(const CUtensorMap* m) { asm volatile("prefetch.tensormap [%0];" ::"l"(m) : "memory"); }
__device__ __forceinline__ void bulk_g2s(uint32_t dst, const void* src, uint32_t bytes, uint32_t bar) {
    asm volatile("cp.async.bulk.shared::cluster.global.mbarrier::complete_tx::bytes [%0], [%1], %2, [%3];" ::"r"(dst), "l"(src), "r"(bytes), "r"(bar) : "memory");
}
__device__ __forceinline__ void bulk_s2g(void* dst, uint32_t src, uint32_t bytes) {
    asm volatile("cp.async.bulk.global.shared::cta.bulk_group [%0], [%1], %2;" ::"l"(dst), "r"(src), "r"(bytes) : "memory");
}
__device__ __forceinline__ void tma_store2d(const CUtensorMap* m, int c0, int c1, uint32_t src) {
    asm volatile("cp.async.bulk.tensor.2d.global.shared::cta.bulk_group [%0, {%1, %2}], [%3];" ::"l"(m), "r"(c0), "r"(c1), "r"(src) : "memory");
}
__device__ __forceinline__ void bulk_commit() { asm volatile("cp.async.bulk.commit_group;" ::: "memory"); }
__device__ __forceinline__ void bulk_wait_read() { asm volatile("cp.async.bulk.wait_group.read 0;" ::: "memory"); }
__device__ __forceinline__ void bulk_wait_all() { asm volatile("cp.async.bulk.wait_group 0;" ::: "memory"); }
__device__ __forceinline__ uint64_t mkdesc(uint32_t addr, uint32_t lbo, uint32_t sbo, uint32_t swz) {
    return (uint64_t)((addr & 0x3FFFF) >> 4) | ((uint64_t)(lbo >> 4) << 16) | ((uint64_t)(sbo >> 4) << 32) | ((uint64_t)swz << 62);
}
__device__ __forceinline__ void wg_fence() { asm volatile("wgmma.fence.sync.aligned;" ::: "memory"); }
__device__ __forceinline__ void wg_commit() { asm volatile("wgmma.commit_group.sync.aligned;" ::: "memory"); }
template <int N> __device__ __forceinline__ void wg_wait() { asm volatile("wgmma.wait_group.sync.aligned %0;" ::"n"(N) : "memory"); }
template <typename T> __device__ __forceinline__ void pin_ptr(T*& p) { asm volatile("" : "+l"(p)); }
template <int N> __device__ __forceinline__ void pin(uint32_t* d) {
#pragma unroll
    for (int i = 0; i < N; i++) asm volatile("" : "+r"(d[i])::"memory");
}
template <int N> __device__ __forceinline__ void pin(float* d) {
#pragma unroll
    for (int i = 0; i < N; i++) asm volatile("" : "+f"(d[i])::"memory");
}

template <int TA, int TB>
__device__ __forceinline__ void wgmma_ss256(float* d, uint64_t da, uint64_t db) {
    asm volatile("wgmma.mma_async.sync.aligned.m64n256k16.f32.bf16.bf16 "
        "{%0, %1, %2, %3, %4, %5, %6, %7, %8, %9, %10, %11, %12, %13, %14, %15, %16, %17, %18, %19, %20, %21, %22, %23, %24, %25, %26, %27, %28, %29, %30, %31, %32, %33, %34, %35, %36, %37, %38, %39, %40, %41, %42, %43, %44, %45, %46, %47, %48, %49, %50, %51, %52, %53, %54, %55, %56, %57, %58, %59, %60, %61, %62, %63, %64, %65, %66, %67, %68, %69, %70, %71, %72, %73, %74, %75, %76, %77, %78, %79, %80, %81, %82, %83, %84, %85, %86, %87, %88, %89, %90, %91, %92, %93, %94, %95, %96, %97, %98, %99, %100, %101, %102, %103, %104, %105, %106, %107, %108, %109, %110, %111, %112, %113, %114, %115, %116, %117, %118, %119, %120, %121, %122, %123, %124, %125, %126, %127}, %128, %129, 1, 1, 1, %130, %131;"
        : "+f"(d[0]), "+f"(d[1]), "+f"(d[2]), "+f"(d[3]), "+f"(d[4]), "+f"(d[5]), "+f"(d[6]), "+f"(d[7]), "+f"(d[8]), "+f"(d[9]), "+f"(d[10]), "+f"(d[11]), "+f"(d[12]), "+f"(d[13]), "+f"(d[14]), "+f"(d[15]), "+f"(d[16]), "+f"(d[17]), "+f"(d[18]), "+f"(d[19]), "+f"(d[20]), "+f"(d[21]), "+f"(d[22]), "+f"(d[23]), "+f"(d[24]), "+f"(d[25]), "+f"(d[26]), "+f"(d[27]), "+f"(d[28]), "+f"(d[29]), "+f"(d[30]), "+f"(d[31]), "+f"(d[32]), "+f"(d[33]), "+f"(d[34]), "+f"(d[35]), "+f"(d[36]), "+f"(d[37]), "+f"(d[38]), "+f"(d[39]), "+f"(d[40]), "+f"(d[41]), "+f"(d[42]), "+f"(d[43]), "+f"(d[44]), "+f"(d[45]), "+f"(d[46]), "+f"(d[47]), "+f"(d[48]), "+f"(d[49]), "+f"(d[50]), "+f"(d[51]), "+f"(d[52]), "+f"(d[53]), "+f"(d[54]), "+f"(d[55]), "+f"(d[56]), "+f"(d[57]), "+f"(d[58]), "+f"(d[59]), "+f"(d[60]), "+f"(d[61]), "+f"(d[62]), "+f"(d[63]), "+f"(d[64]), "+f"(d[65]), "+f"(d[66]), "+f"(d[67]), "+f"(d[68]), "+f"(d[69]), "+f"(d[70]), "+f"(d[71]), "+f"(d[72]), "+f"(d[73]), "+f"(d[74]), "+f"(d[75]), "+f"(d[76]), "+f"(d[77]), "+f"(d[78]), "+f"(d[79]), "+f"(d[80]), "+f"(d[81]), "+f"(d[82]), "+f"(d[83]), "+f"(d[84]), "+f"(d[85]), "+f"(d[86]), "+f"(d[87]), "+f"(d[88]), "+f"(d[89]), "+f"(d[90]), "+f"(d[91]), "+f"(d[92]), "+f"(d[93]), "+f"(d[94]), "+f"(d[95]), "+f"(d[96]), "+f"(d[97]), "+f"(d[98]), "+f"(d[99]), "+f"(d[100]), "+f"(d[101]), "+f"(d[102]), "+f"(d[103]), "+f"(d[104]), "+f"(d[105]), "+f"(d[106]), "+f"(d[107]), "+f"(d[108]), "+f"(d[109]), "+f"(d[110]), "+f"(d[111]), "+f"(d[112]), "+f"(d[113]), "+f"(d[114]), "+f"(d[115]), "+f"(d[116]), "+f"(d[117]), "+f"(d[118]), "+f"(d[119]), "+f"(d[120]), "+f"(d[121]), "+f"(d[122]), "+f"(d[123]), "+f"(d[124]), "+f"(d[125]), "+f"(d[126]), "+f"(d[127])
        : "l"(da), "l"(db), "n"(TA), "n"(TB));
}
template <int TA, int TB>
__device__ __forceinline__ void wgmma_ss256_first(float* d, uint64_t da, uint64_t db) {
    asm volatile("wgmma.mma_async.sync.aligned.m64n256k16.f32.bf16.bf16 "
        "{%0, %1, %2, %3, %4, %5, %6, %7, %8, %9, %10, %11, %12, %13, %14, %15, %16, %17, %18, %19, %20, %21, %22, %23, %24, %25, %26, %27, %28, %29, %30, %31, %32, %33, %34, %35, %36, %37, %38, %39, %40, %41, %42, %43, %44, %45, %46, %47, %48, %49, %50, %51, %52, %53, %54, %55, %56, %57, %58, %59, %60, %61, %62, %63, %64, %65, %66, %67, %68, %69, %70, %71, %72, %73, %74, %75, %76, %77, %78, %79, %80, %81, %82, %83, %84, %85, %86, %87, %88, %89, %90, %91, %92, %93, %94, %95, %96, %97, %98, %99, %100, %101, %102, %103, %104, %105, %106, %107, %108, %109, %110, %111, %112, %113, %114, %115, %116, %117, %118, %119, %120, %121, %122, %123, %124, %125, %126, %127}, %128, %129, 0, 1, 1, %130, %131;"
        : "=f"(d[0]), "=f"(d[1]), "=f"(d[2]), "=f"(d[3]), "=f"(d[4]), "=f"(d[5]), "=f"(d[6]), "=f"(d[7]), "=f"(d[8]), "=f"(d[9]), "=f"(d[10]), "=f"(d[11]), "=f"(d[12]), "=f"(d[13]), "=f"(d[14]), "=f"(d[15]), "=f"(d[16]), "=f"(d[17]), "=f"(d[18]), "=f"(d[19]), "=f"(d[20]), "=f"(d[21]), "=f"(d[22]), "=f"(d[23]), "=f"(d[24]), "=f"(d[25]), "=f"(d[26]), "=f"(d[27]), "=f"(d[28]), "=f"(d[29]), "=f"(d[30]), "=f"(d[31]), "=f"(d[32]), "=f"(d[33]), "=f"(d[34]), "=f"(d[35]), "=f"(d[36]), "=f"(d[37]), "=f"(d[38]), "=f"(d[39]), "=f"(d[40]), "=f"(d[41]), "=f"(d[42]), "=f"(d[43]), "=f"(d[44]), "=f"(d[45]), "=f"(d[46]), "=f"(d[47]), "=f"(d[48]), "=f"(d[49]), "=f"(d[50]), "=f"(d[51]), "=f"(d[52]), "=f"(d[53]), "=f"(d[54]), "=f"(d[55]), "=f"(d[56]), "=f"(d[57]), "=f"(d[58]), "=f"(d[59]), "=f"(d[60]), "=f"(d[61]), "=f"(d[62]), "=f"(d[63]), "=f"(d[64]), "=f"(d[65]), "=f"(d[66]), "=f"(d[67]), "=f"(d[68]), "=f"(d[69]), "=f"(d[70]), "=f"(d[71]), "=f"(d[72]), "=f"(d[73]), "=f"(d[74]), "=f"(d[75]), "=f"(d[76]), "=f"(d[77]), "=f"(d[78]), "=f"(d[79]), "=f"(d[80]), "=f"(d[81]), "=f"(d[82]), "=f"(d[83]), "=f"(d[84]), "=f"(d[85]), "=f"(d[86]), "=f"(d[87]), "=f"(d[88]), "=f"(d[89]), "=f"(d[90]), "=f"(d[91]), "=f"(d[92]), "=f"(d[93]), "=f"(d[94]), "=f"(d[95]), "=f"(d[96]), "=f"(d[97]), "=f"(d[98]), "=f"(d[99]), "=f"(d[100]), "=f"(d[101]), "=f"(d[102]), "=f"(d[103]), "=f"(d[104]), "=f"(d[105]), "=f"(d[106]), "=f"(d[107]), "=f"(d[108]), "=f"(d[109]), "=f"(d[110]), "=f"(d[111]), "=f"(d[112]), "=f"(d[113]), "=f"(d[114]), "=f"(d[115]), "=f"(d[116]), "=f"(d[117]), "=f"(d[118]), "=f"(d[119]), "=f"(d[120]), "=f"(d[121]), "=f"(d[122]), "=f"(d[123]), "=f"(d[124]), "=f"(d[125]), "=f"(d[126]), "=f"(d[127])
        : "l"(da), "l"(db), "n"(TA), "n"(TB));
}
template <int TA, int TB>
__device__ __forceinline__ void wgmma_ss128(float* d, uint64_t da, uint64_t db) {
    asm volatile("wgmma.mma_async.sync.aligned.m64n128k16.f32.bf16.bf16 "
        "{%0, %1, %2, %3, %4, %5, %6, %7, %8, %9, %10, %11, %12, %13, %14, %15, %16, %17, %18, %19, %20, %21, %22, %23, %24, %25, %26, %27, %28, %29, %30, %31, %32, %33, %34, %35, %36, %37, %38, %39, %40, %41, %42, %43, %44, %45, %46, %47, %48, %49, %50, %51, %52, %53, %54, %55, %56, %57, %58, %59, %60, %61, %62, %63}, %64, %65, 1, 1, 1, %66, %67;"
        : "+f"(d[0]), "+f"(d[1]), "+f"(d[2]), "+f"(d[3]), "+f"(d[4]), "+f"(d[5]), "+f"(d[6]), "+f"(d[7]), "+f"(d[8]), "+f"(d[9]), "+f"(d[10]), "+f"(d[11]), "+f"(d[12]), "+f"(d[13]), "+f"(d[14]), "+f"(d[15]), "+f"(d[16]), "+f"(d[17]), "+f"(d[18]), "+f"(d[19]), "+f"(d[20]), "+f"(d[21]), "+f"(d[22]), "+f"(d[23]), "+f"(d[24]), "+f"(d[25]), "+f"(d[26]), "+f"(d[27]), "+f"(d[28]), "+f"(d[29]), "+f"(d[30]), "+f"(d[31]), "+f"(d[32]), "+f"(d[33]), "+f"(d[34]), "+f"(d[35]), "+f"(d[36]), "+f"(d[37]), "+f"(d[38]), "+f"(d[39]), "+f"(d[40]), "+f"(d[41]), "+f"(d[42]), "+f"(d[43]), "+f"(d[44]), "+f"(d[45]), "+f"(d[46]), "+f"(d[47]), "+f"(d[48]), "+f"(d[49]), "+f"(d[50]), "+f"(d[51]), "+f"(d[52]), "+f"(d[53]), "+f"(d[54]), "+f"(d[55]), "+f"(d[56]), "+f"(d[57]), "+f"(d[58]), "+f"(d[59]), "+f"(d[60]), "+f"(d[61]), "+f"(d[62]), "+f"(d[63])
        : "l"(da), "l"(db), "n"(TA), "n"(TB));
}
template <int TA, int TB>
__device__ __forceinline__ void wgmma_ss128_first(float* d, uint64_t da, uint64_t db) {
    asm volatile("wgmma.mma_async.sync.aligned.m64n128k16.f32.bf16.bf16 "
        "{%0, %1, %2, %3, %4, %5, %6, %7, %8, %9, %10, %11, %12, %13, %14, %15, %16, %17, %18, %19, %20, %21, %22, %23, %24, %25, %26, %27, %28, %29, %30, %31, %32, %33, %34, %35, %36, %37, %38, %39, %40, %41, %42, %43, %44, %45, %46, %47, %48, %49, %50, %51, %52, %53, %54, %55, %56, %57, %58, %59, %60, %61, %62, %63}, %64, %65, 0, 1, 1, %66, %67;"
        : "=f"(d[0]), "=f"(d[1]), "=f"(d[2]), "=f"(d[3]), "=f"(d[4]), "=f"(d[5]), "=f"(d[6]), "=f"(d[7]), "=f"(d[8]), "=f"(d[9]), "=f"(d[10]), "=f"(d[11]), "=f"(d[12]), "=f"(d[13]), "=f"(d[14]), "=f"(d[15]), "=f"(d[16]), "=f"(d[17]), "=f"(d[18]), "=f"(d[19]), "=f"(d[20]), "=f"(d[21]), "=f"(d[22]), "=f"(d[23]), "=f"(d[24]), "=f"(d[25]), "=f"(d[26]), "=f"(d[27]), "=f"(d[28]), "=f"(d[29]), "=f"(d[30]), "=f"(d[31]), "=f"(d[32]), "=f"(d[33]), "=f"(d[34]), "=f"(d[35]), "=f"(d[36]), "=f"(d[37]), "=f"(d[38]), "=f"(d[39]), "=f"(d[40]), "=f"(d[41]), "=f"(d[42]), "=f"(d[43]), "=f"(d[44]), "=f"(d[45]), "=f"(d[46]), "=f"(d[47]), "=f"(d[48]), "=f"(d[49]), "=f"(d[50]), "=f"(d[51]), "=f"(d[52]), "=f"(d[53]), "=f"(d[54]), "=f"(d[55]), "=f"(d[56]), "=f"(d[57]), "=f"(d[58]), "=f"(d[59]), "=f"(d[60]), "=f"(d[61]), "=f"(d[62]), "=f"(d[63])
        : "l"(da), "l"(db), "n"(TA), "n"(TB));
}
template <int TB>
__device__ __forceinline__ void wgmma_rs128(float* d, const uint32_t* a, uint64_t db, uint32_t acc) {
    asm volatile("{\n.reg .pred P;\nsetp.ne.u32 P, %69, 0;\nwgmma.mma_async.sync.aligned.m64n128k16.f32.bf16.bf16 "
        "{%0, %1, %2, %3, %4, %5, %6, %7, %8, %9, %10, %11, %12, %13, %14, %15, %16, %17, %18, %19, %20, %21, %22, %23, %24, %25, %26, %27, %28, %29, %30, %31, %32, %33, %34, %35, %36, %37, %38, %39, %40, %41, %42, %43, %44, %45, %46, %47, %48, %49, %50, %51, %52, %53, %54, %55, %56, %57, %58, %59, %60, %61, %62, %63}, {%64, %65, %66, %67}, %68, P, 1, 1, %70;\n}"
        : "+f"(d[0]), "+f"(d[1]), "+f"(d[2]), "+f"(d[3]), "+f"(d[4]), "+f"(d[5]), "+f"(d[6]), "+f"(d[7]), "+f"(d[8]), "+f"(d[9]), "+f"(d[10]), "+f"(d[11]), "+f"(d[12]), "+f"(d[13]), "+f"(d[14]), "+f"(d[15]), "+f"(d[16]), "+f"(d[17]), "+f"(d[18]), "+f"(d[19]), "+f"(d[20]), "+f"(d[21]), "+f"(d[22]), "+f"(d[23]), "+f"(d[24]), "+f"(d[25]), "+f"(d[26]), "+f"(d[27]), "+f"(d[28]), "+f"(d[29]), "+f"(d[30]), "+f"(d[31]), "+f"(d[32]), "+f"(d[33]), "+f"(d[34]), "+f"(d[35]), "+f"(d[36]), "+f"(d[37]), "+f"(d[38]), "+f"(d[39]), "+f"(d[40]), "+f"(d[41]), "+f"(d[42]), "+f"(d[43]), "+f"(d[44]), "+f"(d[45]), "+f"(d[46]), "+f"(d[47]), "+f"(d[48]), "+f"(d[49]), "+f"(d[50]), "+f"(d[51]), "+f"(d[52]), "+f"(d[53]), "+f"(d[54]), "+f"(d[55]), "+f"(d[56]), "+f"(d[57]), "+f"(d[58]), "+f"(d[59]), "+f"(d[60]), "+f"(d[61]), "+f"(d[62]), "+f"(d[63])
        : "r"(a[0]), "r"(a[1]), "r"(a[2]), "r"(a[3]), "l"(db), "r"(acc), "n"(TB));
}
template <int TB>
__device__ __forceinline__ void wgmma_rs64(float* d, const uint32_t* a, uint64_t db, uint32_t acc) {
    asm volatile("{\n.reg .pred P;\nsetp.ne.u32 P, %37, 0;\nwgmma.mma_async.sync.aligned.m64n64k16.f32.bf16.bf16 "
        "{%0, %1, %2, %3, %4, %5, %6, %7, %8, %9, %10, %11, %12, %13, %14, %15, %16, %17, %18, %19, %20, %21, %22, %23, %24, %25, %26, %27, %28, %29, %30, %31}, {%32, %33, %34, %35}, %36, P, 1, 1, %38;\n}"
        : "+f"(d[0]), "+f"(d[1]), "+f"(d[2]), "+f"(d[3]), "+f"(d[4]), "+f"(d[5]), "+f"(d[6]), "+f"(d[7]), "+f"(d[8]), "+f"(d[9]), "+f"(d[10]), "+f"(d[11]), "+f"(d[12]), "+f"(d[13]), "+f"(d[14]), "+f"(d[15]), "+f"(d[16]), "+f"(d[17]), "+f"(d[18]), "+f"(d[19]), "+f"(d[20]), "+f"(d[21]), "+f"(d[22]), "+f"(d[23]), "+f"(d[24]), "+f"(d[25]), "+f"(d[26]), "+f"(d[27]), "+f"(d[28]), "+f"(d[29]), "+f"(d[30]), "+f"(d[31])
        : "r"(a[0]), "r"(a[1]), "r"(a[2]), "r"(a[3]), "l"(db), "r"(acc), "n"(TB));
}
template <int TB>
__device__ __forceinline__ void wgmma_rs16(float* d, const uint32_t* a, uint64_t db, uint32_t acc) {
    asm volatile("{\n.reg .pred P;\nsetp.ne.u32 P, %13, 0;\nwgmma.mma_async.sync.aligned.m64n16k16.f32.bf16.bf16 "
        "{%0, %1, %2, %3, %4, %5, %6, %7}, {%8, %9, %10, %11}, %12, P, 1, 1, %14;\n}"
        : "+f"(d[0]), "+f"(d[1]), "+f"(d[2]), "+f"(d[3]), "+f"(d[4]), "+f"(d[5]), "+f"(d[6]), "+f"(d[7])
        : "r"(a[0]), "r"(a[1]), "r"(a[2]), "r"(a[3]), "l"(db), "r"(acc), "n"(TB));
}

__device__ __forceinline__ uint32_t delay_loop(int n, uint32_t x0) {
    uint32_t z;
    asm volatile("{\n.reg .pred P;\n.reg .u32 c, x;\nmov.u32 c, %1;\nmov.u32 x, %2;\nDL: mad.lo.u32 x, x, 1664525, 1013904223;\nadd.u32 c, c, -1;\nsetp.gt.s32 P, c, 0;\n@P bra DL;\n"
                 "setp.eq.u32 P, x, 0x7fffffff;\nselp.u32 %0, 16, 0, P;\n}" : "=r"(z) : "r"(n), "r"(x0) : "memory");
    return z;
}
__device__ __forceinline__ uint32_t gtime() { uint32_t t; asm volatile("mov.u32 %0, %%globaltimer_lo;" : "=r"(t)); return t; }
__device__ __forceinline__ void wait_time(uint32_t t, uint32_t sb) { while ((int32_t)(gtime() - t) < (int32_t)delay_loop(2, sb)) {} }
__device__ __forceinline__ uint32_t tpc_gpc(uint32_t t) { return t < 32 ? t & 7 : t < 60 ? (t - 32) % 7 + 1 : (t - 54) & 7; }
__device__ __forceinline__ uint32_t latest_stamp(const uint32_t* p, uint32_t seq, uint32_t ref, int backoff, uint32_t sb) {
    for (int n = 0;; n++) {
        uint32_t bad = 0; int32_t m = INT32_MIN;
#pragma unroll
        for (int i = 0; i < 3; i++) { const uint32_t v = ld_relaxed1(p + i * 256); bad |= (v ^ seq) & 31u; m = max(m, (int32_t)(v - (ref << 5)) >> 5); }
        if (__all_sync(0xffffffffu, bad == 0)) return ref + __reduce_max_sync(0xffffffffu, m);
        wait_time(gtime() + backoff, sb);
        if (n > SPIN_LIMIT) spin_fault();
    }
}
__device__ __forceinline__ void release_at(uint32_t t, uint32_t sb, uint32_t bar, int lane) {
    wait_time(t, sb);
    if (lane == 0) mbar_arrive(sb + bar);
}
__host__ __device__ constexpr int frag_word(int u, int f) { return (u == 0 ? 0 : u < 3 ? 3 * u - 1 : u == 3 ? 14 : 3 * u - 4) + f; }
__host__ __device__ constexpr int word_col(int e) { return ((0x32FED987CBA65410ull >> (4 * e)) & 14) * 64 + ((0x32FED987CBA65410ull >> (4 * e)) & 1) * 8; }

constexpr uint32_t CLEAR_LO = 0xFE000000u, CLEAR_HI = 0x5A7FEFEFu;
__device__ __forceinline__ void clear_slot(const Params& P, int slot, int cta, int lane) {
    const int i = cta * 2 + (lane >> 3), x = i & 63;
    if (lane < 16) st_relaxed4(P.gm + slot * M_SLOT + (x >> 1) * 1024 + (x & 1) * 256 + (i >> 7) * 512 + ((i >> 6) & 1) * 128 + (lane & 7) * 16, CLEAR_LO, CLEAR_HI, CLEAR_LO, CLEAR_HI);
    st_relaxed4(g_f + slot * F_SLOT + cta * 512 + lane * 16, 0, 0, 0, 0);
}
__device__ __forceinline__ void mem0_max(const Params& P, uint32_t sb, int tid) {
    uint32_t m = 0;
#pragma unroll
    for (int i = 0; i < 4; i++) {
        const uint4 x = __ldg((const uint4*)P.mem0 + i * 256 + tid);
        m = __vmaxu2(__vmaxu2(__vmaxu2(x.x & 0x7fff7fffu, x.y & 0x7fff7fffu), __vmaxu2(x.z & 0x7fff7fffu, x.w & 0x7fff7fffu)), m);
    }
    sts32(sb + S_COEF + (tid >> 5) * 4, __reduce_max_sync(0xffffffffu, max(m >> 16, m & 0xffffu)));
    bar_arrive(7, 288);
}
__device__ __forceinline__ uint32_t pack_mem0(const Params& P, uint32_t sb, int cta, int lane) {
    bar_sync(7, 288);
    const uint32_t e = __reduce_max_sync(0xffffffffu, lds32(sb + S_COEF + (lane & 7) * 4)) >> 7;
    if (e < 64 || e > 192) return 0x3F803F80u;
    const int i = cta * 2 + (lane >> 4), u = (i >> 5), x = i & 63, L = (i & 3) * 8 + ((lane & 15) >> 1);
    uint64_t w = 32;
#pragma unroll
    for (int f = 0; f < 3; f++) if (f < 2 || u % 3) {
        const float v = __bfloat162float(P.mem0[(L >> 2) * 1024 + word_col(frag_word(u, f)) + ((i >> 2) & 7) * 16 + (L & 3) * 2 + (lane & 1)]);
        w += (uint64_t)(int64_t)__float2int_rn(v * __uint_as_float((271 - e) << 23)) << (45 - 19 * f);
    }
    st_relaxed2(P.gm + 7 * M_SLOT + (x >> 1) * 1024 + (x & 1) * 256 + (i >> 7) * 512 + ((i >> 6) & 1) * 128 + (lane & 15) * 8, (uint32_t)w, (uint32_t)(w >> 32));
    return (e - 30) * 0x00800080u;
}
__device__ __forceinline__ void pacer(const Params& P, const uint32_t sb, const int lane) {
    constexpr uint32_t base = 2;
    int cta = lds32(sb + S_CTA);
#pragma unroll 1
    for (int i = 0; i < 8; i++) clear_slot(P, i, cta, lane);
    __syncwarp();
    if (lane == 0) { uint32_t smid; asm("mov.u32 %0, %%smid;" : "=r"(smid)); st_relaxed1(g_hint + 6144 + cta, smid >> 1); }
    sts32(sb + S_EPOCH + 4, pack_mem0(P, sb, cta, lane));
    SSTAMP(0, lane == 0)
    fence_release();
    __syncwarp();
    float rate = 0.58f;
    uint32_t c0 = 0;
#pragma unroll 1
    for (int s = -1; s < 63; s++) {
        cta = lds32(sb + S_CTA);
        const int pair = cta >> 1;
        const uint32_t ahead = s > 0 ? (uint32_t)(rate * (float)(pair >= 32 ? P.dc - P.dv : P.dc)) : 0;
        mbar_wait(sb + B_GO, s & 1);
        SSTAMP(10, lane == 0 && s == 0)
        const uint32_t t0 = gtime();
        if (lane < 4) st_relaxed1(g_hint + ((s & 1) * 4 + lane) * 768 + (cta >> 5) * 256 + (cta & 31), (t0 + ahead + (lds32(sb + S_REDO) == s ? P.extra : 0)) << 5 | ((base + s) & 31u));
        wait_time(t0 + (s < 0 ? 2000 : s == 0 && pair >= 16 ? P.ds0 : P.ds), sb);
        const uint32_t t = latest_stamp(g_hint + ((s & 1) * 4 + (pair & 3)) * 768 + lane, base + s, t0, P.back, sb);
        if (s < 0) {
            SSTAMP(2, lane == 0)
            fence_acquire();
            const uint32_t g = tpc_gpc(ld_relaxed1(g_hint + 6144 + (lane & 15) * 2));
            const uint32_t key = (__popc(__match_any_sync(0xffffffffu, g)) > 4 ? 0 : g + 1) * 16 + (lane & 15);
            const uint32_t tail = (pair & 48) + __popc(__ballot_sync(0xffffffffu, key < __shfl_sync(0xffffffffu, key, pair & 15))) / 2;
            mbar_wait(sb + B_INIT, 0);
            SSTAMP(4, lane == 0)
            sts32(sb + S_TAIL, tail);
            if (lane < 8) sts32(sb + S_SC + lane * 4, lds32(sb + S_EPOCH + 4));
            __syncwarp();
        }
        release_at(t + P.da, sb, B_RELA, lane);
        SSTAMP(11, lane == 0 && s == 0)
        release_at(t + P.db, sb, B_RELB, lane);
        {
            const uint32_t c1 = clock(), g1 = gtime();
            if (s > 1) rate += P.alpha * (__fdividef((float)(g1 - lds32(sb + S_EPOCH + 4)), (float)(c1 - c0)) - rate);
            __syncwarp();
            c0 = c1; sts32(sb + S_EPOCH + 4, g1);
        }
        if (s == 61) {
            sts32(sb + S_COEF, ITEM(ITEM_OFF(lds32(sb + S_TAIL)) + NPRE + 1) + (uint32_t)(uintptr_t)P.out);
            if (lane < M_CQ) map_prefetch(&P.tm[lane]);
        }
    }
}
__device__ __forceinline__ uint32_t xor_or(uint32_t a, uint32_t b, uint32_t t) { uint32_t d; asm("lop3.b32 %0, %1, %2, %3, 0x7E;" : "=r"(d) : "r"(a), "r"(b), "r"(t)); return d; }
__device__ __forceinline__ bool tags_ok(uint32_t bad) { return __all_sync(0xffffffffu, (bad & 1) == 0); }
#define RETRY(k)
#define RETRY_STAT(a, b)
#define UNIT_STAT(u0)
#define SFENCE() asm volatile("pmevent 1;" ::: "memory")
#define PF1 10
static_assert(NS == 24, "fragment residency");
__host__ __device__ constexpr bool in_smem(int n) { return n < 4 || n == 12 || n == 13; }
__host__ __device__ constexpr int unit_pos(int n) { return n < 4 ? n : n < 12 ? n - 4 : n < 14 ? n - 8 : n - 6; }

__host__ __device__ constexpr int fill_unit(int q) { return q < 4 ? q : q < 6 ? q + 8 : q < 14 ? q - 2 : q; }
__host__ __device__ constexpr int frag_off(int q) { return (q >> 2) * 16384 + ((q >> 1) & 1) * 8192 + (q & 1) * 512; }

constexpr uint32_t QBITS = 0x4B002000u;
constexpr uint64_t W_BIAS = ((uint64_t)QBITS << 45) + ((uint64_t)QBITS << 26) + (uint32_t)(QBITS << 7), W_CLEAR = 0 - 32 * W_BIAS;
static_assert(W_CLEAR == ((uint64_t)CLEAR_HI << 32 | CLEAR_LO), "clear value");
__host__ __device__ constexpr int unit_off(int u) { return (u & 1) * 16384 + (u >> 2) * 512 + ((u >> 1) & 1) * 128; }
__device__ __forceinline__ void red_add64(const uint8_t* p, uint64_t v) { asm volatile("red.relaxed.gpu.global.add.u64 [%0], %1;" ::"l"(p), "l"(v) : "memory"); }
template <int NF>
__device__ __forceinline__ uint64_t encode(const float* x, float S, uint32_t two26, uint32_t& bad) {
    uint32_t b[3];
#pragma unroll
    for (int i = 0; i < 3; i++) b[i] = i < NF ? __float_as_uint(fmaf(x[i], S, 8396800.f)) : QBITS;
    bad = xor_or(b[0], b[1], 0x4B000000u) | (NF == 3 ? b[2] ^ 0x4B000000u : 0);
    uint64_t w;
    asm("{\n.reg .b64 t;\nmov.b64 t, {%2, %3};\nmad.wide.u32 %0, %1, %4, t;\n}" : "=l"(w) : "r"(b[1]), "r"(b[2] << 7), "r"(b[0] << 13), "r"(two26));
    return w;
}
template <int NF>
__device__ __forceinline__ void emit(uint64_t* w, const float (*x)[3], const float* S, uint32_t two26, uint32_t lim, const uint8_t* p) {
    uint32_t bad[2];
    w[0] = encode<NF>(x[0], S[0], two26, bad[0]); w[1] = encode<NF>(x[1], S[1], two26, bad[1]);
    const bool ok = (bad[0] | bad[1]) < lim;
    w[0] |= ok; w[1] |= ok;
    red_add64(p, w[0]); red_add64(p + 1024, w[1]);
}
template <int NF>
__device__ __forceinline__ void repair(const uint64_t* w, const float (*x)[3], const float* S, const uint8_t* p, const uint8_t* pf) {
    if (!(w[0] & 1)) {
#pragma unroll
        for (int j = 0; j < 2; j++) {
            const float T = S[j] * 8192.f;
            asm volatile("red.relaxed.gpu.global.add.v4.f32 [%0], {%1,%2,%3,%4};" ::"l"(pf + j * 512), "f"(x[j][0] * T), "f"(x[j][1] * T), "f"(NF == 3 ? x[j][2] * T : 0.f), "f"(0.f) : "memory");
        }
        fence_release();
#pragma unroll
        for (int j = 0; j < 2; j++) {
            asm volatile("red.relaxed.gpu.global.or.b64 [%0], 64;" ::"l"(p + j * 1024) : "memory");
            red_add64(p + j * 1024, W_BIAS + 1 - w[j]);
        }
    }
    __syncwarp();
}
__device__ __forceinline__ void ld_words(uint32_t* v, const uint8_t* p) {
    asm volatile("{\n.reg .b64 a, b;\nld.relaxed.gpu.global.L1::no_allocate.v2.b64 {a, b}, [%4];\nmov.b64 {%0,%1}, a;\nmov.b64 {%2,%3}, b;\n}" : "=r"(v[0]), "=r"(v[1]), "=r"(v[2]), "=r"(v[3]) : "l"(p) : "memory");
}
__device__ __forceinline__ float field(const uint32_t* w, int f) { return __int2float_rn((int)(f == 0 ? w[1] : f == 1 ? __funnelshift_l(w[0], w[1], 19) : w[0] << 6)); }
template <int U>
__device__ __forceinline__ void decode(uint32_t* b, const uint32_t* v) {
#pragma unroll
    for (int f = 0; f < (U % 3 ? 3 : 2); f++) b[frag_word(U, f)] = pack2(field(v, f), field(v + 2, f));
}
__device__ __forceinline__ uint32_t status(const uint32_t (*v)[4], uint32_t c32) { return xor_or(v[0][0], v[0][2], c32) | xor_or(v[1][0], v[1][2], c32) | xor_or(v[2][0], v[2][2], c32); }
__device__ __forceinline__ void gather_slow(const Params& P, uint32_t* b, const uint8_t* pm, int s, int warp, uint32_t ln, uint32_t u2) {
    if (s == 0 && u2 == 0x3F803F80u) {
#pragma unroll
        for (int i = 0; i < 16; i++) b[i] = __ldg((const uint32_t*)(P.mem0 + (ln >> 2) * 1024 + word_col(i) + warp * 16 + (ln & 3) * 2));
        return;
    }
    uint32_t v[6][4], st;
    for (int n = 0;; n++) {
#pragma unroll
        for (int u = 0; u < 6; u++) ld_words(v[u], pm + unit_off(u));
        st = status(v, 32) | status(v + 3, 32);
        if (!__any_sync(0xffffffffu, st & 32)) break;
        __nanosleep(200);
        if (n > SPIN_LIMIT) spin_fault();
    }
    const bool side = __any_sync(0xffffffffu, st & 64);
    if (side) fence_acquire();
    const uint8_t* pf = g_f + ((s + 7) & 7) * F_SLOT + warp * 1024 + ln * 32;
#pragma unroll
    for (int u = 0; u < 6; u++) {
        float x[2][4] = {};
#pragma unroll
        for (int k = 0; k < 2; k++)
            asm volatile("{\n.reg .pred P;\nsetp.ne.u32 P, %5, 0;\n@P ld.relaxed.gpu.global.v4.f32 {%0,%1,%2,%3}, [%4];\n}"
                         : "+f"(x[k][0]), "+f"(x[k][1]), "+f"(x[k][2]), "+f"(x[k][3]) : "l"(pf + u * 8192 + k * 16), "r"((uint32_t)side) : "memory");
#pragma unroll
        for (int f = 0; f < (u % 3 ? 3 : 2); f++) b[frag_word(u, f)] = pack2(field(v[u], f) + x[0][f], field(v[u] + 2, f) + x[1][f]);
    }
}
__device__ __forceinline__ uint32_t max_abs2(uint32_t a, uint32_t b) { uint32_t d; asm("max.NaN.xorsign.abs.bf16x2 %0, %1, %2;" : "=r"(d) : "r"(a), "r"(b)); return d; }
__device__ __forceinline__ uint32_t max6(const uint32_t* b) {
    const uint32_t m = max_abs2(max_abs2(max_abs2(b[0], b[1]), max_abs2(b[2], b[3])), max_abs2(b[4], b[5]));
    return max(m & 0x7fff0000u, (m << 16) & 0x7fff0000u);
}

template <bool TR>
__device__ __forceinline__ void put_partials(uint32_t a, const float* x, const float* y) {
    if (TR) stsm4t(a, pack2(x[0], x[1]), pack2(x[2], x[3]), pack2(y[0], y[1]), pack2(y[2], y[3]));
    else stsm4(a, pack2(x[0], x[1]), pack2(x[2], x[3]), pack2(y[0], y[1]), pack2(y[2], y[3]));
}
__device__ __forceinline__ void reduce_load(uint32_t (*x)[4], uint32_t a) { ldsm4t(x[0], a); ldsm4t(x[1], a + 512); }
__device__ __forceinline__ uint32_t reduce8(const uint32_t (*x)[4], uint32_t l8, uint32_t u2) {
    uint32_t p[2];
#pragma unroll
    for (int i = 0; i < 2; i++) {
        float d[4] = {};
        mma16816(d, x[i][0], x[i][1], x[i][2], x[i][3], (l8 & 32) ? 0u : u2, (l8 & 32) ? u2 : 0u);
        p[i] = pack2((l8 & 8) ? d[2] : d[0], (l8 & 8) ? d[3] : d[1]);
    }
    return (l8 & 16) ? p[1] : p[0];
}
__device__ __forceinline__ void score_half(float (*a)[4], const uint32_t (*qa)[4], const uint32_t (*kf)[4]) {
#pragma unroll
    for (int w = 0; w < 2; w++) {
        mma16816(a[w], qa[w][0], qa[w][1], qa[w][2], qa[w][3], kf[w][0], kf[w][1]);
        mma16816(a[2 + w], qa[w][0], qa[w][1], qa[w][2], qa[w][3], kf[w][2], kf[w][3]);
    }
}
__device__ __forceinline__ void score_sum(float* S, const float (*a)[4]) {
    S[0] = (a[0][0] + a[1][0]) + (a[2][2] + a[3][2]);
    S[1] = (a[0][1] + a[1][1]) + (a[2][3] + a[3][3]);
}
__device__ __forceinline__ float quad_max(float m) {
    m = fmaxf(m, __shfl_xor_sync(0xffffffffu, m, 1));
    return fmaxf(m, __shfl_xor_sync(0xffffffffu, m, 2));
}

#define ISTAMP(i)
__device__ __forceinline__ float next_scale(uint32_t sb, int slot, int warp, uint32_t u2) {
    uint32_t x[2][4];
    lds128(x[0], sb + S_MX + slot * 32); lds128(x[1], sb + S_MX + slot * 32 + 16);
    const uint32_t mx = max(max(max(x[0][0], x[0][1]), max(x[0][2], x[0][3])), max(max(x[1][0], x[1][1]), max(x[1][2], x[1][3])));
    const float top = fminf(fmaxf(__uint_as_float(mx) * bf_hi(u2), 0x1p-40f), 0x1p40f) * (1.f / (12288.f * 8192.f));
    const uint32_t un = pack2(top, top);
    sts32(sb + S_SC + warp * 4, un);
    return rcp(bf_hi(un) * 8192.f);
}
#define NEARLY 1
#define U3POS 1
#define VPOS 1
#define ROT 0
#define BPOS 1
#define ONLINE 0
#define NBAR 1
#define ORD3 0
#define F2 1
#define EARLY 0
#define TK 0
#define RPOS 1
#define AF 0
#define AFENCE(i) if ((AF >> (i)) & 1) SFENCE();
#define FPOS 99
#define PACE 1
#define PF2 12
__host__ __device__ constexpr int w2_t(int i) { return i < 16 ? i & 1 : 2; }
__host__ __device__ constexpr int w2_k(int i) { return i < 16 ? i >> 1 : i - 16; }
template <typename G>
__device__ __forceinline__ void load_weights(uint32_t (*wr)[4], const uint32_t sb, const int warp, const int lane, G stores_read) {
    const uint32_t frag = sb + warp * 1024 + (lane >> 4) * 8192 + (lane & 7) * 128 + ((((lane >> 3) & 1) ^ (lane & 7)) << 4);
    const uint32_t rel = mapa(sb + B_EMPTY, cluster_rank() ^ (lane & 1));
#define RELEASE(st) { fence_async_smem(); __syncwarp(); if (lane < 2) mbar_arrive_cluster(rel + (st) * 8); }
    mbar_wait(sb + B_FULL, 0); mbar_wait(sb + B_FULL + 8, 0);
    RELEASE(0) RELEASE(1)
#pragma unroll
    for (int st = 2; st < 4; st++) {
        mbar_wait(sb + B_FULL + st * 8, 0);
        ISTAMP(st - 2)
#pragma unroll
        for (int f = 0; f < 12; f++) ldsm4t(wr[st * 12 - 24 + f], (frag ^ ((f & 3) << 5)) + st * STAGE + (f >> 2) * 16384);
        RELEASE(st)
    }
#pragma unroll 2
    for (int u = 0; u < 6; u++) {
        uint32_t x[4][4];
#pragma unroll
        for (int i = 0; i < 4; i++) lds128(x[i], (frag ^ (i << 5)) + u * 16384);
        __syncwarp();
#pragma unroll
        for (int i = 0; i < 4; i++) sts128(sb + warp * 1024 + lane * 16 + u * 16384 + frag_off(i), x[i]);
    }
    stores_read();
    mbar_wait(sb + B_FULL, 1); mbar_wait(sb + B_FULL + 8, 1);
    RELEASE(0) RELEASE(1)
#pragma unroll
    for (int st = 2; st < 4; st++) {
        mbar_wait(sb + B_FULL + st * 8, 1);
#pragma unroll
        for (int f = 0; f < (st == 2 ? 12 : 4); f++) ldsm4t(wr[st * 12 + f], (frag ^ ((f & 3) << 5)) + st * STAGE + (f >> 2) * 16384);
        RELEASE(st)
    }
    ISTAMP(2)
    bar_sync(1, 256);
    if (warp == 7 && lane < 3) mbar_arrive_cluster(mapa(sb + B_INIT, (cluster_rank() & 1) + lane * 2));
}
template <int ROLE>
__device__ __forceinline__ void chain_role(const Params& P, const uint32_t (*wr)[4], const uint32_t sb, const int h, const int warp, const int lane) {
    constexpr int NU = ROLE == 0 ? 2 : 3;
    const bool att = ROLE == 0 && warp < 4;
    uint32_t l8 = opq(sb + lane * 8, lane);
#define PERSIST() { mbar_wait(sb + B_KVGO, slot ^ 1); const uint32_t pa_ = ((l8 - sb) >> 1) + (sb + S_QX + warp * 128); sts32(pa_, r0); sts32(pa_ + 1024, r1); \
                    fence_async_smem(); __syncwarp(); if (l8 == sb) mbar_arrive(sb + B_PERS); }
    if (ROLE) sts32(sb + S_SX + warp * 128 + lane * 4, warp >= 2 ? 0 : (lane & 1) ? CLEAR_HI : CLEAR_LO);
    const uint32_t rdelta = __shfl_sync(0xffffffffu, mapa(sb, (cluster_rank() + (ROLE == 1 ? 4 : 2)) % 6) - sb, 0);
    const uint32_t vdelta = ROLE ? 0 : __shfl_sync(0xffffffffu, mapa(sb, (cluster_rank() + 4) % 6) - sb, 0);
    ISTAMP(3)
    __syncwarp();
#define GATHER_OFF(s) ((((s) + 7) & 7) * M_SLOT + warp * 2048 + (l8 & 56) * 2 + (l8 & 64) * 4 + (l8 & 128) * 8)
    uint32_t mo = GATHER_OFF(0);
    if (ROT) mbar_wait(sb + B_RELA, 0);
    for (int s = 0; s < (ROLE == 0 ? 63 : 64);) {
        const int slot = s & 1;
        l8 += s & P.zero;
        const uint32_t w1a = l8 * 2 + (S_W1 + warp * 1024 - sb);
        PROF(9)
        uint32_t u2, r0, r1, pld, pub, pbar, x[2][4];
        {
#define pm (P.gm + mo)
            uint32_t as[24][4], b[16], v[6][4];
            float acc[8][4];
#define W1LD(n) _Pragma("unroll") for (int i_ = 0; i_ < 4; i_++) ldsm4t(as[unit_pos(n) * 4 + i_], w1a + frag_off(unit_pos(n) * 4 + i_));
#define W1LD2(n, p) { const uint32_t wa_ = w1a + (as[unit_pos(p) * 4][0] & as[unit_pos(p) * 4 + 1][0] & as[unit_pos(p) * 4 + 2][0] & as[unit_pos(p) * 4 + 3][0] & P.zero); \
                      _Pragma("unroll") for (int i_ = 0; i_ < 4; i_++) ldsm4t(as[unit_pos(n) * 4 + i_], wa_ + frag_off(unit_pos(n) * 4 + i_)); }
#define W1MMA(n) _Pragma("unroll") for (int i_ = 0; i_ < 4; i_++) { const uint32_t* a_ = in_smem(n) ? as[unit_pos(n) * 4 + i_] : wr[unit_pos(n) * 4 + i_]; \
                                                                   mma16816(acc[((n) & 1) * 4 + i_], a_[0], a_[1], a_[2], a_[3], b[(n) & 14], b[(n) | 1]); }
#pragma unroll
            for (int T = 0; T < 8; T++) { acc[T][0] = acc[T][1] = acc[T][2] = acc[T][3] = 0.f; }
            if (!ROT) mbar_wait(sb + B_RELA, slot);
            PROF(12)
#pragma unroll
            for (int u = 0; u < 3; u++) ld_words(v[u], pm + unit_off(u));
            __syncwarp();
#pragma unroll
            for (int i = 0; i < PF1; i++) ldsm4t(as[i], w1a + frag_off(i));
            __syncwarp();
            mo += mbar_try(sb + B_RELB, slot) & P.zero;
            PROF(13)
#pragma unroll
            for (int u = 3; u < 6; u++) ld_words(v[u], pm + unit_off(u));
            uint32_t st = status(v, ((uint32_t)((uintptr_t)pm >> 32) & P.zero) + 32);
            pin<1>(&st);
            SFENCE();
            UNIT_STAT(0)
            PROF(0)
            decode<0>(b, v[0]); decode<1>(b, v[1]); decode<2>(b, v[2]);
#pragma unroll
            for (int i = PF1; i < 12; i++) ldsm4t(as[i], w1a + frag_off(i));
            W1MMA(0) W1MMA(1) W1MMA(2)
            if (TK & 1) W1LD2(3, 2) else { W1LD(3) }
            SFENCE();
            if (TK & 8) { W1MMA(5) W1MMA(4) W1MMA(3) W1MMA(6) } else { W1MMA(5) W1MMA(4) W1MMA(6) W1MMA(3) }
            if (U3POS == 0) W1MMA(7)
            if (TK & 2) W1LD2(12, 3) else { W1LD(12) }
            uint32_t mx = max6(b);
            pin<1>(&mx);
            SFENCE();
            PROF(10)
            if (U3POS == 1) W1MMA(7)
            const uint32_t mxa = sb + S_MX + slot * 32 + warp * 4;
            sts32(mxa, __reduce_max_sync(0xffffffffu, mx));
            UNIT_STAT(3)
            st |= status(v + 3, 32);
            const bool redo = __any_sync(0xffffffffu, st & 96);
            const bool kvok = ROLE || mbar_test(sb + B_KVFULL + slot * 8, (s >> 1) & 1);
            decode<4>(b, v[4]); decode<5>(b, v[5]); decode<3>(b, v[3]);
            u2 = lds32(sb + S_SC + warp * 4);
            W1MMA(8) W1MMA(10) if (ORD3) { W1MMA(14) W1MMA(12) } else { W1MMA(12) W1MMA(14) }
            if (TK & 4) W1LD2(13, 12) else { W1LD(13) }
            if (__builtin_expect(redo || !kvok, 0)) {
                if (redo) {
                    RETRY(3)
                    sts32(sb + S_REDO, s);
                    gather_slow(P, b, P.gm + GATHER_OFF(s), s, warp, (l8 - sb) >> 3, u2);
                    sts32(mxa, __reduce_max_sync(0xffffffffu, max6(b)));
#pragma unroll
                    for (int T = 0; T < 8; T++) { acc[T][0] = acc[T][1] = acc[T][2] = acc[T][3] = 0.f; }
#pragma unroll
                    for (int n = 0; n < 15; n += n < 8 ? 1 : 2) {
                        if (in_smem(n)) { W1LD(n) }
                        W1MMA(n)
                    }
                    W1LD(13)
                }
                if (ROLE == 0) mbar_wait(sb + B_KVFULL + slot * 8, (s >> 1) & 1);
            }
#undef pm
            SSTAMP(7, threadIdx.x == 0 && s == 0)
            PROF(14)
            const uint32_t pst = (l8 - sb) * 16 + ((warp * 16) ^ ((l8 * 2) & 112)) + (sb + S_P1);
            put_partials<ROLE == 2>(pst, acc[0], acc[1]); put_partials<ROLE == 2>(pst + 4096, acc[2], acc[3]);
            W1MMA(9)
            SFENCE();
            pld = (l8 & 64) * 4 + (l8 & 128) + (l8 & 56) * 2 + (sb + S_P1 + warp * 1024);
            const uint32_t rd = s == 63 ? 0 : rdelta;
            pub = ((l8 - sb) >> 1) + (ROLE ? sb + rd + (ROLE == 1 ? S_KL : S_VL) + warp * 128 : sb + S_QX + (warp & 4) * 128 + (warp & 1) * 256 + (warp & 2) * 64);
            pbar = sb + rd + (ROLE == 1 && s != 63 ? B_K : B_V);
#define PUBLISH0() { r0 = reduce8(x, l8, u2); if (ROLE) st_async1(pub, r0, pbar); else sts32(pub, r0); }
            if (RPOS == 0) { bar_sync(1, 256); reduce_load(x, pld); SFENCE(); }
            W1MMA(11)
            if (RPOS == 1) { bar_sync(1, 256); reduce_load(x, pld); }
            if (RPOS != 2 || F2) SFENCE();
            W1MMA(15)
            if (RPOS == 0) PUBLISH0()
            if (RPOS == 2) { bar_sync(1, 256); reduce_load(x, pld); }
            if (RPOS != 1 || F2) SFENCE();
            W1MMA(13)
            if (RPOS == 1) PUBLISH0()
            put_partials<ROLE == 2>(pst + 8192, acc[4], acc[5]); put_partials<ROLE == 2>(pst + 12288, acc[6], acc[7]);
            if (RPOS == 2) PUBLISH0()
        }
        SSTAMP(8, threadIdx.x == 0 && s == 0)
        PROF(1)
        if (ROLE) {
            bar_sync(1, 256);
            reduce_load(x, pld + 8192);
            r1 = reduce8(x, l8, u2);
            st_async1(pub + 1024, r1, pbar);
            if (s == 63) {
                PERSIST()
                mbar_wait(sb + B_V, 0);
                break;
            }
            PROF(2)
        }
        uint32_t ln, w2a, ro;
#define W2ADDR(late) { l8 += pub & P.zero; ln = (l8 - sb) >> 3; \
        w2a = sb + S_W2 + (ROLE ? (warp >> 2) * 16384 : late * 32768) + ((((ln & 7) + (ln >> 4) * 8) * 128 + ((((ln >> 3) & 1) ^ (ln & 7)) << 4)) ^ ((warp & 3) << 5)); \
        ro = (s & 7) * M_SLOT + (ROLE ? warp * 2048 + unit_off(ROLE) : (warp & 3) * 2048 + late * unit_off(3)) + (ln & 2) * 128 + (ln & 1) * 64 + (ln >> 2) * 8; }
        constexpr int RO2 = ROLE ? unit_off(ROLE + 3) - unit_off(ROLE) : 8192;
        float Sj[2];
        uint32_t w[24][4], ob[4][4];
        float S;
#define W2LD(i) ldsm4t(w[i], w2a + w2_t(i) * (ROLE ? 32768 : 16384) + (w2_k(i) & 1) * 8192 + (w2_k(i) >> 1) * 2048)
#define W2MMA(d, i) mma16816(d, w[i][0], w[i][1], w[i][2], w[i][3], ob[w2_k(i) >> 1][(w2_k(i) & 1) * 2], ob[w2_k(i) >> 1][(w2_k(i) & 1) * 2 + 1])
#define LEADER(wp) (l8 == sb + ((wp) - warp) * 256)
        if (att) {
            const float cs = 0.08838834764831845f * 1.4426950408889634f;
            uint32_t qa[4][4], kf[4][4], vf[4][4], vv[4];
            float T[5][2], sa[4][4] = {};
            const uint32_t l16 = l8 * 2 - sb;
            const uint32_t kaddr = (l8 & 56) * 16 + (((l8 >> 2) ^ (l8 * 2)) & 48) + ((l8 * 2) & 64) + (sb + S_KV + warp * 1024 + slot * 16384);
            bar_sync(1, 256);
            reduce_load(x, pld + 8192);
            __syncwarp();
#pragma unroll
            for (int i = 0; i < 2; i++) { ldsm4(qa[i], l16 + S_QX + i * 512); ldsm4(kf[i], kaddr ^ (i * 64)); }
            AFENCE(0)
            sts32(pub + 1024, reduce8(x, l8, u2));
            __syncwarp();
#pragma unroll
            for (int i = 2; i < 4; i++) ldsm4(kf[i], (kaddr ^ ((i & 1) * 64)) + 4096);
            score_half(sa, qa, kf);
            bar_sync(2, 256);
            PROF(2)
#pragma unroll
            for (int i = 2; i < 4; i++) ldsm4(qa[i], l16 + S_QX + i * 512);
            float sm[4][4] = {};
            score_half(sa, qa + 2, kf + 2);
            score_sum(T[0], sa);
            sts64(l8 + S_SX + warp * 256, __float_as_uint(T[0][0]), __float_as_uint(T[0][1]));
            PROF(4)
            if (BPOS == 0) bar_sync(4, 128);
            mbar_wait(sb + B_K, slot);
            PROF(11)
#pragma unroll
            for (int i = 0; i < 4; i++) ldsm4(kf[i], l16 + S_KL + i * 512);
            if (BPOS == 1) bar_sync(4, 128); else __syncwarp();
#pragma unroll
            for (int n = 0; n < 4; n++) lds64f(T[n], l8 + S_SX + n * 256);
            score_half(sm, qa, kf);
            score_half(sm, qa + 2, kf + 2);
            const uint32_t vaddr = (l8 & 56) * 16 + (l8 & 128) * 8 + (((warp & 1) * 64 + ((l8 >> 2) & 16)) ^ ((l8 * 2) & 112)) + (sb + S_KV + 8192 + (warp >> 1) * 4096 + slot * 16384);
            float mx = fmaxf(fmaxf(fmaxf(T[0][0], T[0][1]), fmaxf(T[1][0], T[1][1])), fmaxf(fmaxf(T[2][0], T[2][1]), fmaxf(T[3][0], T[3][1])));
            score_sum(T[4], sm);
            float m = quad_max(fmaxf(mx, fmaxf(T[4][0], T[4][1])));
            if (VPOS == 0) {
#pragma unroll
                for (int i = 0; i < 4; i++) ldsm4t(vf[i], (vaddr ^ ((i & 1) << 5)) + (i >> 1) * 2048);
            }
            mbar_wait(sb + B_V, slot);
            if (VPOS == 1) {
#pragma unroll
                for (int i = 0; i < 4; i++) ldsm4t(vf[i], (vaddr ^ ((i & 1) << 5)) + (i >> 1) * 2048);
            }
            ldsm4(vv, l16 + S_VL + warp * 512);
            uint32_t pa[5];
            m *= cs;
#pragma unroll
            for (int n = 0; n < 5; n++) { T[n][0] = ex2(fmaf(T[n][0], cs, -m)); T[n][1] = ex2(fmaf(T[n][1], cs, -m)); pa[n] = pack2(T[n][0], T[n][1]); }
            float sum = (((T[0][0] + T[0][1]) + (T[1][0] + T[1][1])) + ((T[2][0] + T[2][1]) + (T[3][0] + T[3][1]))) + (T[4][0] + T[4][1]);
            PROF(3)
            W2ADDR(1)
            const uint32_t lo = sb + S_O + warp * 512 + (ln & 3) * 64 + (ln >> 2) * 8, ls = sb + S_SUM + (ln & 3) * 32 + (ln & 4) * 4 + (ln >> 3) * 4;
            const uint32_t sdelta = warp < 2 ? rdelta : vdelta;
            sum += __shfl_xor_sync(0xffffffffu, sum, 1);
            sum += __shfl_xor_sync(0xffffffffu, sum, 2);
            float O[2][4];
#pragma unroll
            for (int i = 0; i < 2; i++) { O[i][0] = O[i][1] = O[i][2] = O[i][3] = 0.f; }
#pragma unroll
            for (int i = 0; i < 2; i++) {
                mma16816(O[0], vf[2 * i][0], vf[2 * i][1], vf[2 * i][2], vf[2 * i][3], pa[2 * i], pa[2 * i + 1]);
                mma16816(O[1], vf[2 * i + 1][0], vf[2 * i + 1][1], vf[2 * i + 1][2], vf[2 * i + 1][3], pa[2 * i], pa[2 * i + 1]);
            }
            mma1688(O[0], vv[0], vv[1], pa[4]);
            mma1688(O[1], vv[2], vv[3], pa[4]);
            uint32_t o[2][2];
#pragma unroll
            for (int j = 0; j < 2; j++) { o[j][0] = pack2(O[0][j], O[0][2 + j]); o[j][1] = pack2(O[1][j], O[1][2 + j]); }
#pragma unroll
            for (int j = 0; j < 2; j++) st_async2(lo + rdelta + j * 256, o[j][0], o[j][1], sb + rdelta + B_K);
            st_async1(ls + sdelta + (warp & 1) * 128, __float_as_uint(sum), sb + sdelta + B_K);
#pragma unroll
            for (int j = 0; j < 2; j++) st_async2(lo + vdelta + j * 256, o[j][0], o[j][1], sb + vdelta + B_K);
#pragma unroll
            for (int j = 0; j < 2; j++) sts64(lo + j * 256, o[j][0], o[j][1]);
            sts32(ls + warp * 128, __float_as_uint(sum));
            PROF(5)
            bar_sync(3, 256);
            if (LEADER(0)) { mbar_expect(sb + B_K, 2048); mbar_expect(sb + B_V, 2048); mbar_arrive(sb + B_KVGO + slot * 8); }
            S = next_scale(sb, slot, warp, u2);
            if (s == 0) mbar_wait(sb + B_WO, 0);
            pin<1>(&S);
            SFENCE();
#pragma unroll
            for (int j = 0; j < 4; j++) lds128(ob[j], l8 * 2 - sb + S_O + j * 512);
            lds64f(Sj, sb + S_SUM + (l8 & 24));
#pragma unroll
            for (int i = 0; i < PF2; i++) W2LD(i);
        } else {
            if (ROLE == 0) { bar_sync(1, 256); reduce_load(x, pld + 8192); sts32(pub + 1024, reduce8(x, l8, u2)); bar_arrive(2, 256); }
            if (LEADER(7)) { if (s) mbar_arrive(sb + B_GO); if (ROLE) mbar_expect(sb + B_K, 2304); }
            S = next_scale(sb, slot, warp, u2);
            if (s == 0) mbar_wait(sb + B_WO, 0);
            if (ROLE != 0) PERSIST()
            W2ADDR(0)
#pragma unroll
            for (int i = 0; i < PF2; i++) {
                W2LD(i);
                if (ROLE == 0 && (i & PACE) == PACE) w2a += w[i][0] & P.zero;
            }
            ro = opq(ro, ln);
            const uint32_t sa = opq(sb + S_SUM + (l8 & 24), ln), oa = opq(l8 * 2 - sb + S_O, ln);
            if (ROLE == 0) bar_sync(3, 256); else mbar_wait(sb + B_K, slot);
            lds64f(Sj, sa);
#pragma unroll
            for (int j = 0; j < 4; j++) lds128(ob[j], oa + j * 512);
        }
        SSTAMP(9, threadIdx.x == 224 && s == 0)
        SFENCE();
        PROF(6)
        {
            const uint8_t* pr = P.gm + ro;
            float c[4][4];
            uint32_t lim = 0;
#pragma unroll
            for (int i = 0; i < 4; i++) { c[i][0] = c[i][1] = c[i][2] = c[i][3] = 0.f; }
#pragma unroll
            for (int i = 0; i < 16; i++) {
                W2MMA(c[i & (ROLE ? 1 : 3)], i);
                if (i + PF2 < (ROLE ? 16 + NEARLY : 16)) W2LD(i + PF2);
                if (i == 5) {
                    const uint32_t z = __float_as_uint(c[1][0]) & P.zero;
                    Sj[0] = S * rcp(__uint_as_float(__float_as_uint(Sj[0]) | z)); Sj[1] = S * rcp(__uint_as_float(__float_as_uint(Sj[1]) | z));
                }
                if (i == 5) lim = __any_sync(0xffffffffu, fmaxf(fmaxf(fabsf(c[0][0]), fabsf(c[0][2])), fmaxf(fabsf(c[1][0]), fabsf(c[1][2]))) * Sj[0] >= (ROLE ? 24.f : 20.f)) ? 16384 : 0;
                if (i == FPOS) { pin<1>(&lim); pin<2>(Sj); pin_ptr(pr); SFENCE(); }
            }
            if (ROLE == 0) {
#pragma unroll
                for (int i = 0; i < 8; i++) c[i >> 2][i & 3] += c[2 + (i >> 2)][i & 3];
            }
            const float xa[2][3] = {{c[0][0], c[0][2], c[1][0]}, {c[0][1], c[0][3], c[1][1]}};
            uint64_t wa[2], wb[2];
            emit<NU>(wa, xa, Sj, P.two26, lim, pr);
            PROF(7)
            mo = GATHER_OFF(s + 1);
            pin<1>(&mo);
            if (ROLE) {
                SFENCE();
#pragma unroll
                for (int i = 16 + NEARLY; i < 24; i++) { if (i == 16 + NBAR) bar_sync(2, 256); W2LD(i); __syncwarp(); }
                SFENCE();
#pragma unroll
                for (int i = 16; i < 24; i++) W2MMA(c[2 + (i & 1)], i);
#pragma unroll
                for (int i = 0; i < 4; i++) c[2][i] += c[3][i];
            }
            const float y[2][3] = {{ROLE ? c[1][2] : c[1][0], ROLE ? c[2][0] : c[1][2], c[2][2]}, {ROLE ? c[1][3] : c[1][1], ROLE ? c[2][1] : c[1][3], c[2][3]}};
            const bool released = !ROT || mbar_test(sb + B_RELA, slot ^ 1);
            emit<NU>(wb, y, Sj, P.two26, lim, pr + RO2);
            PROF(8)
            if (!__all_sync(0xffffffffu, (wa[0] & wb[0] & 1) && released && s)) {
                if (__builtin_expect(!__all_sync(0xffffffffu, wa[0] & wb[0] & 1), 0)) {
                    RETRY(5)
                    const uint8_t* pf = g_f + (s & 7) * F_SLOT + (ROLE ? ROLE * 8192 + warp * 1024 : (warp & 3) * 1024 + (att ? 24576 : 0)) + (ln & 3) * 128 + (ln >> 2) * 16;
                    repair<NU>(wa, xa, Sj, pr, pf);
                    repair<NU>(wb, y, Sj, pr + RO2, pf + (ROLE ? 24576 : 4096));
                }
                if (s == 0) { bar_sync(1, 256); if (LEADER(7)) mbar_arrive(sb + B_GO); }
                if (ROT) mbar_wait(sb + B_RELA, slot ^ 1);
            }
        }
        s++;
    }
}
struct Pipe { uint32_t stage, phase; };
struct Cons {
    uint32_t sb, rel;
    int wg, wq, lane, rank, pair;
    uint32_t nst;
    Pipe p;
};
__device__ __forceinline__ void pipe_next(Pipe& p) { p.stage = (p.stage + 1) & (NSTAGE - 1); p.phase ^= (p.stage == 0); }
__device__ __forceinline__ void release(const Cons& c, uint32_t stage) { if (c.lane < 2) mbar_arrive_cluster(c.rel + stage * 8); }

enum { PEND_NONE = 0, PEND_KVO = 1, PEND_HT = 2, PEND_OUT = 3, PEND_OUTH = 4 };
struct Pend { uint32_t pk[64]; int kind, row, col, cnt; };

__device__ __forceinline__ void staging_wait(const Cons& c) { if (c.nst) mbar_wait(c.sb + B_SFREE + c.wg * 8, (c.nst - 1) & 1); }
__device__ __forceinline__ void staging_post(Cons& c, int kind, int row, int col, int cnt) {
    __syncwarp();
    if (c.lane == 0) {
        if (c.wq == 0) { const uint32_t x[4] = {(uint32_t)kind, (uint32_t)row, (uint32_t)col, (uint32_t)cnt}; sts128(c.sb + S_DESC + c.wg * 16, x); }
        mbar_arrive(c.sb + B_SFULL + c.wg * 8);
    }
    c.nst++;
}
template <int HF, bool KVONLY = false>
__device__ __forceinline__ void drain(const Params& P, Cons& c, const Pend& d) {
    const uint32_t* pk = d.pk + HF * 32;
    if (!KVONLY && d.kind >= PEND_OUT) {
        if (HF == 1 && d.kind == PEND_OUTH) return;
        float* o = P.out + (size_t)(d.row + c.wq * 16 + (c.lane >> 2)) * 2048 + d.col + HF * 128 + (c.lane & 3) * 2;
#pragma unroll
        for (int j = 0; j < 16; j++) {
            st_stream2(o + j * 8, bf_lo(pk[j * 2]), bf_hi(pk[j * 2]));
            st_stream2(o + 8 * 2048 + j * 8, bf_lo(pk[j * 2 + 1]), bf_hi(pk[j * 2 + 1]));
        }
    } else if (d.kind != PEND_NONE) {
        const bool ht = !KVONLY && d.kind == PEND_HT;
        const int hi = (c.lane >> 3) & 1;
        const uint32_t base = c.sb + S_STG + c.wg * 16384 + ((ht ? hi * 32 + c.wq * 8 : c.wq * 16 + hi * 8) + (c.lane & 7)) * 128;
        staging_wait(c);
#pragma unroll
        for (int j = 0; j < 8; j++) {
            const int ch = (j & 3) * 2 + (c.lane >> 4);
            stsm4(base + (j >> 2) * 8192 + ((ch ^ (c.lane & 7)) << 4), pk[j * 4], pk[j * 4 + 1], pk[j * 4 + 2], pk[j * 4 + 3]);
        }
        fence_async_smem();
        staging_post(c, d.kind, d.row, d.col + HF * 128, HF ? d.cnt : -1);
    }
}
__device__ __forceinline__ void drain_all(const Params& P, Cons& c, Pend& d) { drain<0>(P, c, d); drain<1>(P, c, d); d.kind = PEND_NONE; }

__device__ __forceinline__ void store_warp(const Params& P, uint32_t sb, int wg) {
    const uint32_t stg = sb + S_STG + wg * 16384;
#pragma unroll 1
    for (uint32_t n = 0;; n++) {
        mbar_wait(sb + B_SFULL + wg * 8, n & 1);
        uint32_t x[4];
        lds128(x, sb + S_DESC + wg * 16);
        if (x[0] == PEND_NONE) break;
        const bool ht = x[0] == PEND_HT;
        const CUtensorMap* m = &P.tm[ht ? M_HTS : M_KVO];
#pragma unroll 1
        for (int i = 0; i < 4; i++) if (!(DBGF(128) && gridDim.x != 96)) tma_store2d(m, x[2] + (i >> 1) * 64, x[1] + (i & 1) * (ht ? 1024 : 32), stg + i * 4096);
        bulk_commit();
        bulk_wait_read();
        mbar_arrive(sb + B_SFREE + wg * 8);
        if ((int)x[3] >= 0) {
            bulk_wait_all(); fence_async();
            asm volatile("red.relaxed.gpu.global.add.u32 [%0], 1;" ::"l"(&g_cnt(x[3])) : "memory");
        }
    }
}

template <int N, int TA, int TB, bool FIRST>
__device__ __forceinline__ void issue_ktile(float* acc, const Cons& c) {
    mbar_wait(c.sb + B_FULL + c.p.stage * 8, c.p.phase);
    const uint32_t a = c.sb + c.p.stage * STAGE + c.wg * 8192, b = c.sb + c.p.stage * STAGE + 16384;
    const uint64_t da = mkdesc(a, TA ? 8192 : 16, 1024, 1), db = mkdesc(b, TB ? 8192 : 16, 1024, 1);
    wg_fence();
#pragma unroll
    for (int k = 0; k < 4; k++) {
        const uint64_t x = da + (TA ? 128 : 2) * k, y = db + (TB ? 128 : 2) * k;
        if (N == 256) { if (FIRST && k == 0) wgmma_ss256_first<TA, TB>(acc, x, y); else wgmma_ss256<TA, TB>(acc, x, y); }
        else { if (FIRST && k == 0) wgmma_ss128_first<TA, TB>(acc, x, y); else wgmma_ss128<TA, TB>(acc, x, y); }
    }
    wg_commit();
}
template <int N, bool FIRST>
__device__ __forceinline__ void issue_any(float* acc, const Cons& c, int type) {
    if (N == 256 && type == T_A1) issue_ktile<N, 0, 0, FIRST>(acc, c);
    else if (type == (N == 256 ? T_A2 : T_A2H)) issue_ktile<N, 1, 0, FIRST>(acc, c);
    else issue_ktile<N, 0, 1, FIRST>(acc, c);
}
template <int N, bool KVONLY = false>
__device__ __forceinline__ void mainloop(float* acc, const Params& P, Cons& c, Pend& d, int type) {
    const int nk = (type == T_OP || type == T_OPH) ? 64 : (type == T_A2 || type == T_A2H) ? 32 : 16;
    issue_any<N, true>(acc, c, type);
    drain<0, KVONLY>(P, c, d);
    uint32_t prev = c.p.stage;
    pipe_next(c.p);
    for (int kt = 1; kt < nk; kt++) {
        issue_any<N, false>(acc, c, type);
        wg_wait<1>();
        release(c, prev);
        if (kt == 2) drain<1, KVONLY>(P, c, d);
        prev = c.p.stage;
        pipe_next(c.p);
    }
    d.kind = PEND_NONE;
    wg_wait<0>();
    pin<N / 2>(acc);
    release(c, prev);
}
__device__ __forceinline__ void pack_half(uint32_t* pk, const float* a) {
#pragma unroll
    for (int i = 0; i < 32; i++) pk[i] = pack2(a[2 * i], a[2 * i + 1]);
}

__device__ __forceinline__ void epi_kv(const float* acc, const Cons& c, Pend& d, int mb, int nb) {
    pack_half(d.pk, acc); pack_half(d.pk + 32, acc + 64);
    d.kind = PEND_KVO; d.row = (nb >> 4) * 2048 + mb * 256 + c.rank * 128 + c.wg * 64; d.col = (nb & 15) * 256; d.cnt = C_KV + mb;
}

__device__ __forceinline__ void epi_qa(const float* acc, Cons& c, Pend& d, int mb, int nb) {
    uint32_t q[64];
    pack_half(q, acc);
    pack_half(q + 32, acc + 64);
#pragma unroll
    for (int i = 0; i < 32; i++) d.pk[32 + i] = 0;
    const int g = c.lane >> 2, t = c.lane & 3;
    const bool sg = c.wq >= 2;
    const int i0 = (c.wq & 1) * 16 + g;
#pragma unroll 1
    for (int hh = 0; hh < 2; hh++) {
        uint32_t pa[5][4];
        {
            float S[32] = {}, Sm[8] = {};
            mbar_wait(c.sb + B_FULL + c.p.stage * 8, c.p.phase);
            const uint32_t st = c.sb + c.p.stage * STAGE;
            const uint64_t dk = mkdesc(st + c.wg * 8192, 16, 1024, 1), dm = mkdesc(st + 32768 + c.wg * 4096, 128, 2048, 0);
            pin<32>(q); pin<32>(S); pin<8>(Sm);
            wg_fence();
#pragma unroll
            for (int i = 0; i < 8; i++) wgmma_rs64<0>(S, q + i * 4, dk + (i >> 2) * 1024 + (i & 3) * 2, i != 0);
#pragma unroll
            for (int i = 0; i < 8; i++) wgmma_rs16<0>(Sm, q + i * 4, dm + i * 16, i != 0);
            wg_commit();
            wg_wait<0>();
            pin<32>(S); pin<8>(Sm);
            release(c, c.p.stage);
            pipe_next(c.p);
            const float scale = 0.08838834764831845f, l2e = 1.4426950408889634f;
            float x[2][10];
#pragma unroll
            for (int r = 0; r < 2; r++) {
#pragma unroll
                for (int j = 0; j < 4; j++)
#pragma unroll
                    for (int e = 0; e < 2; e++) {
                        const float v = sg ? S[16 + j * 4 + r * 2 + e] : S[j * 4 + r * 2 + e];
                        x[r][j * 2 + e] = (j * 8 + 2 * t + e > i0 + r * 8) ? -1e9f : v * scale;
                    }
                x[r][8] = (sg ? Sm[4 + r * 2] : Sm[r * 2]) * scale;
                x[r][9] = (sg ? Sm[5 + r * 2] : Sm[1 + r * 2]) * scale;
                float m = x[r][0];
#pragma unroll
                for (int i = 1; i < 10; i++) m = fmaxf(m, x[r][i]);
                m = fmaxf(m, __shfl_xor_sync(0xffffffffu, m, 1));
                m = fmaxf(m, __shfl_xor_sync(0xffffffffu, m, 2));
                float sum = 0.f;
#pragma unroll
                for (int i = 0; i < 10; i++) { x[r][i] = ex2((x[r][i] - m) * l2e); sum += x[r][i]; }
                sum += __shfl_xor_sync(0xffffffffu, sum, 1);
                sum += __shfl_xor_sync(0xffffffffu, sum, 2);
                const float inv = rcp(sum);
#pragma unroll
                for (int i = 0; i < 10; i++) x[r][i] *= inv;
            }
#pragma unroll
            for (int ks = 0; ks < 2; ks++)
#pragma unroll
                for (int i = 0; i < 4; i++) {
                    const uint32_t p = pack2(x[i & 1][ks * 4 + (i >> 1) * 2], x[i & 1][ks * 4 + (i >> 1) * 2 + 1]);
                    pa[ks][i] = sg ? 0u : p;
                    pa[2 + ks][i] = sg ? p : 0u;
                }
#pragma unroll
            for (int r = 0; r < 2; r++) {
                const uint32_t p = pack2(x[r][8], x[r][9]);
                pa[4][r] = sg ? 0u : p;
                pa[4][2 + r] = sg ? p : 0u;
            }
        }
        float O[64] = {};
        mbar_wait(c.sb + B_FULL + c.p.stage * 8, c.p.phase);
        const uint32_t st = c.sb + c.p.stage * STAGE;
        const uint64_t dv = mkdesc(st + c.wg * 8192, 16384, 1024, 1), dm = mkdesc(st + 32768 + c.wg * 4096, 2048, 128, 0);
        pin<20>(&pa[0][0]); pin<64>(O);
        wg_fence();
#pragma unroll
        for (int ks = 0; ks < 4; ks++) wgmma_rs128<1>(O, pa[ks], dv + ks * 128, ks != 0);
        wgmma_rs128<0>(O, pa[4], dm, 1);
        wg_commit();
        wg_wait<0>();
        pin<64>(O);
        release(c, c.p.stage);
        pipe_next(c.p);
#pragma unroll
        for (int i = 0; i < 32; i++) { q[i] = q[32 + i]; q[32 + i] = d.pk[32 + i]; }
        pack_half(d.pk + 32, O);
    }
#pragma unroll
    for (int i = 0; i < 32; i++) d.pk[i] = q[32 + i];
    d.kind = PEND_KVO; d.row = 4096 + mb * 256 + c.rank * 128 + c.wg * 64; d.col = nb * 256; d.cnt = C_O + mb * 4 + (nb >> 2);
}

__device__ __forceinline__ void epi_op(const float* acc, const Cons& c, Pend& d, int mb, int nb) {
    pack_half(d.pk, acc); pack_half(d.pk + 32, acc + 64);
    d.kind = PEND_OUT; d.row = mb * 256 + c.rank * 128 + c.wg * 64; d.col = 1024 + nb * 256;
}

__device__ __forceinline__ void epi_oph(const float* acc, const Cons& c, Pend& d, int mb, int nb) {
    pack_half(d.pk, acc);
    d.kind = PEND_OUTH; d.row = mb * 256 + c.rank * 128 + c.wg * 64; d.col = 1024 + nb * 128;
}

template <int HF>
__device__ __forceinline__ void epi_a2_half(const float* acc, const Params& P, Cons& c, int mb, int col0) {
    const int g = c.lane >> 2, t = c.lane & 3;
    const int row = mb * 256 + (g >> 1) * 64 + (c.rank * 16 + c.wg * 8 + c.wq * 2) * 2 + (g & 1);
    float* o = P.out + (size_t)row * 2048 + col0 + HF * 128 + t * 2;
    mbar_wait(c.sb + B_FULL + c.p.stage * 8, c.p.phase);
    const uint32_t st = c.sb + c.p.stage * STAGE, da = st + 32768 + (c.lane >> 3) * 16;
    const uint32_t xa = st + (c.wg * 64 + c.wq * 16 + (c.lane & 15)) * 128 + (((c.lane >> 4) ^ (c.lane & 7)) << 4);
#pragma unroll
    for (int j4 = 0; j4 < 4; j4++) {
        uint32_t x[8], dv[4];
        ldsm4(dv, da + j4 * 64);
        ldsm4(x, (xa ^ ((j4 & 1) << 6)) + (j4 >> 1) * 16384);
        ldsm4(x + 4, (xa ^ ((j4 & 1) << 6) ^ 32) + (j4 >> 1) * 16384);
#pragma unroll
        for (int i = 0; i < 4; i++) {
            const int j = j4 * 4 + i;
            const float* a = acc + HF * 64 + j * 4;
            const uint32_t u0 = hmul2(x[2 * i], dv[i]), u1 = hmul2(x[2 * i + 1], dv[i]);
            st_stream2(o + j * 8, a[0] + bf_lo(u0), a[1] + bf_hi(u0));
            st_stream2(o + 2 * 2048 + j * 8, a[2] + bf_lo(u1), a[3] + bf_hi(u1));
        }
    }
    __syncwarp();
    release(c, c.p.stage);
    pipe_next(c.p);
}

#define TSTAMP(i)
__device__ __forceinline__ float2 cmul(float2 a, float2 b) { return make_float2(fmaf(a.x, b.x, -a.y * b.y), fmaf(a.x, b.y, a.y * b.x)); }
__device__ __forceinline__ float2 cfma(float2 a, float2 b, float2 u) { return make_float2(fmaf(a.x, b.x, fmaf(-a.y, b.y, u.x)), fmaf(a.x, b.y, fmaf(a.y, b.x, u.y))); }
__device__ __forceinline__ float4 ssm_coef(float lre, float lim, float logdt) {
    const float dt = __bfloat162float(__float2bfloat16(expf(logdt)));
    const float ea = expf(dt * lre);
    float sn, cn;
    sincosf(dt * lim, &sn, &cn);
    const float br = ea * cn, bi = ea * sn, nr = br - 1.f;
    float cr, ci;
    if (fabsf(lre) >= fabsf(lim)) { const float r = lim / lre, dn = lre + lim * r; cr = (nr + bi * r) / dn; ci = (bi - nr * r) / dn; }
    else { const float r = lre / lim, dn = lre * r + lim; cr = (nr * r + bi) / dn; ci = (bi * r - nr) / dn; }
    return make_float4(br, bi, cr, ci);
}
__device__ __forceinline__ void epi_a1(const float* acc, const Params& P, const Cons& c, Pend& d, int mb, int nb, uint32_t atag) {
    const int t = c.lane & 3;
    const int p = nb * 128 + c.rank * 64 + c.wg * 32 + c.wq * 8 + (c.lane >> 2);
    uint32_t cw[4];
    lds128(cw, c.sb + S_COEF + (p & 63) * 16);
    const float4 cf = make_float4(__uint_as_float(cw[0]), __uint_as_float(cw[1]), __uint_as_float(cw[2]), __uint_as_float(cw[3]));
    TSTAMP(1)
    const float2 lam = make_float2(cf.x, P.swap_ri ? -cf.y : cf.y);
    const float a0 = P.swap_ri ? -2.f * cf.w : 2.f * cf.z, a1 = P.swap_ri ? 2.f * cf.z : -2.f * cf.w;
    const float b0 = P.swap_ri ? -2.f * cf.z : -2.f * cf.w, b1 = P.swap_ri ? -2.f * cf.w : -2.f * cf.z;
    float2 h = make_float2(0.f, 0.f);
#pragma unroll
    for (int round = 0; round < 2; round++) {
#pragma unroll
        for (int j = 0; j < 32; j++) {
            h = cfma(lam, h, make_float2(acc[j * 4], acc[j * 4 + 2]));
            const float r0 = fmaf(a0, h.x, a1 * h.y), m0 = fmaf(b0, h.x, b1 * h.y);
            h = cfma(lam, h, make_float2(acc[j * 4 + 1], acc[j * 4 + 3]));
            d.pk[j * 2] = pack2(r0, fmaf(a0, h.x, a1 * h.y));
            d.pk[j * 2 + 1] = pack2(m0, fmaf(b0, h.x, b1 * h.y));
        }
        if (round) break;
        float2 l64 = lam;
#pragma unroll
        for (int i = 0; i < 6; i++) l64 = cmul(l64, l64);
        const float2 l128 = cmul(l64, l64), l256 = cmul(l128, l128);
        float2 o = make_float2(__shfl_up_sync(0xffffffffu, h.x, 1), __shfl_up_sync(0xffffffffu, h.y, 1));
        if (t >= 1) h = cfma(l64, o, h);
        o = make_float2(__shfl_up_sync(0xffffffffu, h.x, 2), __shfl_up_sync(0xffffffffu, h.y, 2));
        if (t >= 2) h = cfma(l128, o, h);
        TSTAMP(2)
        if (t == 3) st_relaxed2(&g_agg[mb * 1024 + p], (__float_as_uint(h.x) & ~1u) | atag, __float_as_uint(h.y));
        h = make_float2(__shfl_up_sync(0xffffffffu, h.x, 1), __shfl_up_sync(0xffffffffu, h.y, 1));
        if (t == 0) h = make_float2(0.f, 0.f);
        uint32_t ax[7], ay[7];
        int n = 0;
        while (true) {
            uint32_t bad = 0;
#pragma unroll
            for (int j = 0; j < 7; j++) { ax[j] = atag; ay[j] = 0; ld_relaxed2_if(ax[j], ay[j], &g_agg[j * 1024 + p], j < mb); }
#pragma unroll
            for (int j = 0; j < 7; j++) bad |= ax[j] ^ atag;
            if (tags_ok(bad)) break;
            __nanosleep(400);
            if (++n > SPIN_LIMIT) spin_fault();
        }
        float2 carry = make_float2(0.f, 0.f);
#pragma unroll
        for (int j = 0; j < 7; j++) if (j < mb) carry = cfma(l256, carry, make_float2(__uint_as_float(ax[j]), __uint_as_float(ay[j])));
        float2 w = (t & 1) ? l64 : make_float2(1.f, 0.f);
        if (t & 2) w = cmul(w, l128);
        h = cfma(w, carry, h);
        TSTAMP(3)
    }
    TSTAMP(4)
    d.kind = PEND_HT; d.row = nb * 128 + c.rank * 64 + c.wg * 32; d.col = mb * 256; d.cnt = C_HT + mb * 2 + (nb >> 2);
}

__device__ __forceinline__ uint32_t acquire_stage(uint32_t sb, Pipe& p, uint32_t bytes) {
    mbar_wait(sb + B_EMPTY + p.stage * 8, p.phase ^ 1);
    mbar_expect(sb + B_FULL + p.stage * 8, bytes);
    return p.stage;
}
#define AHEAD 1
__device__ __forceinline__ void watcher(const Params& P, const uint32_t sb, const int rank, const int lane) {
    const uint32_t epoch = ld_relaxed1(&g_cnt(C_EPOCH)), e1 = epoch + 1;
    sts32(sb + S_EPOCH, epoch);
    __syncwarp();
    if (lane == 0 && atomicInc(&g_cnt(C_DONE), (DBGF(32) ? 95 : NPAIR * 2 - 1) + (epoch & P.zero)) == (DBGF(32) ? 95 : NPAIR * 2 - 1)) atomicAdd(&g_cnt(C_EPOCH), 1);
    if (gridDim.x != 96) {
        uint32_t v;
        asm("mov.u32 %0, %%smid;" : "=r"(v));
        if (lane == 0 && rank == 0) st_relaxed1(g_hint + 6272 + (blockIdx.x >> 1), e1 << 8 | v >> 1);
        for (int k = 0;; k++) {
            __nanosleep(1000);
            v = ld_relaxed1(g_hint + 6272 + min(lane, 17));
            if (__all_sync(0xffffffffu, (v ^ e1 << 8) < 256)) break;
            if (k > SPIN_LIMIT) spin_fault();
        }
        const uint32_t key = ((v & 255) >= 62 ? 0 : tpc_gpc(v & 255)) * 32 + lane;
        sts32(sb + S_TAIL, 48 + __popc(__ballot_sync(0xffffffffu, key < __shfl_sync(0xffffffffu, key, blockIdx.x >> 1)) & 0x3ffff));
        __syncwarp();
    }
    uint32_t met = 1;
    if (lane == 0) asm volatile("st.release.cta.shared.u32 [%0], 1;" ::"r"(sb + S_DEP) : "memory");
    const int pair = lds32(sb + S_TAIL), first = ITEM_OFF(pair) + (pair < NCHAIN ? NPRE + 1 : 1);
#pragma unroll 1
    for (int it = first; it < ITEM_OFF(pair + 1); it++) {
        const int item = ITEM(it), type = item >> 8, mb = (item >> 5) & 7, nb = item & 31;
        const int n = (0x24021420 >> (type * 4)) & 7;
        for (int k = 0; it > first && (int)lds32(sb + S_CUR) < it - AHEAD; k++) { __nanosleep(200); if (k > SPIN_LIMIT) spin_fault(); }
#pragma unroll 1
        for (int i = 0; i < n; i++) {
            int idx = n == 4 ? C_O + mb * 4 + i : C_HT + mb * 2 + i;
            uint32_t target = e1 * 16;
            if (type == T_A1) { idx = C_COEF; target = e1 * 4; }
            if (type == T_QA) {
                idx = i ? C_FLAG + (lane & 1) * 32 + nb * 2 + ((lane >> 1) & 1) : C_KV + mb;
                target = i ? epoch * 64 + mb * 8 + rank * 4 + 4 : e1 * 128;
            }
            if (lane < 4) { wait_count(&g_cnt(idx), target); fence_async(); }
            __syncwarp();
            if (lane == 0) asm volatile("st.release.cta.shared.u32 [%0], %1;" ::"r"(sb + S_DEP), "r"(++met) : "memory");
        }
    }
}
__device__ __forceinline__ bool dep_met(uint32_t sb, uint32_t n) { uint32_t v; asm volatile("ld.acquire.cta.shared.u32 %0, [%1];" : "=r"(v) : "r"(sb + S_DEP) : "memory"); return v >= n; }
__device__ __forceinline__ void dep_wait(uint32_t sb, uint32_t n) { for (int k = 0; !dep_met(sb, n); k++) { __nanosleep(32); if (k > SPIN_LIMIT * 8) spin_fault(); } }
__device__ __forceinline__ void producer(const Params& P, const uint32_t sb, int pair, const int rank) {
    Pipe p = {0, 0};
    uint32_t dep = 1;
    for (int it = ITEM_OFF(pair); it < ITEM_OFF(pair + 1); it++) {
        const int item = ITEM(it), type = item >> 8, mb = (item >> 5) & 7, nb = item & 31;
        if (type == T_CHAIN) {
            sts32(sb + S_CUR, 0);
            const uint32_t epoch = ld_relaxed1(&g_cnt(C_EPOCH)), e1 = epoch + 1;
            const int role = pair >> 4, h = (pair & 15) * 2 + rank;
#pragma unroll 1
            for (int i = 0, q = 0; i < 8; i++) {
                const int n = (0x13003333 >> (i * 4)) & 3;
                const uint32_t st = acquire_stage(sb, p, n * 16384);
                SSTAMP(1, i == 0) SSTAMP(3, i == 3)
#pragma unroll 1
                for (int k = 0; k < 2 * n; k++, q++)
                    tma3d(sb + st * STAGE + k * 8192, &P.tm[M_CQ + role], h * 128 + (fill_unit(q >> 1) & 1) * 64, word_col((fill_unit(q >> 1) & 14) + (q & 1)) & 8, word_col((fill_unit(q >> 1) & 14) + (q & 1)) >> 4, sb + B_FULL + st * 8);
                pipe_next(p);
            }
            if (role == 0 && !DBGF(1)) { wait_count(&g_cnt(C_KV), e1 * 128); fence_async(); }
            mbar_wait(sb + B_EMPTY + 16, 1); mbar_wait(sb + B_EMPTY + 24, 1);
            mbar_expect(sb + B_WO, role ? 98304 : 65536);
            if (role == 0) { mbar_expect(sb + B_KVFULL, 16384); mbar_expect(sb + B_KVFULL + 8, 16384); }
#pragma unroll 1
            for (int k = role ? 0 : -4; k < 12; k++) {
                const bool kv = role == 0 && (k & 8);
                const int sg = k > 0;
                tma4d(kv ? sb + S_KV + sg * 16384 + (k & 3) * 4096 : sb + S_W2 + k * 8192, &P.tm[kv ? M_KV4 : M_CO + (k & 1)],
                      kv ? h * 128 + (k & 1) * 64 : (role == 0 ? 0 : role == 1 ? 256 : 640) + (k >> 1) * 64, kv ? (k & 2) * 1024 + sg * 32 : h * 8, sb + (kv ? B_KVFULL + sg * 8 : B_WO));
            }
            SSTAMP(5, true)
            if (pair < 16) {
#pragma unroll 1
                for (int s = 2; s < 63; s++) {
                    mbar_wait(sb + B_KVGO + (s & 1) * 8, ((s >> 1) + 1) & 1);
                    wait_time(gtime() + P.dk, sb);
                    SSTAMP(6, s == 2)
                    const uint32_t bar = sb + B_KVFULL + (s & 1) * 8, dst = sb + S_KV + (s & 1) * 16384;
                    if (DBGF(2)) { mbar_arrive(bar); continue; }
                    mbar_expect(bar, 16384);
#pragma unroll 1
                    for (int i = 0; i < 4; i++) tma2d(dst + i * 4096, &P.tm[M_KVO], (pair * 2 + rank) * 128 + (i & 1) * 64, (i >> 1) * 2048 + (DBGF(32 | 512) ? s & 7 : s) * 32, bar);
                    if ((s & 7) == 7 && !DBGF(1)) { wait_count(&g_cnt(C_KV + 1 + (s >> 3)), e1 * 128); fence_async(); }
                }
            } else {
                uint32_t* flag = &g_cnt(C_FLAG + pair * 2 + rank - 32);
                const int x = pair * 2 + rank - 32;
#pragma unroll 1
                for (int s = 0; s < 64; s++) {
                    mbar_wait(sb + B_PERS, s & 1);
                    if (s < 63) wait_time(gtime() + P.dp, sb);
                    if (!DBGF(4)) bulk_s2g((role == 1 ? g_km : g_vmt) + (s * 32 + h) * 512, sb + S_QX, 2048);
                    if (s < 57) {
                        uint8_t* m = P.gm + ((s + 6) & 7) * M_SLOT + (x >> 1) * 1024 + (x & 1) * 256;
                        bulk_s2g(m, sb + S_SX, 256); bulk_s2g(m + 512, sb + S_SX, 128);
                        bulk_s2g(g_f + ((s + 6) & 7) * F_SLOT + x * 768, sb + S_SX + 256, 768);
                    }
                    bulk_commit();
                    bulk_wait_read();
                    mbar_arrive(sb + B_KVGO);
                    bulk_wait_all();
                    fence_async();
                    if ((s & 3) == 3) st_relaxed1(flag, epoch * 64 + s + 1);
                }
            }
            mbar_wait(sb + B_RESUME, 0);
            pair = lds32(sb + S_TAIL);
            it = ITEM_OFF(pair) + NPRE;
            continue;
        }
        if (it == ITEM_OFF(pair) && pair >= NCHAIN) it = -1; else sts32(sb + S_CUR, it);
        const int m0 = mb * 256 + rank * 128;
        if (type <= T_OP) {
            const CUtensorMap* ma = &P.tm[type == T_OP ? M_OA : M_BX];
            const CUtensorMap* mw = &P.tm[type == T_OP ? M_WO : type == T_QA ? M_WQ : nb < 16 ? M_WK : M_WV];
            const int nk = type == T_OP ? 64 : 16, nc = (nb & 15) * 4 + rank * 2, ma0 = type == T_OP ? 4096 + m0 : m0;
#pragma unroll 1
            for (int kt = 0; kt < nk; kt++) {
                if (type == T_OP && (kt & 15) == 0) dep_wait(sb, ++dep);
                if (DBGF(256) && pair >= NCHAIN) { acquire_stage(sb, p, 0); pipe_next(p); continue; }
                const uint32_t st = acquire_stage(sb, p, STAGE), bar = sb + B_FULL + st * 8;
                tma2d(sb + st * STAGE, ma, kt * 64, ma0, bar);
                tma3d_mc(sb + st * STAGE + 16384 + rank * 16384, mw, 0, kt * 64, nc, bar);
                pipe_next(p);
            }
            if (type == T_QA) {
                dep += 2;
                dep_wait(sb, dep);
#pragma unroll 1
                for (int e = 0; e < 4; e++) {
                    const uint32_t st = acquire_stage(sb, p, 40960), bar = sb + B_FULL + st * 8, dst = sb + st * STAGE;
                    tma2d(dst, &P.tm[M_OA], nb * 256 + (e >> 1) * 128, (e & 1) * 2048 + m0, bar);
                    tma2d(dst + 16384, &P.tm[M_OA], nb * 256 + (e >> 1) * 128 + 64, (e & 1) * 2048 + m0, bar);
                    const uint32_t* src = ((e & 1) ? g_vmt : g_km) + ((mb * 8 + rank * 4) * 32 + nb * 2 + (e >> 1)) * 512;
#pragma unroll 1
                    for (int i = 0; i < 4; i++) bulk_g2s(dst + 32768 + i * 2048, src + i * 32 * 512, 2048, bar);
                    pipe_next(p);
                }
            }
        } else if (type == T_OPH) {
#pragma unroll 1
            for (int kt = 0; kt < 64; kt++) {
                if ((kt & 15) == 0) dep_wait(sb, ++dep);
                const uint32_t st = acquire_stage(sb, p, 32768), bar = sb + B_FULL + st * 8;
                tma2d(sb + st * STAGE, &P.tm[M_OA], kt * 64, 4096 + m0, bar);
                tma2d_mc(sb + st * STAGE + 16384 + rank * 8192, &P.tm[M_WOH], nb * 128 + rank * 64, kt * 64, bar);
                pipe_next(p);
            }
        } else if (type == T_A1) {
#pragma unroll 1
            for (int kt = 0; kt < 16; kt++) {
                if (kt == 15) dep_wait(sb, ++dep);
                const uint32_t st = acquire_stage(sb, p, kt == 15 ? STAGE + 1024 : STAGE), bar = sb + B_FULL + st * 8;
                if (kt == 15) bulk_g2s(sb + S_COEF, g_coef + nb * 128 + rank * 64, 1024, bar);
                tma4d(sb + st * STAGE, &P.tm[M_AB], kt * 64, nb * 16 + rank * 8, bar);
                tma4d_mc(sb + st * STAGE + 16384 + rank * 16384, &P.tm[M_AX], kt * 64, mb * 128 + rank * 16, bar);
                pipe_next(p);
            }
        } else {
            const int hw = type == T_A2H ? 64 : 128;
            const CUtensorMap* mc = &P.tm[type == T_A2H ? M_CREH : M_CRE];
#pragma unroll 1
            for (int kt = 0; kt < 32; kt++) {
                if ((kt & 15) == 0) dep_wait(sb, ++dep);
                const uint32_t st = acquire_stage(sb, p, 16384 + hw * 256), bar = sb + B_FULL + st * 8;
                tma3d(sb + st * STAGE, &P.tm[M_HT], 0, (kt & 1) * 1024 + (kt >> 1) * 64, mb * 4 + rank * 2, bar);
                tma2d_mc(sb + st * STAGE + 16384 + rank * hw * 128, mc + (kt & 1), (kt >> 1) * 64, (nb * 2 + rank) * hw, bar);
                pipe_next(p);
            }
#pragma unroll 1
            for (int col = nb * 2 * hw; col < (nb + 1) * 2 * hw; col += 128) {
                const uint32_t st = acquire_stage(sb, p, 32768 + 256), bar = sb + B_FULL + st * 8;
                tma4d(sb + st * STAGE, &P.tm[M_AX], col, mb * 128 + rank * 16, bar);
                tma4d(sb + st * STAGE + 16384, &P.tm[M_AX], col + 64, mb * 128 + rank * 16, bar);
                bulk_g2s(sb + st * STAGE + 32768, P.Dskip + col, 256, bar);
                pipe_next(p);
            }
        }
        if (it < 0) { dep_wait(sb, 1); pair = lds32(sb + S_TAIL); it = ITEM_OFF(pair); }
    }
}

__device__ __forceinline__ uint32_t fresh_tid() { uint32_t t; asm volatile("mov.u32 %0, %%tid.x;" : "=r"(t)); return t; }
__device__ __forceinline__ uint32_t fresh_ctaid() { uint32_t t; asm volatile("mov.u32 %0, %%ctaid.x;" : "=r"(t)); return logical_cta(t); }
__device__ __forceinline__ void reset_state(Cons& c, Pend& d, uint32_t sb, bool resumed) {
    const uint32_t t = fresh_tid(), b = fresh_ctaid();
    const int w = __shfl_sync(0xffffffffu, t >> 5, 0);
    c.sb = sb; c.wg = w >> 2; c.wq = w & 3; c.lane = t & 31;
    c.rank = __shfl_sync(0xffffffffu, b & 1, 0); c.pair = __shfl_sync(0xffffffffu, resumed && b < NCHAIN * 2 ? lds32(sb + S_TAIL) : b >> 1, 0);
    c.rel = mapa(sb + B_EMPTY, cluster_rank() ^ (c.lane & 1));
    c.p.stage = 0; c.p.phase = 0;
    c.nst = resumed && c.pair < NCHAIN ? 2 * NPRE : 0;
    d = Pend{};
}
#define PROF_ITEM(i)
#define PROF_MAIN(i)

__global__ void __launch_bounds__(384, 1) fused_kernel(const __grid_constant__ Params P) {
    extern __shared__ __align__(1024) uint8_t smem[];
    const uint32_t sb = smem_u32(smem);
    asm volatile("griddepcontrol.launch_dependents;");
    const int tid = threadIdx.x, lane = tid & 31;
    const int warp = __shfl_sync(0xffffffffu, tid >> 5, 0);
    const int pair = __shfl_sync(0xffffffffu, logical_cta(blockIdx.x) >> 1, 0), rank = __shfl_sync(0xffffffffu, blockIdx.x & 1, 0);
    if (tid == 0) {
        if (sb & 1023) spin_fault();
        sts32(sb + S_DEP, 0); sts32(sb + S_CUR, 0); sts32(sb + S_TAIL, pair); sts32(sb + S_CTA, pair * 2 + rank);
        for (int i = 0; i < NSTAGE; i++) { mbar_init(sb + B_FULL + i * 8, 1); mbar_init(sb + B_EMPTY + i * 8, 16); }
        mbar_init(sb + B_RESUME, 2);
        mbar_init(sb + B_KVFULL, 1); mbar_init(sb + B_KVFULL + 8, 1);
        mbar_init(sb + B_GO, 1); mbar_init(sb + B_KVGO, 1); mbar_init(sb + B_KVGO + 8, 1); mbar_init(sb + B_K, 1); mbar_init(sb + B_V, 1); mbar_init(sb + B_PERS, 8); mbar_init(sb + B_INIT, 3);
        mbar_init(sb + B_WO, 1);
        for (int i = 0; i < 2; i++) { mbar_init(sb + B_SFULL + i * 8, 4); mbar_init(sb + B_SFREE + i * 8, 1); }
        mbar_init(sb + B_RELA, 1); mbar_init(sb + B_RELB, 1);
        asm volatile("fence.mbarrier_init.release.cluster;" ::: "memory");
        if (pair < 16) mbar_expect(sb + B_K, 2048);
        mbar_expect(sb + B_V, 2048);
    }
    cluster_sync();
    if (warp >= 8) {
        asm volatile("setmaxnreg.dec.sync.aligned.u32 24;");
        if (warp == 10 && lane < M_COUNT) map_prefetch(&P.tm[lane]);
        if (warp == 11 && lane == 0 && pair < NCHAIN) {
            const uint32_t t0 = gtime();
            const int role = pair >> 4, h = (pair & 15) * 2 + rank;
#pragma unroll 1
            for (int i = role ? 32 : 0; i < (role ? 44 : 40); i++) {
                wait_time(t0 + P.pf0 + min(i, 32) * P.pf1 + max(i - 32, 0) * P.pf2, sb);
                if (i < 32) asm volatile("cp.async.bulk.prefetch.tensor.3d.L2.global [%0, {%1, %2, %3}];" ::"l"(&P.tm[M_CQ]), "r"(h * 128 + (i & 1) * 64), "r"((i & 2) * 4), "r"((i >> 2) * 8) : "memory");
                else asm volatile("cp.async.bulk.prefetch.tensor.4d.L2.global [%0, {%1, 0, 0, %2}];" ::"l"(&P.tm[M_CO + (i & 1)]), "r"((role == 0 ? 0 : role == 1 ? 256 : 640) + ((i - 32) >> 1) * 64), "r"(h * 8) : "memory");
            }
        }
        if (warp == 9 && pair < NCHAIN) pacer(P, sb, lane);
        if (warp == 9) watcher(P, sb, rank, lane);
        if (warp >= 10 && lane == 0) store_warp(P, sb, warp - 10);
        if (warp == 8) {
            if (lane == 0) producer(P, sb, lds32(sb + S_CTA) >> 1, rank);
            __syncwarp();
            asm volatile("barrier.cluster.arrive.relaxed.aligned;\nbarrier.cluster.wait.aligned;" ::: "memory");
        }
    } else {
        asm volatile("setmaxnreg.inc.sync.aligned.u32 240;");
        Cons c;
        Pend d;
        if (pair < NCHAIN) {
            mem0_max(P, sb, tid);
            reset_state(c, d, sb, false);
#pragma unroll 1
            for (int i = 0; i < NPRE; i++) {
                PROF_ITEM(i)
                const int item = ITEM(ITEM_OFF(pair) + i);
                float acc[128];
                mainloop<256, true>(acc, P, c, d, T_KV);
                epi_kv(acc, c, d, (item >> 5) & 7, item & 31);
            }
            ISTAMP(4)
            drain<0, true>(P, c, d);
            drain<1, true>(P, c, d);
            PROF_ITEM(NPRE)
            uint32_t wr[NR][4];
            load_weights(wr, sb, warp, lane, [&]() { staging_wait(c); });
            const int h = (pair & 15) * 2 + rank;
            if (pair < 16) chain_role<0>(P, wr, sb, h, warp, lane);
            else if (pair < 32) chain_role<1>(P, wr, sb, h, warp, lane);
            else chain_role<2>(P, wr, sb, h, warp, lane);
            fence_async_smem();
            bar_sync(1, 256);
            const uint32_t t2 = fresh_tid();
            if (t2 < 2) mbar_arrive_cluster(mapa(sb + B_RESUME, cluster_rank() ^ t2));
        } else if (pair >= NPAIR - 2) {
            const int ch = (pair - (NPAIR - 2)) * 512 + rank * 256 + tid;
            g_coef[ch] = ssm_coef(__bfloat162float(P.Lre[ch]), __bfloat162float(P.Lim[ch]), __bfloat162float(P.logdt[ch]));
            bar_sync(1, 256);
            if (tid == 0) red_release(&g_cnt(C_COEF));
        }
        reset_state(c, d, sb, true);
        for (int it = ITEM_OFF(c.pair) + (c.pair < NCHAIN ? NPRE + 1 : 0);; it++) {
            const bool last = it == ITEM_OFF(c.pair + 1);
            if (d.kind != PEND_NONE && (last || !bar_and(5 + c.wg, mbar_test(sb + B_FULL + c.p.stage * 8, c.p.phase)))) drain_all(P, c, d);
            if (last) break;
            const int item = ITEM(it), type = item >> 8, mb = (item >> 5) & 7, nb = item & 31;
            PROF_ITEM(it - ITEM_OFF(c.pair))
            if (type >= T_OPH) {
                float acc[64];
                mainloop<128>(acc, P, c, d, type);
                PROF_MAIN(it - ITEM_OFF(c.pair))
                if (type == T_OPH) epi_oph(acc, c, d, mb, nb);
                else epi_a2_half<0>(acc, P, c, mb, nb * 128);
            } else {
                float acc[128];
                mainloop<256>(acc, P, c, d, type);
                PROF_MAIN(it - ITEM_OFF(c.pair))
                if (type == T_KV) epi_kv(acc, c, d, mb, nb);
                else if (type == T_QA) epi_qa(acc, c, d, mb, nb);
                else if (type == T_OP) epi_op(acc, c, d, mb, nb);
                else if (type == T_A1) epi_a1(acc, P, c, d, mb, nb, (lds32(sb + S_EPOCH) + 1) & 1);
                else { epi_a2_half<0>(acc, P, c, mb, nb * 256); epi_a2_half<1>(acc, P, c, mb, nb * 256); }
            }
            if (it == ITEM_OFF(c.pair)) { dep_wait(sb, 1); c.pair = __shfl_sync(0xffffffffu, lds32(sb + S_TAIL), 0); it = ITEM_OFF(c.pair); }
        }
        staging_wait(c);
        staging_post(c, PEND_NONE, 0, 0, 0);
        asm volatile("barrier.cluster.arrive.relaxed.aligned;\nbarrier.cluster.wait.aligned;" ::: "memory");
    }
}

typedef CUresult (*EncodeFn)(CUtensorMap*, CUtensorMapDataType, cuuint32_t, void*, const cuuint64_t*, const cuuint64_t*, const cuuint32_t*, const cuuint32_t*,
                             CUtensorMapInterleave, CUtensorMapSwizzle, CUtensorMapL2promotion, CUtensorMapFloatOOBfill);
void encode(EncodeFn fn, CUtensorMap* m, const void* base, int rank, const uint64_t* dims, const uint64_t* strides, const uint32_t* box, CUtensorMapSwizzle swz = CU_TENSOR_MAP_SWIZZLE_128B) {
    cuuint64_t d[5], s[5]; cuuint32_t b[5], e[5];
    for (int i = 0; i < rank; i++) { d[i] = dims[i]; b[i] = box[i]; e[i] = 1; if (i) s[i - 1] = strides[i - 1]; }
    fn(m, CU_TENSOR_MAP_DATA_TYPE_BFLOAT16, rank, (void*)base, d, s, b, e, CU_TENSOR_MAP_INTERLEAVE_NONE, swz,
       CU_TENSOR_MAP_L2_PROMOTION_L2_256B, CU_TENSOR_MAP_FLOAT_OOB_FILL_NONE);
}
void map_kmajor(EncodeFn fn, CUtensorMap* m, const void* base, uint64_t rows, uint64_t cols, uint32_t box_rows) {
    const uint64_t d[2] = {cols, rows}, s[1] = {cols * 2}; const uint32_t b[2] = {64, box_rows};
    encode(fn, m, base, 2, d, s, b);
}
void map_mnmajor(EncodeFn fn, CUtensorMap* m, const void* base, uint64_t krows, uint64_t cols) {
    const uint64_t d[3] = {64, krows, cols / 64}, s[2] = {cols * 2, 128}; const uint32_t b[3] = {64, 64, 2};
    encode(fn, m, base, 3, d, s, b);
}

}

extern "C" void kernel_launch(void* const* d_in, const int* in_sizes, int n_in, void* d_out, int out_size) {
    static Params P;
    static EncodeFn fn = nullptr;
    if (!fn) {
        cudaDriverEntryPointQueryResult q;
        cudaGetDriverEntryPoint("cuTensorMapEncodeTiled", (void**)&fn, cudaEnableDefault, &q);
        cudaFuncSetAttribute(fused_kernel, cudaFuncAttributeMaxDynamicSharedMemorySize, S_TOTAL);
    }
    const bf16* in[15];
    for (int i = 0; i < 15; i++) in[i] = (const bf16*)d_in[i];
    void *kvo, *ht, *gm;
    cudaGetSymbolAddress(&gm, g_m);
    P.gm = (uint8_t*)(((uintptr_t)gm + 32767) & ~(uintptr_t)32767);
    cudaGetSymbolAddress(&kvo, g_kvo);
    cudaGetSymbolAddress(&ht, g_ht);
    map_kmajor(fn, &P.tm[M_BX], in[9], 2048, 1024, 128);
    map_mnmajor(fn, &P.tm[M_WQ], in[11], 1024, 4096);
    map_mnmajor(fn, &P.tm[M_WK], in[12], 1024, 4096);
    map_mnmajor(fn, &P.tm[M_WV], in[13], 1024, 4096);
    map_mnmajor(fn, &P.tm[M_WO], in[14], 4096, 1024);
    map_kmajor(fn, &P.tm[M_OA], kvo, 3 * 2048, 4096, 128);
    P.swap_ri = in[4] < in[3];
    {
        const bf16* lo = P.swap_ri ? in[4] : in[3];
        const uint64_t diff = (uint64_t)((const char*)(P.swap_ri ? in[3] : in[4]) - (const char*)lo);
        const uint64_t d[4] = {1024, 8, 2, 128}, s[3] = {2048, diff, 16384}; const uint32_t b[4] = {64, 8, 2, 8};
        encode(fn, &P.tm[M_AB], lo, 4, d, s, b);
    }
    {
        const uint64_t d[4] = {1024, 2, 4, 1024}, s[3] = {2048, 64 * 2048, 4096}; const uint32_t b[4] = {64, 2, 4, 16};
        encode(fn, &P.tm[M_AX], in[0], 4, d, s, b);
    }
    map_mnmajor(fn, &P.tm[M_HT], ht, 2048, 2048);
    map_kmajor(fn, &P.tm[M_CRE], in[5], 1024, 1024, 128);
    map_kmajor(fn, &P.tm[M_CIM], in[6], 1024, 1024, 128);
    map_kmajor(fn, &P.tm[M_KVO], kvo, 3 * 2048, 4096, 32);
    map_kmajor(fn, &P.tm[M_HTS], ht, 2048, 2048, 32);
    map_kmajor(fn, &P.tm[M_WOH], in[14], 4096, 1024, 64);
    map_kmajor(fn, &P.tm[M_CREH], in[5], 1024, 1024, 64);
    map_kmajor(fn, &P.tm[M_CIMH], in[6], 1024, 1024, 64);
    for (int i = 0; i < 3; i++) {
        const uint64_t d[3] = {4096, 16, 64}, s[2] = {8192, 16 * 8192}; const uint32_t b[3] = {64, 8, 8};
        encode(fn, &P.tm[M_CQ + i], in[11 + i], 3, d, s, b);
    }
    {
        const uint64_t d[4] = {4096, 1, 1, 4096}, s[3] = {8192, 8192, 8192}; const uint32_t b[4] = {64, 1, 1, 32};
        encode(fn, &P.tm[M_KV4], kvo, 4, d, s, b);
    }
    for (int e = 0; e < 2; e++) {
        const uint64_t d[4] = {1024, 2, 4, 256}, s[3] = {8 * 2048, 2 * 2048, 16 * 2048}; const uint32_t b[4] = {64, 2, 4, 8};
        encode(fn, &P.tm[M_CO + e], in[14] + e * 1024, 4, d, s, b);
    }
    P.Wq = in[11]; P.Wk = in[12]; P.Wv = in[13]; P.Wo = in[14]; P.mem0 = in[10];
    P.Lre = in[1]; P.Lim = in[2]; P.logdt = in[7]; P.Dskip = in[8];
    P.out = (float*)d_out;
    P.two26 = 1u << 26;
    P.ds = 400; P.dc = 1600; P.alpha = 0.3f; P.extra = 200; P.da = 192; P.db = 432; P.dk = 800; P.dp = 1550; P.dv = 60; P.pf0 = 1500; P.pf1 = 175; P.pf2 = 450; P.back = 150; P.ds0 = 950;
    for (int i = 0; i < (DBGF(32) ? 1 : 2); i++) {
        cudaLaunchConfig_t cfg = {};
        cfg.gridDim = dim3(i ? 36 : 96); cfg.blockDim = dim3(384); cfg.dynamicSmemBytes = S_TOTAL; cfg.stream = cudaStreamPerThread;
        cudaLaunchAttribute at[2];
        at[0].id = cudaLaunchAttributeClusterDimension; at[0].val.clusterDim.x = i ? 2 : 6; at[0].val.clusterDim.y = at[0].val.clusterDim.z = 1;
        at[1].id = cudaLaunchAttributeProgrammaticStreamSerialization; at[1].val.programmaticStreamSerializationAllowed = 1;
        cfg.attrs = at; cfg.numAttrs = 1 + i;
        cudaLaunchKernelEx(&cfg, fused_kernel, P);
    }
}
```

```cpp
#include <cuda_runtime.h>
#include <cuda_bf16.h>
#include <cuda.h>
#include <stdint.h>
#include <string.h>

typedef __nv_bfloat16 bf16;

namespace {

#define POLL 200
constexpr int SPIN_LIMIT = 1 << 22;
constexpr int NPAIR = 66;
constexpr int NCHAIN = 48;
enum { T_KV = 0, T_QA = 1, T_OP = 2, T_A1 = 3, T_A2 = 4, T_CHAIN = 5, T_OPH = 6, T_A2H = 7 };
enum { M_BX = 0, M_WQ, M_WK, M_WV, M_WO, M_OA, M_AB, M_AX, M_HT, M_CRE, M_CIM, M_KVO, M_HTS, M_WOH, M_CREH, M_CIMH, M_CQ, M_CK, M_CV, M_CO, M_CO1, M_KV4, M_COUNT };
enum { C_KV = 0, C_HT = 8, C_DONE = 24, C_EPOCH = 25, C_COEF = 26, C_FLAG = 32, C_O = 96 };

struct Params {
    CUtensorMap tm[M_COUNT];
    const bf16 *Wq, *Wk, *Wv, *Wo, *mem0, *Lre, *Lim, *logdt, *Dskip;
    float* out;
    uint8_t* gm;
    int swap_ri, zero;
    uint32_t two26, lag;
    int ds, da, db, dk, dv, back, ds0, pf0, pf1, pf2, dc, extra, dp;
    float alpha;
#define DBGF(x) false
};

constexpr int NPRE = 1;
__constant__ uint16_t c_off[67] = {0, 5, 10, 15, 19, 23, 27, 31, 35, 39, 43, 48, 52, 56, 60, 64, 68, 73, 78, 83, 87, 91, 95, 101, 106, 110, 114, 118, 122, 127, 132, 136, 140, 145, 150, 155, 159, 163, 167, 173, 179, 183, 187, 191, 195, 199, 204, 208, 212, 232, 252, 271, 291, 311, 331, 350, 370, 390, 409, 429, 449, 468, 488, 505, 524, 543, 562};
__constant__ uint16_t c_items[640] = {
    32, 1280, 423, 495, 1122, 49, 1280, 455, 333, 1057, 34, 1280, 428, 302, 1056, 51, 1280, 422, 642, 36, 1280, 326, 641, 53,
    1280, 330, 545, 38, 1280, 869, 547, 55, 1280, 867, 546, 40, 1280, 931, 608, 57, 1280, 899, 609, 42, 1280, 452, 297, 1185,
    59, 1280, 454, 513, 44, 1280, 836, 675, 61, 1280, 804, 672, 46, 1280, 389, 544, 63, 1280, 388, 576, 0, 1280, 292, 491,
    1250, 1, 1280, 484, 493, 1120, 2, 1280, 492, 334, 1058, 3, 1280, 457, 512, 4, 1280, 490, 673, 5, 1280, 458, 610, 6,
    1280, 425, 301, 460, 1862, 7, 1280, 424, 299, 1025, 8, 1280, 871, 707, 9, 1280, 839, 704, 10, 1280, 963, 736, 11, 1280,
    995, 705, 12, 1280, 992, 902, 1218, 13, 1280, 961, 966, 1249, 14, 1280, 928, 739, 15, 1280, 929, 578, 16, 1280, 356, 494,
    1121, 17, 1280, 364, 335, 1153, 18, 1280, 300, 331, 1248, 19, 1280, 453, 514, 20, 1280, 488, 674, 21, 1280, 486, 737, 22,
    1280, 393, 429, 461, 1857, 23, 1280, 392, 427, 463, 1863, 24, 1280, 903, 611, 25, 1280, 866, 515, 26, 1280, 901, 706, 27,
    1280, 898, 738, 28, 1280, 960, 643, 29, 1280, 993, 934, 1217, 30, 1280, 896, 579, 31, 1280, 897, 577, 33, 66, 84, 102,
    120, 138, 156, 174, 210, 246, 204, 201, 224, 323, 365, 259, 835, 962, 329, 1027, 35, 67, 85, 103, 121, 139, 157, 175,
    221, 223, 213, 220, 354, 229, 419, 367, 384, 261, 964, 1152, 37, 68, 86, 104, 122, 140, 158, 176, 239, 196, 263, 225,
    360, 264, 832, 837, 994, 996, 1059, 39, 69, 87, 105, 123, 141, 159, 177, 207, 199, 195, 237, 396, 296, 322, 390, 489,
    395, 967, 1251, 41, 70, 88, 106, 124, 142, 160, 178, 253, 245, 192, 197, 235, 386, 362, 352, 262, 487, 269, 1216, 43,
    71, 89, 107, 125, 143, 161, 179, 241, 249, 233, 219, 353, 321, 387, 834, 256, 459, 933, 1187, 45, 72, 90, 108, 126,
    144, 162, 180, 203, 250, 226, 358, 327, 805, 324, 449, 900, 332, 1154, 47, 73, 91, 109, 127, 145, 163, 181, 240, 200,
    244, 212, 227, 385, 357, 448, 483, 868, 271, 1026, 48, 74, 92, 110, 128, 146, 164, 182, 206, 248, 218, 216, 247, 238,
    397, 768, 838, 361, 935, 1090, 50, 75, 93, 111, 129, 147, 165, 183, 231, 222, 211, 363, 773, 801, 431, 420, 394, 430,
    1024, 52, 76, 94, 112, 130, 148, 166, 184, 193, 228, 214, 215, 355, 803, 288, 295, 864, 359, 998, 1219, 54, 77, 95,
    113, 131, 149, 167, 185, 243, 198, 194, 205, 325, 417, 303, 294, 481, 456, 366, 1186, 56, 78, 96, 114, 132, 150, 168,
    186, 234, 202, 242, 328, 775, 833, 800, 421, 485, 932, 1089, 58, 79, 97, 115, 133, 151, 169, 187, 217, 208, 209, 290,
    398, 416, 265, 865, 480, 462, 997, 1184, 60, 80, 98, 116, 134, 152, 170, 188, 291, 254, 298, 255, 771, 806, 450, 807,
    640, 62, 81, 99, 117, 135, 153, 171, 189, 257, 251, 232, 769, 772, 289, 451, 870, 426, 999, 1856, 64, 82, 100, 118,
    136, 154, 172, 190, 260, 230, 293, 252, 774, 770, 266, 418, 930, 270, 1123, 65, 83, 101, 119, 137, 155, 173, 191, 267,
    236, 320, 258, 399, 391, 802, 482, 268, 965, 1155,
};
#define ITEM_OFF(p) c_off[p]
#define ITEM(i) c_items[i]

__device__ __align__(1024) bf16 g_kvo[3 * 2048 * 4096];
__device__ __align__(1024) bf16 g_ht[2048 * 2048];
__device__ __align__(1024) uint8_t g_m[9 * 32768];
__device__ __align__(1024) uint8_t g_f[8 * 49152];
__device__ __align__(1024) uint32_t g_km[64 * 32 * 512];
__device__ __align__(1024) uint32_t g_vmt[64 * 32 * 512];
__device__ __align__(1024) float2 g_agg[8 * 1024];
__device__ __align__(1024) float4 g_coef[1024];
__device__ __align__(1024) uint32_t g_cntl[128 * 32];
#define g_cnt(i) g_cntl[(i) * 32]
__device__ __align__(1024) uint32_t g_hint[6144 + 160];
#define SSTAMP(i, cond)
#define PROF(i)
#define GT_EDGE(o)
constexpr int M_SLOT = 32768, F_SLOT = 49152;

constexpr int STAGE = 49152, NSTAGE = 4;
constexpr int S_STG = NSTAGE * STAGE;
constexpr int S_BAR = S_STG + 32768;
constexpr int B_FULL = S_BAR, B_EMPTY = S_BAR + 32, B_RESUME = S_BAR + 64, B_KVFULL = S_BAR + 72, B_GO = S_BAR + 88, B_K = S_BAR + 96, B_PERS = S_BAR + 104, B_INIT = S_BAR + 112, B_RELA = S_BAR + 120, B_V = S_BAR + 128, B_WO = S_BAR + 136,
              B_SFULL = S_BAR + 144, B_SFREE = S_BAR + 160, S_DESC = S_BAR + 176, S_REDO = S_BAR + 256 + 512 + 64, S_EPOCH = S_BAR + 208, B_RELB = S_BAR + 216, B_KVGO = S_BAR + 224, S_DEP = S_BAR + 240, S_CUR = S_BAR + 244, S_TAIL = S_BAR + 248, S_CTA = S_BAR + 252;
constexpr int S_COEF = S_BAR + 256 + 512, S_TOTAL = S_COEF + 1024;
constexpr int S_W1 = 0;
constexpr int S_O = 24 * 4096, S_VL = S_O + 2048, S_MX = 25 * 4096, S_SC = S_MX + 64, S_SUM = S_MX + 128;
constexpr int S_KL = 26 * 4096;
constexpr int S_W2 = 27 * 4096;
constexpr int S_KV = S_W2 + 65536;
constexpr int S_P1 = S_W2 + 98304;
constexpr int S_QX = S_P1 + 16384;
constexpr int S_SX = S_QX + 2048;
static_assert(S_SX + 1280 <= S_BAR, "chain smem overlaps barriers");
constexpr int NR = 40, NS = 64 - NR;

__device__ __forceinline__ uint32_t logical_cta(uint32_t b) {
    const uint32_t c = b / 6, r = b - c * 6;
    return gridDim.x != 96 ? 96 + b : ((r >> 1) + (c >= 8) + (c >= 15)) % 3 * 32 + c * 2 + (r & 1);
}
__device__ __forceinline__ uint32_t cluster_rank() { uint32_t r; asm("mov.u32 %0, %%cluster_ctarank;" : "=r"(r)); return r; }
__device__ __forceinline__ uint16_t pair_mask() { return (uint16_t)(3u << (cluster_rank() & 6)); }
__device__ __forceinline__ void spin_fault() { asm volatile("st.global.u32 [%0], 0;" ::"l"(0ull) : "memory"); }
__device__ __forceinline__ uint32_t smem_u32(const void* p) { return (uint32_t)__cvta_generic_to_shared(p); }
__device__ __forceinline__ uint32_t opq(uint32_t x, int lane) { return __shfl_sync(0xffffffffu, x, lane); }
__device__ __forceinline__ uint32_t mapa(uint32_t a, uint32_t r) { uint32_t d; asm volatile("mapa.shared::cluster.u32 %0, %1, %2;" : "=r"(d) : "r"(a), "r"(r)); return d; }
__device__ __forceinline__ void mma16816(float* d, uint32_t a0, uint32_t a1, uint32_t a2, uint32_t a3, uint32_t b0, uint32_t b1) {
    asm("mma.sync.aligned.m16n8k16.row.col.f32.bf16.bf16.f32 {%0,%1,%2,%3}, {%4,%5,%6,%7}, {%8,%9}, {%0,%1,%2,%3};"
        : "+f"(d[0]), "+f"(d[1]), "+f"(d[2]), "+f"(d[3]) : "r"(a0), "r"(a1), "r"(a2), "r"(a3), "r"(b0), "r"(b1));
}
__device__ __forceinline__ void mma1688(float* d, uint32_t a0, uint32_t a1, uint32_t b0) {
    asm("mma.sync.aligned.m16n8k8.row.col.f32.bf16.bf16.f32 {%0,%1,%2,%3}, {%4,%5}, {%6}, {%0,%1,%2,%3};"
        : "+f"(d[0]), "+f"(d[1]), "+f"(d[2]), "+f"(d[3]) : "r"(a0), "r"(a1), "r"(b0));
}
__device__ __forceinline__ void ldsm4(uint32_t* r, uint32_t a) {
    asm volatile("ldmatrix.sync.aligned.m8n8.x4.shared.b16 {%0,%1,%2,%3}, [%4];" : "=r"(r[0]), "=r"(r[1]), "=r"(r[2]), "=r"(r[3]) : "r"(a));
}
__device__ __forceinline__ void ldsm4t(uint32_t* r, uint32_t a) {
    asm volatile("ldmatrix.sync.aligned.m8n8.x4.trans.shared.b16 {%0,%1,%2,%3}, [%4];" : "=r"(r[0]), "=r"(r[1]), "=r"(r[2]), "=r"(r[3]) : "r"(a));
}
__device__ __forceinline__ void stsm4(uint32_t a, uint32_t r0, uint32_t r1, uint32_t r2, uint32_t r3) {
    asm volatile("stmatrix.sync.aligned.m8n8.x4.shared.b16 [%0], {%1,%2,%3,%4};" ::"r"(a), "r"(r0), "r"(r1), "r"(r2), "r"(r3) : "memory");
}
__device__ __forceinline__ void stsm4t(uint32_t a, uint32_t r0, uint32_t r1, uint32_t r2, uint32_t r3) {
    asm volatile("stmatrix.sync.aligned.m8n8.x4.trans.shared.b16 [%0], {%1,%2,%3,%4};" ::"r"(a), "r"(r0), "r"(r1), "r"(r2), "r"(r3) : "memory");
}
__device__ __forceinline__ uint32_t pack2(float lo, float hi) { uint32_t d; asm("cvt.rn.bf16x2.f32 %0, %1, %2;" : "=r"(d) : "f"(hi), "f"(lo)); return d; }
__device__ __forceinline__ float bf_lo(uint32_t u) { return __uint_as_float(u << 16); }
__device__ __forceinline__ float bf_hi(uint32_t u) { return __uint_as_float(u & 0xffff0000u); }
__device__ __forceinline__ uint32_t hmul2(uint32_t a, uint32_t b) { uint32_t d; asm("mul.rn.bf16x2 %0, %1, %2;" : "=r"(d) : "r"(a), "r"(b)); return d; }
__device__ __forceinline__ float ex2(float x) { float y; asm("ex2.approx.ftz.f32 %0, %1;" : "=f"(y) : "f"(x)); return y; }
__device__ __forceinline__ float rcp(float x) { float y; asm("rcp.approx.ftz.f32 %0, %1;" : "=f"(y) : "f"(x)); return y; }
__device__ __forceinline__ void st_relaxed4(const void* p, uint32_t a, uint32_t b, uint32_t c, uint32_t d) {
    asm volatile("{\n.reg .b128 t;\nmov.b128 t, {%1,%2,%3,%4};\nst.relaxed.gpu.global.b128 [%0], t;\n}" ::"l"(p), "r"(a), "r"(b), "r"(c), "r"(d) : "memory");
}
__device__ __forceinline__ void st_relaxed2(const void* p, uint32_t a, uint32_t b) {
    asm volatile("{\n.reg .b64 t;\nmov.b64 t, {%1,%2};\nst.relaxed.gpu.global.b64 [%0], t;\n}" ::"l"(p), "r"(a), "r"(b) : "memory");
}
__device__ __forceinline__ void ld_relaxed2_if(uint32_t& a, uint32_t& b, const void* p, bool on) {
    asm volatile("{\n.reg .pred P;\n.reg .b64 t;\nsetp.ne.u32 P, %3, 0;\nmov.b64 t, {%0,%1};\n@P ld.relaxed.gpu.global.b64 t, [%2];\nmov.b64 {%0,%1}, t;\n}" : "+r"(a), "+r"(b) : "l"(p), "r"((uint32_t)on) : "memory");
}
__device__ __forceinline__ uint32_t ld_relaxed1(const void* p) { uint32_t v; asm volatile("ld.relaxed.gpu.global.u32 %0, [%1];" : "=r"(v) : "l"(p) : "memory"); return v; }
__device__ __forceinline__ void st_relaxed1(const void* p, uint32_t v) { asm volatile("st.relaxed.gpu.global.u32 [%0], %1;" ::"l"(p), "r"(v) : "memory"); }
__device__ __forceinline__ uint32_t ld_acquire(const void* p) { uint32_t v; asm volatile("ld.acquire.gpu.global.u32 %0, [%1];" : "=r"(v) : "l"(p) : "memory"); return v; }
__device__ __forceinline__ void red_release(void* p) { asm volatile("red.release.gpu.global.add.u32 [%0], 1;" ::"l"(p) : "memory"); }
__device__ __forceinline__ void st_stream2(float* p, float a, float b) { asm volatile("st.global.cs.v2.f32 [%0], {%1, %2};" ::"l"(p), "f"(a), "f"(b) : "memory"); }
__device__ __forceinline__ void fence_acquire() { asm volatile("fence.acquire.gpu;" ::: "memory"); }
__device__ __forceinline__ void fence_release() { asm volatile("fence.release.gpu;" ::: "memory"); }
__device__ __forceinline__ void fence_async() {  asm volatile("fence.proxy.async.global;" ::: "memory"); }
__device__ __forceinline__ void fence_async_smem() { asm volatile("fence.proxy.async.shared::cta;" ::: "memory"); }
__device__ __forceinline__ void wait_count(const uint32_t* p, uint32_t target) {
    int n = 0;
    while ((int32_t)(ld_acquire(p) - target) < 0) { __nanosleep(POLL); if (++n > SPIN_LIMIT) spin_fault(); }
}
__device__ __forceinline__ void bar_sync(int id, int n) { asm volatile("bar.sync %0, %1;" ::"r"(id), "r"(n) : "memory"); }
__device__ __forceinline__ void bar_arrive(int id, int n) { asm volatile("bar.arrive %0, %1;" ::"r"(id), "r"(n) : "memory"); }
__device__ __forceinline__ bool bar_and(int id, bool v) {
    uint32_t r;
    asm volatile("{\n.reg .pred P, Q;\nsetp.ne.u32 Q, %2, 0;\nbar.red.and.pred P, %1, 128, Q;\nselp.u32 %0, 1, 0, P;\n}" : "=r"(r) : "r"(id), "r"((uint32_t)v) : "memory");
    return r;
}
__device__ __forceinline__ void lds128(uint32_t* v, uint32_t a) { asm volatile("ld.shared.v4.b32 {%0,%1,%2,%3}, [%4];" : "=r"(v[0]), "=r"(v[1]), "=r"(v[2]), "=r"(v[3]) : "r"(a) : "memory"); }
__device__ __forceinline__ uint32_t lds32(uint32_t a) { uint32_t v; asm volatile("ld.shared.b32 %0, [%1];" : "=r"(v) : "r"(a) : "memory"); return v; }
__device__ __forceinline__ void lds64f(float* v, uint32_t a) { asm volatile("ld.shared.v2.f32 {%0,%1}, [%2];" : "=f"(v[0]), "=f"(v[1]) : "r"(a) : "memory"); }
__device__ __forceinline__ void sts128(uint32_t a, const uint32_t* v) { asm volatile("st.shared.v4.b32 [%0], {%1,%2,%3,%4};" ::"r"(a), "r"(v[0]), "r"(v[1]), "r"(v[2]), "r"(v[3]) : "memory"); }
__device__ __forceinline__ void sts64(uint32_t a, uint32_t x, uint32_t y) { asm volatile("st.shared.v2.b32 [%0], {%1,%2};" ::"r"(a), "r"(x), "r"(y) : "memory"); }
__device__ __forceinline__ void sts32(uint32_t a, uint32_t x) { asm volatile("st.shared.b32 [%0], %1;" ::"r"(a), "r"(x) : "memory"); }
__device__ __forceinline__ bool mbar_try(uint32_t b, uint32_t par) {
    uint32_t ok;
    asm volatile("{\n.reg .pred P;\nmbarrier.try_wait.parity.shared::cta.b64 P, [%1], %2;\nselp.u32 %0, 1, 0, P;\n}" : "=r"(ok) : "r"(b), "r"(par) : "memory");
    return ok;
}
__device__ __forceinline__ bool mbar_test(uint32_t b, uint32_t par) {
    uint32_t ok;
    asm volatile("{\n.reg .pred P;\nmbarrier.test_wait.parity.shared::cta.b64 P, [%1], %2;\nselp.u32 %0, 1, 0, P;\n}" : "=r"(ok) : "r"(b), "r"(par) : "memory");
    return ok;
}
__device__ __forceinline__ void mbar_wait(uint32_t b, uint32_t par) { int n = 0; while (!mbar_try(b, par)) { if (++n > SPIN_LIMIT) spin_fault(); } }
__device__ __forceinline__ void mbar_init(uint32_t b, uint32_t n) { asm volatile("mbarrier.init.shared::cta.b64 [%0], %1;" ::"r"(b), "r"(n) : "memory"); }
__device__ __forceinline__ void mbar_expect(uint32_t b, uint32_t bytes) { asm volatile("mbarrier.arrive.expect_tx.shared::cta.b64 _, [%0], %1;" ::"r"(b), "r"(bytes) : "memory"); }
__device__ __forceinline__ void mbar_arrive(uint32_t b) { asm volatile("mbarrier.arrive.shared::cta.b64 _, [%0];" ::"r"(b) : "memory"); }
__device__ __forceinline__ void mbar_arrive_cluster(uint32_t b) { asm volatile("mbarrier.arrive.shared::cluster.b64 _, [%0];" ::"r"(b) : "memory"); }
__device__ __forceinline__ void st_async1(uint32_t a, uint32_t x, uint32_t bar) {
    asm volatile("st.async.weak.shared::cluster.mbarrier::complete_tx::bytes.b32 [%0], %1, [%2];" ::"r"(a), "r"(x), "r"(bar) : "memory");
}
__device__ __forceinline__ void st_async2(uint32_t a, uint32_t x, uint32_t y, uint32_t bar) {
    asm volatile("st.async.weak.shared::cluster.mbarrier::complete_tx::bytes.v2.b32 [%0], {%1,%2}, [%3];" ::"r"(a), "r"(x), "r"(y), "r"(bar) : "memory");
}
__device__ __forceinline__ void cluster_sync() { asm volatile("barrier.cluster.arrive.aligned;\nbarrier.cluster.wait.aligned;" ::: "memory"); }
__device__ __forceinline__ void tma2d(uint32_t dst, const CUtensorMap* m, int c0, int c1, uint32_t bar) {
    asm volatile("cp.async.bulk.tensor.2d.shared::cluster.global.mbarrier::complete_tx::bytes [%0], [%1, {%2, %3}], [%4];" ::"r"(dst), "l"(m), "r"(c0), "r"(c1), "r"(bar) : "memory");
}
__device__ __forceinline__ void tma2d_mc(uint32_t dst, const CUtensorMap* m, int c0, int c1, uint32_t bar) {
    asm volatile("cp.async.bulk.tensor.2d.shared::cluster.global.mbarrier::complete_tx::bytes.multicast::cluster [%0], [%1, {%2, %3}], [%4], %5;" ::"r"(dst), "l"(m), "r"(c0), "r"(c1), "r"(bar), "h"(pair_mask()) : "memory");
}
__device__ __forceinline__ void tma3d(uint32_t dst, const CUtensorMap* m, int c0, int c1, int c2, uint32_t bar) {
    asm volatile("cp.async.bulk.tensor.3d.shared::cluster.global.mbarrier::complete_tx::bytes [%0], [%1, {%2, %3, %4}], [%5];" ::"r"(dst), "l"(m), "r"(c0), "r"(c1), "r"(c2), "r"(bar) : "memory");
}
__device__ __forceinline__ void tma3d_mc(uint32_t dst, const CUtensorMap* m, int c0, int c1, int c2, uint32_t bar) {
    asm volatile("cp.async.bulk.tensor.3d.shared::cluster.global.mbarrier::complete_tx::bytes.multicast::cluster [%0], [%1, {%2, %3, %4}], [%5], %6;" ::"r"(dst), "l"(m), "r"(c0), "r"(c1), "r"(c2), "r"(bar), "h"(pair_mask()) : "memory");
}
__device__ __forceinline__ void tma4d(uint32_t dst, const CUtensorMap* m, int c0, int c3, uint32_t bar) {
    asm volatile("cp.async.bulk.tensor.4d.shared::cluster.global.mbarrier::complete_tx::bytes [%0], [%1, {%2, 0, 0, %3}], [%4];" ::"r"(dst), "l"(m), "r"(c0), "r"(c3), "r"(bar) : "memory");
}
__device__ __forceinline__ void tma4d_mc(uint32_t dst, const CUtensorMap* m, int c0, int c3, uint32_t bar) {
    asm volatile("cp.async.bulk.tensor.4d.shared::cluster.global.mbarrier::complete_tx::bytes.multicast::cluster [%0], [%1, {%2, 0, 0, %3}], [%4], %5;" ::"r"(dst), "l"(m), "r"(c0), "r"(c3), "r"(bar), "h"(pair_mask()) : "memory");
}
__device__ __forceinline__ void map_prefetch(const CUtensorMap* m) { asm volatile("prefetch.tensormap [%0];" ::"l"(m) : "memory"); }
__device__ __forceinline__ void bulk_g2s(uint32_t dst, const void* src, uint32_t bytes, uint32_t bar) {
    asm volatile("cp.async.bulk.shared::cluster.global.mbarrier::complete_tx::bytes [%0], [%1], %2, [%3];" ::"r"(dst), "l"(src), "r"(bytes), "r"(bar) : "memory");
}
__device__ __forceinline__ void bulk_s2g(void* dst, uint32_t src, uint32_t bytes) {
    asm volatile("cp.async.bulk.global.shared::cta.bulk_group [%0], [%1], %2;" ::"l"(dst), "r"(src), "r"(bytes) : "memory");
}
__device__ __forceinline__ void tma_store2d(const CUtensorMap* m, int c0, int c1, uint32_t src) {
    asm volatile("cp.async.bulk.tensor.2d.global.shared::cta.bulk_group [%0, {%1, %2}], [%3];" ::"l"(m), "r"(c0), "r"(c1), "r"(src) : "memory");
}
__device__ __forceinline__ void bulk_commit() { asm volatile("cp.async.bulk.commit_group;" ::: "memory"); }
__device__ __forceinline__ void bulk_wait_read() { asm volatile("cp.async.bulk.wait_group.read 0;" ::: "memory"); }
__device__ __forceinline__ void bulk_wait_all() { asm volatile("cp.async.bulk.wait_group 0;" ::: "memory"); }
__device__ __forceinline__ uint64_t mkdesc(uint32_t addr, uint32_t lbo, uint32_t sbo, uint32_t swz) {
    return (uint64_t)((addr & 0x3FFFF) >> 4) | ((uint64_t)(lbo >> 4) << 16) | ((uint64_t)(sbo >> 4) << 32) | ((uint64_t)swz << 62);
}
__device__ __forceinline__ void wg_fence() { asm volatile("wgmma.fence.sync.aligned;" ::: "memory"); }
__device__ __forceinline__ void wg_commit() { asm volatile("wgmma.commit_group.sync.aligned;" ::: "memory"); }
template <int N> __device__ __forceinline__ void wg_wait() { asm volatile("wgmma.wait_group.sync.aligned %0;" ::"n"(N) : "memory"); }
template <typename T> __device__ __forceinline__ void pin_ptr(T*& p) { asm volatile("" : "+l"(p)); }
template <int N> __device__ __forceinline__ void pin(uint32_t* d) {
#pragma unroll
    for (int i = 0; i < N; i++) asm volatile("" : "+r"(d[i])::"memory");
}
template <int N> __device__ __forceinline__ void pin(float* d) {
#pragma unroll
    for (int i = 0; i < N; i++) asm volatile("" : "+f"(d[i])::"memory");
}

template <int TA, int TB>
__device__ __forceinline__ void wgmma_ss256(float* d, uint64_t da, uint64_t db) {
    asm volatile("wgmma.mma_async.sync.aligned.m64n256k16.f32.bf16.bf16 "
        "{%0, %1, %2, %3, %4, %5, %6, %7, %8, %9, %10, %11, %12, %13, %14, %15, %16, %17, %18, %19, %20, %21, %22, %23, %24, %25, %26, %27, %28, %29, %30, %31, %32, %33, %34, %35, %36, %37, %38, %39, %40, %41, %42, %43, %44, %45, %46, %47, %48, %49, %50, %51, %52, %53, %54, %55, %56, %57, %58, %59, %60, %61, %62, %63, %64, %65, %66, %67, %68, %69, %70, %71, %72, %73, %74, %75, %76, %77, %78, %79, %80, %81, %82, %83, %84, %85, %86, %87, %88, %89, %90, %91, %92, %93, %94, %95, %96, %97, %98, %99, %100, %101, %102, %103, %104, %105, %106, %107, %108, %109, %110, %111, %112, %113, %114, %115, %116, %117, %118, %119, %120, %121, %122, %123, %124, %125, %126, %127}, %128, %129, 1, 1, 1, %130, %131;"
        : "+f"(d[0]), "+f"(d[1]), "+f"(d[2]), "+f"(d[3]), "+f"(d[4]), "+f"(d[5]), "+f"(d[6]), "+f"(d[7]), "+f"(d[8]), "+f"(d[9]), "+f"(d[10]), "+f"(d[11]), "+f"(d[12]), "+f"(d[13]), "+f"(d[14]), "+f"(d[15]), "+f"(d[16]), "+f"(d[17]), "+f"(d[18]), "+f"(d[19]), "+f"(d[20]), "+f"(d[21]), "+f"(d[22]), "+f"(d[23]), "+f"(d[24]), "+f"(d[25]), "+f"(d[26]), "+f"(d[27]), "+f"(d[28]), "+f"(d[29]), "+f"(d[30]), "+f"(d[31]), "+f"(d[32]), "+f"(d[33]), "+f"(d[34]), "+f"(d[35]), "+f"(d[36]), "+f"(d[37]), "+f"(d[38]), "+f"(d[39]), "+f"(d[40]), "+f"(d[41]), "+f"(d[42]), "+f"(d[43]), "+f"(d[44]), "+f"(d[45]), "+f"(d[46]), "+f"(d[47]), "+f"(d[48]), "+f"(d[49]), "+f"(d[50]), "+f"(d[51]), "+f"(d[52]), "+f"(d[53]), "+f"(d[54]), "+f"(d[55]), "+f"(d[56]), "+f"(d[57]), "+f"(d[58]), "+f"(d[59]), "+f"(d[60]), "+f"(d[61]), "+f"(d[62]), "+f"(d[63]), "+f"(d[64]), "+f"(d[65]), "+f"(d[66]), "+f"(d[67]), "+f"(d[68]), "+f"(d[69]), "+f"(d[70]), "+f"(d[71]), "+f"(d[72]), "+f"(d[73]), "+f"(d[74]), "+f"(d[75]), "+f"(d[76]), "+f"(d[77]), "+f"(d[78]), "+f"(d[79]), "+f"(d[80]), "+f"(d[81]), "+f"(d[82]), "+f"(d[83]), "+f"(d[84]), "+f"(d[85]), "+f"(d[86]), "+f"(d[87]), "+f"(d[88]), "+f"(d[89]), "+f"(d[90]), "+f"(d[91]), "+f"(d[92]), "+f"(d[93]), "+f"(d[94]), "+f"(d[95]), "+f"(d[96]), "+f"(d[97]), "+f"(d[98]), "+f"(d[99]), "+f"(d[100]), "+f"(d[101]), "+f"(d[102]), "+f"(d[103]), "+f"(d[104]), "+f"(d[105]), "+f"(d[106]), "+f"(d[107]), "+f"(d[108]), "+f"(d[109]), "+f"(d[110]), "+f"(d[111]), "+f"(d[112]), "+f"(d[113]), "+f"(d[114]), "+f"(d[115]), "+f"(d[116]), "+f"(d[117]), "+f"(d[118]), "+f"(d[119]), "+f"(d[120]), "+f"(d[121]), "+f"(d[122]), "+f"(d[123]), "+f"(d[124]), "+f"(d[125]), "+f"(d[126]), "+f"(d[127])
        : "l"(da), "l"(db), "n"(TA), "n"(TB));
}
template <int TA, int TB>
__device__ __forceinline__ void wgmma_ss256_first(float* d, uint64_t da, uint64_t db) {
    asm volatile("wgmma.mma_async.sync.aligned.m64n256k16.f32.bf16.bf16 "
        "{%0, %1, %2, %3, %4, %5, %6, %7, %8, %9, %10, %11, %12, %13, %14, %15, %16, %17, %18, %19, %20, %21, %22, %23, %24, %25, %26, %27, %28, %29, %30, %31, %32, %33, %34, %35, %36, %37, %38, %39, %40, %41, %42, %43, %44, %45, %46, %47, %48, %49, %50, %51, %52, %53, %54, %55, %56, %57, %58, %59, %60, %61, %62, %63, %64, %65, %66, %67, %68, %69, %70, %71, %72, %73, %74, %75, %76, %77, %78, %79, %80, %81, %82, %83, %84, %85, %86, %87, %88, %89, %90, %91, %92, %93, %94, %95, %96, %97, %98, %99, %100, %101, %102, %103, %104, %105, %106, %107, %108, %109, %110, %111, %112, %113, %114, %115, %116, %117, %118, %119, %120, %121, %122, %123, %124, %125, %126, %127}, %128, %129, 0, 1, 1, %130, %131;"
        : "=f"(d[0]), "=f"(d[1]), "=f"(d[2]), "=f"(d[3]), "=f"(d[4]), "=f"(d[5]), "=f"(d[6]), "=f"(d[7]), "=f"(d[8]), "=f"(d[9]), "=f"(d[10]), "=f"(d[11]), "=f"(d[12]), "=f"(d[13]), "=f"(d[14]), "=f"(d[15]), "=f"(d[16]), "=f"(d[17]), "=f"(d[18]), "=f"(d[19]), "=f"(d[20]), "=f"(d[21]), "=f"(d[22]), "=f"(d[23]), "=f"(d[24]), "=f"(d[25]), "=f"(d[26]), "=f"(d[27]), "=f"(d[28]), "=f"(d[29]), "=f"(d[30]), "=f"(d[31]), "=f"(d[32]), "=f"(d[33]), "=f"(d[34]), "=f"(d[35]), "=f"(d[36]), "=f"(d[37]), "=f"(d[38]), "=f"(d[39]), "=f"(d[40]), "=f"(d[41]), "=f"(d[42]), "=f"(d[43]), "=f"(d[44]), "=f"(d[45]), "=f"(d[46]), "=f"(d[47]), "=f"(d[48]), "=f"(d[49]), "=f"(d[50]), "=f"(d[51]), "=f"(d[52]), "=f"(d[53]), "=f"(d[54]), "=f"(d[55]), "=f"(d[56]), "=f"(d[57]), "=f"(d[58]), "=f"(d[59]), "=f"(d[60]), "=f"(d[61]), "=f"(d[62]), "=f"(d[63]), "=f"(d[64]), "=f"(d[65]), "=f"(d[66]), "=f"(d[67]), "=f"(d[68]), "=f"(d[69]), "=f"(d[70]), "=f"(d[71]), "=f"(d[72]), "=f"(d[73]), "=f"(d[74]), "=f"(d[75]), "=f"(d[76]), "=f"(d[77]), "=f"(d[78]), "=f"(d[79]), "=f"(d[80]), "=f"(d[81]), "=f"(d[82]), "=f"(d[83]), "=f"(d[84]), "=f"(d[85]), "=f"(d[86]), "=f"(d[87]), "=f"(d[88]), "=f"(d[89]), "=f"(d[90]), "=f"(d[91]), "=f"(d[92]), "=f"(d[93]), "=f"(d[94]), "=f"(d[95]), "=f"(d[96]), "=f"(d[97]), "=f"(d[98]), "=f"(d[99]), "=f"(d[100]), "=f"(d[101]), "=f"(d[102]), "=f"(d[103]), "=f"(d[104]), "=f"(d[105]), "=f"(d[106]), "=f"(d[107]), "=f"(d[108]), "=f"(d[109]), "=f"(d[110]), "=f"(d[111]), "=f"(d[112]), "=f"(d[113]), "=f"(d[114]), "=f"(d[115]), "=f"(d[116]), "=f"(d[117]), "=f"(d[118]), "=f"(d[119]), "=f"(d[120]), "=f"(d[121]), "=f"(d[122]), "=f"(d[123]), "=f"(d[124]), "=f"(d[125]), "=f"(d[126]), "=f"(d[127])
        : "l"(da), "l"(db), "n"(TA), "n"(TB));
}
template <int TA, int TB>
__device__ __forceinline__ void wgmma_ss128(float* d, uint64_t da, uint64_t db) {
    asm volatile("wgmma.mma_async.sync.aligned.m64n128k16.f32.bf16.bf16 "
        "{%0, %1, %2, %3, %4, %5, %6, %7, %8, %9, %10, %11, %12, %13, %14, %15, %16, %17, %18, %19, %20, %21, %22, %23, %24, %25, %26, %27, %28, %29, %30, %31, %32, %33, %34, %35, %36, %37, %38, %39, %40, %41, %42, %43, %44, %45, %46, %47, %48, %49, %50, %51, %52, %53, %54, %55, %56, %57, %58, %59, %60, %61, %62, %63}, %64, %65, 1, 1, 1, %66, %67;"
        : "+f"(d[0]), "+f"(d[1]), "+f"(d[2]), "+f"(d[3]), "+f"(d[4]), "+f"(d[5]), "+f"(d[6]), "+f"(d[7]), "+f"(d[8]), "+f"(d[9]), "+f"(d[10]), "+f"(d[11]), "+f"(d[12]), "+f"(d[13]), "+f"(d[14]), "+f"(d[15]), "+f"(d[16]), "+f"(d[17]), "+f"(d[18]), "+f"(d[19]), "+f"(d[20]), "+f"(d[21]), "+f"(d[22]), "+f"(d[23]), "+f"(d[24]), "+f"(d[25]), "+f"(d[26]), "+f"(d[27]), "+f"(d[28]), "+f"(d[29]), "+f"(d[30]), "+f"(d[31]), "+f"(d[32]), "+f"(d[33]), "+f"(d[34]), "+f"(d[35]), "+f"(d[36]), "+f"(d[37]), "+f"(d[38]), "+f"(d[39]), "+f"(d[40]), "+f"(d[41]), "+f"(d[42]), "+f"(d[43]), "+f"(d[44]), "+f"(d[45]), "+f"(d[46]), "+f"(d[47]), "+f"(d[48]), "+f"(d[49]), "+f"(d[50]), "+f"(d[51]), "+f"(d[52]), "+f"(d[53]), "+f"(d[54]), "+f"(d[55]), "+f"(d[56]), "+f"(d[57]), "+f"(d[58]), "+f"(d[59]), "+f"(d[60]), "+f"(d[61]), "+f"(d[62]), "+f"(d[63])
        : "l"(da), "l"(db), "n"(TA), "n"(TB));
}
template <int TA, int TB>
__device__ __forceinline__ void wgmma_ss128_first(float* d, uint64_t da, uint64_t db) {
    asm volatile("wgmma.mma_async.sync.aligned.m64n128k16.f32.bf16.bf16 "
        "{%0, %1, %2, %3, %4, %5, %6, %7, %8, %9, %10, %11, %12, %13, %14, %15, %16, %17, %18, %19, %20, %21, %22, %23, %24, %25, %26, %27, %28, %29, %30, %31, %32, %33, %34, %35, %36, %37, %38, %39, %40, %41, %42, %43, %44, %45, %46, %47, %48, %49, %50, %51, %52, %53, %54, %55, %56, %57, %58, %59, %60, %61, %62, %63}, %64, %65, 0, 1, 1, %66, %67;"
        : "=f"(d[0]), "=f"(d[1]), "=f"(d[2]), "=f"(d[3]), "=f"(d[4]), "=f"(d[5]), "=f"(d[6]), "=f"(d[7]), "=f"(d[8]), "=f"(d[9]), "=f"(d[10]), "=f"(d[11]), "=f"(d[12]), "=f"(d[13]), "=f"(d[14]), "=f"(d[15]), "=f"(d[16]), "=f"(d[17]), "=f"(d[18]), "=f"(d[19]), "=f"(d[20]), "=f"(d[21]), "=f"(d[22]), "=f"(d[23]), "=f"(d[24]), "=f"(d[25]), "=f"(d[26]), "=f"(d[27]), "=f"(d[28]), "=f"(d[29]), "=f"(d[30]), "=f"(d[31]), "=f"(d[32]), "=f"(d[33]), "=f"(d[34]), "=f"(d[35]), "=f"(d[36]), "=f"(d[37]), "=f"(d[38]), "=f"(d[39]), "=f"(d[40]), "=f"(d[41]), "=f"(d[42]), "=f"(d[43]), "=f"(d[44]), "=f"(d[45]), "=f"(d[46]), "=f"(d[47]), "=f"(d[48]), "=f"(d[49]), "=f"(d[50]), "=f"(d[51]), "=f"(d[52]), "=f"(d[53]), "=f"(d[54]), "=f"(d[55]), "=f"(d[56]), "=f"(d[57]), "=f"(d[58]), "=f"(d[59]), "=f"(d[60]), "=f"(d[61]), "=f"(d[62]), "=f"(d[63])
        : "l"(da), "l"(db), "n"(TA), "n"(TB));
}
template <int TB>
__device__ __forceinline__ void wgmma_rs128(float* d, const uint32_t* a, uint64_t db, uint32_t acc) {
    asm volatile("{\n.reg .pred P;\nsetp.ne.u32 P, %69, 0;\nwgmma.mma_async.sync.aligned.m64n128k16.f32.bf16.bf16 "
        "{%0, %1, %2, %3, %4, %5, %6, %7, %8, %9, %10, %11, %12, %13, %14, %15, %16, %17, %18, %19, %20, %21, %22, %23, %24, %25, %26, %27, %28, %29, %30, %31, %32, %33, %34, %35, %36, %37, %38, %39, %40, %41, %42, %43, %44, %45, %46, %47, %48, %49, %50, %51, %52, %53, %54, %55, %56, %57, %58, %59, %60, %61, %62, %63}, {%64, %65, %66, %67}, %68, P, 1, 1, %70;\n}"
        : "+f"(d[0]), "+f"(d[1]), "+f"(d[2]), "+f"(d[3]), "+f"(d[4]), "+f"(d[5]), "+f"(d[6]), "+f"(d[7]), "+f"(d[8]), "+f"(d[9]), "+f"(d[10]), "+f"(d[11]), "+f"(d[12]), "+f"(d[13]), "+f"(d[14]), "+f"(d[15]), "+f"(d[16]), "+f"(d[17]), "+f"(d[18]), "+f"(d[19]), "+f"(d[20]), "+f"(d[21]), "+f"(d[22]), "+f"(d[23]), "+f"(d[24]), "+f"(d[25]), "+f"(d[26]), "+f"(d[27]), "+f"(d[28]), "+f"(d[29]), "+f"(d[30]), "+f"(d[31]), "+f"(d[32]), "+f"(d[33]), "+f"(d[34]), "+f"(d[35]), "+f"(d[36]), "+f"(d[37]), "+f"(d[38]), "+f"(d[39]), "+f"(d[40]), "+f"(d[41]), "+f"(d[42]), "+f"(d[43]), "+f"(d[44]), "+f"(d[45]), "+f"(d[46]), "+f"(d[47]), "+f"(d[48]), "+f"(d[49]), "+f"(d[50]), "+f"(d[51]), "+f"(d[52]), "+f"(d[53]), "+f"(d[54]), "+f"(d[55]), "+f"(d[56]), "+f"(d[57]), "+f"(d[58]), "+f"(d[59]), "+f"(d[60]), "+f"(d[61]), "+f"(d[62]), "+f"(d[63])
        : "r"(a[0]), "r"(a[1]), "r"(a[2]), "r"(a[3]), "l"(db), "r"(acc), "n"(TB));
}
template <int TB>
__device__ __forceinline__ void wgmma_rs64(float* d, const uint32_t* a, uint64_t db, uint32_t acc) {
    asm volatile("{\n.reg .pred P;\nsetp.ne.u32 P, %37, 0;\nwgmma.mma_async.sync.aligned.m64n64k16.f32.bf16.bf16 "
        "{%0, %1, %2, %3, %4, %5, %6, %7, %8, %9, %10, %11, %12, %13, %14, %15, %16, %17, %18, %19, %20, %21, %22, %23, %24, %25, %26, %27, %28, %29, %30, %31}, {%32, %33, %34, %35}, %36, P, 1, 1, %38;\n}"
        : "+f"(d[0]), "+f"(d[1]), "+f"(d[2]), "+f"(d[3]), "+f"(d[4]), "+f"(d[5]), "+f"(d[6]), "+f"(d[7]), "+f"(d[8]), "+f"(d[9]), "+f"(d[10]), "+f"(d[11]), "+f"(d[12]), "+f"(d[13]), "+f"(d[14]), "+f"(d[15]), "+f"(d[16]), "+f"(d[17]), "+f"(d[18]), "+f"(d[19]), "+f"(d[20]), "+f"(d[21]), "+f"(d[22]), "+f"(d[23]), "+f"(d[24]), "+f"(d[25]), "+f"(d[26]), "+f"(d[27]), "+f"(d[28]), "+f"(d[29]), "+f"(d[30]), "+f"(d[31])
        : "r"(a[0]), "r"(a[1]), "r"(a[2]), "r"(a[3]), "l"(db), "r"(acc), "n"(TB));
}
template <int TB>
__device__ __forceinline__ void wgmma_rs16(float* d, const uint32_t* a, uint64_t db, uint32_t acc) {
    asm volatile("{\n.reg .pred P;\nsetp.ne.u32 P, %13, 0;\nwgmma.mma_async.sync.aligned.m64n16k16.f32.bf16.bf16 "
        "{%0, %1, %2, %3, %4, %5, %6, %7}, {%8, %9, %10, %11}, %12, P, 1, 1, %14;\n}"
        : "+f"(d[0]), "+f"(d[1]), "+f"(d[2]), "+f"(d[3]), "+f"(d[4]), "+f"(d[5]), "+f"(d[6]), "+f"(d[7])
        : "r"(a[0]), "r"(a[1]), "r"(a[2]), "r"(a[3]), "l"(db), "r"(acc), "n"(TB));
}

__device__ __forceinline__ uint32_t delay_loop(int n, uint32_t x0) {
    uint32_t z;
    asm volatile("{\n.reg .pred P;\n.reg .u32 c, x;\nmov.u32 c, %1;\nmov.u32 x, %2;\nDL: mad.lo.u32 x, x, 1664525, 1013904223;\nadd.u32 c, c, -1;\nsetp.gt.s32 P, c, 0;\n@P bra DL;\n"
                 "setp.eq.u32 P, x, 0x7fffffff;\nselp.u32 %0, 16, 0, P;\n}" : "=r"(z) : "r"(n), "r"(x0) : "memory");
    return z;
}
__device__ __forceinline__ uint32_t gtime() { uint32_t t; asm volatile("mov.u32 %0, %%globaltimer_lo;" : "=r"(t)); return t; }
__device__ __forceinline__ void wait_time(uint32_t t, uint32_t sb) { while ((int32_t)(gtime() - t) < (int32_t)delay_loop(2, sb)) {} }
__device__ __forceinline__ uint32_t tpc_gpc(uint32_t t) { return t < 32 ? t & 7 : t < 60 ? (t - 32) % 7 + 1 : (t - 54) & 7; }
__device__ __forceinline__ uint32_t latest_stamp(const uint32_t* p, uint32_t seq, uint32_t ref, int backoff, uint32_t sb) {
    for (int n = 0;; n++) {
        uint32_t bad = 0; int32_t m = INT32_MIN;
#pragma unroll
        for (int i = 0; i < 3; i++) { const uint32_t v = ld_relaxed1(p + i * 256); bad |= (v ^ seq) & 31u; m = max(m, (int32_t)(v - (ref << 5)) >> 5); }
        if (__all_sync(0xffffffffu, bad == 0)) return ref + __reduce_max_sync(0xffffffffu, m);
        wait_time(gtime() + backoff, sb);
        if (n > SPIN_LIMIT) spin_fault();
    }
}
__device__ __forceinline__ void release_at(uint32_t t, uint32_t sb, uint32_t bar, int lane) {
    wait_time(t, sb);
    if (lane == 0) mbar_arrive(sb + bar);
}
__host__ __device__ constexpr int frag_word(int u, int f) { return (u == 0 ? 0 : u < 3 ? 3 * u - 1 : u == 3 ? 14 : 3 * u - 4) + f; }
__host__ __device__ constexpr int word_col(int e) { return ((0x32FED987CBA65410ull >> (4 * e)) & 14) * 64 + ((0x32FED987CBA65410ull >> (4 * e)) & 1) * 8; }

constexpr uint32_t CLEAR_LO = 0xFE000000u, CLEAR_HI = 0x5A7FEFEFu;
__device__ __forceinline__ void clear_slot(const Params& P, int slot, int cta, int lane) {
    const int i = cta * 2 + (lane >> 3), x = i & 63;
    if (lane < 16) st_relaxed4(P.gm + slot * M_SLOT + (x >> 1) * 1024 + (x & 1) * 256 + (i >> 7) * 512 + ((i >> 6) & 1) * 128 + (lane & 7) * 16, CLEAR_LO, CLEAR_HI, CLEAR_LO, CLEAR_HI);
    st_relaxed4(g_f + slot * F_SLOT + cta * 512 + lane * 16, 0, 0, 0, 0);
}
__device__ __forceinline__ void mem0_max(const Params& P, uint32_t sb, int tid) {
    uint32_t m = 0;
#pragma unroll
    for (int i = 0; i < 4; i++) {
        const uint4 x = __ldg((const uint4*)P.mem0 + i * 256 + tid);
        m = __vmaxu2(__vmaxu2(__vmaxu2(x.x & 0x7fff7fffu, x.y & 0x7fff7fffu), __vmaxu2(x.z & 0x7fff7fffu, x.w & 0x7fff7fffu)), m);
    }
    sts32(sb + S_COEF + (tid >> 5) * 4, __reduce_max_sync(0xffffffffu, max(m >> 16, m & 0xffffu)));
    bar_arrive(7, 288);
}
__device__ __forceinline__ uint32_t pack_mem0(const Params& P, uint32_t sb, int cta, int lane) {
    bar_sync(7, 288);
    const uint32_t e = __reduce_max_sync(0xffffffffu, lds32(sb + S_COEF + (lane & 7) * 4)) >> 7;
    if (e < 64 || e > 192) return 0x3F803F80u;
    const int i = cta * 2 + (lane >> 4), u = (i >> 5), x = i & 63, L = (i & 3) * 8 + ((lane & 15) >> 1);
    uint64_t w = 32;
#pragma unroll
    for (int f = 0; f < 3; f++) if (f < 2 || u % 3) {
        const float v = __bfloat162float(P.mem0[(L >> 2) * 1024 + word_col(frag_word(u, f)) + ((i >> 2) & 7) * 16 + (L & 3) * 2 + (lane & 1)]);
        w += (uint64_t)(int64_t)__float2int_rn(v * __uint_as_float((271 - e) << 23)) << (45 - 19 * f);
    }
    st_relaxed2(P.gm + 7 * M_SLOT + (x >> 1) * 1024 + (x & 1) * 256 + (i >> 7) * 512 + ((i >> 6) & 1) * 128 + (lane & 15) * 8, (uint32_t)w, (uint32_t)(w >> 32));
    return (e - 30) * 0x00800080u;
}
__device__ __forceinline__ void pacer(const Params& P, const uint32_t sb, const int lane) {
    constexpr uint32_t base = 2;
    int cta = lds32(sb + S_CTA);
#pragma unroll 1
    for (int i = 0; i < 8; i++) clear_slot(P, i, cta, lane);
    __syncwarp();
    if (lane == 0) { uint32_t smid; asm("mov.u32 %0, %%smid;" : "=r"(smid)); st_relaxed1(g_hint + 6144 + cta, smid >> 1); }
    sts32(sb + S_EPOCH + 4, pack_mem0(P, sb, cta, lane));
    SSTAMP(0, lane == 0)
    fence_release();
    __syncwarp();
    float rate = 0.58f;
    uint32_t c0 = 0;
#pragma unroll 1
    for (int s = -1; s < 63; s++) {
        cta = lds32(sb + S_CTA);
        const int pair = cta >> 1;
        const uint32_t ahead = s > 0 ? (uint32_t)(rate * (float)(pair >= 32 ? P.dc - P.dv : P.dc)) : 0;
        mbar_wait(sb + B_GO, s & 1);
        SSTAMP(10, lane == 0 && s == 0)
        const uint32_t t0 = gtime();
        if (lane < 4) st_relaxed1(g_hint + ((s & 1) * 4 + lane) * 768 + (cta >> 5) * 256 + (cta & 31), (t0 + ahead + (lds32(sb + S_REDO) == s ? P.extra : 0)) << 5 | ((base + s) & 31u));
        wait_time(t0 + (s < 0 ? 2000 : s == 0 && pair >= 16 ? P.ds0 : P.ds), sb);
        const uint32_t t = latest_stamp(g_hint + ((s & 1) * 4 + (pair & 3)) * 768 + lane, base + s, t0, P.back, sb);
        if (s < 0) {
            SSTAMP(2, lane == 0)
            fence_acquire();
            const uint32_t g = tpc_gpc(ld_relaxed1(g_hint + 6144 + (lane & 15) * 2));
            const uint32_t key = (__popc(__match_any_sync(0xffffffffu, g)) > 4 ? 0 : g + 1) * 16 + (lane & 15);
            const uint32_t tail = (pair & 48) + __popc(__ballot_sync(0xffffffffu, key < __shfl_sync(0xffffffffu, key, pair & 15))) / 2;
            mbar_wait(sb + B_INIT, 0);
            SSTAMP(4, lane == 0)
            sts32(sb + S_TAIL, tail);
            if (lane < 8) sts32(sb + S_SC + lane * 4, lds32(sb + S_EPOCH + 4));
            __syncwarp();
        }
        release_at(t + P.da, sb, B_RELA, lane);
        SSTAMP(11, lane == 0 && s == 0)
        release_at(t + P.db, sb, B_RELB, lane);
        {
            const uint32_t c1 = clock(), g1 = gtime();
            if (s > 1) rate += P.alpha * (__fdividef((float)(g1 - lds32(sb + S_EPOCH + 4)), (float)(c1 - c0)) - rate);
            __syncwarp();
            c0 = c1; sts32(sb + S_EPOCH + 4, g1);
        }
        if (s == 61) {
            sts32(sb + S_COEF, ITEM(ITEM_OFF(lds32(sb + S_TAIL)) + NPRE + 1) + (uint32_t)(uintptr_t)P.out);
            if (lane < M_CQ) map_prefetch(&P.tm[lane]);
        }
    }
}
__device__ __forceinline__ uint32_t xor_or(uint32_t a, uint32_t b, uint32_t t) { uint32_t d; asm("lop3.b32 %0, %1, %2, %3, 0x7E;" : "=r"(d) : "r"(a), "r"(b), "r"(t)); return d; }
__device__ __forceinline__ bool tags_ok(uint32_t bad) { return __all_sync(0xffffffffu, (bad & 1) == 0); }
#define RETRY(k)
#define RETRY_STAT(a, b)
#define UNIT_STAT(u0)
#define SFENCE() asm volatile("pmevent 1;" ::: "memory")
#define PF1 10
static_assert(NS == 24, "fragment residency");
__host__ __device__ constexpr bool in_smem(int n) { return n < 4 || n == 12 || n == 13; }
__host__ __device__ constexpr int unit_pos(int n) { return n < 4 ? n : n < 12 ? n - 4 : n < 14 ? n - 8 : n - 6; }

__host__ __device__ constexpr int fill_unit(int q) { return q < 4 ? q : q < 6 ? q + 8 : q < 14 ? q - 2 : q; }
__host__ __device__ constexpr int frag_off(int q) { return (q >> 2) * 16384 + ((q >> 1) & 1) * 8192 + (q & 1) * 512; }

constexpr uint32_t QBITS = 0x4B002000u;
constexpr uint64_t W_BIAS = ((uint64_t)QBITS << 45) + ((uint64_t)QBITS << 26) + (uint32_t)(QBITS << 7), W_CLEAR = 0 - 32 * W_BIAS;
static_assert(W_CLEAR == ((uint64_t)CLEAR_HI << 32 | CLEAR_LO), "clear value");
__host__ __device__ constexpr int unit_off(int u) { return (u & 1) * 16384 + (u >> 2) * 512 + ((u >> 1) & 1) * 128; }
__device__ __forceinline__ void red_add64(const uint8_t* p, uint64_t v) { asm volatile("red.relaxed.gpu.global.add.u64 [%0], %1;" ::"l"(p), "l"(v) : "memory"); }
template <int NF>
__device__ __forceinline__ uint64_t encode(const float* x, float S, uint32_t two26, uint32_t& bad) {
    uint32_t b[3];
#pragma unroll
    for (int i = 0; i < 3; i++) b[i] = i < NF ? __float_as_uint(fmaf(x[i], S, 8396800.f)) : QBITS;
    bad = xor_or(b[0], b[1], 0x4B000000u) | (NF == 3 ? b[2] ^ 0x4B000000u : 0);
    uint64_t w;
    asm("{\n.reg .b64 t;\nmov.b64 t, {%2, %3};\nmad.wide.u32 %0, %1, %4, t;\n}" : "=l"(w) : "r"(b[1]), "r"(b[2] << 7), "r"(b[0] << 13), "r"(two26));
    return w;
}
template <int NF>
__device__ __forceinline__ void emit(uint64_t* w, const float (*x)[3], const float* S, uint32_t two26, uint32_t lim, const uint8_t* p) {
    uint32_t bad[2];
    w[0] = encode<NF>(x[0], S[0], two26, bad[0]); w[1] = encode<NF>(x[1], S[1], two26, bad[1]);
    const bool ok = (bad[0] | bad[1]) < lim;
    w[0] |= ok; w[1] |= ok;
    red_add64(p, w[0]); red_add64(p + 1024, w[1]);
}
template <int NF>
__device__ __forceinline__ void repair(const uint64_t* w, const float (*x)[3], const float* S, const uint8_t* p, const uint8_t* pf) {
    if (!(w[0] & 1)) {
#pragma unroll
        for (int j = 0; j < 2; j++) {
            const float T = S[j] * 8192.f;
            asm volatile("red.relaxed.gpu.global.add.v4.f32 [%0], {%1,%2,%3,%4};" ::"l"(pf + j * 512), "f"(x[j][0] * T), "f"(x[j][1] * T), "f"(NF == 3 ? x[j][2] * T : 0.f), "f"(0.f) : "memory");
        }
        fence_release();
#pragma unroll
        for (int j = 0; j < 2; j++) {
            asm volatile("red.relaxed.gpu.global.or.b64 [%0], 64;" ::"l"(p + j * 1024) : "memory");
            red_add64(p + j * 1024, W_BIAS + 1 - w[j]);
        }
    }
    __syncwarp();
}
__device__ __forceinline__ void ld_words(uint32_t* v, const uint8_t* p) {
    asm volatile("{\n.reg .b64 a, b;\nld.relaxed.gpu.global.L1::no_allocate.v2.b64 {a, b}, [%4];\nmov.b64 {%0,%1}, a;\nmov.b64 {%2,%3}, b;\n}" : "=r"(v[0]), "=r"(v[1]), "=r"(v[2]), "=r"(v[3]) : "l"(p) : "memory");
}
__device__ __forceinline__ float field(const uint32_t* w, int f) { return __int2float_rn((int)(f == 0 ? w[1] : f == 1 ? __funnelshift_l(w[0], w[1], 19) : w[0] << 6)); }
template <int U>
__device__ __forceinline__ void decode(uint32_t* b, const uint32_t* v) {
#pragma unroll
    for (int f = 0; f < (U % 3 ? 3 : 2); f++) b[frag_word(U, f)] = pack2(field(v, f), field(v + 2, f));
}
__device__ __forceinline__ uint32_t status(const uint32_t (*v)[4], uint32_t c32) { return xor_or(v[0][0], v[0][2], c32) | xor_or(v[1][0], v[1][2], c32) | xor_or(v[2][0], v[2][2], c32); }
__device__ __forceinline__ void gather_slow(const Params& P, uint32_t* b, const uint8_t* pm, int s, int warp, uint32_t ln, uint32_t u2) {
    if (s == 0 && u2 == 0x3F803F80u) {
#pragma unroll
        for (int i = 0; i < 16; i++) b[i] = __ldg((const uint32_t*)(P.mem0 + (ln >> 2) * 1024 + word_col(i) + warp * 16 + (ln & 3) * 2));
        return;
    }
    uint32_t v[6][4], st;
    for (int n = 0;; n++) {
#pragma unroll
        for (int u = 0; u < 6; u++) ld_words(v[u], pm + unit_off(u));
        st = status(v, 32) | status(v + 3, 32);
        if (!__any_sync(0xffffffffu, st & 32)) break;
        __nanosleep(200);
        if (n > SPIN_LIMIT) spin_fault();
    }
    const bool side = __any_sync(0xffffffffu, st & 64);
    if (side) fence_acquire();
    const uint8_t* pf = g_f + ((s + 7) & 7) * F_SLOT + warp * 1024 + ln * 32;
#pragma unroll
    for (int u = 0; u < 6; u++) {
        float x[2][4] = {};
#pragma unroll
        for (int k = 0; k < 2; k++)
            asm volatile("{\n.reg .pred P;\nsetp.ne.u32 P, %5, 0;\n@P ld.relaxed.gpu.global.v4.f32 {%0,%1,%2,%3}, [%4];\n}"
                         : "+f"(x[k][0]), "+f"(x[k][1]), "+f"(x[k][2]), "+f"(x[k][3]) : "l"(pf + u * 8192 + k * 16), "r"((uint32_t)side) : "memory");
#pragma unroll
        for (int f = 0; f < (u % 3 ? 3 : 2); f++) b[frag_word(u, f)] = pack2(field(v[u], f) + x[0][f], field(v[u] + 2, f) + x[1][f]);
    }
}
__device__ __forceinline__ uint32_t max_abs2(uint32_t a, uint32_t b) { uint32_t d; asm("max.NaN.xorsign.abs.bf16x2 %0, %1, %2;" : "=r"(d) : "r"(a), "r"(b)); return d; }
__device__ __forceinline__ uint32_t max6(const uint32_t* b) {
    const uint32_t m = max_abs2(max_abs2(max_abs2(b[0], b[1]), max_abs2(b[2], b[3])), max_abs2(b[4], b[5]));
    return max(m & 0x7fff0000u, (m << 16) & 0x7fff0000u);
}

template <bool TR>
__device__ __forceinline__ void put_partials(uint32_t a, const float* x, const float* y) {
    if (TR) stsm4t(a, pack2(x[0], x[1]), pack2(x[2], x[3]), pack2(y[0], y[1]), pack2(y[2], y[3]));
    else stsm4(a, pack2(x[0], x[1]), pack2(x[2], x[3]), pack2(y[0], y[1]), pack2(y[2], y[3]));
}
__device__ __forceinline__ void reduce_load(uint32_t (*x)[4], uint32_t a) { ldsm4t(x[0], a); ldsm4t(x[1], a + 512); }
__device__ __forceinline__ uint32_t reduce8(const uint32_t (*x)[4], uint32_t l8, uint32_t u2) {
    uint32_t p[2];
#pragma unroll
    for (int i = 0; i < 2; i++) {
        float d[4] = {};
        mma16816(d, x[i][0], x[i][1], x[i][2], x[i][3], (l8 & 32) ? 0u : u2, (l8 & 32) ? u2 : 0u);
        p[i] = pack2((l8 & 8) ? d[2] : d[0], (l8 & 8) ? d[3] : d[1]);
    }
    return (l8 & 16) ? p[1] : p[0];
}
__device__ __forceinline__ void score_half(float (*a)[4], const uint32_t (*qa)[4], const uint32_t (*kf)[4]) {
#pragma unroll
    for (int w = 0; w < 2; w++) {
        mma16816(a[w], qa[w][0], qa[w][1], qa[w][2], qa[w][3], kf[w][0], kf[w][1]);
        mma16816(a[2 + w], qa[w][0], qa[w][1], qa[w][2], qa[w][3], kf[w][2], kf[w][3]);
    }
}
__device__ __forceinline__ void score_sum(float* S, const float (*a)[4]) {
    S[0] = (a[0][0] + a[1][0]) + (a[2][2] + a[3][2]);
    S[1] = (a[0][1] + a[1][1]) + (a[2][3] + a[3][3]);
}
__device__ __forceinline__ float quad_max(float m) {
    m = fmaxf(m, __shfl_xor_sync(0xffffffffu, m, 1));
    return fmaxf(m, __shfl_xor_sync(0xffffffffu, m, 2));
}

#define ISTAMP(i)
__device__ __forceinline__ float next_scale(uint32_t sb, int slot, int warp, uint32_t u2) {
    uint32_t x[2][4];
    lds128(x[0], sb + S_MX + slot * 32); lds128(x[1], sb + S_MX + slot * 32 + 16);
    const uint32_t mx = max(max(max(x[0][0], x[0][1]), max(x[0][2], x[0][3])), max(max(x[1][0], x[1][1]), max(x[1][2], x[1][3])));
    const float top = fminf(fmaxf(__uint_as_float(mx) * bf_hi(u2), 0x1p-40f), 0x1p40f) * (1.f / (12288.f * 8192.f));
    const uint32_t un = pack2(top, top);
    sts32(sb + S_SC + warp * 4, un);
    return rcp(bf_hi(un) * 8192.f);
}
#define NEARLY 1
#define U3POS 1
#define VPOS 1
#define ROT 0
#define BPOS 1
#define ONLINE 0
#define NBAR 1
#define ORD3 0
#define F2 1
#define EARLY 0
#define TK 0
#define RPOS 1
#define AF 0
#define AFENCE(i) if ((AF >> (i)) & 1) SFENCE();
#define FPOS 99
#define PACE 1
#define PF2 12
__host__ __device__ constexpr int w2_t(int i) { return i < 16 ? i & 1 : 2; }
__host__ __device__ constexpr int w2_k(int i) { return i < 16 ? i >> 1 : i - 16; }
template <typename G>
__device__ __forceinline__ void load_weights(uint32_t (*wr)[4], const uint32_t sb, const int warp, const int lane, G stores_read) {
    const uint32_t frag = sb + warp * 1024 + (lane >> 4) * 8192 + (lane & 7) * 128 + ((((lane >> 3) & 1) ^ (lane & 7)) << 4);
    const uint32_t rel = mapa(sb + B_EMPTY, cluster_rank() ^ (lane & 1));
#define RELEASE(st) { fence_async_smem(); __syncwarp(); if (lane < 2) mbar_arrive_cluster(rel + (st) * 8); }
    mbar_wait(sb + B_FULL, 0); mbar_wait(sb + B_FULL + 8, 0);
    RELEASE(0) RELEASE(1)
#pragma unroll
    for (int st = 2; st < 4; st++) {
        mbar_wait(sb + B_FULL + st * 8, 0);
        ISTAMP(st - 2)
#pragma unroll
        for (int f = 0; f < 12; f++) ldsm4t(wr[st * 12 - 24 + f], (frag ^ ((f & 3) << 5)) + st * STAGE + (f >> 2) * 16384);
        RELEASE(st)
    }
#pragma unroll 2
    for (int u = 0; u < 6; u++) {
        uint32_t x[4][4];
#pragma unroll
        for (int i = 0; i < 4; i++) lds128(x[i], (frag ^ (i << 5)) + u * 16384);
        __syncwarp();
#pragma unroll
        for (int i = 0; i < 4; i++) sts128(sb + warp * 1024 + lane * 16 + u * 16384 + frag_off(i), x[i]);
    }
    stores_read();
    mbar_wait(sb + B_FULL, 1); mbar_wait(sb + B_FULL + 8, 1);
    RELEASE(0) RELEASE(1)
#pragma unroll
    for (int st = 2; st < 4; st++) {
        mbar_wait(sb + B_FULL + st * 8, 1);
#pragma unroll
        for (int f = 0; f < (st == 2 ? 12 : 4); f++) ldsm4t(wr[st * 12 + f], (frag ^ ((f & 3) << 5)) + st * STAGE + (f >> 2) * 16384);
        RELEASE(st)
    }
    ISTAMP(2)
    bar_sync(1, 256);
    if (warp == 7 && lane < 3) mbar_arrive_cluster(mapa(sb + B_INIT, (cluster_rank() & 1) + lane * 2));
}
template <int ROLE>
__device__ __forceinline__ void chain_role(const Params& P, const uint32_t (*wr)[4], const uint32_t sb, const int h, const int warp, const int lane) {
    constexpr int NU = ROLE == 0 ? 2 : 3;
    const bool att = ROLE == 0 && warp < 4;
    uint32_t l8 = opq(sb + lane * 8, lane);
#define PERSIST() { mbar_wait(sb + B_KVGO, slot ^ 1); const uint32_t pa_ = ((l8 - sb) >> 1) + (sb + S_QX + warp * 128); sts32(pa_, r0); sts32(pa_ + 1024, r1); \
                    fence_async_smem(); __syncwarp(); if (l8 == sb) mbar_arrive(sb + B_PERS); }
    if (ROLE) sts32(sb + S_SX + warp * 128 + lane * 4, warp >= 2 ? 0 : (lane & 1) ? CLEAR_HI : CLEAR_LO);
    const uint32_t rdelta = __shfl_sync(0xffffffffu, mapa(sb, (cluster_rank() + (ROLE == 1 ? 4 : 2)) % 6) - sb, 0);
    const uint32_t vdelta = ROLE ? 0 : __shfl_sync(0xffffffffu, mapa(sb, (cluster_rank() + 4) % 6) - sb, 0);
    ISTAMP(3)
    __syncwarp();
#define GATHER_OFF(s) ((((s) + 7) & 7) * M_SLOT + warp * 2048 + (l8 & 56) * 2 + (l8 & 64) * 4 + (l8 & 128) * 8)
    uint32_t mo = GATHER_OFF(0);
    if (ROT) mbar_wait(sb + B_RELA, 0);
    for (int s = 0; s < (ROLE == 0 ? 63 : 64);) {
        const int slot = s & 1;
        l8 += s & P.zero;
        const uint32_t w1a = l8 * 2 + (S_W1 + warp * 1024 - sb);
        PROF(9)
        uint32_t u2, r0, r1, pld, pub, pbar, x[2][4];
        {
#define pm (P.gm + mo)
            uint32_t as[24][4], b[16], v[6][4];
            float acc[8][4];
#define W1LD(n) _Pragma("unroll") for (int i_ = 0; i_ < 4; i_++) ldsm4t(as[unit_pos(n) * 4 + i_], w1a + frag_off(unit_pos(n) * 4 + i_));
#define W1LD2(n, p) { const uint32_t wa_ = w1a + (as[unit_pos(p) * 4][0] & as[unit_pos(p) * 4 + 1][0] & as[unit_pos(p) * 4 + 2][0] & as[unit_pos(p) * 4 + 3][0] & P.zero); \
                      _Pragma("unroll") for (int i_ = 0; i_ < 4; i_++) ldsm4t(as[unit_pos(n) * 4 + i_], wa_ + frag_off(unit_pos(n) * 4 + i_)); }
#define W1MMA(n) _Pragma("unroll") for (int i_ = 0; i_ < 4; i_++) { const uint32_t* a_ = in_smem(n) ? as[unit_pos(n) * 4 + i_] : wr[unit_pos(n) * 4 + i_]; \
                                                                   mma16816(acc[((n) & 1) * 4 + i_], a_[0], a_[1], a_[2], a_[3], b[(n) & 14], b[(n) | 1]); }
#pragma unroll
            for (int T = 0; T < 8; T++) { acc[T][0] = acc[T][1] = acc[T][2] = acc[T][3] = 0.f; }
            if (!ROT) mbar_wait(sb + B_RELA, slot);
            PROF(12)
#pragma unroll
            for (int u = 0; u < 3; u++) ld_words(v[u], pm + unit_off(u));
            __syncwarp();
#pragma unroll
            for (int i = 0; i < PF1; i++) ldsm4t(as[i], w1a + frag_off(i));
            __syncwarp();
            mo += mbar_try(sb + B_RELB, slot) & P.zero;
            PROF(13)
#pragma unroll
            for (int u = 3; u < 6; u++) ld_words(v[u], pm + unit_off(u));
            uint32_t st = status(v, ((uint32_t)((uintptr_t)pm >> 32) & P.zero) + 32);
            pin<1>(&st);
            SFENCE();
            UNIT_STAT(0)
            PROF(0)
            decode<0>(b, v[0]); decode<1>(b, v[1]); decode<2>(b, v[2]);
#pragma unroll
            for (int i = PF1; i < 12; i++) ldsm4t(as[i], w1a + frag_off(i));
            W1MMA(0) W1MMA(1) W1MMA(2)
            if (TK & 1) W1LD2(3, 2) else { W1LD(3) }
            SFENCE();
            if (TK & 8) { W1MMA(5) W1MMA(4) W1MMA(3) W1MMA(6) } else { W1MMA(5) W1MMA(4) W1MMA(6) W1MMA(3) }
            if (U3POS == 0) W1MMA(7)
            if (TK & 2) W1LD2(12, 3) else { W1LD(12) }
            uint32_t mx = max6(b);
            pin<1>(&mx);
            SFENCE();
            PROF(10)
            if (U3POS == 1) W1MMA(7)
            const uint32_t mxa = sb + S_MX + slot * 32 + warp * 4;
            sts32(mxa, __reduce_max_sync(0xffffffffu, mx));
            UNIT_STAT(3)
            st |= status(v + 3, 32);
            const bool redo = __any_sync(0xffffffffu, st & 96);
            const bool kvok = ROLE || mbar_test(sb + B_KVFULL + slot * 8, (s >> 1) & 1);
            decode<4>(b, v[4]); decode<5>(b, v[5]); decode<3>(b, v[3]);
            u2 = lds32(sb + S_SC + warp * 4);
            W1MMA(8) W1MMA(10) if (ORD3) { W1MMA(14) W1MMA(12) } else { W1MMA(12) W1MMA(14) }
            if (TK & 4) W1LD2(13, 12) else { W1LD(13) }
            if (__builtin_expect(redo || !kvok, 0)) {
                if (redo) {
                    RETRY(3)
                    sts32(sb + S_REDO, s);
                    gather_slow(P, b, P.gm + GATHER_OFF(s), s, warp, (l8 - sb) >> 3, u2);
                    sts32(mxa, __reduce_max_sync(0xffffffffu, max6(b)));
#pragma unroll
                    for (int T = 0; T < 8; T++) { acc[T][0] = acc[T][1] = acc[T][2] = acc[T][3] = 0.f; }
#pragma unroll
                    for (int n = 0; n < 15; n += n < 8 ? 1 : 2) {
                        if (in_smem(n)) { W1LD(n) }
                        W1MMA(n)
                    }
                    W1LD(13)
                }
                if (ROLE == 0) mbar_wait(sb + B_KVFULL + slot * 8, (s >> 1) & 1);
            }
#undef pm
            SSTAMP(7, threadIdx.x == 0 && s == 0)
            PROF(14)
            const uint32_t pst = (l8 - sb) * 16 + ((warp * 16) ^ ((l8 * 2) & 112)) + (sb + S_P1);
            put_partials<ROLE == 2>(pst, acc[0], acc[1]); put_partials<ROLE == 2>(pst + 4096, acc[2], acc[3]);
            W1MMA(9)
            SFENCE();
            pld = (l8 & 64) * 4 + (l8 & 128) + (l8 & 56) * 2 + (sb + S_P1 + warp * 1024);
            const uint32_t rd = s == 63 ? 0 : rdelta;
            pub = ((l8 - sb) >> 1) + (ROLE ? sb + rd + (ROLE == 1 ? S_KL : S_VL) + warp * 128 : sb + S_QX + (warp & 4) * 128 + (warp & 1) * 256 + (warp & 2) * 64);
            pbar = sb + rd + (ROLE == 1 && s != 63 ? B_K : B_V);
#define PUBLISH0() { r0 = reduce8(x, l8, u2); if (ROLE) st_async1(pub, r0, pbar); else sts32(pub, r0); }
            if (RPOS == 0) { bar_sync(1, 256); reduce_load(x, pld); SFENCE(); }
            W1MMA(11)
            if (RPOS == 1) { bar_sync(1, 256); reduce_load(x, pld); }
            if (RPOS != 2 || F2) SFENCE();
            W1MMA(15)
            if (RPOS == 0) PUBLISH0()
            if (RPOS == 2) { bar_sync(1, 256); reduce_load(x, pld); }
            if (RPOS != 1 || F2) SFENCE();
            W1MMA(13)
            if (RPOS == 1) PUBLISH0()
            put_partials<ROLE == 2>(pst + 8192, acc[4], acc[5]); put_partials<ROLE == 2>(pst + 12288, acc[6], acc[7]);
            if (RPOS == 2) PUBLISH0()
        }
        SSTAMP(8, threadIdx.x == 0 && s == 0)
        PROF(1)
        if (ROLE) {
            bar_sync(1, 256);
            reduce_load(x, pld + 8192);
            r1 = reduce8(x, l8, u2);
            st_async1(pub + 1024, r1, pbar);
            if (s == 63) {
                PERSIST()
                mbar_wait(sb + B_V, 0);
                break;
            }
            PROF(2)
        }
        uint32_t ln, w2a, ro;
#define W2ADDR(late) { l8 += pub & P.zero; ln = (l8 - sb) >> 3; \
        w2a = sb + S_W2 + (ROLE ? (warp >> 2) * 16384 : late * 32768) + ((((ln & 7) + (ln >> 4) * 8) * 128 + ((((ln >> 3) & 1) ^ (ln & 7)) << 4)) ^ ((warp & 3) << 5)); \
        ro = (s & 7) * M_SLOT + (ROLE ? warp * 2048 + unit_off(ROLE) : (warp & 3) * 2048 + late * unit_off(3)) + (ln & 2) * 128 + (ln & 1) * 64 + (ln >> 2) * 8; }
        constexpr int RO2 = ROLE ? unit_off(ROLE + 3) - unit_off(ROLE) : 8192;
        float Sj[2];
        uint32_t w[24][4], ob[4][4];
        float S;
#define W2LD(i) ldsm4t(w[i], w2a + w2_t(i) * (ROLE ? 32768 : 16384) + (w2_k(i) & 1) * 8192 + (w2_k(i) >> 1) * 2048)
#define W2MMA(d, i) mma16816(d, w[i][0], w[i][1], w[i][2], w[i][3], ob[w2_k(i) >> 1][(w2_k(i) & 1) * 2], ob[w2_k(i) >> 1][(w2_k(i) & 1) * 2 + 1])
#define LEADER(wp) (l8 == sb + ((wp) - warp) * 256)
        if (att) {
            const float cs = 0.08838834764831845f * 1.4426950408889634f;
            uint32_t qa[4][4], kf[4][4], vf[4][4], vv[4];
            float T[5][2], sa[4][4] = {};
            const uint32_t l16 = l8 * 2 - sb;
            const uint32_t kaddr = (l8 & 56) * 16 + (((l8 >> 2) ^ (l8 * 2)) & 48) + ((l8 * 2) & 64) + (sb + S_KV + warp * 1024 + slot * 16384);
            bar_sync(1, 256);
            reduce_load(x, pld + 8192);
            __syncwarp();
#pragma unroll
            for (int i = 0; i < 2; i++) { ldsm4(qa[i], l16 + S_QX + i * 512); ldsm4(kf[i], kaddr ^ (i * 64)); }
            AFENCE(0)
            sts32(pub + 1024, reduce8(x, l8, u2));
            __syncwarp();
#pragma unroll
            for (int i = 2; i < 4; i++) ldsm4(kf[i], (kaddr ^ ((i & 1) * 64)) + 4096);
            score_half(sa, qa, kf);
            bar_sync(2, 256);
            PROF(2)
#pragma unroll
            for (int i = 2; i < 4; i++) ldsm4(qa[i], l16 + S_QX + i * 512);
            float sm[4][4] = {};
            score_half(sa, qa + 2, kf + 2);
            score_sum(T[0], sa);
            sts64(l8 + S_SX + warp * 256, __float_as_uint(T[0][0]), __float_as_uint(T[0][1]));
            PROF(4)
            if (BPOS == 0) bar_sync(4, 128);
            mbar_wait(sb + B_K, slot);
            PROF(11)
#pragma unroll
            for (int i = 0; i < 4; i++) ldsm4(kf[i], l16 + S_KL + i * 512);
            if (BPOS == 1) bar_sync(4, 128); else __syncwarp();
#pragma unroll
            for (int n = 0; n < 4; n++) lds64f(T[n], l8 + S_SX + n * 256);
            score_half(sm, qa, kf);
            score_half(sm, qa + 2, kf + 2);
            const uint32_t vaddr = (l8 & 56) * 16 + (l8 & 128) * 8 + (((warp & 1) * 64 + ((l8 >> 2) & 16)) ^ ((l8 * 2) & 112)) + (sb + S_KV + 8192 + (warp >> 1) * 4096 + slot * 16384);
            float mx = fmaxf(fmaxf(fmaxf(T[0][0], T[0][1]), fmaxf(T[1][0], T[1][1])), fmaxf(fmaxf(T[2][0], T[2][1]), fmaxf(T[3][0], T[3][1])));
            score_sum(T[4], sm);
            float m = quad_max(fmaxf(mx, fmaxf(T[4][0], T[4][1])));
            if (VPOS == 0) {
#pragma unroll
                for (int i = 0; i < 4; i++) ldsm4t(vf[i], (vaddr ^ ((i & 1) << 5)) + (i >> 1) * 2048);
            }
            mbar_wait(sb + B_V, slot);
            if (VPOS == 1) {
#pragma unroll
                for (int i = 0; i < 4; i++) ldsm4t(vf[i], (vaddr ^ ((i & 1) << 5)) + (i >> 1) * 2048);
            }
            ldsm4(vv, l16 + S_VL + warp * 512);
            uint32_t pa[5];
            m *= cs;
#pragma unroll
            for (int n = 0; n < 5; n++) { T[n][0] = ex2(fmaf(T[n][0], cs, -m)); T[n][1] = ex2(fmaf(T[n][1], cs, -m)); pa[n] = pack2(T[n][0], T[n][1]); }
            float sum = (((T[0][0] + T[0][1]) + (T[1][0] + T[1][1])) + ((T[2][0] + T[2][1]) + (T[3][0] + T[3][1]))) + (T[4][0] + T[4][1]);
            PROF(3)
            W2ADDR(1)
            const uint32_t lo = sb + S_O + warp * 512 + (ln & 3) * 64 + (ln >> 2) * 8, ls = sb + S_SUM + (ln & 3) * 32 + (ln & 4) * 4 + (ln >> 3) * 4;
            const uint32_t sdelta = warp < 2 ? rdelta : vdelta;
            sum += __shfl_xor_sync(0xffffffffu, sum, 1);
            sum += __shfl_xor_sync(0xffffffffu, sum, 2);
            float O[2][4];
#pragma unroll
            for (int i = 0; i < 2; i++) { O[i][0] = O[i][1] = O[i][2] = O[i][3] = 0.f; }
#pragma unroll
            for (int i = 0; i < 2; i++) {
                mma16816(O[0], vf[2 * i][0], vf[2 * i][1], vf[2 * i][2], vf[2 * i][3], pa[2 * i], pa[2 * i + 1]);
                mma16816(O[1], vf[2 * i + 1][0], vf[2 * i + 1][1], vf[2 * i + 1][2], vf[2 * i + 1][3], pa[2 * i], pa[2 * i + 1]);
            }
            mma1688(O[0], vv[0], vv[1], pa[4]);
            mma1688(O[1], vv[2], vv[3], pa[4]);
            uint32_t o[2][2];
#pragma unroll
            for (int j = 0; j < 2; j++) { o[j][0] = pack2(O[0][j], O[0][2 + j]); o[j][1] = pack2(O[1][j], O[1][2 + j]); }
#pragma unroll
            for (int j = 0; j < 2; j++) st_async2(lo + rdelta + j * 256, o[j][0], o[j][1], sb + rdelta + B_K);
            st_async1(ls + sdelta + (warp & 1) * 128, __float_as_uint(sum), sb + sdelta + B_K);
#pragma unroll
            for (int j = 0; j < 2; j++) st_async2(lo + vdelta + j * 256, o[j][0], o[j][1], sb + vdelta + B_K);
#pragma unroll
            for (int j = 0; j < 2; j++) sts64(lo + j * 256, o[j][0], o[j][1]);
            sts32(ls + warp * 128, __float_as_uint(sum));
            PROF(5)
            bar_sync(3, 256);
            if (LEADER(0)) { mbar_expect(sb + B_K, 2048); mbar_expect(sb + B_V, 2048); mbar_arrive(sb + B_KVGO + slot * 8); }
            S = next_scale(sb, slot, warp, u2);
            if (s == 0) mbar_wait(sb + B_WO, 0);
            pin<1>(&S);
            SFENCE();
#pragma unroll
            for (int j = 0; j < 4; j++) lds128(ob[j], l8 * 2 - sb + S_O + j * 512);
            lds64f(Sj, sb + S_SUM + (l8 & 24));
#pragma unroll
            for (int i = 0; i < PF2; i++) W2LD(i);
        } else {
            if (ROLE == 0) { bar_sync(1, 256); reduce_load(x, pld + 8192); sts32(pub + 1024, reduce8(x, l8, u2)); bar_arrive(2, 256); }
            if (LEADER(7)) { if (s) mbar_arrive(sb + B_GO); if (ROLE) mbar_expect(sb + B_K, 2304); }
            S = next_scale(sb, slot, warp, u2);
            if (s == 0) mbar_wait(sb + B_WO, 0);
            if (ROLE != 0) PERSIST()
            W2ADDR(0)
#pragma unroll
            for (int i = 0; i < PF2; i++) {
                W2LD(i);
                if (ROLE == 0 && (i & PACE) == PACE) w2a += w[i][0] & P.zero;
            }
            ro = opq(ro, ln);
            const uint32_t sa = opq(sb + S_SUM + (l8 & 24), ln), oa = opq(l8 * 2 - sb + S_O, ln);
            if (ROLE == 0) bar_sync(3, 256); else mbar_wait(sb + B_K, slot);
            lds64f(Sj, sa);
#pragma unroll
            for (int j = 0; j < 4; j++) lds128(ob[j], oa + j * 512);
        }
        SSTAMP(9, threadIdx.x == 224 && s == 0)
        SFENCE();
        PROF(6)
        {
            const uint8_t* pr = P.gm + ro;
            float c[4][4];
            uint32_t lim = 0;
#pragma unroll
            for (int i = 0; i < 4; i++) { c[i][0] = c[i][1] = c[i][2] = c[i][3] = 0.f; }
#pragma unroll
            for (int i = 0; i < 16; i++) {
                W2MMA(c[i & (ROLE ? 1 : 3)], i);
                if (i + PF2 < (ROLE ? 16 + NEARLY : 16)) W2LD(i + PF2);
                if (i == 5) {
                    const uint32_t z = __float_as_uint(c[1][0]) & P.zero;
                    Sj[0] = S * rcp(__uint_as_float(__float_as_uint(Sj[0]) | z)); Sj[1] = S * rcp(__uint_as_float(__float_as_uint(Sj[1]) | z));
                }
                if (i == 5) lim = __any_sync(0xffffffffu, fmaxf(fmaxf(fabsf(c[0][0]), fabsf(c[0][2])), fmaxf(fabsf(c[1][0]), fabsf(c[1][2]))) * Sj[0] >= (ROLE ? 24.f : 20.f)) ? 16384 : 0;
                if (i == FPOS) { pin<1>(&lim); pin<2>(Sj); pin_ptr(pr); SFENCE(); }
            }
            if (ROLE == 0) {
#pragma unroll
                for (int i = 0; i < 8; i++) c[i >> 2][i & 3] += c[2 + (i >> 2)][i & 3];
            }
            const float xa[2][3] = {{c[0][0], c[0][2], c[1][0]}, {c[0][1], c[0][3], c[1][1]}};
            uint64_t wa[2], wb[2];
            emit<NU>(wa, xa, Sj, P.two26, lim, pr);
            PROF(7)
            mo = GATHER_OFF(s + 1);
            pin<1>(&mo);
            if (ROLE) {
                SFENCE();
#pragma unroll
                for (int i = 16 + NEARLY; i < 24; i++) { if (i == 16 + NBAR) bar_sync(2, 256); W2LD(i); __syncwarp(); }
                SFENCE();
#pragma unroll
                for (int i = 16; i < 24; i++) W2MMA(c[2 + (i & 1)], i);
#pragma unroll
                for (int i = 0; i < 4; i++) c[2][i] += c[3][i];
            }
            const float y[2][3] = {{ROLE ? c[1][2] : c[1][0], ROLE ? c[2][0] : c[1][2], c[2][2]}, {ROLE ? c[1][3] : c[1][1], ROLE ? c[2][1] : c[1][3], c[2][3]}};
            const bool released = !ROT || mbar_test(sb + B_RELA, slot ^ 1);
            emit<NU>(wb, y, Sj, P.two26, lim, pr + RO2);
            PROF(8)
            if (!__all_sync(0xffffffffu, (wa[0] & wb[0] & 1) && released && s)) {
                if (__builtin_expect(!__all_sync(0xffffffffu, wa[0] & wb[0] & 1), 0)) {
                    RETRY(5)
                    const uint8_t* pf = g_f + (s & 7) * F_SLOT + (ROLE ? ROLE * 8192 + warp * 1024 : (warp & 3) * 1024 + (att ? 24576 : 0)) + (ln & 3) * 128 + (ln >> 2) * 16;
                    repair<NU>(wa, xa, Sj, pr, pf);
                    repair<NU>(wb, y, Sj, pr + RO2, pf + (ROLE ? 24576 : 4096));
                }
                if (s == 0) { bar_sync(1, 256); if (LEADER(7)) mbar_arrive(sb + B_GO); }
                if (ROT) mbar_wait(sb + B_RELA, slot ^ 1);
            }
        }
        s++;
    }
}
struct Pipe { uint32_t stage, phase; };
struct Cons {
    uint32_t sb, rel;
    int wg, wq, lane, rank, pair;
    uint32_t nst;
    Pipe p;
};
__device__ __forceinline__ void pipe_next(Pipe& p) { p.stage = (p.stage + 1) & (NSTAGE - 1); p.phase ^= (p.stage == 0); }
__device__ __forceinline__ void release(const Cons& c, uint32_t stage) { if (c.lane < 2) mbar_arrive_cluster(c.rel + stage * 8); }

enum { PEND_NONE = 0, PEND_KVO = 1, PEND_HT = 2, PEND_OUT = 3, PEND_OUTH = 4 };
struct Pend { uint32_t pk[64]; int kind, row, col, cnt; };

__device__ __forceinline__ void staging_wait(const Cons& c) { if (c.nst) mbar_wait(c.sb + B_SFREE + c.wg * 8, (c.nst - 1) & 1); }
__device__ __forceinline__ void staging_post(Cons& c, int kind, int row, int col, int cnt) {
    __syncwarp();
    if (c.lane == 0) {
        if (c.wq == 0) { const uint32_t x[4] = {(uint32_t)kind, (uint32_t)row, (uint32_t)col, (uint32_t)cnt}; sts128(c.sb + S_DESC + c.wg * 16, x); }
        mbar_arrive(c.sb + B_SFULL + c.wg * 8);
    }
    c.nst++;
}
template <int HF, bool KVONLY = false>
__device__ __forceinline__ void drain(const Params& P, Cons& c, const Pend& d) {
    const uint32_t* pk = d.pk + HF * 32;
    if (!KVONLY && d.kind >= PEND_OUT) {
        if (HF == 1 && d.kind == PEND_OUTH) return;
        float* o = P.out + (size_t)(d.row + c.wq * 16 + (c.lane >> 2)) * 2048 + d.col + HF * 128 + (c.lane & 3) * 2;
#pragma unroll
        for (int j = 0; j < 16; j++) {
            st_stream2(o + j * 8, bf_lo(pk[j * 2]), bf_hi(pk[j * 2]));
            st_stream2(o + 8 * 2048 + j * 8, bf_lo(pk[j * 2 + 1]), bf_hi(pk[j * 2 + 1]));
        }
    } else if (d.kind != PEND_NONE) {
        const bool ht = !KVONLY && d.kind == PEND_HT;
        const int hi = (c.lane >> 3) & 1;
        const uint32_t base = c.sb + S_STG + c.wg * 16384 + ((ht ? hi * 32 + c.wq * 8 : c.wq * 16 + hi * 8) + (c.lane & 7)) * 128;
        staging_wait(c);
#pragma unroll
        for (int j = 0; j < 8; j++) {
            const int ch = (j & 3) * 2 + (c.lane >> 4);
            stsm4(base + (j >> 2) * 8192 + ((ch ^ (c.lane & 7)) << 4), pk[j * 4], pk[j * 4 + 1], pk[j * 4 + 2], pk[j * 4 + 3]);
        }
        fence_async_smem();
        staging_post(c, d.kind, d.row, d.col + HF * 128, HF ? d.cnt : -1);
    }
}
__device__ __forceinline__ void drain_all(const Params& P, Cons& c, Pend& d) { drain<0>(P, c, d); drain<1>(P, c, d); d.kind = PEND_NONE; }

__device__ __forceinline__ void store_warp(const Params& P, uint32_t sb, int wg) {
    const uint32_t stg = sb + S_STG + wg * 16384;
#pragma unroll 1
    for (uint32_t n = 0;; n++) {
        mbar_wait(sb + B_SFULL + wg * 8, n & 1);
        uint32_t x[4];
        lds128(x, sb + S_DESC + wg * 16);
        if (x[0] == PEND_NONE) break;
        const bool ht = x[0] == PEND_HT;
        const CUtensorMap* m = &P.tm[ht ? M_HTS : M_KVO];
#pragma unroll 1
        for (int i = 0; i < 4; i++) if (!(DBGF(128) && gridDim.x != 96)) tma_store2d(m, x[2] + (i >> 1) * 64, x[1] + (i & 1) * (ht ? 1024 : 32), stg + i * 4096);
        bulk_commit();
        bulk_wait_read();
        mbar_arrive(sb + B_SFREE + wg * 8);
        if ((int)x[3] >= 0) {
            bulk_wait_all(); fence_async();
            asm volatile("red.relaxed.gpu.global.add.u32 [%0], 1;" ::"l"(&g_cnt(x[3])) : "memory");
        }
    }
}

template <int N, int TA, int TB, bool FIRST>
__device__ __forceinline__ void issue_ktile(float* acc, const Cons& c) {
    mbar_wait(c.sb + B_FULL + c.p.stage * 8, c.p.phase);
    const uint32_t a = c.sb + c.p.stage * STAGE + c.wg * 8192, b = c.sb + c.p.stage * STAGE + 16384;
    const uint64_t da = mkdesc(a, TA ? 8192 : 16, 1024, 1), db = mkdesc(b, TB ? 8192 : 16, 1024, 1);
    wg_fence();
#pragma unroll
    for (int k = 0; k < 4; k++) {
        const uint64_t x = da + (TA ? 128 : 2) * k, y = db + (TB ? 128 : 2) * k;
        if (N == 256) { if (FIRST && k == 0) wgmma_ss256_first<TA, TB>(acc, x, y); else wgmma_ss256<TA, TB>(acc, x, y); }
        else { if (FIRST && k == 0) wgmma_ss128_first<TA, TB>(acc, x, y); else wgmma_ss128<TA, TB>(acc, x, y); }
    }
    wg_commit();
}
template <int N, bool FIRST>
__device__ __forceinline__ void issue_any(float* acc, const Cons& c, int type) {
    if (N == 256 && type == T_A1) issue_ktile<N, 0, 0, FIRST>(acc, c);
    else if (type == (N == 256 ? T_A2 : T_A2H)) issue_ktile<N, 1, 0, FIRST>(acc, c);
    else issue_ktile<N, 0, 1, FIRST>(acc, c);
}
template <int N, bool KVONLY = false>
__device__ __forceinline__ void mainloop(float* acc, const Params& P, Cons& c, Pend& d, int type) {
    const int nk = (type == T_OP || type == T_OPH) ? 64 : (type == T_A2 || type == T_A2H) ? 32 : 16;
    issue_any<N, true>(acc, c, type);
    drain<0, KVONLY>(P, c, d);
    uint32_t prev = c.p.stage;
    pipe_next(c.p);
    const int hold = c.wg ? nk - (int)((P.lag >> (4 * type)) & 7) : -1;
    for (int kt = 1; kt < nk; kt++) {
        if (kt == hold) bar_sync(8, 256);
        issue_any<N, false>(acc, c, type);
        wg_wait<1>();
        release(c, prev);
        if (kt == 2) drain<1, KVONLY>(P, c, d);
        prev = c.p.stage;
        pipe_next(c.p);
    }
    if (c.wg == 0 && ((P.lag >> (4 * type)) & 7)) bar_arrive(8, 256);
    d.kind = PEND_NONE;
    wg_wait<0>();
    pin<N / 2>(acc);
    release(c, prev);
}
__device__ __forceinline__ void pack_half(uint32_t* pk, const float* a) {
#pragma unroll
    for (int i = 0; i < 32; i++) pk[i] = pack2(a[2 * i], a[2 * i + 1]);
}

__device__ __forceinline__ void epi_kv(const float* acc, const Cons& c, Pend& d, int mb, int nb) {
    pack_half(d.pk, acc); pack_half(d.pk + 32, acc + 64);
    d.kind = PEND_KVO; d.row = (nb >> 4) * 2048 + mb * 256 + c.rank * 128 + c.wg * 64; d.col = (nb & 15) * 256; d.cnt = C_KV + mb;
}

__device__ __forceinline__ void epi_qa(const float* acc, Cons& c, Pend& d, int mb, int nb) {
    uint32_t q[64];
    pack_half(q, acc);
    pack_half(q + 32, acc + 64);
#pragma unroll
    for (int i = 0; i < 32; i++) d.pk[32 + i] = 0;
    const int g = c.lane >> 2, t = c.lane & 3;
    const bool sg = c.wq >= 2;
    const int i0 = (c.wq & 1) * 16 + g;
#pragma unroll 1
    for (int hh = 0; hh < 2; hh++) {
        uint32_t pa[5][4];
        {
            float S[32] = {}, Sm[8] = {};
            mbar_wait(c.sb + B_FULL + c.p.stage * 8, c.p.phase);
            const uint32_t st = c.sb + c.p.stage * STAGE;
            const uint64_t dk = mkdesc(st + c.wg * 8192, 16, 1024, 1), dm = mkdesc(st + 32768 + c.wg * 4096, 128, 2048, 0);
            pin<32>(q); pin<32>(S); pin<8>(Sm);
            wg_fence();
#pragma unroll
            for (int i = 0; i < 8; i++) wgmma_rs64<0>(S, q + i * 4, dk + (i >> 2) * 1024 + (i & 3) * 2, i != 0);
#pragma unroll
            for (int i = 0; i < 8; i++) wgmma_rs16<0>(Sm, q + i * 4, dm + i * 16, i != 0);
            wg_commit();
            wg_wait<0>();
            pin<32>(S); pin<8>(Sm);
            release(c, c.p.stage);
            pipe_next(c.p);
            const float scale = 0.08838834764831845f, l2e = 1.4426950408889634f;
            float x[2][10];
#pragma unroll
            for (int r = 0; r < 2; r++) {
#pragma unroll
                for (int j = 0; j < 4; j++)
#pragma unroll
                    for (int e = 0; e < 2; e++) {
                        const float v = sg ? S[16 + j * 4 + r * 2 + e] : S[j * 4 + r * 2 + e];
                        x[r][j * 2 + e] = (j * 8 + 2 * t + e > i0 + r * 8) ? -1e9f : v * scale;
                    }
                x[r][8] = (sg ? Sm[4 + r * 2] : Sm[r * 2]) * scale;
                x[r][9] = (sg ? Sm[5 + r * 2] : Sm[1 + r * 2]) * scale;
                float m = x[r][0];
#pragma unroll
                for (int i = 1; i < 10; i++) m = fmaxf(m, x[r][i]);
                m = fmaxf(m, __shfl_xor_sync(0xffffffffu, m, 1));
                m = fmaxf(m, __shfl_xor_sync(0xffffffffu, m, 2));
                float sum = 0.f;
#pragma unroll
                for (int i = 0; i < 10; i++) { x[r][i] = ex2((x[r][i] - m) * l2e); sum += x[r][i]; }
                sum += __shfl_xor_sync(0xffffffffu, sum, 1);
                sum += __shfl_xor_sync(0xffffffffu, sum, 2);
                const float inv = rcp(sum);
#pragma unroll
                for (int i = 0; i < 10; i++) x[r][i] *= inv;
            }
#pragma unroll
            for (int ks = 0; ks < 2; ks++)
#pragma unroll
                for (int i = 0; i < 4; i++) {
                    const uint32_t p = pack2(x[i & 1][ks * 4 + (i >> 1) * 2], x[i & 1][ks * 4 + (i >> 1) * 2 + 1]);
                    pa[ks][i] = sg ? 0u : p;
                    pa[2 + ks][i] = sg ? p : 0u;
                }
#pragma unroll
            for (int r = 0; r < 2; r++) {
                const uint32_t p = pack2(x[r][8], x[r][9]);
                pa[4][r] = sg ? 0u : p;
                pa[4][2 + r] = sg ? p : 0u;
            }
        }
        float O[64] = {};
        mbar_wait(c.sb + B_FULL + c.p.stage * 8, c.p.phase);
        const uint32_t st = c.sb + c.p.stage * STAGE;
        const uint64_t dv = mkdesc(st + c.wg * 8192, 16384, 1024, 1), dm = mkdesc(st + 32768 + c.wg * 4096, 2048, 128, 0);
        pin<20>(&pa[0][0]); pin<64>(O);
        wg_fence();
#pragma unroll
        for (int ks = 0; ks < 4; ks++) wgmma_rs128<1>(O, pa[ks], dv + ks * 128, ks != 0);
        wgmma_rs128<0>(O, pa[4], dm, 1);
        wg_commit();
        wg_wait<0>();
        pin<64>(O);
        release(c, c.p.stage);
        pipe_next(c.p);
#pragma unroll
        for (int i = 0; i < 32; i++) { q[i] = q[32 + i]; q[32 + i] = d.pk[32 + i]; }
        pack_half(d.pk + 32, O);
    }
#pragma unroll
    for (int i = 0; i < 32; i++) d.pk[i] = q[32 + i];
    d.kind = PEND_KVO; d.row = 4096 + mb * 256 + c.rank * 128 + c.wg * 64; d.col = nb * 256; d.cnt = C_O + mb * 4 + (nb >> 2);
}

__device__ __forceinline__ void epi_op(const float* acc, const Cons& c, Pend& d, int mb, int nb) {
    pack_half(d.pk, acc); pack_half(d.pk + 32, acc + 64);
    d.kind = PEND_OUT; d.row = mb * 256 + c.rank * 128 + c.wg * 64; d.col = 1024 + nb * 256;
}

__device__ __forceinline__ void epi_oph(const float* acc, const Cons& c, Pend& d, int mb, int nb) {
    pack_half(d.pk, acc);
    d.kind = PEND_OUTH; d.row = mb * 256 + c.rank * 128 + c.wg * 64; d.col = 1024 + nb * 128;
}

template <int HF>
__device__ __forceinline__ void epi_a2_half(const float* acc, const Params& P, Cons& c, int mb, int col0) {
    const int g = c.lane >> 2, t = c.lane & 3;
    const int row = mb * 256 + (g >> 1) * 64 + (c.rank * 16 + c.wg * 8 + c.wq * 2) * 2 + (g & 1);
    float* o = P.out + (size_t)row * 2048 + col0 + HF * 128 + t * 2;
    mbar_wait(c.sb + B_FULL + c.p.stage * 8, c.p.phase);
    const uint32_t st = c.sb + c.p.stage * STAGE, da = st + 32768 + (c.lane >> 3) * 16;
    const uint32_t xa = st + (c.wg * 64 + c.wq * 16 + (c.lane & 15)) * 128 + (((c.lane >> 4) ^ (c.lane & 7)) << 4);
#pragma unroll
    for (int j4 = 0; j4 < 4; j4++) {
        uint32_t x[8], dv[4];
        ldsm4(dv, da + j4 * 64);
        ldsm4(x, (xa ^ ((j4 & 1) << 6)) + (j4 >> 1) * 16384);
        ldsm4(x + 4, (xa ^ ((j4 & 1) << 6) ^ 32) + (j4 >> 1) * 16384);
#pragma unroll
        for (int i = 0; i < 4; i++) {
            const int j = j4 * 4 + i;
            const float* a = acc + HF * 64 + j * 4;
            const uint32_t u0 = hmul2(x[2 * i], dv[i]), u1 = hmul2(x[2 * i + 1], dv[i]);
            st_stream2(o + j * 8, a[0] + bf_lo(u0), a[1] + bf_hi(u0));
            st_stream2(o + 2 * 2048 + j * 8, a[2] + bf_lo(u1), a[3] + bf_hi(u1));
        }
    }
    __syncwarp();
    release(c, c.p.stage);
    pipe_next(c.p);
}

#define TSTAMP(i)
__device__ __forceinline__ float2 cmul(float2 a, float2 b) { return make_float2(fmaf(a.x, b.x, -a.y * b.y), fmaf(a.x, b.y, a.y * b.x)); }
__device__ __forceinline__ float2 cfma(float2 a, float2 b, float2 u) { return make_float2(fmaf(a.x, b.x, fmaf(-a.y, b.y, u.x)), fmaf(a.x, b.y, fmaf(a.y, b.x, u.y))); }
__device__ __forceinline__ float4 ssm_coef(float lre, float lim, float logdt) {
    const float dt = __bfloat162float(__float2bfloat16(expf(logdt)));
    const float ea = expf(dt * lre);
    float sn, cn;
    sincosf(dt * lim, &sn, &cn);
    const float br = ea * cn, bi = ea * sn, nr = br - 1.f;
    float cr, ci;
    if (fabsf(lre) >= fabsf(lim)) { const float r = lim / lre, dn = lre + lim * r; cr = (nr + bi * r) / dn; ci = (bi - nr * r) / dn; }
    else { const float r = lre / lim, dn = lre * r + lim; cr = (nr * r + bi) / dn; ci = (bi * r - nr) / dn; }
    return make_float4(br, bi, cr, ci);
}
__device__ __forceinline__ void epi_a1(const float* acc, const Params& P, const Cons& c, Pend& d, int mb, int nb, uint32_t atag) {
    const int t = c.lane & 3;
    const int p = nb * 128 + c.rank * 64 + c.wg * 32 + c.wq * 8 + (c.lane >> 2);
    uint32_t cw[4];
    lds128(cw, c.sb + S_COEF + (p & 63) * 16);
    const float4 cf = make_float4(__uint_as_float(cw[0]), __uint_as_float(cw[1]), __uint_as_float(cw[2]), __uint_as_float(cw[3]));
    TSTAMP(1)
    const float2 lam = make_float2(cf.x, P.swap_ri ? -cf.y : cf.y);
    const float a0 = P.swap_ri ? -2.f * cf.w : 2.f * cf.z, a1 = P.swap_ri ? 2.f * cf.z : -2.f * cf.w;
    const float b0 = P.swap_ri ? -2.f * cf.z : -2.f * cf.w, b1 = P.swap_ri ? -2.f * cf.w : -2.f * cf.z;
    float2 h = make_float2(0.f, 0.f);
#pragma unroll
    for (int round = 0; round < 2; round++) {
#pragma unroll
        for (int j = 0; j < 32; j++) {
            h = cfma(lam, h, make_float2(acc[j * 4], acc[j * 4 + 2]));
            const float r0 = fmaf(a0, h.x, a1 * h.y), m0 = fmaf(b0, h.x, b1 * h.y);
            h = cfma(lam, h, make_float2(acc[j * 4 + 1], acc[j * 4 + 3]));
            d.pk[j * 2] = pack2(r0, fmaf(a0, h.x, a1 * h.y));
            d.pk[j * 2 + 1] = pack2(m0, fmaf(b0, h.x, b1 * h.y));
        }
        if (round) break;
        float2 l64 = lam;
#pragma unroll
        for (int i = 0; i < 6; i++) l64 = cmul(l64, l64);
        const float2 l128 = cmul(l64, l64), l256 = cmul(l128, l128);
        float2 o = make_float2(__shfl_up_sync(0xffffffffu, h.x, 1), __shfl_up_sync(0xffffffffu, h.y, 1));
        if (t >= 1) h = cfma(l64, o, h);
        o = make_float2(__shfl_up_sync(0xffffffffu, h.x, 2), __shfl_up_sync(0xffffffffu, h.y, 2));
        if (t >= 2) h = cfma(l128, o, h);
        TSTAMP(2)
        if (t == 3) st_relaxed2(&g_agg[mb * 1024 + p], (__float_as_uint(h.x) & ~1u) | atag, __float_as_uint(h.y));
        h = make_float2(__shfl_up_sync(0xffffffffu, h.x, 1), __shfl_up_sync(0xffffffffu, h.y, 1));
        if (t == 0) h = make_float2(0.f, 0.f);
        uint32_t ax[7], ay[7];
        int n = 0;
        while (true) {
            uint32_t bad = 0;
#pragma unroll
            for (int j = 0; j < 7; j++) { ax[j] = atag; ay[j] = 0; ld_relaxed2_if(ax[j], ay[j], &g_agg[j * 1024 + p], j < mb); }
#pragma unroll
            for (int j = 0; j < 7; j++) bad |= ax[j] ^ atag;
            if (tags_ok(bad)) break;
            __nanosleep(400);
            if (++n > SPIN_LIMIT) spin_fault();
        }
        float2 carry = make_float2(0.f, 0.f);
#pragma unroll
        for (int j = 0; j < 7; j++) if (j < mb) carry = cfma(l256, carry, make_float2(__uint_as_float(ax[j]), __uint_as_float(ay[j])));
        float2 w = (t & 1) ? l64 : make_float2(1.f, 0.f);
        if (t & 2) w = cmul(w, l128);
        h = cfma(w, carry, h);
        TSTAMP(3)
    }
    TSTAMP(4)
    d.kind = PEND_HT; d.row = nb * 128 + c.rank * 64 + c.wg * 32; d.col = mb * 256; d.cnt = C_HT + mb * 2 + (nb >> 2);
}

__device__ __forceinline__ uint32_t acquire_stage(uint32_t sb, Pipe& p, uint32_t bytes) {
    mbar_wait(sb + B_EMPTY + p.stage * 8, p.phase ^ 1);
    mbar_expect(sb + B_FULL + p.stage * 8, bytes);
    return p.stage;
}
#define AHEAD 1
__device__ __forceinline__ void watcher(const Params& P, const uint32_t sb, const int rank, const int lane) {
    const uint32_t epoch = ld_relaxed1(&g_cnt(C_EPOCH)), e1 = epoch + 1;
    sts32(sb + S_EPOCH, epoch);
    __syncwarp();
    if (lane == 0 && atomicInc(&g_cnt(C_DONE), (DBGF(32) ? 95 : NPAIR * 2 - 1) + (epoch & P.zero)) == (DBGF(32) ? 95 : NPAIR * 2 - 1)) atomicAdd(&g_cnt(C_EPOCH), 1);
    if (gridDim.x != 96) {
        uint32_t v;
        asm("mov.u32 %0, %%smid;" : "=r"(v));
        if (lane == 0 && rank == 0) st_relaxed1(g_hint + 6272 + (blockIdx.x >> 1), e1 << 8 | v >> 1);
        for (int k = 0;; k++) {
            __nanosleep(1000);
            v = ld_relaxed1(g_hint + 6272 + min(lane, 17));
            if (__all_sync(0xffffffffu, (v ^ e1 << 8) < 256)) break;
            if (k > SPIN_LIMIT) spin_fault();
        }
        const uint32_t key = ((v & 255) >= 62 ? 0 : tpc_gpc(v & 255)) * 32 + lane;
        sts32(sb + S_TAIL, 48 + __popc(__ballot_sync(0xffffffffu, key < __shfl_sync(0xffffffffu, key, blockIdx.x >> 1)) & 0x3ffff));
        __syncwarp();
    }
    uint32_t met = 1;
    if (lane == 0) asm volatile("st.release.cta.shared.u32 [%0], 1;" ::"r"(sb + S_DEP) : "memory");
    const int pair = lds32(sb + S_TAIL), first = ITEM_OFF(pair) + (pair < NCHAIN ? NPRE + 1 : 1);
#pragma unroll 1
    for (int it = first; it < ITEM_OFF(pair + 1); it++) {
        const int item = ITEM(it), type = item >> 8, mb = (item >> 5) & 7, nb = item & 31;
        const int n = (0x24021420 >> (type * 4)) & 7;
        for (int k = 0; it > first && (int)lds32(sb + S_CUR) < it - AHEAD; k++) { __nanosleep(200); if (k > SPIN_LIMIT) spin_fault(); }
#pragma unroll 1
        for (int i = 0; i < n; i++) {
            int idx = n == 4 ? C_O + mb * 4 + i : C_HT + mb * 2 + i;
            uint32_t target = e1 * 16;
            if (type == T_A1) { idx = C_COEF; target = e1 * 4; }
            if (type == T_QA) {
                idx = i ? C_FLAG + (lane & 1) * 32 + nb * 2 + ((lane >> 1) & 1) : C_KV + mb;
                target = i ? epoch * 64 + mb * 8 + rank * 4 + 4 : e1 * 128;
            }
            if (lane < 4) { wait_count(&g_cnt(idx), target); fence_async(); }
            __syncwarp();
            if (lane == 0) asm volatile("st.release.cta.shared.u32 [%0], %1;" ::"r"(sb + S_DEP), "r"(++met) : "memory");
        }
    }
}
__device__ __forceinline__ bool dep_met(uint32_t sb, uint32_t n) { uint32_t v; asm volatile("ld.acquire.cta.shared.u32 %0, [%1];" : "=r"(v) : "r"(sb + S_DEP) : "memory"); return v >= n; }
__device__ __forceinline__ void dep_wait(uint32_t sb, uint32_t n) { for (int k = 0; !dep_met(sb, n); k++) { __nanosleep(32); if (k > SPIN_LIMIT * 8) spin_fault(); } }
__device__ __forceinline__ void producer(const Params& P, const uint32_t sb, int pair, const int rank) {
    Pipe p = {0, 0};
    uint32_t dep = 1;
    for (int it = ITEM_OFF(pair); it < ITEM_OFF(pair + 1); it++) {
        const int item = ITEM(it), type = item >> 8, mb = (item >> 5) & 7, nb = item & 31;
        if (type == T_CHAIN) {
            sts32(sb + S_CUR, 0);
            const uint32_t epoch = ld_relaxed1(&g_cnt(C_EPOCH)), e1 = epoch + 1;
            const int role = pair >> 4, h = (pair & 15) * 2 + rank;
#pragma unroll 1
            for (int i = 0, q = 0; i < 8; i++) {
                const int n = (0x13003333 >> (i * 4)) & 3;
                const uint32_t st = acquire_stage(sb, p, n * 16384);
                SSTAMP(1, i == 0) SSTAMP(3, i == 3)
#pragma unroll 1
                for (int k = 0; k < 2 * n; k++, q++)
                    tma3d(sb + st * STAGE + k * 8192, &P.tm[M_CQ + role], h * 128 + (fill_unit(q >> 1) & 1) * 64, word_col((fill_unit(q >> 1) & 14) + (q & 1)) & 8, word_col((fill_unit(q >> 1) & 14) + (q & 1)) >> 4, sb + B_FULL + st * 8);
                pipe_next(p);
            }
            if (role == 0 && !DBGF(1)) { wait_count(&g_cnt(C_KV), e1 * 128); fence_async(); }
            mbar_wait(sb + B_EMPTY + 16, 1); mbar_wait(sb + B_EMPTY + 24, 1);
            mbar_expect(sb + B_WO, role ? 98304 : 65536);
            if (role == 0) { mbar_expect(sb + B_KVFULL, 16384); mbar_expect(sb + B_KVFULL + 8, 16384); }
#pragma unroll 1
            for (int k = role ? 0 : -4; k < 12; k++) {
                const bool kv = role == 0 && (k & 8);
                const int sg = k > 0;
                tma4d(kv ? sb + S_KV + sg * 16384 + (k & 3) * 4096 : sb + S_W2 + k * 8192, &P.tm[kv ? M_KV4 : M_CO + (k & 1)],
                      kv ? h * 128 + (k & 1) * 64 : (role == 0 ? 0 : role == 1 ? 256 : 640) + (k >> 1) * 64, kv ? (k & 2) * 1024 + sg * 32 : h * 8, sb + (kv ? B_KVFULL + sg * 8 : B_WO));
            }
            SSTAMP(5, true)
            if (pair < 16) {
#pragma unroll 1
                for (int s = 2; s < 63; s++) {
                    mbar_wait(sb + B_KVGO + (s & 1) * 8, ((s >> 1) + 1) & 1);
                    wait_time(gtime() + P.dk, sb);
                    SSTAMP(6, s == 2)
                    const uint32_t bar = sb + B_KVFULL + (s & 1) * 8, dst = sb + S_KV + (s & 1) * 16384;
                    if (DBGF(2)) { mbar_arrive(bar); continue; }
                    mbar_expect(bar, 16384);
#pragma unroll 1
                    for (int i = 0; i < 4; i++) tma2d(dst + i * 4096, &P.tm[M_KVO], (pair * 2 + rank) * 128 + (i & 1) * 64, (i >> 1) * 2048 + (DBGF(32 | 512) ? s & 7 : s) * 32, bar);
                    if ((s & 7) == 7 && !DBGF(1)) { wait_count(&g_cnt(C_KV + 1 + (s >> 3)), e1 * 128); fence_async(); }
                }
            } else {
                uint32_t* flag = &g_cnt(C_FLAG + pair * 2 + rank - 32);
                const int x = pair * 2 + rank - 32;
#pragma unroll 1
                for (int s = 0; s < 64; s++) {
                    mbar_wait(sb + B_PERS, s & 1);
                    if (s < 63) wait_time(gtime() + P.dp, sb);
                    if (!DBGF(4)) bulk_s2g((role == 1 ? g_km : g_vmt) + (s * 32 + h) * 512, sb + S_QX, 2048);
                    if (s < 57) {
                        uint8_t* m = P.gm + ((s + 6) & 7) * M_SLOT + (x >> 1) * 1024 + (x & 1) * 256;
                        bulk_s2g(m, sb + S_SX, 256); bulk_s2g(m + 512, sb + S_SX, 128);
                        bulk_s2g(g_f + ((s + 6) & 7) * F_SLOT + x * 768, sb + S_SX + 256, 768);
                    }
                    bulk_commit();
                    bulk_wait_read();
                    mbar_arrive(sb + B_KVGO);
                    bulk_wait_all();
                    fence_async();
                    if ((s & 3) == 3) st_relaxed1(flag, epoch * 64 + s + 1);
                }
            }
            mbar_wait(sb + B_RESUME, 0);
            pair = lds32(sb + S_TAIL);
            it = ITEM_OFF(pair) + NPRE;
            continue;
        }
        if (it == ITEM_OFF(pair) && pair >= NCHAIN) it = -1; else sts32(sb + S_CUR, it);
        const int m0 = mb * 256 + rank * 128;
        if (type <= T_OP) {
            const CUtensorMap* ma = &P.tm[type == T_OP ? M_OA : M_BX];
            const CUtensorMap* mw = &P.tm[type == T_OP ? M_WO : type == T_QA ? M_WQ : nb < 16 ? M_WK : M_WV];
            const int nk = type == T_OP ? 64 : 16, nc = (nb & 15) * 4 + rank * 2, ma0 = type == T_OP ? 4096 + m0 : m0;
#pragma unroll 1
            for (int kt = 0; kt < nk; kt++) {
                if (type == T_OP && (kt & 15) == 0) dep_wait(sb, ++dep);
                if (DBGF(256) && pair >= NCHAIN) { acquire_stage(sb, p, 0); pipe_next(p); continue; }
                const uint32_t st = acquire_stage(sb, p, STAGE), bar = sb + B_FULL + st * 8;
                tma2d(sb + st * STAGE, ma, kt * 64, ma0, bar);
                tma3d_mc(sb + st * STAGE + 16384 + rank * 16384, mw, 0, kt * 64, nc, bar);
                pipe_next(p);
            }
            if (type == T_QA) {
                dep += 2;
                dep_wait(sb, dep);
#pragma unroll 1
                for (int e = 0; e < 4; e++) {
                    const uint32_t st = acquire_stage(sb, p, 40960), bar = sb + B_FULL + st * 8, dst = sb + st * STAGE;
                    tma2d(dst, &P.tm[M_OA], nb * 256 + (e >> 1) * 128, (e & 1) * 2048 + m0, bar);
                    tma2d(dst + 16384, &P.tm[M_OA], nb * 256 + (e >> 1) * 128 + 64, (e & 1) * 2048 + m0, bar);
                    const uint32_t* src = ((e & 1) ? g_vmt : g_km) + ((mb * 8 + rank * 4) * 32 + nb * 2 + (e >> 1)) * 512;
#pragma unroll 1
                    for (int i = 0; i < 4; i++) bulk_g2s(dst + 32768 + i * 2048, src + i * 32 * 512, 2048, bar);
                    pipe_next(p);
                }
            }
        } else if (type == T_OPH) {
#pragma unroll 1
            for (int kt = 0; kt < 64; kt++) {
                if ((kt & 15) == 0) dep_wait(sb, ++dep);
                const uint32_t st = acquire_stage(sb, p, 32768), bar = sb + B_FULL + st * 8;
                tma2d(sb + st * STAGE, &P.tm[M_OA], kt * 64, 4096 + m0, bar);
                tma2d_mc(sb + st * STAGE + 16384 + rank * 8192, &P.tm[M_WOH], nb * 128 + rank * 64, kt * 64, bar);
                pipe_next(p);
            }
        } else if (type == T_A1) {
#pragma unroll 1
            for (int kt = 0; kt < 16; kt++) {
                if (kt == 15) dep_wait(sb, ++dep);
                const uint32_t st = acquire_stage(sb, p, kt == 15 ? STAGE + 1024 : STAGE), bar = sb + B_FULL + st * 8;
                if (kt == 15) bulk_g2s(sb + S_COEF, g_coef + nb * 128 + rank * 64, 1024, bar);
                tma4d(sb + st * STAGE, &P.tm[M_AB], kt * 64, nb * 16 + rank * 8, bar);
                tma4d_mc(sb + st * STAGE + 16384 + rank * 16384, &P.tm[M_AX], kt * 64, mb * 128 + rank * 16, bar);
                pipe_next(p);
            }
        } else {
            const int hw = type == T_A2H ? 64 : 128;
            const CUtensorMap* mc = &P.tm[type == T_A2H ? M_CREH : M_CRE];
#pragma unroll 1
            for (int kt = 0; kt < 32; kt++) {
                if ((kt & 15) == 0) dep_wait(sb, ++dep);
                const uint32_t st = acquire_stage(sb, p, 16384 + hw * 256), bar = sb + B_FULL + st * 8;
                tma3d(sb + st * STAGE, &P.tm[M_HT], 0, (kt & 1) * 1024 + (kt >> 1) * 64, mb * 4 + rank * 2, bar);
                tma2d_mc(sb + st * STAGE + 16384 + rank * hw * 128, mc + (kt & 1), (kt >> 1) * 64, (nb * 2 + rank) * hw, bar);
                pipe_next(p);
            }
#pragma unroll 1
            for (int col = nb * 2 * hw; col < (nb + 1) * 2 * hw; col += 128) {
                const uint32_t st = acquire_stage(sb, p, 32768 + 256), bar = sb + B_FULL + st * 8;
                tma4d(sb + st * STAGE, &P.tm[M_AX], col, mb * 128 + rank * 16, bar);
                tma4d(sb + st * STAGE + 16384, &P.tm[M_AX], col + 64, mb * 128 + rank * 16, bar);
                bulk_g2s(sb + st * STAGE + 32768, P.Dskip + col, 256, bar);
                pipe_next(p);
            }
        }
        if (it < 0) { dep_wait(sb, 1); pair = lds32(sb + S_TAIL); it = ITEM_OFF(pair); }
    }
}

__device__ __forceinline__ uint32_t fresh_tid() { uint32_t t; asm volatile("mov.u32 %0, %%tid.x;" : "=r"(t)); return t; }
__device__ __forceinline__ uint32_t fresh_ctaid() { uint32_t t; asm volatile("mov.u32 %0, %%ctaid.x;" : "=r"(t)); return logical_cta(t); }
__device__ __forceinline__ void reset_state(Cons& c, Pend& d, uint32_t sb, bool resumed) {
    const uint32_t t = fresh_tid(), b = fresh_ctaid();
    const int w = __shfl_sync(0xffffffffu, t >> 5, 0);
    c.sb = sb; c.wg = w >> 2; c.wq = w & 3; c.lane = t & 31;
    c.rank = __shfl_sync(0xffffffffu, b & 1, 0); c.pair = __shfl_sync(0xffffffffu, resumed && b < NCHAIN * 2 ? lds32(sb + S_TAIL) : b >> 1, 0);
    c.rel = mapa(sb + B_EMPTY, cluster_rank() ^ (c.lane & 1));
    c.p.stage = 0; c.p.phase = 0;
    c.nst = resumed && c.pair < NCHAIN ? 2 * NPRE : 0;
    d = Pend{};
}
#define PROF_ITEM(i)
#define PROF_MAIN(i)

__global__ void __launch_bounds__(384, 1) fused_kernel(const __grid_constant__ Params P) {
    extern __shared__ __align__(1024) uint8_t smem[];
    const uint32_t sb = smem_u32(smem);
    asm volatile("griddepcontrol.launch_dependents;");
    const int tid = threadIdx.x, lane = tid & 31;
    const int warp = __shfl_sync(0xffffffffu, tid >> 5, 0);
    const int pair = __shfl_sync(0xffffffffu, logical_cta(blockIdx.x) >> 1, 0), rank = __shfl_sync(0xffffffffu, blockIdx.x & 1, 0);
    if (tid == 0) {
        if (sb & 1023) spin_fault();
        sts32(sb + S_DEP, 0); sts32(sb + S_CUR, 0); sts32(sb + S_TAIL, pair); sts32(sb + S_CTA, pair * 2 + rank);
        for (int i = 0; i < NSTAGE; i++) { mbar_init(sb + B_FULL + i * 8, 1); mbar_init(sb + B_EMPTY + i * 8, 16); }
        mbar_init(sb + B_RESUME, 2);
        mbar_init(sb + B_KVFULL, 1); mbar_init(sb + B_KVFULL + 8, 1);
        mbar_init(sb + B_GO, 1); mbar_init(sb + B_KVGO, 1); mbar_init(sb + B_KVGO + 8, 1); mbar_init(sb + B_K, 1); mbar_init(sb + B_V, 1); mbar_init(sb + B_PERS, 8); mbar_init(sb + B_INIT, 3);
        mbar_init(sb + B_WO, 1);
        for (int i = 0; i < 2; i++) { mbar_init(sb + B_SFULL + i * 8, 4); mbar_init(sb + B_SFREE + i * 8, 1); }
        mbar_init(sb + B_RELA, 1); mbar_init(sb + B_RELB, 1);
        asm volatile("fence.mbarrier_init.release.cluster;" ::: "memory");
        if (pair < 16) mbar_expect(sb + B_K, 2048);
        mbar_expect(sb + B_V, 2048);
    }
    cluster_sync();
    if (warp >= 8) {
        asm volatile("setmaxnreg.dec.sync.aligned.u32 24;");
        if (warp == 10 && lane < M_COUNT) map_prefetch(&P.tm[lane]);
        if (warp == 11 && lane == 0 && pair < NCHAIN) {
            const uint32_t t0 = gtime();
            const int role = pair >> 4, h = (pair & 15) * 2 + rank;
#pragma unroll 1
            for (int i = role ? 32 : 0; i < (role ? 44 : 40); i++) {
                wait_time(t0 + P.pf0 + min(i, 32) * P.pf1 + max(i - 32, 0) * P.pf2, sb);
                if (i < 32) asm volatile("cp.async.bulk.prefetch.tensor.3d.L2.global [%0, {%1, %2, %3}];" ::"l"(&P.tm[M_CQ]), "r"(h * 128 + (i & 1) * 64), "r"((i & 2) * 4), "r"((i >> 2) * 8) : "memory");
                else asm volatile("cp.async.bulk.prefetch.tensor.4d.L2.global [%0, {%1, 0, 0, %2}];" ::"l"(&P.tm[M_CO + (i & 1)]), "r"((role == 0 ? 0 : role == 1 ? 256 : 640) + ((i - 32) >> 1) * 64), "r"(h * 8) : "memory");
            }
        }
        if (warp == 9 && pair < NCHAIN) pacer(P, sb, lane);
        if (warp == 9) watcher(P, sb, rank, lane);
        if (warp >= 10 && lane == 0) store_warp(P, sb, warp - 10);
        if (warp == 8) {
            if (lane == 0) producer(P, sb, lds32(sb + S_CTA) >> 1, rank);
            __syncwarp();
            asm volatile("barrier.cluster.arrive.relaxed.aligned;\nbarrier.cluster.wait.aligned;" ::: "memory");
        }
    } else {
        asm volatile("setmaxnreg.inc.sync.aligned.u32 240;");
        Cons c;
        Pend d;
        if (pair < NCHAIN) {
            mem0_max(P, sb, tid);
            reset_state(c, d, sb, false);
#pragma unroll 1
            for (int i = 0; i < NPRE; i++) {
                PROF_ITEM(i)
                const int item = ITEM(ITEM_OFF(pair) + i);
                float acc[128];
                mainloop<256, true>(acc, P, c, d, T_KV);
                epi_kv(acc, c, d, (item >> 5) & 7, item & 31);
            }
            ISTAMP(4)
            drain<0, true>(P, c, d);
            drain<1, true>(P, c, d);
            PROF_ITEM(NPRE)
            uint32_t wr[NR][4];
            load_weights(wr, sb, warp, lane, [&]() { staging_wait(c); });
            const int h = (pair & 15) * 2 + rank;
            if (pair < 16) chain_role<0>(P, wr, sb, h, warp, lane);
            else if (pair < 32) chain_role<1>(P, wr, sb, h, warp, lane);
            else chain_role<2>(P, wr, sb, h, warp, lane);
            fence_async_smem();
            bar_sync(1, 256);
            const uint32_t t2 = fresh_tid();
            if (t2 < 2) mbar_arrive_cluster(mapa(sb + B_RESUME, cluster_rank() ^ t2));
        } else if (pair >= NPAIR - 2) {
            const int ch = (pair - (NPAIR - 2)) * 512 + rank * 256 + tid;
            g_coef[ch] = ssm_coef(__bfloat162float(P.Lre[ch]), __bfloat162float(P.Lim[ch]), __bfloat162float(P.logdt[ch]));
            bar_sync(1, 256);
            if (tid == 0) red_release(&g_cnt(C_COEF));
        }
        reset_state(c, d, sb, true);
        for (int it = ITEM_OFF(c.pair) + (c.pair < NCHAIN ? NPRE + 1 : 0);; it++) {
            const bool last = it == ITEM_OFF(c.pair + 1);
            if (d.kind != PEND_NONE && (last || !bar_and(5 + c.wg, mbar_test(sb + B_FULL + c.p.stage * 8, c.p.phase)))) drain_all(P, c, d);
            if (last) break;
            const int item = ITEM(it), type = item >> 8, mb = (item >> 5) & 7, nb = item & 31;
            PROF_ITEM(it - ITEM_OFF(c.pair))
            if (type >= T_OPH) {
                float acc[64];
                mainloop<128>(acc, P, c, d, type);
                PROF_MAIN(it - ITEM_OFF(c.pair))
                if (type == T_OPH) epi_oph(acc, c, d, mb, nb);
                else epi_a2_half<0>(acc, P, c, mb, nb * 128);
            } else {
                float acc[128];
                mainloop<256>(acc, P, c, d, type);
                PROF_MAIN(it - ITEM_OFF(c.pair))
                if (type == T_KV) epi_kv(acc, c, d, mb, nb);
                else if (type == T_QA) epi_qa(acc, c, d, mb, nb);
                else if (type == T_OP) epi_op(acc, c, d, mb, nb);
                else if (type == T_A1) epi_a1(acc, P, c, d, mb, nb, (lds32(sb + S_EPOCH) + 1) & 1);
                else { epi_a2_half<0>(acc, P, c, mb, nb * 256); epi_a2_half<1>(acc, P, c, mb, nb * 256); }
            }
            if (it == ITEM_OFF(c.pair)) { dep_wait(sb, 1); c.pair = __shfl_sync(0xffffffffu, lds32(sb + S_TAIL), 0); it = ITEM_OFF(c.pair); }
        }
        staging_wait(c);
        staging_post(c, PEND_NONE, 0, 0, 0);
        asm volatile("barrier.cluster.arrive.relaxed.aligned;\nbarrier.cluster.wait.aligned;" ::: "memory");
    }
}

typedef CUresult (*EncodeFn)(CUtensorMap*, CUtensorMapDataType, cuuint32_t, void*, const cuuint64_t*, const cuuint64_t*, const cuuint32_t*, const cuuint32_t*,
                             CUtensorMapInterleave, CUtensorMapSwizzle, CUtensorMapL2promotion, CUtensorMapFloatOOBfill);
void encode(EncodeFn fn, CUtensorMap* m, const void* base, int rank, const uint64_t* dims, const uint64_t* strides, const uint32_t* box, CUtensorMapSwizzle swz = CU_TENSOR_MAP_SWIZZLE_128B) {
    cuuint64_t d[5], s[5]; cuuint32_t b[5], e[5];
    for (int i = 0; i < rank; i++) { d[i] = dims[i]; b[i] = box[i]; e[i] = 1; if (i) s[i - 1] = strides[i - 1]; }
    fn(m, CU_TENSOR_MAP_DATA_TYPE_BFLOAT16, rank, (void*)base, d, s, b, e, CU_TENSOR_MAP_INTERLEAVE_NONE, swz,
       CU_TENSOR_MAP_L2_PROMOTION_L2_256B, CU_TENSOR_MAP_FLOAT_OOB_FILL_NONE);
}
void map_kmajor(EncodeFn fn, CUtensorMap* m, const void* base, uint64_t rows, uint64_t cols, uint32_t box_rows) {
    const uint64_t d[2] = {cols, rows}, s[1] = {cols * 2}; const uint32_t b[2] = {64, box_rows};
    encode(fn, m, base, 2, d, s, b);
}
void map_mnmajor(EncodeFn fn, CUtensorMap* m, const void* base, uint64_t krows, uint64_t cols) {
    const uint64_t d[3] = {64, krows, cols / 64}, s[2] = {cols * 2, 128}; const uint32_t b[3] = {64, 64, 2};
    encode(fn, m, base, 3, d, s, b);
}

}

extern "C" void kernel_launch(void* const* d_in, const int* in_sizes, int n_in, void* d_out, int out_size) {
    static Params P;
    static EncodeFn fn = nullptr;
    if (!fn) {
        cudaDriverEntryPointQueryResult q;
        cudaGetDriverEntryPoint("cuTensorMapEncodeTiled", (void**)&fn, cudaEnableDefault, &q);
        cudaFuncSetAttribute(fused_kernel, cudaFuncAttributeMaxDynamicSharedMemorySize, S_TOTAL);
    }
    const bf16* in[15];
    for (int i = 0; i < 15; i++) in[i] = (const bf16*)d_in[i];
    void *kvo, *ht, *gm;
    cudaGetSymbolAddress(&gm, g_m);
    P.gm = (uint8_t*)(((uintptr_t)gm + 32767) & ~(uintptr_t)32767);
    cudaGetSymbolAddress(&kvo, g_kvo);
    cudaGetSymbolAddress(&ht, g_ht);
    map_kmajor(fn, &P.tm[M_BX], in[9], 2048, 1024, 128);
    map_mnmajor(fn, &P.tm[M_WQ], in[11], 1024, 4096);
    map_mnmajor(fn, &P.tm[M_WK], in[12], 1024, 4096);
    map_mnmajor(fn, &P.tm[M_WV], in[13], 1024, 4096);
    map_mnmajor(fn, &P.tm[M_WO], in[14], 4096, 1024);
    map_kmajor(fn, &P.tm[M_OA], kvo, 3 * 2048, 4096, 128);
    P.swap_ri = in[4] < in[3];
    {
        const bf16* lo = P.swap_ri ? in[4] : in[3];
        const uint64_t diff = (uint64_t)((const char*)(P.swap_ri ? in[3] : in[4]) - (const char*)lo);
        const uint64_t d[4] = {1024, 8, 2, 128}, s[3] = {2048, diff, 16384}; const uint32_t b[4] = {64, 8, 2, 8};
        encode(fn, &P.tm[M_AB], lo, 4, d, s, b);
    }
    {
        const uint64_t d[4] = {1024, 2, 4, 1024}, s[3] = {2048, 64 * 2048, 4096}; const uint32_t b[4] = {64, 2, 4, 16};
        encode(fn, &P.tm[M_AX], in[0], 4, d, s, b);
    }
    map_mnmajor(fn, &P.tm[M_HT], ht, 2048, 2048);
    map_kmajor(fn, &P.tm[M_CRE], in[5], 1024, 1024, 128);
    map_kmajor(fn, &P.tm[M_CIM], in[6], 1024, 1024, 128);
    map_kmajor(fn, &P.tm[M_KVO], kvo, 3 * 2048, 4096, 32);
    map_kmajor(fn, &P.tm[M_HTS], ht, 2048, 2048, 32);
    map_kmajor(fn, &P.tm[M_WOH], in[14], 4096, 1024, 64);
    map_kmajor(fn, &P.tm[M_CREH], in[5], 1024, 1024, 64);
    map_kmajor(fn, &P.tm[M_CIMH], in[6], 1024, 1024, 64);
    for (int i = 0; i < 3; i++) {
        const uint64_t d[3] = {4096, 16, 64}, s[2] = {8192, 16 * 8192}; const uint32_t b[3] = {64, 8, 8};
        encode(fn, &P.tm[M_CQ + i], in[11 + i], 3, d, s, b);
    }
    {
        const uint64_t d[4] = {4096, 1, 1, 4096}, s[3] = {8192, 8192, 8192}; const uint32_t b[4] = {64, 1, 1, 32};
        encode(fn, &P.tm[M_KV4], kvo, 4, d, s, b);
    }
    for (int e = 0; e < 2; e++) {
        const uint64_t d[4] = {1024, 2, 4, 256}, s[3] = {8 * 2048, 2 * 2048, 16 * 2048}; const uint32_t b[4] = {64, 2, 4, 8};
        encode(fn, &P.tm[M_CO + e], in[14] + e * 1024, 4, d, s, b);
    }
    P.Wq = in[11]; P.Wk = in[12]; P.Wv = in[13]; P.Wo = in[14]; P.mem0 = in[10];
    P.Lre = in[1]; P.Lim = in[2]; P.logdt = in[7]; P.Dskip = in[8];
    P.out = (float*)d_out;
    P.two26 = 1u << 26;
    P.lag = 0x22023302;
    P.ds = 400; P.dc = 1600; P.alpha = 0.3f; P.extra = 200; P.da = 192; P.db = 432; P.dk = 800; P.dp = 1550; P.dv = 60; P.pf0 = 1500; P.pf1 = 175; P.pf2 = 450; P.back = 150; P.ds0 = 950;
    for (int i = 0; i < (DBGF(32) ? 1 : 2); i++) {
        cudaLaunchConfig_t cfg = {};
        cfg.gridDim = dim3(i ? 36 : 96); cfg.blockDim = dim3(384); cfg.dynamicSmemBytes = S_TOTAL; cfg.stream = cudaStreamPerThread;
        cudaLaunchAttribute at[2];
        at[0].id = cudaLaunchAttributeClusterDimension; at[0].val.clusterDim.x = i ? 2 : 6; at[0].val.clusterDim.y = at[0].val.clusterDim.z = 1;
        at[1].id = cudaLaunchAttributeProgrammaticStreamSerialization; at[1].val.programmaticStreamSerializationAllowed = 1;
        cfg.attrs = at; cfg.numAttrs = 1 + i;
        cudaLaunchKernelEx(&cfg, fused_kernel, P);
    }
}
```

```cpp
#include <cuda_runtime.h>
#include <cuda_bf16.h>
#include <cuda.h>
#include <stdint.h>
#include <string.h>

typedef __nv_bfloat16 bf16;

namespace {

#define POLL 200
constexpr int SPIN_LIMIT = 1 << 22;
constexpr int NPAIR = 66;
constexpr int NCHAIN = 48;
enum { T_KV = 0, T_QA = 1, T_OP = 2, T_A1 = 3, T_A2 = 4, T_CHAIN = 5, T_OPH = 6, T_A2H = 7 };
enum { M_BX = 0, M_WQ, M_WK, M_WV, M_WO, M_OA, M_AB, M_AX, M_HT, M_CRE, M_CIM, M_KVO, M_HTS, M_WOH, M_CREH, M_CIMH, M_CQ, M_CK, M_CV, M_CO, M_CO1, M_KV4, M_COUNT };
enum { C_KV = 0, C_HT = 8, C_DONE = 24, C_EPOCH = 25, C_COEF = 26, C_FLAG = 32, C_O = 96 };

struct Params {
    CUtensorMap tm[M_COUNT];
    const bf16 *Wq, *Wk, *Wv, *Wo, *mem0, *Lre, *Lim, *logdt, *Dskip;
    float* out;
    uint8_t* gm;
    int swap_ri, zero;
    uint32_t two26, lag;
    int ds, da, db, dk, dv, back, ds0, pf0, pf1, pf2, dc, extra, dp;
    float alpha;
#define DBGF(x) false
};

constexpr int NPRE = 1;
__constant__ uint16_t c_off[67] = {0, 5, 10, 15, 21, 25, 29, 35, 39, 43, 47, 51, 55, 59, 63, 67, 71, 76, 81, 86, 91, 95, 99, 103, 108, 112, 116, 120, 124, 128, 133, 137, 142, 147, 152, 157, 162, 166, 170, 175, 179, 183, 187, 191, 195, 200, 205, 209, 213, 232, 252, 272, 291, 311, 331, 349, 369, 389, 407, 427, 446, 466, 485, 505, 524, 543, 562};
__constant__ uint16_t c_items[640] = {
    32, 1280, 453, 492, 1056, 49, 1280, 485, 494, 1249, 34, 1280, 293, 301, 1120, 51, 1280, 458, 457, 428, 1959, 36, 1280, 896,
    642, 53, 1280, 898, 546, 38, 1280, 833, 961, 996, 1957, 55, 1280, 865, 578, 40, 1280, 495, 576, 57, 1280, 463, 579, 42,
    1280, 262, 675, 59, 1280, 264, 739, 44, 1280, 335, 608, 61, 1280, 897, 738, 46, 1280, 361, 707, 63, 1280, 265, 705, 0,
    1280, 388, 302, 1217, 1, 1280, 489, 493, 1248, 2, 1280, 391, 333, 1250, 3, 1280, 263, 459, 1088, 4, 1280, 866, 673, 5,
    1280, 931, 640, 6, 1280, 835, 737, 7, 1280, 899, 488, 1185, 8, 1280, 838, 643, 9, 1280, 839, 641, 10, 1280, 870, 672,
    11, 1280, 864, 515, 12, 1280, 871, 674, 13, 1280, 935, 933, 1219, 14, 1280, 772, 736, 15, 1280, 994, 964, 1091, 16, 1280,
    393, 332, 1216, 17, 1280, 484, 300, 1121, 18, 1280, 487, 364, 1058, 19, 1280, 423, 462, 1152, 20, 1280, 867, 544, 21, 1280,
    930, 545, 22, 1280, 900, 424, 1089, 23, 1280, 836, 577, 24, 1280, 903, 611, 25, 1280, 902, 609, 26, 1280, 928, 547, 27,
    1280, 869, 512, 28, 1280, 868, 901, 1251, 29, 1280, 932, 965, 1218, 30, 1280, 804, 704, 31, 1280, 962, 706, 33, 66, 84,
    102, 120, 138, 156, 230, 212, 188, 324, 352, 399, 422, 289, 425, 392, 490, 1024, 35, 67, 85, 103, 121, 139, 157, 175,
    200, 240, 252, 323, 254, 292, 418, 417, 386, 299, 365, 1956, 37, 68, 86, 104, 122, 140, 158, 165, 177, 238, 217, 226,
    334, 426, 366, 448, 449, 491, 430, 1123, 39, 69, 87, 105, 123, 141, 159, 176, 214, 161, 197, 198, 247, 234, 358, 288,
    321, 452, 514, 41, 70, 88, 106, 124, 142, 203, 227, 171, 192, 195, 206, 244, 325, 296, 420, 482, 268, 396, 1059, 43,
    71, 89, 107, 125, 143, 196, 179, 215, 166, 210, 202, 297, 363, 266, 326, 303, 455, 431, 1153, 45, 72, 90, 108, 126,
    144, 219, 180, 221, 190, 329, 231, 355, 356, 805, 837, 929, 610, 47, 73, 91, 109, 127, 145, 163, 181, 242, 169, 213,
    209, 232, 773, 832, 290, 480, 995, 966, 1057, 48, 74, 92, 110, 128, 146, 205, 182, 199, 164, 211, 207, 250, 256, 257,
    390, 389, 934, 997, 1090, 50, 75, 93, 111, 129, 147, 249, 183, 233, 248, 228, 223, 258, 771, 427, 421, 483, 513, 52,
    76, 94, 112, 130, 148, 173, 225, 172, 218, 201, 770, 774, 359, 775, 801, 963, 993, 397, 1958, 54, 77, 95, 113, 131,
    149, 167, 222, 237, 174, 362, 270, 394, 353, 807, 806, 960, 367, 1184, 56, 78, 96, 114, 132, 150, 168, 186, 235, 239,
    243, 255, 384, 245, 357, 387, 320, 486, 429, 1026, 58, 79, 97, 115, 133, 151, 191, 187, 236, 189, 267, 800, 224, 419,
    291, 295, 328, 269, 1027, 60, 80, 98, 116, 134, 152, 220, 178, 194, 208, 216, 322, 253, 398, 802, 803, 395, 454, 461,
    1155, 62, 81, 99, 117, 135, 153, 229, 170, 327, 204, 241, 768, 769, 260, 416, 481, 967, 999, 1122, 64, 82, 100, 118,
    136, 154, 160, 184, 271, 354, 259, 251, 261, 294, 450, 834, 992, 998, 1025, 65, 83, 101, 119, 137, 155, 185, 162, 298,
    246, 193, 385, 331, 330, 360, 451, 456, 460, 1154,
};
#define ITEM_OFF(p) c_off[p]
#define ITEM(i) c_items[i]

__device__ __align__(1024) bf16 g_kvo[3 * 2048 * 4096];
__device__ __align__(1024) bf16 g_ht[2048 * 2048];
__device__ __align__(1024) uint8_t g_m[9 * 32768];
__device__ __align__(1024) uint8_t g_f[8 * 49152];
__device__ __align__(1024) uint32_t g_km[64 * 32 * 512];
__device__ __align__(1024) uint32_t g_vmt[64 * 32 * 512];
__device__ __align__(1024) float2 g_agg[8 * 1024];
__device__ __align__(1024) float4 g_coef[1024];
__device__ __align__(1024) uint32_t g_cntl[128 * 32];
#define g_cnt(i) g_cntl[(i) * 32]
__device__ __align__(1024) uint32_t g_hint[6144 + 160];
#define SSTAMP(i, cond)
#define PROF(i)
#define GT_EDGE(o)
constexpr int M_SLOT = 32768, F_SLOT = 49152;

constexpr int STAGE = 49152, NSTAGE = 4;
constexpr int S_STG = NSTAGE * STAGE;
constexpr int S_BAR = S_STG + 32768;
constexpr int B_FULL = S_BAR, B_EMPTY = S_BAR + 32, B_RESUME = S_BAR + 64, B_KVFULL = S_BAR + 72, B_GO = S_BAR + 88, B_K = S_BAR + 96, B_PERS = S_BAR + 104, B_INIT = S_BAR + 112, B_RELA = S_BAR + 120, B_V = S_BAR + 128, B_WO = S_BAR + 136,
              B_SFULL = S_BAR + 144, B_SFREE = S_BAR + 160, S_DESC = S_BAR + 176, S_REDO = S_BAR + 256 + 512 + 64, S_EPOCH = S_BAR + 208, B_RELB = S_BAR + 216, B_KVGO = S_BAR + 224, S_DEP = S_BAR + 240, S_CUR = S_BAR + 244, S_TAIL = S_BAR + 248, S_CTA = S_BAR + 252;
constexpr int S_COEF = S_BAR + 256 + 512, S_TOTAL = S_COEF + 1024;
constexpr int S_W1 = 0;
constexpr int S_O = 24 * 4096, S_VL = S_O + 2048, S_MX = 25 * 4096, S_SC = S_MX + 64, S_SUM = S_MX + 128;
constexpr int S_KL = 26 * 4096;
constexpr int S_W2 = 27 * 4096;
constexpr int S_KV = S_W2 + 65536;
constexpr int S_P1 = S_W2 + 98304;
constexpr int S_QX = S_P1 + 16384;
constexpr int S_SX = S_QX + 2048;
static_assert(S_SX + 1280 <= S_BAR, "chain smem overlaps barriers");
constexpr int NR = 40, NS = 64 - NR;

__device__ __forceinline__ uint32_t logical_cta(uint32_t b) {
    const uint32_t c = b / 6, r = b - c * 6;
    return gridDim.x != 96 ? 96 + b : ((r >> 1) + (c >= 8) + (c >= 15)) % 3 * 32 + c * 2 + (r & 1);
}
__device__ __forceinline__ uint32_t cluster_rank() { uint32_t r; asm("mov.u32 %0, %%cluster_ctarank;" : "=r"(r)); return r; }
__device__ __forceinline__ uint16_t pair_mask() { return (uint16_t)(3u << (cluster_rank() & 6)); }
__device__ __forceinline__ void spin_fault() { asm volatile("st.global.u32 [%0], 0;" ::"l"(0ull) : "memory"); }
__device__ __forceinline__ uint32_t smem_u32(const void* p) { return (uint32_t)__cvta_generic_to_shared(p); }
__device__ __forceinline__ uint32_t opq(uint32_t x, int lane) { return __shfl_sync(0xffffffffu, x, lane); }
__device__ __forceinline__ uint32_t mapa(uint32_t a, uint32_t r) { uint32_t d; asm volatile("mapa.shared::cluster.u32 %0, %1, %2;" : "=r"(d) : "r"(a), "r"(r)); return d; }
__device__ __forceinline__ void mma16816(float* d, uint32_t a0, uint32_t a1, uint32_t a2, uint32_t a3, uint32_t b0, uint32_t b1) {
    asm("mma.sync.aligned.m16n8k16.row.col.f32.bf16.bf16.f32 {%0,%1,%2,%3}, {%4,%5,%6,%7}, {%8,%9}, {%0,%1,%2,%3};"
        : "+f"(d[0]), "+f"(d[1]), "+f"(d[2]), "+f"(d[3]) : "r"(a0), "r"(a1), "r"(a2), "r"(a3), "r"(b0), "r"(b1));
}
__device__ __forceinline__ void mma1688(float* d, uint32_t a0, uint32_t a1, uint32_t b0) {
    asm("mma.sync.aligned.m16n8k8.row.col.f32.bf16.bf16.f32 {%0,%1,%2,%3}, {%4,%5}, {%6}, {%0,%1,%2,%3};"
        : "+f"(d[0]), "+f"(d[1]), "+f"(d[2]), "+f"(d[3]) : "r"(a0), "r"(a1), "r"(b0));
}
__device__ __forceinline__ void ldsm4(uint32_t* r, uint32_t a) {
    asm volatile("ldmatrix.sync.aligned.m8n8.x4.shared.b16 {%0,%1,%2,%3}, [%4];" : "=r"(r[0]), "=r"(r[1]), "=r"(r[2]), "=r"(r[3]) : "r"(a));
}
__device__ __forceinline__ void ldsm4t(uint32_t* r, uint32_t a) {
    asm volatile("ldmatrix.sync.aligned.m8n8.x4.trans.shared.b16 {%0,%1,%2,%3}, [%4];" : "=r"(r[0]), "=r"(r[1]), "=r"(r[2]), "=r"(r[3]) : "r"(a));
}
__device__ __forceinline__ void stsm4(uint32_t a, uint32_t r0, uint32_t r1, uint32_t r2, uint32_t r3) {
    asm volatile("stmatrix.sync.aligned.m8n8.x4.shared.b16 [%0], {%1,%2,%3,%4};" ::"r"(a), "r"(r0), "r"(r1), "r"(r2), "r"(r3) : "memory");
}
__device__ __forceinline__ void stsm4t(uint32_t a, uint32_t r0, uint32_t r1, uint32_t r2, uint32_t r3) {
    asm volatile("stmatrix.sync.aligned.m8n8.x4.trans.shared.b16 [%0], {%1,%2,%3,%4};" ::"r"(a), "r"(r0), "r"(r1), "r"(r2), "r"(r3) : "memory");
}
__device__ __forceinline__ uint32_t pack2(float lo, float hi) { uint32_t d; asm("cvt.rn.bf16x2.f32 %0, %1, %2;" : "=r"(d) : "f"(hi), "f"(lo)); return d; }
__device__ __forceinline__ float bf_lo(uint32_t u) { return __uint_as_float(u << 16); }
__device__ __forceinline__ float bf_hi(uint32_t u) { return __uint_as_float(u & 0xffff0000u); }
__device__ __forceinline__ uint32_t hmul2(uint32_t a, uint32_t b) { uint32_t d; asm("mul.rn.bf16x2 %0, %1, %2;" : "=r"(d) : "r"(a), "r"(b)); return d; }
__device__ __forceinline__ float ex2(float x) { float y; asm("ex2.approx.ftz.f32 %0, %1;" : "=f"(y) : "f"(x)); return y; }
__device__ __forceinline__ float rcp(float x) { float y; asm("rcp.approx.ftz.f32 %0, %1;" : "=f"(y) : "f"(x)); return y; }
__device__ __forceinline__ void st_relaxed4(const void* p, uint32_t a, uint32_t b, uint32_t c, uint32_t d) {
    asm volatile("{\n.reg .b128 t;\nmov.b128 t, {%1,%2,%3,%4};\nst.relaxed.gpu.global.b128 [%0], t;\n}" ::"l"(p), "r"(a), "r"(b), "r"(c), "r"(d) : "memory");
}
__device__ __forceinline__ void st_relaxed2(const void* p, uint32_t a, uint32_t b) {
    asm volatile("{\n.reg .b64 t;\nmov.b64 t, {%1,%2};\nst.relaxed.gpu.global.b64 [%0], t;\n}" ::"l"(p), "r"(a), "r"(b) : "memory");
}
__device__ __forceinline__ void ld_relaxed2_if(uint32_t& a, uint32_t& b, const void* p, bool on) {
    asm volatile("{\n.reg .pred P;\n.reg .b64 t;\nsetp.ne.u32 P, %3, 0;\nmov.b64 t, {%0,%1};\n@P ld.relaxed.gpu.global.b64 t, [%2];\nmov.b64 {%0,%1}, t;\n}" : "+r"(a), "+r"(b) : "l"(p), "r"((uint32_t)on) : "memory");
}
__device__ __forceinline__ uint32_t ld_relaxed1(const void* p) { uint32_t v; asm volatile("ld.relaxed.gpu.global.u32 %0, [%1];" : "=r"(v) : "l"(p) : "memory"); return v; }
__device__ __forceinline__ void st_relaxed1(const void* p, uint32_t v) { asm volatile("st.relaxed.gpu.global.u32 [%0], %1;" ::"l"(p), "r"(v) : "memory"); }
__device__ __forceinline__ uint32_t ld_acquire(const void* p) { uint32_t v; asm volatile("ld.acquire.gpu.global.u32 %0, [%1];" : "=r"(v) : "l"(p) : "memory"); return v; }
__device__ __forceinline__ void red_release(void* p) { asm volatile("red.release.gpu.global.add.u32 [%0], 1;" ::"l"(p) : "memory"); }
__device__ __forceinline__ void st_stream2(float* p, float a, float b) { asm volatile("st.global.cs.v2.f32 [%0], {%1, %2};" ::"l"(p), "f"(a), "f"(b) : "memory"); }
__device__ __forceinline__ void fence_acquire() { asm volatile("fence.acquire.gpu;" ::: "memory"); }
__device__ __forceinline__ void fence_release() { asm volatile("fence.release.gpu;" ::: "memory"); }
__device__ __forceinline__ void fence_async() {  asm volatile("fence.proxy.async.global;" ::: "memory"); }
__device__ __forceinline__ void fence_async_smem() { asm volatile("fence.proxy.async.shared::cta;" ::: "memory"); }
__device__ __forceinline__ void wait_count(const uint32_t* p, uint32_t target) {
    int n = 0;
    while ((int32_t)(ld_acquire(p) - target) < 0) { __nanosleep(POLL); if (++n > SPIN_LIMIT) spin_fault(); }
}
__device__ __forceinline__ void bar_sync(int id, int n) { asm volatile("bar.sync %0, %1;" ::"r"(id), "r"(n) : "memory"); }
__device__ __forceinline__ void bar_arrive(int id, int n) { asm volatile("bar.arrive %0, %1;" ::"r"(id), "r"(n) : "memory"); }
__device__ __forceinline__ bool bar_and(int id, bool v) {
    uint32_t r;
    asm volatile("{\n.reg .pred P, Q;\nsetp.ne.u32 Q, %2, 0;\nbar.red.and.pred P, %1, 128, Q;\nselp.u32 %0, 1, 0, P;\n}" : "=r"(r) : "r"(id), "r"((uint32_t)v) : "memory");
    return r;
}
__device__ __forceinline__ void lds128(uint32_t* v, uint32_t a) { asm volatile("ld.shared.v4.b32 {%0,%1,%2,%3}, [%4];" : "=r"(v[0]), "=r"(v[1]), "=r"(v[2]), "=r"(v[3]) : "r"(a) : "memory"); }
__device__ __forceinline__ uint32_t lds32(uint32_t a) { uint32_t v; asm volatile("ld.shared.b32 %0, [%1];" : "=r"(v) : "r"(a) : "memory"); return v; }
__device__ __forceinline__ void lds64f(float* v, uint32_t a) { asm volatile("ld.shared.v2.f32 {%0,%1}, [%2];" : "=f"(v[0]), "=f"(v[1]) : "r"(a) : "memory"); }
__device__ __forceinline__ void sts128(uint32_t a, const uint32_t* v) { asm volatile("st.shared.v4.b32 [%0], {%1,%2,%3,%4};" ::"r"(a), "r"(v[0]), "r"(v[1]), "r"(v[2]), "r"(v[3]) : "memory"); }
__device__ __forceinline__ void sts64(uint32_t a, uint32_t x, uint32_t y) { asm volatile("st.shared.v2.b32 [%0], {%1,%2};" ::"r"(a), "r"(x), "r"(y) : "memory"); }
__device__ __forceinline__ void sts32(uint32_t a, uint32_t x) { asm volatile("st.shared.b32 [%0], %1;" ::"r"(a), "r"(x) : "memory"); }
__device__ __forceinline__ bool mbar_try(uint32_t b, uint32_t par) {
    uint32_t ok;
    asm volatile("{\n.reg .pred P;\nmbarrier.try_wait.parity.shared::cta.b64 P, [%1], %2;\nselp.u32 %0, 1, 0, P;\n}" : "=r"(ok) : "r"(b), "r"(par) : "memory");
    return ok;
}
__device__ __forceinline__ bool mbar_test(uint32_t b, uint32_t par) {
    uint32_t ok;
    asm volatile("{\n.reg .pred P;\nmbarrier.test_wait.parity.shared::cta.b64 P, [%1], %2;\nselp.u32 %0, 1, 0, P;\n}" : "=r"(ok) : "r"(b), "r"(par) : "memory");
    return ok;
}
__device__ __forceinline__ void mbar_wait(uint32_t b, uint32_t par) { int n = 0; while (!mbar_try(b, par)) { if (++n > SPIN_LIMIT) spin_fault(); } }
__device__ __forceinline__ void mbar_init(uint32_t b, uint32_t n) { asm volatile("mbarrier.init.shared::cta.b64 [%0], %1;" ::"r"(b), "r"(n) : "memory"); }
__device__ __forceinline__ void mbar_expect(uint32_t b, uint32_t bytes) { asm volatile("mbarrier.arrive.expect_tx.shared::cta.b64 _, [%0], %1;" ::"r"(b), "r"(bytes) : "memory"); }
__device__ __forceinline__ void mbar_arrive(uint32_t b) { asm volatile("mbarrier.arrive.shared::cta.b64 _, [%0];" ::"r"(b) : "memory"); }
__device__ __forceinline__ void mbar_arrive_cluster(uint32_t b) { asm volatile("mbarrier.arrive.shared::cluster.b64 _, [%0];" ::"r"(b) : "memory"); }
__device__ __forceinline__ void st_async1(uint32_t a, uint32_t x, uint32_t bar) {
    asm volatile("st.async.weak.shared::cluster.mbarrier::complete_tx::bytes.b32 [%0], %1, [%2];" ::"r"(a), "r"(x), "r"(bar) : "memory");
}
__device__ __forceinline__ void st_async2(uint32_t a, uint32_t x, uint32_t y, uint32_t bar) {
    asm volatile("st.async.weak.shared::cluster.mbarrier::complete_tx::bytes.v2.b32 [%0], {%1,%2}, [%3];" ::"r"(a), "r"(x), "r"(y), "r"(bar) : "memory");
}
__device__ __forceinline__ void cluster_sync() { asm volatile("barrier.cluster.arrive.aligned;\nbarrier.cluster.wait.aligned;" ::: "memory"); }
__device__ __forceinline__ void tma2d(uint32_t dst, const CUtensorMap* m, int c0, int c1, uint32_t bar) {
    asm volatile("cp.async.bulk.tensor.2d.shared::cluster.global.mbarrier::complete_tx::bytes [%0], [%1, {%2, %3}], [%4];" ::"r"(dst), "l"(m), "r"(c0), "r"(c1), "r"(bar) : "memory");
}
__device__ __forceinline__ void tma2d_mc(uint32_t dst, const CUtensorMap* m, int c0, int c1, uint32_t bar) {
    asm volatile("cp.async.bulk.tensor.2d.shared::cluster.global.mbarrier::complete_tx::bytes.multicast::cluster [%0], [%1, {%2, %3}], [%4], %5;" ::"r"(dst), "l"(m), "r"(c0), "r"(c1), "r"(bar), "h"(pair_mask()) : "memory");
}
__device__ __forceinline__ void tma3d(uint32_t dst, const CUtensorMap* m, int c0, int c1, int c2, uint32_t bar) {
    asm volatile("cp.async.bulk.tensor.3d.shared::cluster.global.mbarrier::complete_tx::bytes [%0], [%1, {%2, %3, %4}], [%5];" ::"r"(dst), "l"(m), "r"(c0), "r"(c1), "r"(c2), "r"(bar) : "memory");
}
__device__ __forceinline__ void tma3d_mc(uint32_t dst, const CUtensorMap* m, int c0, int c1, int c2, uint32_t bar) {
    asm volatile("cp.async.bulk.tensor.3d.shared::cluster.global.mbarrier::complete_tx::bytes.multicast::cluster [%0], [%1, {%2, %3, %4}], [%5], %6;" ::"r"(dst), "l"(m), "r"(c0), "r"(c1), "r"(c2), "r"(bar), "h"(pair_mask()) : "memory");
}
__device__ __forceinline__ void tma4d(uint32_t dst, const CUtensorMap* m, int c0, int c3, uint32_t bar) {
    asm volatile("cp.async.bulk.tensor.4d.shared::cluster.global.mbarrier::complete_tx::bytes [%0], [%1, {%2, 0, 0, %3}], [%4];" ::"r"(dst), "l"(m), "r"(c0), "r"(c3), "r"(bar) : "memory");
}
__device__ __forceinline__ void tma4d_mc(uint32_t dst, const CUtensorMap* m, int c0, int c3, uint32_t bar) {
    asm volatile("cp.async.bulk.tensor.4d.shared::cluster.global.mbarrier::complete_tx::bytes.multicast::cluster [%0], [%1, {%2, 0, 0, %3}], [%4], %5;" ::"r"(dst), "l"(m), "r"(c0), "r"(c3), "r"(bar), "h"(pair_mask()) : "memory");
}
__device__ __forceinline__ void map_prefetch(const CUtensorMap* m) { asm volatile("prefetch.tensormap [%0];" ::"l"(m) : "memory"); }
__device__ __forceinline__ void bulk_g2s(uint32_t dst, const void* src, uint32_t bytes, uint32_t bar) {
    asm volatile("cp.async.bulk.shared::cluster.global.mbarrier::complete_tx::bytes [%0], [%1], %2, [%3];" ::"r"(dst), "l"(src), "r"(bytes), "r"(bar) : "memory");
}
__device__ __forceinline__ void bulk_s2g(void* dst, uint32_t src, uint32_t bytes) {
    asm volatile("cp.async.bulk.global.shared::cta.bulk_group [%0], [%1], %2;" ::"l"(dst), "r"(src), "r"(bytes) : "memory");
}
__device__ __forceinline__ void tma_store2d(const CUtensorMap* m, int c0, int c1, uint32_t src) {
    asm volatile("cp.async.bulk.tensor.2d.global.shared::cta.bulk_group [%0, {%1, %2}], [%3];" ::"l"(m), "r"(c0), "r"(c1), "r"(src) : "memory");
}
__device__ __forceinline__ void bulk_commit() { asm volatile("cp.async.bulk.commit_group;" ::: "memory"); }
__device__ __forceinline__ void bulk_wait_read() { asm volatile("cp.async.bulk.wait_group.read 0;" ::: "memory"); }
__device__ __forceinline__ void bulk_wait_all() { asm volatile("cp.async.bulk.wait_group 0;" ::: "memory"); }
__device__ __forceinline__ uint64_t mkdesc(uint32_t addr, uint32_t lbo, uint32_t sbo, uint32_t swz) {
    return (uint64_t)((addr & 0x3FFFF) >> 4) | ((uint64_t)(lbo >> 4) << 16) | ((uint64_t)(sbo >> 4) << 32) | ((uint64_t)swz << 62);
}
__device__ __forceinline__ void wg_fence() { asm volatile("wgmma.fence.sync.aligned;" ::: "memory"); }
__device__ __forceinline__ void wg_commit() { asm volatile("wgmma.commit_group.sync.aligned;" ::: "memory"); }
template <int N> __device__ __forceinline__ void wg_wait() { asm volatile("wgmma.wait_group.sync.aligned %0;" ::"n"(N) : "memory"); }
template <typename T> __device__ __forceinline__ void pin_ptr(T*& p) { asm volatile("" : "+l"(p)); }
template <int N> __device__ __forceinline__ void pin(uint32_t* d) {
#pragma unroll
    for (int i = 0; i < N; i++) asm volatile("" : "+r"(d[i])::"memory");
}
template <int N> __device__ __forceinline__ void pin(float* d) {
#pragma unroll
    for (int i = 0; i < N; i++) asm volatile("" : "+f"(d[i])::"memory");
}

template <int TA, int TB>
__device__ __forceinline__ void wgmma_ss256(float* d, uint64_t da, uint64_t db) {
    asm volatile("wgmma.mma_async.sync.aligned.m64n256k16.f32.bf16.bf16 "
        "{%0, %1, %2, %3, %4, %5, %6, %7, %8, %9, %10, %11, %12, %13, %14, %15, %16, %17, %18, %19, %20, %21, %22, %23, %24, %25, %26, %27, %28, %29, %30, %31, %32, %33, %34, %35, %36, %37, %38, %39, %40, %41, %42, %43, %44, %45, %46, %47, %48, %49, %50, %51, %52, %53, %54, %55, %56, %57, %58, %59, %60, %61, %62, %63, %64, %65, %66, %67, %68, %69, %70, %71, %72, %73, %74, %75, %76, %77, %78, %79, %80, %81, %82, %83, %84, %85, %86, %87, %88, %89, %90, %91, %92, %93, %94, %95, %96, %97, %98, %99, %100, %101, %102, %103, %104, %105, %106, %107, %108, %109, %110, %111, %112, %113, %114, %115, %116, %117, %118, %119, %120, %121, %122, %123, %124, %125, %126, %127}, %128, %129, 1, 1, 1, %130, %131;"
        : "+f"(d[0]), "+f"(d[1]), "+f"(d[2]), "+f"(d[3]), "+f"(d[4]), "+f"(d[5]), "+f"(d[6]), "+f"(d[7]), "+f"(d[8]), "+f"(d[9]), "+f"(d[10]), "+f"(d[11]), "+f"(d[12]), "+f"(d[13]), "+f"(d[14]), "+f"(d[15]), "+f"(d[16]), "+f"(d[17]), "+f"(d[18]), "+f"(d[19]), "+f"(d[20]), "+f"(d[21]), "+f"(d[22]), "+f"(d[23]), "+f"(d[24]), "+f"(d[25]), "+f"(d[26]), "+f"(d[27]), "+f"(d[28]), "+f"(d[29]), "+f"(d[30]), "+f"(d[31]), "+f"(d[32]), "+f"(d[33]), "+f"(d[34]), "+f"(d[35]), "+f"(d[36]), "+f"(d[37]), "+f"(d[38]), "+f"(d[39]), "+f"(d[40]), "+f"(d[41]), "+f"(d[42]), "+f"(d[43]), "+f"(d[44]), "+f"(d[45]), "+f"(d[46]), "+f"(d[47]), "+f"(d[48]), "+f"(d[49]), "+f"(d[50]), "+f"(d[51]), "+f"(d[52]), "+f"(d[53]), "+f"(d[54]), "+f"(d[55]), "+f"(d[56]), "+f"(d[57]), "+f"(d[58]), "+f"(d[59]), "+f"(d[60]), "+f"(d[61]), "+f"(d[62]), "+f"(d[63]), "+f"(d[64]), "+f"(d[65]), "+f"(d[66]), "+f"(d[67]), "+f"(d[68]), "+f"(d[69]), "+f"(d[70]), "+f"(d[71]), "+f"(d[72]), "+f"(d[73]), "+f"(d[74]), "+f"(d[75]), "+f"(d[76]), "+f"(d[77]), "+f"(d[78]), "+f"(d[79]), "+f"(d[80]), "+f"(d[81]), "+f"(d[82]), "+f"(d[83]), "+f"(d[84]), "+f"(d[85]), "+f"(d[86]), "+f"(d[87]), "+f"(d[88]), "+f"(d[89]), "+f"(d[90]), "+f"(d[91]), "+f"(d[92]), "+f"(d[93]), "+f"(d[94]), "+f"(d[95]), "+f"(d[96]), "+f"(d[97]), "+f"(d[98]), "+f"(d[99]), "+f"(d[100]), "+f"(d[101]), "+f"(d[102]), "+f"(d[103]), "+f"(d[104]), "+f"(d[105]), "+f"(d[106]), "+f"(d[107]), "+f"(d[108]), "+f"(d[109]), "+f"(d[110]), "+f"(d[111]), "+f"(d[112]), "+f"(d[113]), "+f"(d[114]), "+f"(d[115]), "+f"(d[116]), "+f"(d[117]), "+f"(d[118]), "+f"(d[119]), "+f"(d[120]), "+f"(d[121]), "+f"(d[122]), "+f"(d[123]), "+f"(d[124]), "+f"(d[125]), "+f"(d[126]), "+f"(d[127])
        : "l"(da), "l"(db), "n"(TA), "n"(TB));
}
template <int TA, int TB>
__device__ __forceinline__ void wgmma_ss256_first(float* d, uint64_t da, uint64_t db) {
    asm volatile("wgmma.mma_async.sync.aligned.m64n256k16.f32.bf16.bf16 "
        "{%0, %1, %2, %3, %4, %5, %6, %7, %8, %9, %10, %11, %12, %13, %14, %15, %16, %17, %18, %19, %20, %21, %22, %23, %24, %25, %26, %27, %28, %29, %30, %31, %32, %33, %34, %35, %36, %37, %38, %39, %40, %41, %42, %43, %44, %45, %46, %47, %48, %49, %50, %51, %52, %53, %54, %55, %56, %57, %58, %59, %60, %61, %62, %63, %64, %65, %66, %67, %68, %69, %70, %71, %72, %73, %74, %75, %76, %77, %78, %79, %80, %81, %82, %83, %84, %85, %86, %87, %88, %89, %90, %91, %92, %93, %94, %95, %96, %97, %98, %99, %100, %101, %102, %103, %104, %105, %106, %107, %108, %109, %110, %111, %112, %113, %114, %115, %116, %117, %118, %119, %120, %121, %122, %123, %124, %125, %126, %127}, %128, %129, 0, 1, 1, %130, %131;"
        : "=f"(d[0]), "=f"(d[1]), "=f"(d[2]), "=f"(d[3]), "=f"(d[4]), "=f"(d[5]), "=f"(d[6]), "=f"(d[7]), "=f"(d[8]), "=f"(d[9]), "=f"(d[10]), "=f"(d[11]), "=f"(d[12]), "=f"(d[13]), "=f"(d[14]), "=f"(d[15]), "=f"(d[16]), "=f"(d[17]), "=f"(d[18]), "=f"(d[19]), "=f"(d[20]), "=f"(d[21]), "=f"(d[22]), "=f"(d[23]), "=f"(d[24]), "=f"(d[25]), "=f"(d[26]), "=f"(d[27]), "=f"(d[28]), "=f"(d[29]), "=f"(d[30]), "=f"(d[31]), "=f"(d[32]), "=f"(d[33]), "=f"(d[34]), "=f"(d[35]), "=f"(d[36]), "=f"(d[37]), "=f"(d[38]), "=f"(d[39]), "=f"(d[40]), "=f"(d[41]), "=f"(d[42]), "=f"(d[43]), "=f"(d[44]), "=f"(d[45]), "=f"(d[46]), "=f"(d[47]), "=f"(d[48]), "=f"(d[49]), "=f"(d[50]), "=f"(d[51]), "=f"(d[52]), "=f"(d[53]), "=f"(d[54]), "=f"(d[55]), "=f"(d[56]), "=f"(d[57]), "=f"(d[58]), "=f"(d[59]), "=f"(d[60]), "=f"(d[61]), "=f"(d[62]), "=f"(d[63]), "=f"(d[64]), "=f"(d[65]), "=f"(d[66]), "=f"(d[67]), "=f"(d[68]), "=f"(d[69]), "=f"(d[70]), "=f"(d[71]), "=f"(d[72]), "=f"(d[73]), "=f"(d[74]), "=f"(d[75]), "=f"(d[76]), "=f"(d[77]), "=f"(d[78]), "=f"(d[79]), "=f"(d[80]), "=f"(d[81]), "=f"(d[82]), "=f"(d[83]), "=f"(d[84]), "=f"(d[85]), "=f"(d[86]), "=f"(d[87]), "=f"(d[88]), "=f"(d[89]), "=f"(d[90]), "=f"(d[91]), "=f"(d[92]), "=f"(d[93]), "=f"(d[94]), "=f"(d[95]), "=f"(d[96]), "=f"(d[97]), "=f"(d[98]), "=f"(d[99]), "=f"(d[100]), "=f"(d[101]), "=f"(d[102]), "=f"(d[103]), "=f"(d[104]), "=f"(d[105]), "=f"(d[106]), "=f"(d[107]), "=f"(d[108]), "=f"(d[109]), "=f"(d[110]), "=f"(d[111]), "=f"(d[112]), "=f"(d[113]), "=f"(d[114]), "=f"(d[115]), "=f"(d[116]), "=f"(d[117]), "=f"(d[118]), "=f"(d[119]), "=f"(d[120]), "=f"(d[121]), "=f"(d[122]), "=f"(d[123]), "=f"(d[124]), "=f"(d[125]), "=f"(d[126]), "=f"(d[127])
        : "l"(da), "l"(db), "n"(TA), "n"(TB));
}
template <int TA, int TB>
__device__ __forceinline__ void wgmma_ss128(float* d, uint64_t da, uint64_t db) {
    asm volatile("wgmma.mma_async.sync.aligned.m64n128k16.f32.bf16.bf16 "
        "{%0, %1, %2, %3, %4, %5, %6, %7, %8, %9, %10, %11, %12, %13, %14, %15, %16, %17, %18, %19, %20, %21, %22, %23, %24, %25, %26, %27, %28, %29, %30, %31, %32, %33, %34, %35, %36, %37, %38, %39, %40, %41, %42, %43, %44, %45, %46, %47, %48, %49, %50, %51, %52, %53, %54, %55, %56, %57, %58, %59, %60, %61, %62, %63}, %64, %65, 1, 1, 1, %66, %67;"
        : "+f"(d[0]), "+f"(d[1]), "+f"(d[2]), "+f"(d[3]), "+f"(d[4]), "+f"(d[5]), "+f"(d[6]), "+f"(d[7]), "+f"(d[8]), "+f"(d[9]), "+f"(d[10]), "+f"(d[11]), "+f"(d[12]), "+f"(d[13]), "+f"(d[14]), "+f"(d[15]), "+f"(d[16]), "+f"(d[17]), "+f"(d[18]), "+f"(d[19]), "+f"(d[20]), "+f"(d[21]), "+f"(d[22]), "+f"(d[23]), "+f"(d[24]), "+f"(d[25]), "+f"(d[26]), "+f"(d[27]), "+f"(d[28]), "+f"(d[29]), "+f"(d[30]), "+f"(d[31]), "+f"(d[32]), "+f"(d[33]), "+f"(d[34]), "+f"(d[35]), "+f"(d[36]), "+f"(d[37]), "+f"(d[38]), "+f"(d[39]), "+f"(d[40]), "+f"(d[41]), "+f"(d[42]), "+f"(d[43]), "+f"(d[44]), "+f"(d[45]), "+f"(d[46]), "+f"(d[47]), "+f"(d[48]), "+f"(d[49]), "+f"(d[50]), "+f"(d[51]), "+f"(d[52]), "+f"(d[53]), "+f"(d[54]), "+f"(d[55]), "+f"(d[56]), "+f"(d[57]), "+f"(d[58]), "+f"(d[59]), "+f"(d[60]), "+f"(d[61]), "+f"(d[62]), "+f"(d[63])
        : "l"(da), "l"(db), "n"(TA), "n"(TB));
}
template <int TA, int TB>
__device__ __forceinline__ void wgmma_ss128_first(float* d, uint64_t da, uint64_t db) {
    asm volatile("wgmma.mma_async.sync.aligned.m64n128k16.f32.bf16.bf16 "
        "{%0, %1, %2, %3, %4, %5, %6, %7, %8, %9, %10, %11, %12, %13, %14, %15, %16, %17, %18, %19, %20, %21, %22, %23, %24, %25, %26, %27, %28, %29, %30, %31, %32, %33, %34, %35, %36, %37, %38, %39, %40, %41, %42, %43, %44, %45, %46, %47, %48, %49, %50, %51, %52, %53, %54, %55, %56, %57, %58, %59, %60, %61, %62, %63}, %64, %65, 0, 1, 1, %66, %67;"
        : "=f"(d[0]), "=f"(d[1]), "=f"(d[2]), "=f"(d[3]), "=f"(d[4]), "=f"(d[5]), "=f"(d[6]), "=f"(d[7]), "=f"(d[8]), "=f"(d[9]), "=f"(d[10]), "=f"(d[11]), "=f"(d[12]), "=f"(d[13]), "=f"(d[14]), "=f"(d[15]), "=f"(d[16]), "=f"(d[17]), "=f"(d[18]), "=f"(d[19]), "=f"(d[20]), "=f"(d[21]), "=f"(d[22]), "=f"(d[23]), "=f"(d[24]), "=f"(d[25]), "=f"(d[26]), "=f"(d[27]), "=f"(d[28]), "=f"(d[29]), "=f"(d[30]), "=f"(d[31]), "=f"(d[32]), "=f"(d[33]), "=f"(d[34]), "=f"(d[35]), "=f"(d[36]), "=f"(d[37]), "=f"(d[38]), "=f"(d[39]), "=f"(d[40]), "=f"(d[41]), "=f"(d[42]), "=f"(d[43]), "=f"(d[44]), "=f"(d[45]), "=f"(d[46]), "=f"(d[47]), "=f"(d[48]), "=f"(d[49]), "=f"(d[50]), "=f"(d[51]), "=f"(d[52]), "=f"(d[53]), "=f"(d[54]), "=f"(d[55]), "=f"(d[56]), "=f"(d[57]), "=f"(d[58]), "=f"(d[59]), "=f"(d[60]), "=f"(d[61]), "=f"(d[62]), "=f"(d[63])
        : "l"(da), "l"(db), "n"(TA), "n"(TB));
}
template <int TB>
__device__ __forceinline__ void wgmma_rs128(float* d, const uint32_t* a, uint64_t db, uint32_t acc) {
    asm volatile("{\n.reg .pred P;\nsetp.ne.u32 P, %69, 0;\nwgmma.mma_async.sync.aligned.m64n128k16.f32.bf16.bf16 "
        "{%0, %1, %2, %3, %4, %5, %6, %7, %8, %9, %10, %11, %12, %13, %14, %15, %16, %17, %18, %19, %20, %21, %22, %23, %24, %25, %26, %27, %28, %29, %30, %31, %32, %33, %34, %35, %36, %37, %38, %39, %40, %41, %42, %43, %44, %45, %46, %47, %48, %49, %50, %51, %52, %53, %54, %55, %56, %57, %58, %59, %60, %61, %62, %63}, {%64, %65, %66, %67}, %68, P, 1, 1, %70;\n}"
        : "+f"(d[0]), "+f"(d[1]), "+f"(d[2]), "+f"(d[3]), "+f"(d[4]), "+f"(d[5]), "+f"(d[6]), "+f"(d[7]), "+f"(d[8]), "+f"(d[9]), "+f"(d[10]), "+f"(d[11]), "+f"(d[12]), "+f"(d[13]), "+f"(d[14]), "+f"(d[15]), "+f"(d[16]), "+f"(d[17]), "+f"(d[18]), "+f"(d[19]), "+f"(d[20]), "+f"(d[21]), "+f"(d[22]), "+f"(d[23]), "+f"(d[24]), "+f"(d[25]), "+f"(d[26]), "+f"(d[27]), "+f"(d[28]), "+f"(d[29]), "+f"(d[30]), "+f"(d[31]), "+f"(d[32]), "+f"(d[33]), "+f"(d[34]), "+f"(d[35]), "+f"(d[36]), "+f"(d[37]), "+f"(d[38]), "+f"(d[39]), "+f"(d[40]), "+f"(d[41]), "+f"(d[42]), "+f"(d[43]), "+f"(d[44]), "+f"(d[45]), "+f"(d[46]), "+f"(d[47]), "+f"(d[48]), "+f"(d[49]), "+f"(d[50]), "+f"(d[51]), "+f"(d[52]), "+f"(d[53]), "+f"(d[54]), "+f"(d[55]), "+f"(d[56]), "+f"(d[57]), "+f"(d[58]), "+f"(d[59]), "+f"(d[60]), "+f"(d[61]), "+f"(d[62]), "+f"(d[63])
        : "r"(a[0]), "r"(a[1]), "r"(a[2]), "r"(a[3]), "l"(db), "r"(acc), "n"(TB));
}
template <int TB>
__device__ __forceinline__ void wgmma_rs64(float* d, const uint32_t* a, uint64_t db, uint32_t acc) {
    asm volatile("{\n.reg .pred P;\nsetp.ne.u32 P, %37, 0;\nwgmma.mma_async.sync.aligned.m64n64k16.f32.bf16.bf16 "
        "{%0, %1, %2, %3, %4, %5, %6, %7, %8, %9, %10, %11, %12, %13, %14, %15, %16, %17, %18, %19, %20, %21, %22, %23, %24, %25, %26, %27, %28, %29, %30, %31}, {%32, %33, %34, %35}, %36, P, 1, 1, %38;\n}"
        : "+f"(d[0]), "+f"(d[1]), "+f"(d[2]), "+f"(d[3]), "+f"(d[4]), "+f"(d[5]), "+f"(d[6]), "+f"(d[7]), "+f"(d[8]), "+f"(d[9]), "+f"(d[10]), "+f"(d[11]), "+f"(d[12]), "+f"(d[13]), "+f"(d[14]), "+f"(d[15]), "+f"(d[16]), "+f"(d[17]), "+f"(d[18]), "+f"(d[19]), "+f"(d[20]), "+f"(d[21]), "+f"(d[22]), "+f"(d[23]), "+f"(d[24]), "+f"(d[25]), "+f"(d[26]), "+f"(d[27]), "+f"(d[28]), "+f"(d[29]), "+f"(d[30]), "+f"(d[31])
        : "r"(a[0]), "r"(a[1]), "r"(a[2]), "r"(a[3]), "l"(db), "r"(acc), "n"(TB));
}
template <int TB>
__device__ __forceinline__ void wgmma_rs16(float* d, const uint32_t* a, uint64_t db, uint32_t acc) {
    asm volatile("{\n.reg .pred P;\nsetp.ne.u32 P, %13, 0;\nwgmma.mma_async.sync.aligned.m64n16k16.f32.bf16.bf16 "
        "{%0, %1, %2, %3, %4, %5, %6, %7}, {%8, %9, %10, %11}, %12, P, 1, 1, %14;\n}"
        : "+f"(d[0]), "+f"(d[1]), "+f"(d[2]), "+f"(d[3]), "+f"(d[4]), "+f"(d[5]), "+f"(d[6]), "+f"(d[7])
        : "r"(a[0]), "r"(a[1]), "r"(a[2]), "r"(a[3]), "l"(db), "r"(acc), "n"(TB));
}

__device__ __forceinline__ uint32_t delay_loop(int n, uint32_t x0) {
    uint32_t z;
    asm volatile("{\n.reg .pred P;\n.reg .u32 c, x;\nmov.u32 c, %1;\nmov.u32 x, %2;\nDL: mad.lo.u32 x, x, 1664525, 1013904223;\nadd.u32 c, c, -1;\nsetp.gt.s32 P, c, 0;\n@P bra DL;\n"
                 "setp.eq.u32 P, x, 0x7fffffff;\nselp.u32 %0, 16, 0, P;\n}" : "=r"(z) : "r"(n), "r"(x0) : "memory");
    return z;
}
__device__ __forceinline__ uint32_t gtime() { uint32_t t; asm volatile("mov.u32 %0, %%globaltimer_lo;" : "=r"(t)); return t; }
__device__ __forceinline__ void wait_time(uint32_t t, uint32_t sb) { while ((int32_t)(gtime() - t) < (int32_t)delay_loop(2, sb)) {} }
__device__ __forceinline__ uint32_t tpc_gpc(uint32_t t) { return t < 32 ? t & 7 : t < 60 ? (t - 32) % 7 + 1 : (t - 54) & 7; }
__device__ __forceinline__ uint32_t latest_stamp(const uint32_t* p, uint32_t seq, uint32_t ref, int backoff, uint32_t sb) {
    for (int n = 0;; n++) {
        uint32_t bad = 0; int32_t m = INT32_MIN;
#pragma unroll
        for (int i = 0; i < 3; i++) { const uint32_t v = ld_relaxed1(p + i * 256); bad |= (v ^ seq) & 31u; m = max(m, (int32_t)(v - (ref << 5)) >> 5); }
        if (__all_sync(0xffffffffu, bad == 0)) return ref + __reduce_max_sync(0xffffffffu, m);
        wait_time(gtime() + backoff, sb);
        if (n > SPIN_LIMIT) spin_fault();
    }
}
__device__ __forceinline__ void release_at(uint32_t t, uint32_t sb, uint32_t bar, int lane) {
    wait_time(t, sb);
    if (lane == 0) mbar_arrive(sb + bar);
}
__host__ __device__ constexpr int frag_word(int u, int f) { return (u == 0 ? 0 : u < 3 ? 3 * u - 1 : u == 3 ? 14 : 3 * u - 4) + f; }
__host__ __device__ constexpr int word_col(int e) { return ((0x32FED987CBA65410ull >> (4 * e)) & 14) * 64 + ((0x32FED987CBA65410ull >> (4 * e)) & 1) * 8; }

constexpr uint32_t CLEAR_LO = 0xFE000000u, CLEAR_HI = 0x5A7FEFEFu;
__device__ __forceinline__ void clear_slot(const Params& P, int slot, int cta, int lane) {
    const int i = cta * 2 + (lane >> 3), x = i & 63;
    if (lane < 16) st_relaxed4(P.gm + slot * M_SLOT + (x >> 1) * 1024 + (x & 1) * 256 + (i >> 7) * 512 + ((i >> 6) & 1) * 128 + (lane & 7) * 16, CLEAR_LO, CLEAR_HI, CLEAR_LO, CLEAR_HI);
    st_relaxed4(g_f + slot * F_SLOT + cta * 512 + lane * 16, 0, 0, 0, 0);
}
__device__ __forceinline__ void mem0_max(const Params& P, uint32_t sb, int tid) {
    uint32_t m = 0;
#pragma unroll
    for (int i = 0; i < 4; i++) {
        const uint4 x = __ldg((const uint4*)P.mem0 + i * 256 + tid);
        m = __vmaxu2(__vmaxu2(__vmaxu2(x.x & 0x7fff7fffu, x.y & 0x7fff7fffu), __vmaxu2(x.z & 0x7fff7fffu, x.w & 0x7fff7fffu)), m);
    }
    sts32(sb + S_COEF + (tid >> 5) * 4, __reduce_max_sync(0xffffffffu, max(m >> 16, m & 0xffffu)));
    bar_arrive(7, 288);
}
__device__ __forceinline__ uint32_t pack_mem0(const Params& P, uint32_t sb, int cta, int lane) {
    bar_sync(7, 288);
    const uint32_t e = __reduce_max_sync(0xffffffffu, lds32(sb + S_COEF + (lane & 7) * 4)) >> 7;
    if (e < 64 || e > 192) return 0x3F803F80u;
    const int i = cta * 2 + (lane >> 4), u = (i >> 5), x = i & 63, L = (i & 3) * 8 + ((lane & 15) >> 1);
    uint64_t w = 32;
#pragma unroll
    for (int f = 0; f < 3; f++) if (f < 2 || u % 3) {
        const float v = __bfloat162float(P.mem0[(L >> 2) * 1024 + word_col(frag_word(u, f)) + ((i >> 2) & 7) * 16 + (L & 3) * 2 + (lane & 1)]);
        w += (uint64_t)(int64_t)__float2int_rn(v * __uint_as_float((271 - e) << 23)) << (45 - 19 * f);
    }
    st_relaxed2(P.gm + 7 * M_SLOT + (x >> 1) * 1024 + (x & 1) * 256 + (i >> 7) * 512 + ((i >> 6) & 1) * 128 + (lane & 15) * 8, (uint32_t)w, (uint32_t)(w >> 32));
    return (e - 30) * 0x00800080u;
}
__device__ __forceinline__ void pacer(const Params& P, const uint32_t sb, const int lane) {
    constexpr uint32_t base = 2;
    int cta = lds32(sb + S_CTA);
#pragma unroll 1
    for (int i = 0; i < 8; i++) clear_slot(P, i, cta, lane);
    __syncwarp();
    if (lane == 0) { uint32_t smid; asm("mov.u32 %0, %%smid;" : "=r"(smid)); st_relaxed1(g_hint + 6144 + cta, smid >> 1); }
    sts32(sb + S_EPOCH + 4, pack_mem0(P, sb, cta, lane));
    SSTAMP(0, lane == 0)
    fence_release();
    __syncwarp();
    float rate = 0.58f;
    uint32_t c0 = 0;
#pragma unroll 1
    for (int s = -1; s < 63; s++) {
        cta = lds32(sb + S_CTA);
        const int pair = cta >> 1;
        const uint32_t ahead = s > 0 ? (uint32_t)(rate * (float)(pair >= 32 ? P.dc - P.dv : P.dc)) : 0;
        mbar_wait(sb + B_GO, s & 1);
        SSTAMP(10, lane == 0 && s == 0)
        const uint32_t t0 = gtime();
        if (lane < 4) st_relaxed1(g_hint + ((s & 1) * 4 + lane) * 768 + (cta >> 5) * 256 + (cta & 31), (t0 + ahead + (lds32(sb + S_REDO) == s ? P.extra : 0)) << 5 | ((base + s) & 31u));
        wait_time(t0 + (s < 0 ? 2000 : s == 0 && pair >= 16 ? P.ds0 : P.ds), sb);
        const uint32_t t = latest_stamp(g_hint + ((s & 1) * 4 + (pair & 3)) * 768 + lane, base + s, t0, P.back, sb);
        if (s < 0) {
            SSTAMP(2, lane == 0)
            fence_acquire();
            const uint32_t g = tpc_gpc(ld_relaxed1(g_hint + 6144 + (lane & 15) * 2));
            const uint32_t key = (__popc(__match_any_sync(0xffffffffu, g)) > 4 ? 0 : g + 1) * 16 + (lane & 15);
            const uint32_t tail = (pair & 48) + __popc(__ballot_sync(0xffffffffu, key < __shfl_sync(0xffffffffu, key, pair & 15))) / 2;
            mbar_wait(sb + B_INIT, 0);
            SSTAMP(4, lane == 0)
            sts32(sb + S_TAIL, tail);
            if (lane < 8) sts32(sb + S_SC + lane * 4, lds32(sb + S_EPOCH + 4));
            __syncwarp();
        }
        release_at(t + P.da, sb, B_RELA, lane);
        SSTAMP(11, lane == 0 && s == 0)
        release_at(t + P.db, sb, B_RELB, lane);
        {
            const uint32_t c1 = clock(), g1 = gtime();
            if (s > 1) rate += P.alpha * (__fdividef((float)(g1 - lds32(sb + S_EPOCH + 4)), (float)(c1 - c0)) - rate);
            __syncwarp();
            c0 = c1; sts32(sb + S_EPOCH + 4, g1);
        }
        if (s == 61) {
            sts32(sb + S_COEF, ITEM(ITEM_OFF(lds32(sb + S_TAIL)) + NPRE + 1) + (uint32_t)(uintptr_t)P.out);
            if (lane < M_CQ) map_prefetch(&P.tm[lane]);
        }
    }
}
__device__ __forceinline__ uint32_t xor_or(uint32_t a, uint32_t b, uint32_t t) { uint32_t d; asm("lop3.b32 %0, %1, %2, %3, 0x7E;" : "=r"(d) : "r"(a), "r"(b), "r"(t)); return d; }
__device__ __forceinline__ bool tags_ok(uint32_t bad) { return __all_sync(0xffffffffu, (bad & 1) == 0); }
#define RETRY(k)
#define RETRY_STAT(a, b)
#define UNIT_STAT(u0)
#define SFENCE() asm volatile("pmevent 1;" ::: "memory")
#define PF1 10
static_assert(NS == 24, "fragment residency");
__host__ __device__ constexpr bool in_smem(int n) { return n < 4 || n == 12 || n == 13; }
__host__ __device__ constexpr int unit_pos(int n) { return n < 4 ? n : n < 12 ? n - 4 : n < 14 ? n - 8 : n - 6; }

__host__ __device__ constexpr int fill_unit(int q) { return q < 4 ? q : q < 6 ? q + 8 : q < 14 ? q - 2 : q; }
__host__ __device__ constexpr int frag_off(int q) { return (q >> 2) * 16384 + ((q >> 1) & 1) * 8192 + (q & 1) * 512; }

constexpr uint32_t QBITS = 0x4B002000u;
constexpr uint64_t W_BIAS = ((uint64_t)QBITS << 45) + ((uint64_t)QBITS << 26) + (uint32_t)(QBITS << 7), W_CLEAR = 0 - 32 * W_BIAS;
static_assert(W_CLEAR == ((uint64_t)CLEAR_HI << 32 | CLEAR_LO), "clear value");
__host__ __device__ constexpr int unit_off(int u) { return (u & 1) * 16384 + (u >> 2) * 512 + ((u >> 1) & 1) * 128; }
__device__ __forceinline__ void red_add64(const uint8_t* p, uint64_t v) { asm volatile("red.relaxed.gpu.global.add.u64 [%0], %1;" ::"l"(p), "l"(v) : "memory"); }
template <int NF>
__device__ __forceinline__ uint64_t encode(const float* x, float S, uint32_t two26, uint32_t& bad) {
    uint32_t b[3];
#pragma unroll
    for (int i = 0; i < 3; i++) b[i] = i < NF ? __float_as_uint(fmaf(x[i], S, 8396800.f)) : QBITS;
    bad = xor_or(b[0], b[1], 0x4B000000u) | (NF == 3 ? b[2] ^ 0x4B000000u : 0);
    uint64_t w;
    asm("{\n.reg .b64 t;\nmov.b64 t, {%2, %3};\nmad.wide.u32 %0, %1, %4, t;\n}" : "=l"(w) : "r"(b[1]), "r"(b[2] << 7), "r"(b[0] << 13), "r"(two26));
    return w;
}
template <int NF>
__device__ __forceinline__ void emit(uint64_t* w, const float (*x)[3], const float* S, uint32_t two26, uint32_t lim, const uint8_t* p) {
    uint32_t bad[2];
    w[0] = encode<NF>(x[0], S[0], two26, bad[0]); w[1] = encode<NF>(x[1], S[1], two26, bad[1]);
    const bool ok = (bad[0] | bad[1]) < lim;
    w[0] |= ok; w[1] |= ok;
    red_add64(p, w[0]); red_add64(p + 1024, w[1]);
}
template <int NF>
__device__ __forceinline__ void repair(const uint64_t* w, const float (*x)[3], const float* S, const uint8_t* p, const uint8_t* pf) {
    if (!(w[0] & 1)) {
#pragma unroll
        for (int j = 0; j < 2; j++) {
            const float T = S[j] * 8192.f;
            asm volatile("red.relaxed.gpu.global.add.v4.f32 [%0], {%1,%2,%3,%4};" ::"l"(pf + j * 512), "f"(x[j][0] * T), "f"(x[j][1] * T), "f"(NF == 3 ? x[j][2] * T : 0.f), "f"(0.f) : "memory");
        }
        fence_release();
#pragma unroll
        for (int j = 0; j < 2; j++) {
            asm volatile("red.relaxed.gpu.global.or.b64 [%0], 64;" ::"l"(p + j * 1024) : "memory");
            red_add64(p + j * 1024, W_BIAS + 1 - w[j]);
        }
    }
    __syncwarp();
}
__device__ __forceinline__ void ld_words(uint32_t* v, const uint8_t* p) {
    asm volatile("{\n.reg .b64 a, b;\nld.relaxed.gpu.global.L1::no_allocate.v2.b64 {a, b}, [%4];\nmov.b64 {%0,%1}, a;\nmov.b64 {%2,%3}, b;\n}" : "=r"(v[0]), "=r"(v[1]), "=r"(v[2]), "=r"(v[3]) : "l"(p) : "memory");
}
__device__ __forceinline__ float field(const uint32_t* w, int f) { return __int2float_rn((int)(f == 0 ? w[1] : f == 1 ? __funnelshift_l(w[0], w[1], 19) : w[0] << 6)); }
template <int U>
__device__ __forceinline__ void decode(uint32_t* b, const uint32_t* v) {
#pragma unroll
    for (int f = 0; f < (U % 3 ? 3 : 2); f++) b[frag_word(U, f)] = pack2(field(v, f), field(v + 2, f));
}
__device__ __forceinline__ uint32_t status(const uint32_t (*v)[4], uint32_t c32) { return xor_or(v[0][0], v[0][2], c32) | xor_or(v[1][0], v[1][2], c32) | xor_or(v[2][0], v[2][2], c32); }
__device__ __forceinline__ void gather_slow(const Params& P, uint32_t* b, const uint8_t* pm, int s, int warp, uint32_t ln, uint32_t u2) {
    if (s == 0 && u2 == 0x3F803F80u) {
#pragma unroll
        for (int i = 0; i < 16; i++) b[i] = __ldg((const uint32_t*)(P.mem0 + (ln >> 2) * 1024 + word_col(i) + warp * 16 + (ln & 3) * 2));
        return;
    }
    uint32_t v[6][4], st;
    for (int n = 0;; n++) {
#pragma unroll
        for (int u = 0; u < 6; u++) ld_words(v[u], pm + unit_off(u));
        st = status(v, 32) | status(v + 3, 32);
        if (!__any_sync(0xffffffffu, st & 32)) break;
        __nanosleep(200);
        if (n > SPIN_LIMIT) spin_fault();
    }
    const bool side = __any_sync(0xffffffffu, st & 64);
    if (side) fence_acquire();
    const uint8_t* pf = g_f + ((s + 7) & 7) * F_SLOT + warp * 1024 + ln * 32;
#pragma unroll
    for (int u = 0; u < 6; u++) {
        float x[2][4] = {};
#pragma unroll
        for (int k = 0; k < 2; k++)
            asm volatile("{\n.reg .pred P;\nsetp.ne.u32 P, %5, 0;\n@P ld.relaxed.gpu.global.v4.f32 {%0,%1,%2,%3}, [%4];\n}"
                         : "+f"(x[k][0]), "+f"(x[k][1]), "+f"(x[k][2]), "+f"(x[k][3]) : "l"(pf + u * 8192 + k * 16), "r"((uint32_t)side) : "memory");
#pragma unroll
        for (int f = 0; f < (u % 3 ? 3 : 2); f++) b[frag_word(u, f)] = pack2(field(v[u], f) + x[0][f], field(v[u] + 2, f) + x[1][f]);
    }
}
__device__ __forceinline__ uint32_t max_abs2(uint32_t a, uint32_t b) { uint32_t d; asm("max.NaN.xorsign.abs.bf16x2 %0, %1, %2;" : "=r"(d) : "r"(a), "r"(b)); return d; }
__device__ __forceinline__ uint32_t max6(const uint32_t* b) {
    const uint32_t m = max_abs2(max_abs2(max_abs2(b[0], b[1]), max_abs2(b[2], b[3])), max_abs2(b[4], b[5]));
    return max(m & 0x7fff0000u, (m << 16) & 0x7fff0000u);
}

template <bool TR>
__device__ __forceinline__ void put_partials(uint32_t a, const float* x, const float* y) {
    if (TR) stsm4t(a, pack2(x[0], x[1]), pack2(x[2], x[3]), pack2(y[0], y[1]), pack2(y[2], y[3]));
    else stsm4(a, pack2(x[0], x[1]), pack2(x[2], x[3]), pack2(y[0], y[1]), pack2(y[2], y[3]));
}
__device__ __forceinline__ void reduce_load(uint32_t (*x)[4], uint32_t a) { ldsm4t(x[0], a); ldsm4t(x[1], a + 512); }
__device__ __forceinline__ uint32_t reduce8(const uint32_t (*x)[4], uint32_t l8, uint32_t u2) {
    uint32_t p[2];
#pragma unroll
    for (int i = 0; i < 2; i++) {
        float d[4] = {};
        mma16816(d, x[i][0], x[i][1], x[i][2], x[i][3], (l8 & 32) ? 0u : u2, (l8 & 32) ? u2 : 0u);
        p[i] = pack2((l8 & 8) ? d[2] : d[0], (l8 & 8) ? d[3] : d[1]);
    }
    return (l8 & 16) ? p[1] : p[0];
}
__device__ __forceinline__ void score_half(float (*a)[4], const uint32_t (*qa)[4], const uint32_t (*kf)[4]) {
#pragma unroll
    for (int w = 0; w < 2; w++) {
        mma16816(a[w], qa[w][0], qa[w][1], qa[w][2], qa[w][3], kf[w][0], kf[w][1]);
        mma16816(a[2 + w], qa[w][0], qa[w][1], qa[w][2], qa[w][3], kf[w][2], kf[w][3]);
    }
}
__device__ __forceinline__ void score_sum(float* S, const float (*a)[4]) {
    S[0] = (a[0][0] + a[1][0]) + (a[2][2] + a[3][2]);
    S[1] = (a[0][1] + a[1][1]) + (a[2][3] + a[3][3]);
}
__device__ __forceinline__ float quad_max(float m) {
    m = fmaxf(m, __shfl_xor_sync(0xffffffffu, m, 1));
    return fmaxf(m, __shfl_xor_sync(0xffffffffu, m, 2));
}

#define ISTAMP(i)
__device__ __forceinline__ float next_scale(uint32_t sb, int slot, int warp, uint32_t u2) {
    uint32_t x[2][4];
    lds128(x[0], sb + S_MX + slot * 32); lds128(x[1], sb + S_MX + slot * 32 + 16);
    const uint32_t mx = max(max(max(x[0][0], x[0][1]), max(x[0][2], x[0][3])), max(max(x[1][0], x[1][1]), max(x[1][2], x[1][3])));
    const float top = fminf(fmaxf(__uint_as_float(mx) * bf_hi(u2), 0x1p-40f), 0x1p40f) * (1.f / (12288.f * 8192.f));
    const uint32_t un = pack2(top, top);
    sts32(sb + S_SC + warp * 4, un);
    return rcp(bf_hi(un) * 8192.f);
}
#define NEARLY 1
#define U3POS 1
#define VPOS 1
#define ROT 0
#define BPOS 1
#define ONLINE 0
#define NBAR 1
#define ORD3 0
#define F2 1
#define EARLY 0
#define TK 0
#define OBN 4
#define CH4 1
#define RPOS 1
#define AF 0
#define AFENCE(i) if ((AF >> (i)) & 1) SFENCE();
#define FPOS 99
#define PACE 1
#define PF2 12
__host__ __device__ constexpr int w2_t(int i) { return i < 16 ? i & 1 : 2; }
__host__ __device__ constexpr int w2_k(int i) { return i < 16 ? i >> 1 : i - 16; }
template <typename G>
__device__ __forceinline__ void load_weights(uint32_t (*wr)[4], const uint32_t sb, const int warp, const int lane, G stores_read) {
    const uint32_t frag = sb + warp * 1024 + (lane >> 4) * 8192 + (lane & 7) * 128 + ((((lane >> 3) & 1) ^ (lane & 7)) << 4);
    const uint32_t rel = mapa(sb + B_EMPTY, cluster_rank() ^ (lane & 1));
#define RELEASE(st) { fence_async_smem(); __syncwarp(); if (lane < 2) mbar_arrive_cluster(rel + (st) * 8); }
    mbar_wait(sb + B_FULL, 0); mbar_wait(sb + B_FULL + 8, 0);
    RELEASE(0) RELEASE(1)
#pragma unroll
    for (int st = 2; st < 4; st++) {
        mbar_wait(sb + B_FULL + st * 8, 0);
        ISTAMP(st - 2)
#pragma unroll
        for (int f = 0; f < 12; f++) ldsm4t(wr[st * 12 - 24 + f], (frag ^ ((f & 3) << 5)) + st * STAGE + (f >> 2) * 16384);
        RELEASE(st)
    }
#pragma unroll 2
    for (int u = 0; u < 6; u++) {
        uint32_t x[4][4];
#pragma unroll
        for (int i = 0; i < 4; i++) lds128(x[i], (frag ^ (i << 5)) + u * 16384);
        __syncwarp();
#pragma unroll
        for (int i = 0; i < 4; i++) sts128(sb + warp * 1024 + lane * 16 + u * 16384 + frag_off(i), x[i]);
    }
    stores_read();
    mbar_wait(sb + B_FULL, 1); mbar_wait(sb + B_FULL + 8, 1);
    RELEASE(0) RELEASE(1)
#pragma unroll
    for (int st = 2; st < 4; st++) {
        mbar_wait(sb + B_FULL + st * 8, 1);
#pragma unroll
        for (int f = 0; f < (st == 2 ? 12 : 4); f++) ldsm4t(wr[st * 12 + f], (frag ^ ((f & 3) << 5)) + st * STAGE + (f >> 2) * 16384);
        RELEASE(st)
    }
    ISTAMP(2)
    bar_sync(1, 256);
    if (warp == 7 && lane < 3) mbar_arrive_cluster(mapa(sb + B_INIT, (cluster_rank() & 1) + lane * 2));
}
template <int ROLE>
__device__ __forceinline__ void chain_role(const Params& P, const uint32_t (*wr)[4], const uint32_t sb, const int h, const int warp, const int lane) {
    constexpr int NU = ROLE == 0 ? 2 : 3;
    const bool att = ROLE == 0 && warp < 4;
    uint32_t l8 = opq(sb + lane * 8, lane);
#define PERSIST() { mbar_wait(sb + B_KVGO, slot ^ 1); const uint32_t pa_ = ((l8 - sb) >> 1) + (sb + S_QX + warp * 128); sts32(pa_, r0); sts32(pa_ + 1024, r1); \
                    fence_async_smem(); __syncwarp(); if (l8 == sb) mbar_arrive(sb + B_PERS); }
    if (ROLE) sts32(sb + S_SX + warp * 128 + lane * 4, warp >= 2 ? 0 : (lane & 1) ? CLEAR_HI : CLEAR_LO);
    const uint32_t rdelta = __shfl_sync(0xffffffffu, mapa(sb, (cluster_rank() + (ROLE == 1 ? 4 : 2)) % 6) - sb, 0);
    const uint32_t vdelta = ROLE ? 0 : __shfl_sync(0xffffffffu, mapa(sb, (cluster_rank() + 4) % 6) - sb, 0);
    ISTAMP(3)
    __syncwarp();
#define GATHER_OFF(s) ((((s) + 7) & 7) * M_SLOT + warp * 2048 + (l8 & 56) * 2 + (l8 & 64) * 4 + (l8 & 128) * 8)
    uint32_t mo = GATHER_OFF(0);
    if (ROT) mbar_wait(sb + B_RELA, 0);
    for (int s = 0; s < (ROLE == 0 ? 63 : 64);) {
        const int slot = s & 1;
        l8 += s & P.zero;
        const uint32_t w1a = l8 * 2 + (S_W1 + warp * 1024 - sb);
        PROF(9)
        uint32_t u2, r0, r1, pld, pub, pbar, x[2][4];
        {
#define pm (P.gm + mo)
            uint32_t as[24][4], b[16], v[6][4];
            float acc[8][4];
#define W1LD(n) _Pragma("unroll") for (int i_ = 0; i_ < 4; i_++) ldsm4t(as[unit_pos(n) * 4 + i_], w1a + frag_off(unit_pos(n) * 4 + i_));
#define W1LD2(n, p) { const uint32_t wa_ = w1a + (as[unit_pos(p) * 4][0] & as[unit_pos(p) * 4 + 1][0] & as[unit_pos(p) * 4 + 2][0] & as[unit_pos(p) * 4 + 3][0] & P.zero); \
                      _Pragma("unroll") for (int i_ = 0; i_ < 4; i_++) ldsm4t(as[unit_pos(n) * 4 + i_], wa_ + frag_off(unit_pos(n) * 4 + i_)); }
#define W1MMA(n) _Pragma("unroll") for (int i_ = 0; i_ < 4; i_++) { const uint32_t* a_ = in_smem(n) ? as[unit_pos(n) * 4 + i_] : wr[unit_pos(n) * 4 + i_]; \
                                                                   mma16816(acc[((n) & 1) * 4 + i_], a_[0], a_[1], a_[2], a_[3], b[(n) & 14], b[(n) | 1]); }
#pragma unroll
            for (int T = 0; T < 8; T++) { acc[T][0] = acc[T][1] = acc[T][2] = acc[T][3] = 0.f; }
            if (!ROT) mbar_wait(sb + B_RELA, slot);
            PROF(12)
#pragma unroll
            for (int u = 0; u < 3; u++) ld_words(v[u], pm + unit_off(u));
            __syncwarp();
#pragma unroll
            for (int i = 0; i < PF1; i++) ldsm4t(as[i], w1a + frag_off(i));
            __syncwarp();
            mo += mbar_try(sb + B_RELB, slot) & P.zero;
            PROF(13)
#pragma unroll
            for (int u = 3; u < 6; u++) ld_words(v[u], pm + unit_off(u));
            uint32_t st = status(v, ((uint32_t)((uintptr_t)pm >> 32) & P.zero) + 32);
            pin<1>(&st);
            SFENCE();
            UNIT_STAT(0)
            PROF(0)
            decode<0>(b, v[0]); decode<1>(b, v[1]); decode<2>(b, v[2]);
#pragma unroll
            for (int i = PF1; i < 12; i++) ldsm4t(as[i], w1a + frag_off(i));
            W1MMA(0) W1MMA(1) W1MMA(2)
            if (TK & 1) W1LD2(3, 2) else { W1LD(3) }
            SFENCE();
            if (TK & 8) { W1MMA(5) W1MMA(4) W1MMA(3) W1MMA(6) } else { W1MMA(5) W1MMA(4) W1MMA(6) W1MMA(3) }
            if (U3POS == 0) W1MMA(7)
            if (TK & 2) W1LD2(12, 3) else { W1LD(12) }
            uint32_t mx = max6(b);
            pin<1>(&mx);
            SFENCE();
            PROF(10)
            if (U3POS == 1) W1MMA(7)
            const uint32_t mxa = sb + S_MX + slot * 32 + warp * 4;
            sts32(mxa, __reduce_max_sync(0xffffffffu, mx));
            UNIT_STAT(3)
            st |= status(v + 3, 32);
            const bool redo = __any_sync(0xffffffffu, st & 96);
            const bool kvok = ROLE || mbar_test(sb + B_KVFULL + slot * 8, (s >> 1) & 1);
            decode<4>(b, v[4]); decode<5>(b, v[5]); decode<3>(b, v[3]);
            u2 = lds32(sb + S_SC + warp * 4);
            W1MMA(8) W1MMA(10) if (ORD3) { W1MMA(14) W1MMA(12) } else { W1MMA(12) W1MMA(14) }
            if (TK & 4) W1LD2(13, 12) else { W1LD(13) }
            if (__builtin_expect(redo || !kvok, 0)) {
                if (redo) {
                    RETRY(3)
                    sts32(sb + S_REDO, s);
                    gather_slow(P, b, P.gm + GATHER_OFF(s), s, warp, (l8 - sb) >> 3, u2);
                    sts32(mxa, __reduce_max_sync(0xffffffffu, max6(b)));
#pragma unroll
                    for (int T = 0; T < 8; T++) { acc[T][0] = acc[T][1] = acc[T][2] = acc[T][3] = 0.f; }
#pragma unroll
                    for (int n = 0; n < 15; n += n < 8 ? 1 : 2) {
                        if (in_smem(n)) { W1LD(n) }
                        W1MMA(n)
                    }
                    W1LD(13)
                }
                if (ROLE == 0) mbar_wait(sb + B_KVFULL + slot * 8, (s >> 1) & 1);
            }
#undef pm
            SSTAMP(7, threadIdx.x == 0 && s == 0)
            PROF(14)
            const uint32_t pst = (l8 - sb) * 16 + ((warp * 16) ^ ((l8 * 2) & 112)) + (sb + S_P1);
            put_partials<ROLE == 2>(pst, acc[0], acc[1]); put_partials<ROLE == 2>(pst + 4096, acc[2], acc[3]);
            W1MMA(9)
            SFENCE();
            pld = (l8 & 64) * 4 + (l8 & 128) + (l8 & 56) * 2 + (sb + S_P1 + warp * 1024);
            const uint32_t rd = s == 63 ? 0 : rdelta;
            pub = ((l8 - sb) >> 1) + (ROLE ? sb + rd + (ROLE == 1 ? S_KL : S_VL) + warp * 128 : sb + S_QX + (warp & 4) * 128 + (warp & 1) * 256 + (warp & 2) * 64);
            pbar = sb + rd + (ROLE == 1 && s != 63 ? B_K : B_V);
#define PUBLISH0() { r0 = reduce8(x, l8, u2); if (ROLE) st_async1(pub, r0, pbar); else sts32(pub, r0); }
            if (RPOS == 0) { bar_sync(1, 256); reduce_load(x, pld); SFENCE(); }
            W1MMA(11)
            if (RPOS == 1) { bar_sync(1, 256); reduce_load(x, pld); }
            if (RPOS != 2 || F2) SFENCE();
            W1MMA(15)
            if (RPOS == 0) PUBLISH0()
            if (RPOS == 2) { bar_sync(1, 256); reduce_load(x, pld); }
            if (RPOS != 1 || F2) SFENCE();
            W1MMA(13)
            if (RPOS == 1) PUBLISH0()
            put_partials<ROLE == 2>(pst + 8192, acc[4], acc[5]); put_partials<ROLE == 2>(pst + 12288, acc[6], acc[7]);
            if (RPOS == 2) PUBLISH0()
        }
        SSTAMP(8, threadIdx.x == 0 && s == 0)
        PROF(1)
        if (ROLE) {
            bar_sync(1, 256);
            reduce_load(x, pld + 8192);
            r1 = reduce8(x, l8, u2);
            st_async1(pub + 1024, r1, pbar);
            if (s == 63) {
                PERSIST()
                mbar_wait(sb + B_V, 0);
                break;
            }
            PROF(2)
        }
        uint32_t ln, w2a, ro;
#define W2ADDR(late) { l8 += pub & P.zero; ln = (l8 - sb) >> 3; \
        w2a = sb + S_W2 + (ROLE ? (warp >> 2) * 16384 : late * 32768) + ((((ln & 7) + (ln >> 4) * 8) * 128 + ((((ln >> 3) & 1) ^ (ln & 7)) << 4)) ^ ((warp & 3) << 5)); \
        ro = (s & 7) * M_SLOT + (ROLE ? warp * 2048 + unit_off(ROLE) : (warp & 3) * 2048 + late * unit_off(3)) + (ln & 2) * 128 + (ln & 1) * 64 + (ln >> 2) * 8; }
        constexpr int RO2 = ROLE ? unit_off(ROLE + 3) - unit_off(ROLE) : 8192;
        float Sj[2];
        uint32_t w[24][4], ob[4][4];
        float S;
#define W2LD(i) ldsm4t(w[i], w2a + w2_t(i) * (ROLE ? 32768 : 16384) + (w2_k(i) & 1) * 8192 + (w2_k(i) >> 1) * 2048)
#define W2MMA(d, i) mma16816(d, w[i][0], w[i][1], w[i][2], w[i][3], ob[w2_k(i) >> 1][(w2_k(i) & 1) * 2], ob[w2_k(i) >> 1][(w2_k(i) & 1) * 2 + 1])
#define LEADER(wp) (l8 == sb + ((wp) - warp) * 256)
        if (att) {
            const float cs = 0.08838834764831845f * 1.4426950408889634f;
            uint32_t qa[4][4], kf[4][4], vf[4][4], vv[4];
            float T[5][2], sa[4][4] = {};
            const uint32_t l16 = l8 * 2 - sb;
            const uint32_t kaddr = (l8 & 56) * 16 + (((l8 >> 2) ^ (l8 * 2)) & 48) + ((l8 * 2) & 64) + (sb + S_KV + warp * 1024 + slot * 16384);
            bar_sync(1, 256);
            reduce_load(x, pld + 8192);
            __syncwarp();
#pragma unroll
            for (int i = 0; i < 2; i++) { ldsm4(qa[i], l16 + S_QX + i * 512); ldsm4(kf[i], kaddr ^ (i * 64)); }
            AFENCE(0)
            sts32(pub + 1024, reduce8(x, l8, u2));
            __syncwarp();
#pragma unroll
            for (int i = 2; i < 4; i++) ldsm4(kf[i], (kaddr ^ ((i & 1) * 64)) + 4096);
            score_half(sa, qa, kf);
            bar_sync(2, 256);
            PROF(2)
#pragma unroll
            for (int i = 2; i < 4; i++) ldsm4(qa[i], l16 + S_QX + i * 512);
            float sm[4][4] = {};
            score_half(sa, qa + 2, kf + 2);
            score_sum(T[0], sa);
            sts64(l8 + S_SX + warp * 256, __float_as_uint(T[0][0]), __float_as_uint(T[0][1]));
            PROF(4)
            if (BPOS == 0) bar_sync(4, 128);
            mbar_wait(sb + B_K, slot);
            PROF(11)
#pragma unroll
            for (int i = 0; i < 4; i++) ldsm4(kf[i], l16 + S_KL + i * 512);
            if (BPOS == 1) bar_sync(4, 128); else __syncwarp();
#pragma unroll
            for (int n = 0; n < 4; n++) lds64f(T[n], l8 + S_SX + n * 256);
            score_half(sm, qa, kf);
            score_half(sm, qa + 2, kf + 2);
            const uint32_t vaddr = (l8 & 56) * 16 + (l8 & 128) * 8 + (((warp & 1) * 64 + ((l8 >> 2) & 16)) ^ ((l8 * 2) & 112)) + (sb + S_KV + 8192 + (warp >> 1) * 4096 + slot * 16384);
            float mx = fmaxf(fmaxf(fmaxf(T[0][0], T[0][1]), fmaxf(T[1][0], T[1][1])), fmaxf(fmaxf(T[2][0], T[2][1]), fmaxf(T[3][0], T[3][1])));
            score_sum(T[4], sm);
            float m = quad_max(fmaxf(mx, fmaxf(T[4][0], T[4][1])));
            if (VPOS == 0) {
#pragma unroll
                for (int i = 0; i < 4; i++) ldsm4t(vf[i], (vaddr ^ ((i & 1) << 5)) + (i >> 1) * 2048);
            }
            mbar_wait(sb + B_V, slot);
            if (VPOS == 1) {
#pragma unroll
                for (int i = 0; i < 4; i++) ldsm4t(vf[i], (vaddr ^ ((i & 1) << 5)) + (i >> 1) * 2048);
            }
            ldsm4(vv, l16 + S_VL + warp * 512);
            uint32_t pa[5];
            m *= cs;
#pragma unroll
            for (int n = 0; n < 5; n++) { T[n][0] = ex2(fmaf(T[n][0], cs, -m)); T[n][1] = ex2(fmaf(T[n][1], cs, -m)); pa[n] = pack2(T[n][0], T[n][1]); }
            float sum = (((T[0][0] + T[0][1]) + (T[1][0] + T[1][1])) + ((T[2][0] + T[2][1]) + (T[3][0] + T[3][1]))) + (T[4][0] + T[4][1]);
            PROF(3)
            W2ADDR(1)
            const uint32_t lo = sb + S_O + warp * 512 + (ln & 3) * 64 + (ln >> 2) * 8, ls = sb + S_SUM + (ln & 3) * 32 + (ln & 4) * 4 + (ln >> 3) * 4;
            const uint32_t sdelta = warp < 2 ? rdelta : vdelta;
            sum += __shfl_xor_sync(0xffffffffu, sum, 1);
            sum += __shfl_xor_sync(0xffffffffu, sum, 2);
            float O[2][4];
#pragma unroll
            for (int i = 0; i < 2; i++) { O[i][0] = O[i][1] = O[i][2] = O[i][3] = 0.f; }
#pragma unroll
            for (int i = 0; i < 2; i++) {
                mma16816(O[0], vf[2 * i][0], vf[2 * i][1], vf[2 * i][2], vf[2 * i][3], pa[2 * i], pa[2 * i + 1]);
                mma16816(O[1], vf[2 * i + 1][0], vf[2 * i + 1][1], vf[2 * i + 1][2], vf[2 * i + 1][3], pa[2 * i], pa[2 * i + 1]);
            }
            mma1688(O[0], vv[0], vv[1], pa[4]);
            mma1688(O[1], vv[2], vv[3], pa[4]);
            uint32_t o[2][2];
#pragma unroll
            for (int j = 0; j < 2; j++) { o[j][0] = pack2(O[0][j], O[0][2 + j]); o[j][1] = pack2(O[1][j], O[1][2 + j]); }
#pragma unroll
            for (int j = 0; j < 2; j++) st_async2(lo + rdelta + j * 256, o[j][0], o[j][1], sb + rdelta + B_K);
            st_async1(ls + sdelta + (warp & 1) * 128, __float_as_uint(sum), sb + sdelta + B_K);
#pragma unroll
            for (int j = 0; j < 2; j++) st_async2(lo + vdelta + j * 256, o[j][0], o[j][1], sb + vdelta + B_K);
#pragma unroll
            for (int j = 0; j < 2; j++) sts64(lo + j * 256, o[j][0], o[j][1]);
            sts32(ls + warp * 128, __float_as_uint(sum));
            PROF(5)
            bar_sync(3, 256);
            if (LEADER(0)) { mbar_expect(sb + B_K, 2048); mbar_expect(sb + B_V, 2048); mbar_arrive(sb + B_KVGO + slot * 8); }
            S = next_scale(sb, slot, warp, u2);
            if (s == 0) mbar_wait(sb + B_WO, 0);
            pin<1>(&S);
            SFENCE();
#pragma unroll
            for (int j = 0; j < 4; j++) lds128(ob[j], l8 * 2 - sb + S_O + j * 512);
            lds64f(Sj, sb + S_SUM + (l8 & 24));
#pragma unroll
            for (int i = 0; i < PF2; i++) W2LD(i);
        } else {
            if (ROLE == 0) { bar_sync(1, 256); reduce_load(x, pld + 8192); sts32(pub + 1024, reduce8(x, l8, u2)); bar_arrive(2, 256); }
            if (LEADER(7)) { if (s) mbar_arrive(sb + B_GO); if (ROLE) mbar_expect(sb + B_K, 2304); }
            S = next_scale(sb, slot, warp, u2);
            if (s == 0) mbar_wait(sb + B_WO, 0);
            if (ROLE != 0) PERSIST()
            W2ADDR(0)
#pragma unroll
            for (int i = 0; i < PF2; i++) {
                W2LD(i);
                if (ROLE == 0 && (i & PACE) == PACE) w2a += w[i][0] & P.zero;
            }
            ro = opq(ro, ln);
            const uint32_t sa = opq(sb + S_SUM + (l8 & 24), ln), oa = opq(l8 * 2 - sb + S_O, ln);
            if (ROLE == 0) bar_sync(3, 256); else mbar_wait(sb + B_K, slot);
            if (OBN == 4 || !ROLE) lds64f(Sj, sa);
#pragma unroll
            for (int j = 0; j < 4; j++) { if (ROLE && j == OBN) SFENCE(); lds128(ob[j], oa + j * 512); }
            if (OBN < 4 && ROLE) lds64f(Sj, sa);
        }
        SSTAMP(9, threadIdx.x == 224 && s == 0)
        if (OBN == 4 || !ROLE) SFENCE();
        PROF(6)
        {
            const uint8_t* pr = P.gm + ro;
            float c[4][4];
            uint32_t lim = 0;
#pragma unroll
            for (int i = 0; i < 4; i++) { c[i][0] = c[i][1] = c[i][2] = c[i][3] = 0.f; }
#pragma unroll
            for (int i = 0; i < 16; i++) {
                W2MMA(c[i & (ROLE && !CH4 ? 1 : 3)], i);
                if (i + PF2 < (ROLE ? 16 + NEARLY : 16)) W2LD(i + PF2);
                if (i == 5) {
                    const uint32_t z = __float_as_uint(c[1][0]) & P.zero;
                    Sj[0] = S * rcp(__uint_as_float(__float_as_uint(Sj[0]) | z)); Sj[1] = S * rcp(__uint_as_float(__float_as_uint(Sj[1]) | z));
                }
                if (i == 5) lim = __any_sync(0xffffffffu, fmaxf(fmaxf(fabsf(c[0][0]), fabsf(c[0][2])), fmaxf(fabsf(c[1][0]), fabsf(c[1][2]))) * Sj[0] >= (ROLE && !CH4 ? 24.f : 20.f)) ? 16384 : 0;
                if (i == FPOS) { pin<1>(&lim); pin<2>(Sj); pin_ptr(pr); SFENCE(); }
            }
            if (ROLE == 0 || CH4) {
#pragma unroll
                for (int i = 0; i < 8; i++) { c[i >> 2][i & 3] += c[2 + (i >> 2)][i & 3]; c[2 + (i >> 2)][i & 3] = 0.f; }
            }
            const float xa[2][3] = {{c[0][0], c[0][2], c[1][0]}, {c[0][1], c[0][3], c[1][1]}};
            uint64_t wa[2], wb[2];
            emit<NU>(wa, xa, Sj, P.two26, lim, pr);
            PROF(7)
            mo = GATHER_OFF(s + 1);
            pin<1>(&mo);
            if (ROLE) {
                SFENCE();
#pragma unroll
                for (int i = 16 + NEARLY; i < 24; i++) { if (i == 16 + NBAR) bar_sync(2, 256); W2LD(i); __syncwarp(); }
                SFENCE();
#pragma unroll
                for (int i = 16; i < 24; i++) W2MMA(c[2 + (i & 1)], i);
#pragma unroll
                for (int i = 0; i < 4; i++) c[2][i] += c[3][i];
            }
            const float y[2][3] = {{ROLE ? c[1][2] : c[1][0], ROLE ? c[2][0] : c[1][2], c[2][2]}, {ROLE ? c[1][3] : c[1][1], ROLE ? c[2][1] : c[1][3], c[2][3]}};
            const bool released = !ROT || mbar_test(sb + B_RELA, slot ^ 1);
            emit<NU>(wb, y, Sj, P.two26, lim, pr + RO2);
            PROF(8)
            if (!__all_sync(0xffffffffu, (wa[0] & wb[0] & 1) && released && s)) {
                if (__builtin_expect(!__all_sync(0xffffffffu, wa[0] & wb[0] & 1), 0)) {
                    RETRY(5)
                    const uint8_t* pf = g_f + (s & 7) * F_SLOT + (ROLE ? ROLE * 8192 + warp * 1024 : (warp & 3) * 1024 + (att ? 24576 : 0)) + (ln & 3) * 128 + (ln >> 2) * 16;
                    repair<NU>(wa, xa, Sj, pr, pf);
                    repair<NU>(wb, y, Sj, pr + RO2, pf + (ROLE ? 24576 : 4096));
                }
                if (s == 0) { bar_sync(1, 256); if (LEADER(7)) mbar_arrive(sb + B_GO); }
                if (ROT) mbar_wait(sb + B_RELA, slot ^ 1);
            }
        }
        s++;
    }
}
struct Pipe { uint32_t stage, phase; };
struct Cons {
    uint32_t sb, rel;
    int wg, wq, lane, rank, pair;
    uint32_t nst;
    Pipe p;
};
__device__ __forceinline__ void pipe_next(Pipe& p) { p.stage = (p.stage + 1) & (NSTAGE - 1); p.phase ^= (p.stage == 0); }
__device__ __forceinline__ void release(const Cons& c, uint32_t stage) { if (c.lane < 2) mbar_arrive_cluster(c.rel + stage * 8); }

enum { PEND_NONE = 0, PEND_KVO = 1, PEND_HT = 2, PEND_OUT = 3, PEND_OUTH = 4 };
struct Pend { uint32_t pk[64]; int kind, row, col, cnt; };

__device__ __forceinline__ void staging_wait(const Cons& c) { if (c.nst) mbar_wait(c.sb + B_SFREE + c.wg * 8, (c.nst - 1) & 1); }
__device__ __forceinline__ void staging_post(Cons& c, int kind, int row, int col, int cnt) {
    __syncwarp();
    if (c.lane == 0) {
        if (c.wq == 0) { const uint32_t x[4] = {(uint32_t)kind, (uint32_t)row, (uint32_t)col, (uint32_t)cnt}; sts128(c.sb + S_DESC + c.wg * 16, x); }
        mbar_arrive(c.sb + B_SFULL + c.wg * 8);
    }
    c.nst++;
}
template <int HF, bool KVONLY = false>
__device__ __forceinline__ void drain(const Params& P, Cons& c, const Pend& d) {
    const uint32_t* pk = d.pk + HF * 32;
    if (!KVONLY && d.kind >= PEND_OUT) {
        if (HF == 1 && d.kind == PEND_OUTH) return;
        float* o = P.out + (size_t)(d.row + c.wq * 16 + (c.lane >> 2)) * 2048 + d.col + HF * 128 + (c.lane & 3) * 2;
#pragma unroll
        for (int j = 0; j < 16; j++) {
            st_stream2(o + j * 8, bf_lo(pk[j * 2]), bf_hi(pk[j * 2]));
            st_stream2(o + 8 * 2048 + j * 8, bf_lo(pk[j * 2 + 1]), bf_hi(pk[j * 2 + 1]));
        }
    } else if (d.kind != PEND_NONE) {
        const bool ht = !KVONLY && d.kind == PEND_HT;
        const int hi = (c.lane >> 3) & 1;
        const uint32_t base = c.sb + S_STG + c.wg * 16384 + ((ht ? hi * 32 + c.wq * 8 : c.wq * 16 + hi * 8) + (c.lane & 7)) * 128;
        staging_wait(c);
#pragma unroll
        for (int j = 0; j < 8; j++) {
            const int ch = (j & 3) * 2 + (c.lane >> 4);
            stsm4(base + (j >> 2) * 8192 + ((ch ^ (c.lane & 7)) << 4), pk[j * 4], pk[j * 4 + 1], pk[j * 4 + 2], pk[j * 4 + 3]);
        }
        fence_async_smem();
        staging_post(c, d.kind, d.row, d.col + HF * 128, HF ? d.cnt : -1);
    }
}
__device__ __forceinline__ void drain_all(const Params& P, Cons& c, Pend& d) { drain<0>(P, c, d); drain<1>(P, c, d); d.kind = PEND_NONE; }

__device__ __forceinline__ void store_warp(const Params& P, uint32_t sb, int wg) {
    const uint32_t stg = sb + S_STG + wg * 16384;
#pragma unroll 1
    for (uint32_t n = 0;; n++) {
        mbar_wait(sb + B_SFULL + wg * 8, n & 1);
        uint32_t x[4];
        lds128(x, sb + S_DESC + wg * 16);
        if (x[0] == PEND_NONE) break;
        const bool ht = x[0] == PEND_HT;
        const CUtensorMap* m = &P.tm[ht ? M_HTS : M_KVO];
#pragma unroll 1
        for (int i = 0; i < 4; i++) if (!(DBGF(128) && gridDim.x != 96)) tma_store2d(m, x[2] + (i >> 1) * 64, x[1] + (i & 1) * (ht ? 1024 : 32), stg + i * 4096);
        bulk_commit();
        bulk_wait_read();
        mbar_arrive(sb + B_SFREE + wg * 8);
        if ((int)x[3] >= 0) {
            bulk_wait_all(); fence_async();
            asm volatile("red.relaxed.gpu.global.add.u32 [%0], 1;" ::"l"(&g_cnt(x[3])) : "memory");
        }
    }
}

template <int N, int TA, int TB, bool FIRST>
__device__ __forceinline__ void issue_ktile(float* acc, const Cons& c) {
    mbar_wait(c.sb + B_FULL + c.p.stage * 8, c.p.phase);
    const uint32_t a = c.sb + c.p.stage * STAGE + c.wg * 8192, b = c.sb + c.p.stage * STAGE + 16384;
    const uint64_t da = mkdesc(a, TA ? 8192 : 16, 1024, 1), db = mkdesc(b, TB ? 8192 : 16, 1024, 1);
    wg_fence();
#pragma unroll
    for (int k = 0; k < 4; k++) {
        const uint64_t x = da + (TA ? 128 : 2) * k, y = db + (TB ? 128 : 2) * k;
        if (N == 256) { if (FIRST && k == 0) wgmma_ss256_first<TA, TB>(acc, x, y); else wgmma_ss256<TA, TB>(acc, x, y); }
        else { if (FIRST && k == 0) wgmma_ss128_first<TA, TB>(acc, x, y); else wgmma_ss128<TA, TB>(acc, x, y); }
    }
    wg_commit();
}
template <int N, bool FIRST>
__device__ __forceinline__ void issue_any(float* acc, const Cons& c, int type) {
    if (N == 256 && type == T_A1) issue_ktile<N, 0, 0, FIRST>(acc, c);
    else if (type == (N == 256 ? T_A2 : T_A2H)) issue_ktile<N, 1, 0, FIRST>(acc, c);
    else issue_ktile<N, 0, 1, FIRST>(acc, c);
}
template <int N, bool KVONLY = false>
__device__ __forceinline__ void mainloop(float* acc, const Params& P, Cons& c, Pend& d, int type) {
    const int nk = (type == T_OP || type == T_OPH) ? 64 : (type == T_A2 || type == T_A2H) ? 32 : 16;
    issue_any<N, true>(acc, c, type);
    drain<0, KVONLY>(P, c, d);
    uint32_t prev = c.p.stage;
    pipe_next(c.p);
    const int hold = c.wg ? nk - (int)((P.lag >> (4 * type)) & 7) : -1;
    for (int kt = 1; kt < nk; kt++) {
        if (kt == hold) bar_sync(8, 256);
        issue_any<N, false>(acc, c, type);
        wg_wait<1>();
        release(c, prev);
        if (kt == 2) drain<1, KVONLY>(P, c, d);
        prev = c.p.stage;
        pipe_next(c.p);
    }
    if (c.wg == 0 && ((P.lag >> (4 * type)) & 7)) bar_arrive(8, 256);
    d.kind = PEND_NONE;
    wg_wait<0>();
    pin<N / 2>(acc);
    release(c, prev);
}
__device__ __forceinline__ void pack_half(uint32_t* pk, const float* a) {
#pragma unroll
    for (int i = 0; i < 32; i++) pk[i] = pack2(a[2 * i], a[2 * i + 1]);
}

__device__ __forceinline__ void epi_kv(const float* acc, const Cons& c, Pend& d, int mb, int nb) {
    pack_half(d.pk, acc); pack_half(d.pk + 32, acc + 64);
    d.kind = PEND_KVO; d.row = (nb >> 4) * 2048 + mb * 256 + c.rank * 128 + c.wg * 64; d.col = (nb & 15) * 256; d.cnt = C_KV + mb;
}

__device__ __forceinline__ void epi_qa(const float* acc, Cons& c, Pend& d, int mb, int nb) {
    uint32_t q[64];
    pack_half(q, acc);
    pack_half(q + 32, acc + 64);
#pragma unroll
    for (int i = 0; i < 32; i++) d.pk[32 + i] = 0;
    const int g = c.lane >> 2, t = c.lane & 3;
    const bool sg = c.wq >= 2;
    const int i0 = (c.wq & 1) * 16 + g;
#pragma unroll 1
    for (int hh = 0; hh < 2; hh++) {
        uint32_t pa[5][4];
        {
            float S[32] = {}, Sm[8] = {};
            mbar_wait(c.sb + B_FULL + c.p.stage * 8, c.p.phase);
            const uint32_t st = c.sb + c.p.stage * STAGE;
            const uint64_t dk = mkdesc(st + c.wg * 8192, 16, 1024, 1), dm = mkdesc(st + 32768 + c.wg * 4096, 128, 2048, 0);
            pin<32>(q); pin<32>(S); pin<8>(Sm);
            wg_fence();
#pragma unroll
            for (int i = 0; i < 8; i++) wgmma_rs64<0>(S, q + i * 4, dk + (i >> 2) * 1024 + (i & 3) * 2, i != 0);
#pragma unroll
            for (int i = 0; i < 8; i++) wgmma_rs16<0>(Sm, q + i * 4, dm + i * 16, i != 0);
            wg_commit();
            wg_wait<0>();
            pin<32>(S); pin<8>(Sm);
            release(c, c.p.stage);
            pipe_next(c.p);
            const float scale = 0.08838834764831845f, l2e = 1.4426950408889634f;
            float x[2][10];
#pragma unroll
            for (int r = 0; r < 2; r++) {
#pragma unroll
                for (int j = 0; j < 4; j++)
#pragma unroll
                    for (int e = 0; e < 2; e++) {
                        const float v = sg ? S[16 + j * 4 + r * 2 + e] : S[j * 4 + r * 2 + e];
                        x[r][j * 2 + e] = (j * 8 + 2 * t + e > i0 + r * 8) ? -1e9f : v * scale;
                    }
                x[r][8] = (sg ? Sm[4 + r * 2] : Sm[r * 2]) * scale;
                x[r][9] = (sg ? Sm[5 + r * 2] : Sm[1 + r * 2]) * scale;
                float m = x[r][0];
#pragma unroll
                for (int i = 1; i < 10; i++) m = fmaxf(m, x[r][i]);
                m = fmaxf(m, __shfl_xor_sync(0xffffffffu, m, 1));
                m = fmaxf(m, __shfl_xor_sync(0xffffffffu, m, 2));
                float sum = 0.f;
#pragma unroll
                for (int i = 0; i < 10; i++) { x[r][i] = ex2((x[r][i] - m) * l2e); sum += x[r][i]; }
                sum += __shfl_xor_sync(0xffffffffu, sum, 1);
                sum += __shfl_xor_sync(0xffffffffu, sum, 2);
                const float inv = rcp(sum);
#pragma unroll
                for (int i = 0; i < 10; i++) x[r][i] *= inv;
            }
#pragma unroll
            for (int ks = 0; ks < 2; ks++)
#pragma unroll
                for (int i = 0; i < 4; i++) {
                    const uint32_t p = pack2(x[i & 1][ks * 4 + (i >> 1) * 2], x[i & 1][ks * 4 + (i >> 1) * 2 + 1]);
                    pa[ks][i] = sg ? 0u : p;
                    pa[2 + ks][i] = sg ? p : 0u;
                }
#pragma unroll
            for (int r = 0; r < 2; r++) {
                const uint32_t p = pack2(x[r][8], x[r][9]);
                pa[4][r] = sg ? 0u : p;
                pa[4][2 + r] = sg ? p : 0u;
            }
        }
        float O[64] = {};
        mbar_wait(c.sb + B_FULL + c.p.stage * 8, c.p.phase);
        const uint32_t st = c.sb + c.p.stage * STAGE;
        const uint64_t dv = mkdesc(st + c.wg * 8192, 16384, 1024, 1), dm = mkdesc(st + 32768 + c.wg * 4096, 2048, 128, 0);
        pin<20>(&pa[0][0]); pin<64>(O);
        wg_fence();
#pragma unroll
        for (int ks = 0; ks < 4; ks++) wgmma_rs128<1>(O, pa[ks], dv + ks * 128, ks != 0);
        wgmma_rs128<0>(O, pa[4], dm, 1);
        wg_commit();
        wg_wait<0>();
        pin<64>(O);
        release(c, c.p.stage);
        pipe_next(c.p);
#pragma unroll
        for (int i = 0; i < 32; i++) { q[i] = q[32 + i]; q[32 + i] = d.pk[32 + i]; }
        pack_half(d.pk + 32, O);
    }
#pragma unroll
    for (int i = 0; i < 32; i++) d.pk[i] = q[32 + i];
    d.kind = PEND_KVO; d.row = 4096 + mb * 256 + c.rank * 128 + c.wg * 64; d.col = nb * 256; d.cnt = C_O + mb * 4 + (nb >> 2);
}

__device__ __forceinline__ void epi_op(const float* acc, const Cons& c, Pend& d, int mb, int nb) {
    pack_half(d.pk, acc); pack_half(d.pk + 32, acc + 64);
    d.kind = PEND_OUT; d.row = mb * 256 + c.rank * 128 + c.wg * 64; d.col = 1024 + nb * 256;
}

__device__ __forceinline__ void epi_oph(const float* acc, const Cons& c, Pend& d, int mb, int nb) {
    pack_half(d.pk, acc);
    d.kind = PEND_OUTH; d.row = mb * 256 + c.rank * 128 + c.wg * 64; d.col = 1024 + nb * 128;
}

template <int HF>
__device__ __forceinline__ void epi_a2_half(const float* acc, const Params& P, Cons& c, int mb, int col0) {
    const int g = c.lane >> 2, t = c.lane & 3;
    const int row = mb * 256 + (g >> 1) * 64 + (c.rank * 16 + c.wg * 8 + c.wq * 2) * 2 + (g & 1);
    float* o = P.out + (size_t)row * 2048 + col0 + HF * 128 + t * 2;
    mbar_wait(c.sb + B_FULL + c.p.stage * 8, c.p.phase);
    const uint32_t st = c.sb + c.p.stage * STAGE, da = st + 32768 + (c.lane >> 3) * 16;
    const uint32_t xa = st + (c.wg * 64 + c.wq * 16 + (c.lane & 15)) * 128 + (((c.lane >> 4) ^ (c.lane & 7)) << 4);
#pragma unroll
    for (int j4 = 0; j4 < 4; j4++) {
        uint32_t x[8], dv[4];
        ldsm4(dv, da + j4 * 64);
        ldsm4(x, (xa ^ ((j4 & 1) << 6)) + (j4 >> 1) * 16384);
        ldsm4(x + 4, (xa ^ ((j4 & 1) << 6) ^ 32) + (j4 >> 1) * 16384);
#pragma unroll
        for (int i = 0; i < 4; i++) {
            const int j = j4 * 4 + i;
            const float* a = acc + HF * 64 + j * 4;
            const uint32_t u0 = hmul2(x[2 * i], dv[i]), u1 = hmul2(x[2 * i + 1], dv[i]);
            st_stream2(o + j * 8, a[0] + bf_lo(u0), a[1] + bf_hi(u0));
            st_stream2(o + 2 * 2048 + j * 8, a[2] + bf_lo(u1), a[3] + bf_hi(u1));
        }
    }
    __syncwarp();
    release(c, c.p.stage);
    pipe_next(c.p);
}

#define TSTAMP(i)
__device__ __forceinline__ float2 cmul(float2 a, float2 b) { return make_float2(fmaf(a.x, b.x, -a.y * b.y), fmaf(a.x, b.y, a.y * b.x)); }
__device__ __forceinline__ float2 cfma(float2 a, float2 b, float2 u) { return make_float2(fmaf(a.x, b.x, fmaf(-a.y, b.y, u.x)), fmaf(a.x, b.y, fmaf(a.y, b.x, u.y))); }
__device__ __forceinline__ float4 ssm_coef(float lre, float lim, float logdt) {
    const float dt = __bfloat162float(__float2bfloat16(expf(logdt)));
    const float ea = expf(dt * lre);
    float sn, cn;
    sincosf(dt * lim, &sn, &cn);
    const float br = ea * cn, bi = ea * sn, nr = br - 1.f;
    float cr, ci;
    if (fabsf(lre) >= fabsf(lim)) { const float r = lim / lre, dn = lre + lim * r; cr = (nr + bi * r) / dn; ci = (bi - nr * r) / dn; }
    else { const float r = lre / lim, dn = lre * r + lim; cr = (nr * r + bi) / dn; ci = (bi * r - nr) / dn; }
    return make_float4(br, bi, cr, ci);
}
__device__ __forceinline__ void epi_a1(const float* acc, const Params& P, const Cons& c, Pend& d, int mb, int nb, uint32_t atag) {
    const int t = c.lane & 3;
    const int p = nb * 128 + c.rank * 64 + c.wg * 32 + c.wq * 8 + (c.lane >> 2);
    uint32_t cw[4];
    lds128(cw, c.sb + S_COEF + (p & 63) * 16);
    const float4 cf = make_float4(__uint_as_float(cw[0]), __uint_as_float(cw[1]), __uint_as_float(cw[2]), __uint_as_float(cw[3]));
    TSTAMP(1)
    const float2 lam = make_float2(cf.x, P.swap_ri ? -cf.y : cf.y);
    const float a0 = P.swap_ri ? -2.f * cf.w : 2.f * cf.z, a1 = P.swap_ri ? 2.f * cf.z : -2.f * cf.w;
    const float b0 = P.swap_ri ? -2.f * cf.z : -2.f * cf.w, b1 = P.swap_ri ? -2.f * cf.w : -2.f * cf.z;
    float2 h = make_float2(0.f, 0.f);
#pragma unroll
    for (int round = 0; round < 2; round++) {
#pragma unroll
        for (int j = 0; j < 32; j++) {
            h = cfma(lam, h, make_float2(acc[j * 4], acc[j * 4 + 2]));
            const float r0 = fmaf(a0, h.x, a1 * h.y), m0 = fmaf(b0, h.x, b1 * h.y);
            h = cfma(lam, h, make_float2(acc[j * 4 + 1], acc[j * 4 + 3]));
            d.pk[j * 2] = pack2(r0, fmaf(a0, h.x, a1 * h.y));
            d.pk[j * 2 + 1] = pack2(m0, fmaf(b0, h.x, b1 * h.y));
        }
        if (round) break;
        float2 l64 = lam;
#pragma unroll
        for (int i = 0; i < 6; i++) l64 = cmul(l64, l64);
        const float2 l128 = cmul(l64, l64), l256 = cmul(l128, l128);
        float2 o = make_float2(__shfl_up_sync(0xffffffffu, h.x, 1), __shfl_up_sync(0xffffffffu, h.y, 1));
        if (t >= 1) h = cfma(l64, o, h);
        o = make_float2(__shfl_up_sync(0xffffffffu, h.x, 2), __shfl_up_sync(0xffffffffu, h.y, 2));
        if (t >= 2) h = cfma(l128, o, h);
        TSTAMP(2)
        if (t == 3) st_relaxed2(&g_agg[mb * 1024 + p], (__float_as_uint(h.x) & ~1u) | atag, __float_as_uint(h.y));
        h = make_float2(__shfl_up_sync(0xffffffffu, h.x, 1), __shfl_up_sync(0xffffffffu, h.y, 1));
        if (t == 0) h = make_float2(0.f, 0.f);
        uint32_t ax[7], ay[7];
        int n = 0;
        while (true) {
            uint32_t bad = 0;
#pragma unroll
            for (int j = 0; j < 7; j++) { ax[j] = atag; ay[j] = 0; ld_relaxed2_if(ax[j], ay[j], &g_agg[j * 1024 + p], j < mb); }
#pragma unroll
            for (int j = 0; j < 7; j++) bad |= ax[j] ^ atag;
            if (tags_ok(bad)) break;
            __nanosleep(400);
            if (++n > SPIN_LIMIT) spin_fault();
        }
        float2 carry = make_float2(0.f, 0.f);
#pragma unroll
        for (int j = 0; j < 7; j++) if (j < mb) carry = cfma(l256, carry, make_float2(__uint_as_float(ax[j]), __uint_as_float(ay[j])));
        float2 w = (t & 1) ? l64 : make_float2(1.f, 0.f);
        if (t & 2) w = cmul(w, l128);
        h = cfma(w, carry, h);
        TSTAMP(3)
    }
    TSTAMP(4)
    d.kind = PEND_HT; d.row = nb * 128 + c.rank * 64 + c.wg * 32; d.col = mb * 256; d.cnt = C_HT + mb * 2 + (nb >> 2);
}

__device__ __forceinline__ uint32_t acquire_stage(uint32_t sb, Pipe& p, uint32_t bytes) {
    mbar_wait(sb + B_EMPTY + p.stage * 8, p.phase ^ 1);
    mbar_expect(sb + B_FULL + p.stage * 8, bytes);
    return p.stage;
}
#define AHEAD 1
__device__ __forceinline__ void watcher(const Params& P, const uint32_t sb, const int rank, const int lane) {
    const uint32_t epoch = ld_relaxed1(&g_cnt(C_EPOCH)), e1 = epoch + 1;
    sts32(sb + S_EPOCH, epoch);
    __syncwarp();
    if (lane == 0 && atomicInc(&g_cnt(C_DONE), (DBGF(32) ? 95 : NPAIR * 2 - 1) + (epoch & P.zero)) == (DBGF(32) ? 95 : NPAIR * 2 - 1)) atomicAdd(&g_cnt(C_EPOCH), 1);
    if (gridDim.x != 96) {
        uint32_t v;
        asm("mov.u32 %0, %%smid;" : "=r"(v));
        if (lane == 0 && rank == 0) st_relaxed1(g_hint + 6272 + (blockIdx.x >> 1), e1 << 8 | v >> 1);
        for (int k = 0;; k++) {
            __nanosleep(1000);
            v = ld_relaxed1(g_hint + 6272 + min(lane, 17));
            if (__all_sync(0xffffffffu, (v ^ e1 << 8) < 256)) break;
            if (k > SPIN_LIMIT) spin_fault();
        }
        const uint32_t key = ((v & 255) >= 62 ? 0 : tpc_gpc(v & 255)) * 32 + lane;
        sts32(sb + S_TAIL, 48 + __popc(__ballot_sync(0xffffffffu, key < __shfl_sync(0xffffffffu, key, blockIdx.x >> 1)) & 0x3ffff));
        __syncwarp();
    }
    uint32_t met = 1;
    if (lane == 0) asm volatile("st.release.cta.shared.u32 [%0], 1;" ::"r"(sb + S_DEP) : "memory");
    const int pair = lds32(sb + S_TAIL), first = ITEM_OFF(pair) + (pair < NCHAIN ? NPRE + 1 : 1);
#pragma unroll 1
    for (int it = first; it < ITEM_OFF(pair + 1); it++) {
        const int item = ITEM(it), type = item >> 8, mb = (item >> 5) & 7, nb = item & 31;
        const int n = (0x24021420 >> (type * 4)) & 7;
        for (int k = 0; it > first && (int)lds32(sb + S_CUR) < it - AHEAD; k++) { __nanosleep(200); if (k > SPIN_LIMIT) spin_fault(); }
#pragma unroll 1
        for (int i = 0; i < n; i++) {
            int idx = n == 4 ? C_O + mb * 4 + i : C_HT + mb * 2 + i;
            uint32_t target = e1 * 16;
            if (type == T_A1) { idx = C_COEF; target = e1 * 4; }
            if (type == T_QA) {
                idx = i ? C_FLAG + (lane & 1) * 32 + nb * 2 + ((lane >> 1) & 1) : C_KV + mb;
                target = i ? epoch * 64 + mb * 8 + rank * 4 + 4 : e1 * 128;
            }
            if (lane < 4) { wait_count(&g_cnt(idx), target); fence_async(); }
            __syncwarp();
            if (lane == 0) asm volatile("st.release.cta.shared.u32 [%0], %1;" ::"r"(sb + S_DEP), "r"(++met) : "memory");
        }
    }
}
__device__ __forceinline__ bool dep_met(uint32_t sb, uint32_t n) { uint32_t v; asm volatile("ld.acquire.cta.shared.u32 %0, [%1];" : "=r"(v) : "r"(sb + S_DEP) : "memory"); return v >= n; }
__device__ __forceinline__ void dep_wait(uint32_t sb, uint32_t n) { for (int k = 0; !dep_met(sb, n); k++) { __nanosleep(32); if (k > SPIN_LIMIT * 8) spin_fault(); } }
__device__ __forceinline__ void producer(const Params& P, const uint32_t sb, int pair, const int rank) {
    Pipe p = {0, 0};
    uint32_t dep = 1;
    for (int it = ITEM_OFF(pair); it < ITEM_OFF(pair + 1); it++) {
        const int item = ITEM(it), type = item >> 8, mb = (item >> 5) & 7, nb = item & 31;
        if (type == T_CHAIN) {
            sts32(sb + S_CUR, 0);
            const uint32_t epoch = ld_relaxed1(&g_cnt(C_EPOCH)), e1 = epoch + 1;
            const int role = pair >> 4, h = (pair & 15) * 2 + rank;
#pragma unroll 1
            for (int i = 0, q = 0; i < 8; i++) {
                const int n = (0x13003333 >> (i * 4)) & 3;
                const uint32_t st = acquire_stage(sb, p, n * 16384);
                SSTAMP(1, i == 0) SSTAMP(3, i == 3)
#pragma unroll 1
                for (int k = 0; k < 2 * n; k++, q++)
                    tma3d(sb + st * STAGE + k * 8192, &P.tm[M_CQ + role], h * 128 + (fill_unit(q >> 1) & 1) * 64, word_col((fill_unit(q >> 1) & 14) + (q & 1)) & 8, word_col((fill_unit(q >> 1) & 14) + (q & 1)) >> 4, sb + B_FULL + st * 8);
                pipe_next(p);
            }
            if (role == 0 && !DBGF(1)) { wait_count(&g_cnt(C_KV), e1 * 128); fence_async(); }
            mbar_wait(sb + B_EMPTY + 16, 1); mbar_wait(sb + B_EMPTY + 24, 1);
            mbar_expect(sb + B_WO, role ? 98304 : 65536);
            if (role == 0) { mbar_expect(sb + B_KVFULL, 16384); mbar_expect(sb + B_KVFULL + 8, 16384); }
#pragma unroll 1
            for (int k = role ? 0 : -4; k < 12; k++) {
                const bool kv = role == 0 && (k & 8);
                const int sg = k > 0;
                tma4d(kv ? sb + S_KV + sg * 16384 + (k & 3) * 4096 : sb + S_W2 + k * 8192, &P.tm[kv ? M_KV4 : M_CO + (k & 1)],
                      kv ? h * 128 + (k & 1) * 64 : (role == 0 ? 0 : role == 1 ? 256 : 640) + (k >> 1) * 64, kv ? (k & 2) * 1024 + sg * 32 : h * 8, sb + (kv ? B_KVFULL + sg * 8 : B_WO));
            }
            SSTAMP(5, true)
            if (pair < 16) {
#pragma unroll 1
                for (int s = 2; s < 63; s++) {
                    mbar_wait(sb + B_KVGO + (s & 1) * 8, ((s >> 1) + 1) & 1);
                    wait_time(gtime() + P.dk, sb);
                    SSTAMP(6, s == 2)
                    const uint32_t bar = sb + B_KVFULL + (s & 1) * 8, dst = sb + S_KV + (s & 1) * 16384;
                    if (DBGF(2)) { mbar_arrive(bar); continue; }
                    mbar_expect(bar, 16384);
#pragma unroll 1
                    for (int i = 0; i < 4; i++) tma2d(dst + i * 4096, &P.tm[M_KVO], (pair * 2 + rank) * 128 + (i & 1) * 64, (i >> 1) * 2048 + (DBGF(32 | 512) ? s & 7 : s) * 32, bar);
                    if ((s & 7) == 7 && !DBGF(1)) { wait_count(&g_cnt(C_KV + 1 + (s >> 3)), e1 * 128); fence_async(); }
                }
            } else {
                uint32_t* flag = &g_cnt(C_FLAG + pair * 2 + rank - 32);
                const int x = pair * 2 + rank - 32;
#pragma unroll 1
                for (int s = 0; s < 64; s++) {
                    mbar_wait(sb + B_PERS, s & 1);
                    if (s < 63) wait_time(gtime() + P.dp, sb);
                    if (!DBGF(4)) bulk_s2g((role == 1 ? g_km : g_vmt) + (s * 32 + h) * 512, sb + S_QX, 2048);
                    if (s < 57) {
                        uint8_t* m = P.gm + ((s + 6) & 7) * M_SLOT + (x >> 1) * 1024 + (x & 1) * 256;
                        bulk_s2g(m, sb + S_SX, 256); bulk_s2g(m + 512, sb + S_SX, 128);
                        bulk_s2g(g_f + ((s + 6) & 7) * F_SLOT + x * 768, sb + S_SX + 256, 768);
                    }
                    bulk_commit();
                    bulk_wait_read();
                    mbar_arrive(sb + B_KVGO);
                    bulk_wait_all();
                    fence_async();
                    if ((s & 3) == 3) st_relaxed1(flag, epoch * 64 + s + 1);
                }
            }
            mbar_wait(sb + B_RESUME, 0);
            pair = lds32(sb + S_TAIL);
            it = ITEM_OFF(pair) + NPRE;
            continue;
        }
        if (it == ITEM_OFF(pair) && pair >= NCHAIN) it = -1; else sts32(sb + S_CUR, it);
        const int m0 = mb * 256 + rank * 128;
        if (type <= T_OP) {
            const CUtensorMap* ma = &P.tm[type == T_OP ? M_OA : M_BX];
            const CUtensorMap* mw = &P.tm[type == T_OP ? M_WO : type == T_QA ? M_WQ : nb < 16 ? M_WK : M_WV];
            const int nk = type == T_OP ? 64 : 16, nc = (nb & 15) * 4 + rank * 2, ma0 = type == T_OP ? 4096 + m0 : m0;
#pragma unroll 1
            for (int kt = 0; kt < nk; kt++) {
                if (type == T_OP && (kt & 15) == 0) dep_wait(sb, ++dep);
                if (DBGF(256) && pair >= NCHAIN) { acquire_stage(sb, p, 0); pipe_next(p); continue; }
                const uint32_t st = acquire_stage(sb, p, STAGE), bar = sb + B_FULL + st * 8;
                tma2d(sb + st * STAGE, ma, kt * 64, ma0, bar);
                tma3d_mc(sb + st * STAGE + 16384 + rank * 16384, mw, 0, kt * 64, nc, bar);
                pipe_next(p);
            }
            if (type == T_QA) {
                dep += 2;
                dep_wait(sb, dep);
#pragma unroll 1
                for (int e = 0; e < 4; e++) {
                    const uint32_t st = acquire_stage(sb, p, 40960), bar = sb + B_FULL + st * 8, dst = sb + st * STAGE;
                    tma2d(dst, &P.tm[M_OA], nb * 256 + (e >> 1) * 128, (e & 1) * 2048 + m0, bar);
                    tma2d(dst + 16384, &P.tm[M_OA], nb * 256 + (e >> 1) * 128 + 64, (e & 1) * 2048 + m0, bar);
                    const uint32_t* src = ((e & 1) ? g_vmt : g_km) + ((mb * 8 + rank * 4) * 32 + nb * 2 + (e >> 1)) * 512;
#pragma unroll 1
                    for (int i = 0; i < 4; i++) bulk_g2s(dst + 32768 + i * 2048, src + i * 32 * 512, 2048, bar);
                    pipe_next(p);
                }
            }
        } else if (type == T_OPH) {
#pragma unroll 1
            for (int kt = 0; kt < 64; kt++) {
                if ((kt & 15) == 0) dep_wait(sb, ++dep);
                const uint32_t st = acquire_stage(sb, p, 32768), bar = sb + B_FULL + st * 8;
                tma2d(sb + st * STAGE, &P.tm[M_OA], kt * 64, 4096 + m0, bar);
                tma2d_mc(sb + st * STAGE + 16384 + rank * 8192, &P.tm[M_WOH], nb * 128 + rank * 64, kt * 64, bar);
                pipe_next(p);
            }
        } else if (type == T_A1) {
#pragma unroll 1
            for (int kt = 0; kt < 16; kt++) {
                if (kt == 15) dep_wait(sb, ++dep);
                const uint32_t st = acquire_stage(sb, p, kt == 15 ? STAGE + 1024 : STAGE), bar = sb + B_FULL + st * 8;
                if (kt == 15) bulk_g2s(sb + S_COEF, g_coef + nb * 128 + rank * 64, 1024, bar);
                tma4d(sb + st * STAGE, &P.tm[M_AB], kt * 64, nb * 16 + rank * 8, bar);
                tma4d_mc(sb + st * STAGE + 16384 + rank * 16384, &P.tm[M_AX], kt * 64, mb * 128 + rank * 16, bar);
                pipe_next(p);
            }
        } else {
            const int hw = type == T_A2H ? 64 : 128;
            const CUtensorMap* mc = &P.tm[type == T_A2H ? M_CREH : M_CRE];
#pragma unroll 1
            for (int kt = 0; kt < 32; kt++) {
                if ((kt & 15) == 0) dep_wait(sb, ++dep);
                const uint32_t st = acquire_stage(sb, p, 16384 + hw * 256), bar = sb + B_FULL + st * 8;
                tma3d(sb + st * STAGE, &P.tm[M_HT], 0, (kt & 1) * 1024 + (kt >> 1) * 64, mb * 4 + rank * 2, bar);
                tma2d_mc(sb + st * STAGE + 16384 + rank * hw * 128, mc + (kt & 1), (kt >> 1) * 64, (nb * 2 + rank) * hw, bar);
                pipe_next(p);
            }
#pragma unroll 1
            for (int col = nb * 2 * hw; col < (nb + 1) * 2 * hw; col += 128) {
                const uint32_t st = acquire_stage(sb, p, 32768 + 256), bar = sb + B_FULL + st * 8;
                tma4d(sb + st * STAGE, &P.tm[M_AX], col, mb * 128 + rank * 16, bar);
                tma4d(sb + st * STAGE + 16384, &P.tm[M_AX], col + 64, mb * 128 + rank * 16, bar);
                bulk_g2s(sb + st * STAGE + 32768, P.Dskip + col, 256, bar);
                pipe_next(p);
            }
        }
        if (it < 0) { dep_wait(sb, 1); pair = lds32(sb + S_TAIL); it = ITEM_OFF(pair); }
    }
}

__device__ __forceinline__ uint32_t fresh_tid() { uint32_t t; asm volatile("mov.u32 %0, %%tid.x;" : "=r"(t)); return t; }
__device__ __forceinline__ uint32_t fresh_ctaid() { uint32_t t; asm volatile("mov.u32 %0, %%ctaid.x;" : "=r"(t)); return logical_cta(t); }
__device__ __forceinline__ void reset_state(Cons& c, Pend& d, uint32_t sb, bool resumed) {
    const uint32_t t = fresh_tid(), b = fresh_ctaid();
    const int w = __shfl_sync(0xffffffffu, t >> 5, 0);
    c.sb = sb; c.wg = w >> 2; c.wq = w & 3; c.lane = t & 31;
    c.rank = __shfl_sync(0xffffffffu, b & 1, 0); c.pair = __shfl_sync(0xffffffffu, resumed && b < NCHAIN * 2 ? lds32(sb + S_TAIL) : b >> 1, 0);
    c.rel = mapa(sb + B_EMPTY, cluster_rank() ^ (c.lane & 1));
    c.p.stage = 0; c.p.phase = 0;
    c.nst = resumed && c.pair < NCHAIN ? 2 * NPRE : 0;
    d = Pend{};
}
#define PROF_ITEM(i)
#define PROF_MAIN(i)

__global__ void __launch_bounds__(384, 1) fused_kernel(const __grid_constant__ Params P) {
    extern __shared__ __align__(1024) uint8_t smem[];
    const uint32_t sb = smem_u32(smem);
    asm volatile("griddepcontrol.launch_dependents;");
    const int tid = threadIdx.x, lane = tid & 31;
    const int warp = __shfl_sync(0xffffffffu, tid >> 5, 0);
    const int pair = __shfl_sync(0xffffffffu, logical_cta(blockIdx.x) >> 1, 0), rank = __shfl_sync(0xffffffffu, blockIdx.x & 1, 0);
    if (tid == 0) {
        if (sb & 1023) spin_fault();
        sts32(sb + S_DEP, 0); sts32(sb + S_CUR, 0); sts32(sb + S_TAIL, pair); sts32(sb + S_CTA, pair * 2 + rank);
        for (int i = 0; i < NSTAGE; i++) { mbar_init(sb + B_FULL + i * 8, 1); mbar_init(sb + B_EMPTY + i * 8, 16); }
        mbar_init(sb + B_RESUME, 2);
        mbar_init(sb + B_KVFULL, 1); mbar_init(sb + B_KVFULL + 8, 1);
        mbar_init(sb + B_GO, 1); mbar_init(sb + B_KVGO, 1); mbar_init(sb + B_KVGO + 8, 1); mbar_init(sb + B_K, 1); mbar_init(sb + B_V, 1); mbar_init(sb + B_PERS, 8); mbar_init(sb + B_INIT, 3);
        mbar_init(sb + B_WO, 1);
        for (int i = 0; i < 2; i++) { mbar_init(sb + B_SFULL + i * 8, 4); mbar_init(sb + B_SFREE + i * 8, 1); }
        mbar_init(sb + B_RELA, 1); mbar_init(sb + B_RELB, 1);
        asm volatile("fence.mbarrier_init.release.cluster;" ::: "memory");
        if (pair < 16) mbar_expect(sb + B_K, 2048);
        mbar_expect(sb + B_V, 2048);
    }
    cluster_sync();
    if (warp >= 8) {
        asm volatile("setmaxnreg.dec.sync.aligned.u32 24;");
        if (warp == 10 && lane < M_COUNT) map_prefetch(&P.tm[lane]);
        if (warp == 11 && lane == 0 && pair < NCHAIN) {
            const uint32_t t0 = gtime();
            const int role = pair >> 4, h = (pair & 15) * 2 + rank;
#pragma unroll 1
            for (int i = role ? 32 : 0; i < (role ? 44 : 40); i++) {
                wait_time(t0 + P.pf0 + min(i, 32) * P.pf1 + max(i - 32, 0) * P.pf2, sb);
                if (i < 32) asm volatile("cp.async.bulk.prefetch.tensor.3d.L2.global [%0, {%1, %2, %3}];" ::"l"(&P.tm[M_CQ]), "r"(h * 128 + (i & 1) * 64), "r"((i & 2) * 4), "r"((i >> 2) * 8) : "memory");
                else asm volatile("cp.async.bulk.prefetch.tensor.4d.L2.global [%0, {%1, 0, 0, %2}];" ::"l"(&P.tm[M_CO + (i & 1)]), "r"((role == 0 ? 0 : role == 1 ? 256 : 640) + ((i - 32) >> 1) * 64), "r"(h * 8) : "memory");
            }
        }
        if (warp == 9 && pair < NCHAIN) pacer(P, sb, lane);
        if (warp == 9) watcher(P, sb, rank, lane);
        if (warp >= 10 && lane == 0) store_warp(P, sb, warp - 10);
        if (warp == 8) {
            if (lane == 0) producer(P, sb, lds32(sb + S_CTA) >> 1, rank);
            __syncwarp();
            asm volatile("barrier.cluster.arrive.relaxed.aligned;\nbarrier.cluster.wait.aligned;" ::: "memory");
        }
    } else {
        asm volatile("setmaxnreg.inc.sync.aligned.u32 240;");
        Cons c;
        Pend d;
        if (pair < NCHAIN) {
            mem0_max(P, sb, tid);
            reset_state(c, d, sb, false);
#pragma unroll 1
            for (int i = 0; i < NPRE; i++) {
                PROF_ITEM(i)
                const int item = ITEM(ITEM_OFF(pair) + i);
                float acc[128];
                mainloop<256, true>(acc, P, c, d, T_KV);
                epi_kv(acc, c, d, (item >> 5) & 7, item & 31);
            }
            ISTAMP(4)
            drain<0, true>(P, c, d);
            drain<1, true>(P, c, d);
            PROF_ITEM(NPRE)
            uint32_t wr[NR][4];
            load_weights(wr, sb, warp, lane, [&]() { staging_wait(c); });
            const int h = (pair & 15) * 2 + rank;
            if (pair < 16) chain_role<0>(P, wr, sb, h, warp, lane);
            else if (pair < 32) chain_role<1>(P, wr, sb, h, warp, lane);
            else chain_role<2>(P, wr, sb, h, warp, lane);
            fence_async_smem();
            bar_sync(1, 256);
            const uint32_t t2 = fresh_tid();
            if (t2 < 2) mbar_arrive_cluster(mapa(sb + B_RESUME, cluster_rank() ^ t2));
        } else if (pair >= NPAIR - 2) {
            const int ch = (pair - (NPAIR - 2)) * 512 + rank * 256 + tid;
            g_coef[ch] = ssm_coef(__bfloat162float(P.Lre[ch]), __bfloat162float(P.Lim[ch]), __bfloat162float(P.logdt[ch]));
            bar_sync(1, 256);
            if (tid == 0) red_release(&g_cnt(C_COEF));
        }
        reset_state(c, d, sb, true);
        for (int it = ITEM_OFF(c.pair) + (c.pair < NCHAIN ? NPRE + 1 : 0);; it++) {
            const bool last = it == ITEM_OFF(c.pair + 1);
            if (d.kind != PEND_NONE && (last || !bar_and(5 + c.wg, mbar_test(sb + B_FULL + c.p.stage * 8, c.p.phase)))) drain_all(P, c, d);
            if (last) break;
            const int item = ITEM(it), type = item >> 8, mb = (item >> 5) & 7, nb = item & 31;
            PROF_ITEM(it - ITEM_OFF(c.pair))
            if (type >= T_OPH) {
                float acc[64];
                mainloop<128>(acc, P, c, d, type);
                PROF_MAIN(it - ITEM_OFF(c.pair))
                if (type == T_OPH) epi_oph(acc, c, d, mb, nb);
                else epi_a2_half<0>(acc, P, c, mb, nb * 128);
            } else {
                float acc[128];
                mainloop<256>(acc, P, c, d, type);
                PROF_MAIN(it - ITEM_OFF(c.pair))
                if (type == T_KV) epi_kv(acc, c, d, mb, nb);
                else if (type == T_QA) epi_qa(acc, c, d, mb, nb);
                else if (type == T_OP) epi_op(acc, c, d, mb, nb);
                else if (type == T_A1) epi_a1(acc, P, c, d, mb, nb, (lds32(sb + S_EPOCH) + 1) & 1);
                else { epi_a2_half<0>(acc, P, c, mb, nb * 256); epi_a2_half<1>(acc, P, c, mb, nb * 256); }
            }
            if (it == ITEM_OFF(c.pair)) { dep_wait(sb, 1); c.pair = __shfl_sync(0xffffffffu, lds32(sb + S_TAIL), 0); it = ITEM_OFF(c.pair); }
        }
        staging_wait(c);
        staging_post(c, PEND_NONE, 0, 0, 0);
        asm volatile("barrier.cluster.arrive.relaxed.aligned;\nbarrier.cluster.wait.aligned;" ::: "memory");
    }
}

typedef CUresult (*EncodeFn)(CUtensorMap*, CUtensorMapDataType, cuuint32_t, void*, const cuuint64_t*, const cuuint64_t*, const cuuint32_t*, const cuuint32_t*,
                             CUtensorMapInterleave, CUtensorMapSwizzle, CUtensorMapL2promotion, CUtensorMapFloatOOBfill);
void encode(EncodeFn fn, CUtensorMap* m, const void* base, int rank, const uint64_t* dims, const uint64_t* strides, const uint32_t* box, CUtensorMapSwizzle swz = CU_TENSOR_MAP_SWIZZLE_128B) {
    cuuint64_t d[5], s[5]; cuuint32_t b[5], e[5];
    for (int i = 0; i < rank; i++) { d[i] = dims[i]; b[i] = box[i]; e[i] = 1; if (i) s[i - 1] = strides[i - 1]; }
    fn(m, CU_TENSOR_MAP_DATA_TYPE_BFLOAT16, rank, (void*)base, d, s, b, e, CU_TENSOR_MAP_INTERLEAVE_NONE, swz,
       CU_TENSOR_MAP_L2_PROMOTION_L2_256B, CU_TENSOR_MAP_FLOAT_OOB_FILL_NONE);
}
void map_kmajor(EncodeFn fn, CUtensorMap* m, const void* base, uint64_t rows, uint64_t cols, uint32_t box_rows) {
    const uint64_t d[2] = {cols, rows}, s[1] = {cols * 2}; const uint32_t b[2] = {64, box_rows};
    encode(fn, m, base, 2, d, s, b);
}
void map_mnmajor(EncodeFn fn, CUtensorMap* m, const void* base, uint64_t krows, uint64_t cols) {
    const uint64_t d[3] = {64, krows, cols / 64}, s[2] = {cols * 2, 128}; const uint32_t b[3] = {64, 64, 2};
    encode(fn, m, base, 3, d, s, b);
}

}

extern "C" void kernel_launch(void* const* d_in, const int* in_sizes, int n_in, void* d_out, int out_size) {
    static Params P;
    static EncodeFn fn = nullptr;
    if (!fn) {
        cudaDriverEntryPointQueryResult q;
        cudaGetDriverEntryPoint("cuTensorMapEncodeTiled", (void**)&fn, cudaEnableDefault, &q);
        cudaFuncSetAttribute(fused_kernel, cudaFuncAttributeMaxDynamicSharedMemorySize, S_TOTAL);
    }
    const bf16* in[15];
    for (int i = 0; i < 15; i++) in[i] = (const bf16*)d_in[i];
    void *kvo, *ht, *gm;
    cudaGetSymbolAddress(&gm, g_m);
    P.gm = (uint8_t*)(((uintptr_t)gm + 32767) & ~(uintptr_t)32767);
    cudaGetSymbolAddress(&kvo, g_kvo);
    cudaGetSymbolAddress(&ht, g_ht);
    map_kmajor(fn, &P.tm[M_BX], in[9], 2048, 1024, 128);
    map_mnmajor(fn, &P.tm[M_WQ], in[11], 1024, 4096);
    map_mnmajor(fn, &P.tm[M_WK], in[12], 1024, 4096);
    map_mnmajor(fn, &P.tm[M_WV], in[13], 1024, 4096);
    map_mnmajor(fn, &P.tm[M_WO], in[14], 4096, 1024);
    map_kmajor(fn, &P.tm[M_OA], kvo, 3 * 2048, 4096, 128);
    P.swap_ri = in[4] < in[3];
    {
        const bf16* lo = P.swap_ri ? in[4] : in[3];
        const uint64_t diff = (uint64_t)((const char*)(P.swap_ri ? in[3] : in[4]) - (const char*)lo);
        const uint64_t d[4] = {1024, 8, 2, 128}, s[3] = {2048, diff, 16384}; const uint32_t b[4] = {64, 8, 2, 8};
        encode(fn, &P.tm[M_AB], lo, 4, d, s, b);
    }
    {
        const uint64_t d[4] = {1024, 2, 4, 1024}, s[3] = {2048, 64 * 2048, 4096}; const uint32_t b[4] = {64, 2, 4, 16};
        encode(fn, &P.tm[M_AX], in[0], 4, d, s, b);
    }
    map_mnmajor(fn, &P.tm[M_HT], ht, 2048, 2048);
    map_kmajor(fn, &P.tm[M_CRE], in[5], 1024, 1024, 128);
    map_kmajor(fn, &P.tm[M_CIM], in[6], 1024, 1024, 128);
    map_kmajor(fn, &P.tm[M_KVO], kvo, 3 * 2048, 4096, 32);
    map_kmajor(fn, &P.tm[M_HTS], ht, 2048, 2048, 32);
    map_kmajor(fn, &P.tm[M_WOH], in[14], 4096, 1024, 64);
    map_kmajor(fn, &P.tm[M_CREH], in[5], 1024, 1024, 64);
    map_kmajor(fn, &P.tm[M_CIMH], in[6], 1024, 1024, 64);
    for (int i = 0; i < 3; i++) {
        const uint64_t d[3] = {4096, 16, 64}, s[2] = {8192, 16 * 8192}; const uint32_t b[3] = {64, 8, 8};
        encode(fn, &P.tm[M_CQ + i], in[11 + i], 3, d, s, b);
    }
    {
        const uint64_t d[4] = {4096, 1, 1, 4096}, s[3] = {8192, 8192, 8192}; const uint32_t b[4] = {64, 1, 1, 32};
        encode(fn, &P.tm[M_KV4], kvo, 4, d, s, b);
    }
    for (int e = 0; e < 2; e++) {
        const uint64_t d[4] = {1024, 2, 4, 256}, s[3] = {8 * 2048, 2 * 2048, 16 * 2048}; const uint32_t b[4] = {64, 2, 4, 8};
        encode(fn, &P.tm[M_CO + e], in[14] + e * 1024, 4, d, s, b);
    }
    P.Wq = in[11]; P.Wk = in[12]; P.Wv = in[13]; P.Wo = in[14]; P.mem0 = in[10];
    P.Lre = in[1]; P.Lim = in[2]; P.logdt = in[7]; P.Dskip = in[8];
    P.out = (float*)d_out;
    P.two26 = 1u << 26;
    P.lag = 0x22023302;
    P.ds = 400; P.dc = 1600; P.alpha = 0.3f; P.extra = 200; P.da = 176; P.db = 416; P.dk = 800; P.dp = 1550; P.dv = 60; P.pf0 = 1500; P.pf1 = 175; P.pf2 = 450; P.back = 150; P.ds0 = 950;
    for (int i = 0; i < (DBGF(32) ? 1 : 2); i++) {
        cudaLaunchConfig_t cfg = {};
        cfg.gridDim = dim3(i ? 36 : 96); cfg.blockDim = dim3(384); cfg.dynamicSmemBytes = S_TOTAL; cfg.stream = cudaStreamPerThread;
        cudaLaunchAttribute at[2];
        at[0].id = cudaLaunchAttributeClusterDimension; at[0].val.clusterDim.x = i ? 2 : 6; at[0].val.clusterDim.y = at[0].val.clusterDim.z = 1;
        at[1].id = cudaLaunchAttributeProgrammaticStreamSerialization; at[1].val.programmaticStreamSerializationAllowed = 1;
        cfg.attrs = at; cfg.numAttrs = 1 + i;
        cudaLaunchKernelEx(&cfg, fused_kernel, P);
    }
}
```

```cpp
#include <cuda_runtime.h>
#include <cuda_bf16.h>
#include <cuda.h>
#include <stdint.h>
#include <string.h>

typedef __nv_bfloat16 bf16;

namespace {

#define POLL 200
constexpr int SPIN_LIMIT = 1 << 22;
constexpr int NPAIR = 66;
constexpr int NCHAIN = 48;
enum { T_KV = 0, T_QA = 1, T_OP = 2, T_A1 = 3, T_A2 = 4, T_CHAIN = 5, T_OPH = 6, T_A2H = 7 };
enum { M_BX = 0, M_WQ, M_WK, M_WV, M_WO, M_OA, M_AB, M_AX, M_HT, M_CRE, M_CIM, M_KVO, M_HTS, M_WOH, M_CREH, M_CIMH, M_CQ, M_CK, M_CV, M_CO, M_CO1, M_KV4, M_COUNT };
enum { C_KV = 0, C_HT = 8, C_DONE = 24, C_EPOCH = 25, C_COEF = 26, C_FLAG = 32, C_O = 96 };

struct Params {
    CUtensorMap tm[M_COUNT];
    const bf16 *Wq, *Wk, *Wv, *Wo, *mem0, *Lre, *Lim, *logdt, *Dskip;
    float* out;
    uint8_t* gm;
    int swap_ri, zero;
    uint32_t two26, lag;
    int ds, da, db, dk, dv, back, ds0, pf0, pf1, pf2, dc, extra, dp;
    float alpha;
#define DBGF(x) false
};

constexpr int NPRE = 1;
__constant__ uint16_t c_off[67] = {0, 5, 10, 15, 21, 25, 29, 35, 39, 43, 47, 51, 55, 59, 63, 67, 71, 76, 81, 86, 91, 95, 99, 103, 108, 112, 116, 120, 124, 128, 133, 137, 142, 147, 152, 157, 162, 166, 170, 175, 179, 183, 187, 191, 195, 200, 205, 209, 213, 232, 252, 272, 291, 311, 331, 349, 369, 389, 407, 427, 446, 466, 485, 505, 524, 543, 562};
__constant__ uint16_t c_items[640] = {
    32, 1280, 453, 492, 1056, 49, 1280, 485, 494, 1249, 34, 1280, 293, 301, 1120, 51, 1280, 458, 457, 428, 1959, 36, 1280, 896,
    642, 53, 1280, 898, 546, 38, 1280, 833, 961, 996, 1957, 55, 1280, 865, 578, 40, 1280, 495, 576, 57, 1280, 463, 579, 42,
    1280, 262, 675, 59, 1280, 264, 739, 44, 1280, 335, 608, 61, 1280, 897, 738, 46, 1280, 361, 707, 63, 1280, 265, 705, 0,
    1280, 388, 302, 1217, 1, 1280, 489, 493, 1248, 2, 1280, 391, 333, 1250, 3, 1280, 263, 459, 1088, 4, 1280, 866, 673, 5,
    1280, 931, 640, 6, 1280, 835, 737, 7, 1280, 899, 488, 1185, 8, 1280, 838, 643, 9, 1280, 839, 641, 10, 1280, 870, 672,
    11, 1280, 864, 515, 12, 1280, 871, 674, 13, 1280, 935, 933, 1219, 14, 1280, 772, 736, 15, 1280, 994, 964, 1091, 16, 1280,
    393, 332, 1216, 17, 1280, 484, 300, 1121, 18, 1280, 487, 364, 1058, 19, 1280, 423, 462, 1152, 20, 1280, 867, 544, 21, 1280,
    930, 545, 22, 1280, 900, 424, 1089, 23, 1280, 836, 577, 24, 1280, 903, 611, 25, 1280, 902, 609, 26, 1280, 928, 547, 27,
    1280, 869, 512, 28, 1280, 868, 901, 1251, 29, 1280, 932, 965, 1218, 30, 1280, 804, 704, 31, 1280, 962, 706, 33, 95, 94,
    127, 126, 159, 158, 255, 223, 191, 324, 352, 399, 422, 289, 425, 392, 490, 1024, 35, 93, 92, 125, 124, 157, 156, 189,
    221, 253, 252, 323, 254, 292, 418, 417, 386, 299, 365, 1956, 37, 91, 90, 123, 122, 155, 154, 187, 186, 251, 219, 250,
    334, 426, 366, 448, 449, 491, 430, 1123, 39, 89, 88, 121, 120, 153, 152, 185, 217, 184, 216, 218, 249, 248, 358, 288,
    321, 452, 514, 41, 87, 86, 119, 118, 151, 215, 247, 183, 214, 200, 199, 246, 325, 296, 420, 482, 268, 396, 1059, 43,
    85, 84, 117, 116, 149, 213, 181, 212, 180, 195, 193, 297, 363, 266, 326, 303, 455, 431, 1153, 45, 83, 82, 115, 114,
    147, 211, 179, 210, 178, 329, 243, 355, 356, 805, 837, 929, 610, 47, 81, 80, 113, 112, 145, 177, 176, 241, 190, 209,
    208, 240, 773, 832, 290, 480, 995, 966, 1057, 48, 79, 78, 111, 143, 142, 207, 175, 206, 174, 222, 192, 239, 256, 257,
    390, 389, 934, 997, 1090, 50, 77, 76, 109, 141, 140, 237, 173, 236, 234, 245, 205, 258, 771, 427, 421, 483, 513, 52,
    75, 74, 107, 139, 138, 171, 235, 170, 203, 202, 770, 774, 359, 775, 801, 963, 993, 397, 1958, 54, 73, 72, 105, 137,
    136, 169, 201, 233, 168, 362, 270, 394, 353, 807, 806, 960, 367, 1184, 56, 71, 103, 104, 135, 150, 167, 182, 231, 232,
    242, 238, 384, 224, 357, 387, 320, 486, 429, 1026, 58, 70, 102, 110, 134, 148, 166, 172, 230, 188, 267, 800, 244, 419,
    291, 295, 328, 269, 1027, 60, 69, 101, 108, 133, 146, 197, 165, 204, 198, 220, 322, 229, 398, 802, 803, 395, 454, 461,
    1155, 62, 68, 100, 106, 132, 144, 228, 164, 327, 196, 225, 768, 769, 260, 416, 481, 967, 999, 1122, 64, 67, 99, 97,
    131, 129, 163, 161, 271, 354, 259, 227, 261, 294, 450, 834, 992, 998, 1025, 65, 66, 98, 96, 130, 128, 162, 160, 298,
    226, 194, 385, 331, 330, 360, 451, 456, 460, 1154,
};
#define ITEM_OFF(p) c_off[p]
#define ITEM(i) c_items[i]

__device__ __align__(1024) bf16 g_kvo[3 * 2048 * 4096];
__device__ __align__(1024) bf16 g_ht[2048 * 2048];
__device__ __align__(1024) uint8_t g_m[9 * 32768];
__device__ __align__(1024) uint8_t g_f[8 * 49152];
__device__ __align__(1024) uint32_t g_km[64 * 32 * 512];
__device__ __align__(1024) uint32_t g_vmt[64 * 32 * 512];
__device__ __align__(1024) float2 g_agg[8 * 1024];
__device__ __align__(1024) float4 g_coef[1024];
__device__ __align__(1024) uint32_t g_cntl[128 * 32];
#define g_cnt(i) g_cntl[(i) * 32]
__device__ __align__(1024) uint32_t g_hint[6144 + 160];
#define SSTAMP(i, cond)
#define PROF(i)
#define GT_EDGE(o)
constexpr int M_SLOT = 32768, F_SLOT = 49152;

constexpr int STAGE = 49152, NSTAGE = 4;
constexpr int S_STG = NSTAGE * STAGE;
constexpr int S_BAR = S_STG + 32768;
constexpr int B_FULL = S_BAR, B_EMPTY = S_BAR + 32, B_RESUME = S_BAR + 64, B_KVFULL = S_BAR + 72, B_GO = S_BAR + 88, B_K = S_BAR + 96, B_PERS = S_BAR + 104, B_INIT = S_BAR + 112, B_RELA = S_BAR + 120, B_V = S_BAR + 128, B_WO = S_BAR + 136,
              B_SFULL = S_BAR + 144, B_SFREE = S_BAR + 160, S_DESC = S_BAR + 176, S_REDO = S_BAR + 256 + 512 + 64, S_EPOCH = S_BAR + 208, B_RELB = S_BAR + 216, B_KVGO = S_BAR + 224, S_DEP = S_BAR + 240, S_CUR = S_BAR + 244, S_TAIL = S_BAR + 248, S_CTA = S_BAR + 252;
constexpr int S_COEF = S_BAR + 256 + 512, S_TOTAL = S_COEF + 1024;
constexpr int S_W1 = 0;
constexpr int S_O = 24 * 4096, S_VL = S_O + 2048, S_MX = 25 * 4096, S_SC = S_MX + 64, S_SUM = S_MX + 128;
constexpr int S_KL = 26 * 4096;
constexpr int S_W2 = 27 * 4096;
constexpr int S_KV = S_W2 + 65536;
constexpr int S_P1 = S_W2 + 98304;
constexpr int S_QX = S_P1 + 16384;
constexpr int S_SX = S_QX + 2048;
static_assert(S_SX + 1280 <= S_BAR, "chain smem overlaps barriers");
constexpr int NR = 40, NS = 64 - NR;

__device__ __forceinline__ uint32_t logical_cta(uint32_t b) {
    const uint32_t c = b / 6, r = b - c * 6;
    return gridDim.x != 96 ? 96 + b : ((r >> 1) + (c >= 8) + (c >= 15)) % 3 * 32 + c * 2 + (r & 1);
}
__device__ __forceinline__ uint32_t cluster_rank() { uint32_t r; asm("mov.u32 %0, %%cluster_ctarank;" : "=r"(r)); return r; }
__device__ __forceinline__ uint16_t pair_mask() { return (uint16_t)(3u << (cluster_rank() & 6)); }
__device__ __forceinline__ void spin_fault() { asm volatile("st.global.u32 [%0], 0;" ::"l"(0ull) : "memory"); }
__device__ __forceinline__ uint32_t smem_u32(const void* p) { return (uint32_t)__cvta_generic_to_shared(p); }
__device__ __forceinline__ uint32_t opq(uint32_t x, int lane) { return __shfl_sync(0xffffffffu, x, lane); }
__device__ __forceinline__ uint32_t mapa(uint32_t a, uint32_t r) { uint32_t d; asm volatile("mapa.shared::cluster.u32 %0, %1, %2;" : "=r"(d) : "r"(a), "r"(r)); return d; }
__device__ __forceinline__ void mma16816(float* d, uint32_t a0, uint32_t a1, uint32_t a2, uint32_t a3, uint32_t b0, uint32_t b1) {
    asm("mma.sync.aligned.m16n8k16.row.col.f32.bf16.bf16.f32 {%0,%1,%2,%3}, {%4,%5,%6,%7}, {%8,%9}, {%0,%1,%2,%3};"
        : "+f"(d[0]), "+f"(d[1]), "+f"(d[2]), "+f"(d[3]) : "r"(a0), "r"(a1), "r"(a2), "r"(a3), "r"(b0), "r"(b1));
}
__device__ __forceinline__ void mma1688(float* d, uint32_t a0, uint32_t a1, uint32_t b0) {
    asm("mma.sync.aligned.m16n8k8.row.col.f32.bf16.bf16.f32 {%0,%1,%2,%3}, {%4,%5}, {%6}, {%0,%1,%2,%3};"
        : "+f"(d[0]), "+f"(d[1]), "+f"(d[2]), "+f"(d[3]) : "r"(a0), "r"(a1), "r"(b0));
}
__device__ __forceinline__ void ldsm4(uint32_t* r, uint32_t a) {
    asm volatile("ldmatrix.sync.aligned.m8n8.x4.shared.b16 {%0,%1,%2,%3}, [%4];" : "=r"(r[0]), "=r"(r[1]), "=r"(r[2]), "=r"(r[3]) : "r"(a));
}
__device__ __forceinline__ void ldsm4t(uint32_t* r, uint32_t a) {
    asm volatile("ldmatrix.sync.aligned.m8n8.x4.trans.shared.b16 {%0,%1,%2,%3}, [%4];" : "=r"(r[0]), "=r"(r[1]), "=r"(r[2]), "=r"(r[3]) : "r"(a));
}
__device__ __forceinline__ void stsm4(uint32_t a, uint32_t r0, uint32_t r1, uint32_t r2, uint32_t r3) {
    asm volatile("stmatrix.sync.aligned.m8n8.x4.shared.b16 [%0], {%1,%2,%3,%4};" ::"r"(a), "r"(r0), "r"(r1), "r"(r2), "r"(r3) : "memory");
}
__device__ __forceinline__ void stsm4t(uint32_t a, uint32_t r0, uint32_t r1, uint32_t r2, uint32_t r3) {
    asm volatile("stmatrix.sync.aligned.m8n8.x4.trans.shared.b16 [%0], {%1,%2,%3,%4};" ::"r"(a), "r"(r0), "r"(r1), "r"(r2), "r"(r3) : "memory");
}
__device__ __forceinline__ uint32_t pack2(float lo, float hi) { uint32_t d; asm("cvt.rn.bf16x2.f32 %0, %1, %2;" : "=r"(d) : "f"(hi), "f"(lo)); return d; }
__device__ __forceinline__ float bf_lo(uint32_t u) { return __uint_as_float(u << 16); }
__device__ __forceinline__ float bf_hi(uint32_t u) { return __uint_as_float(u & 0xffff0000u); }
__device__ __forceinline__ uint32_t hmul2(uint32_t a, uint32_t b) { uint32_t d; asm("mul.rn.bf16x2 %0, %1, %2;" : "=r"(d) : "r"(a), "r"(b)); return d; }
__device__ __forceinline__ float ex2(float x) { float y; asm("ex2.approx.ftz.f32 %0, %1;" : "=f"(y) : "f"(x)); return y; }
__device__ __forceinline__ float rcp(float x) { float y; asm("rcp.approx.ftz.f32 %0, %1;" : "=f"(y) : "f"(x)); return y; }
__device__ __forceinline__ void st_relaxed4(const void* p, uint32_t a, uint32_t b, uint32_t c, uint32_t d) {
    asm volatile("{\n.reg .b128 t;\nmov.b128 t, {%1,%2,%3,%4};\nst.relaxed.gpu.global.b128 [%0], t;\n}" ::"l"(p), "r"(a), "r"(b), "r"(c), "r"(d) : "memory");
}
__device__ __forceinline__ void st_relaxed2(const void* p, uint32_t a, uint32_t b) {
    asm volatile("{\n.reg .b64 t;\nmov.b64 t, {%1,%2};\nst.relaxed.gpu.global.b64 [%0], t;\n}" ::"l"(p), "r"(a), "r"(b) : "memory");
}
__device__ __forceinline__ void ld_relaxed2_if(uint32_t& a, uint32_t& b, const void* p, bool on) {
    asm volatile("{\n.reg .pred P;\n.reg .b64 t;\nsetp.ne.u32 P, %3, 0;\nmov.b64 t, {%0,%1};\n@P ld.relaxed.gpu.global.b64 t, [%2];\nmov.b64 {%0,%1}, t;\n}" : "+r"(a), "+r"(b) : "l"(p), "r"((uint32_t)on) : "memory");
}
__device__ __forceinline__ uint32_t ld_relaxed1(const void* p) { uint32_t v; asm volatile("ld.relaxed.gpu.global.u32 %0, [%1];" : "=r"(v) : "l"(p) : "memory"); return v; }
__device__ __forceinline__ void st_relaxed1(const void* p, uint32_t v) { asm volatile("st.relaxed.gpu.global.u32 [%0], %1;" ::"l"(p), "r"(v) : "memory"); }
__device__ __forceinline__ uint32_t ld_acquire(const void* p) { uint32_t v; asm volatile("ld.acquire.gpu.global.u32 %0, [%1];" : "=r"(v) : "l"(p) : "memory"); return v; }
__device__ __forceinline__ void red_release(void* p) { asm volatile("red.release.gpu.global.add.u32 [%0], 1;" ::"l"(p) : "memory"); }
__device__ __forceinline__ void st_stream2(float* p, float a, float b) { asm volatile("st.global.cs.v2.f32 [%0], {%1, %2};" ::"l"(p), "f"(a), "f"(b) : "memory"); }
__device__ __forceinline__ void fence_acquire() { asm volatile("fence.acquire.gpu;" ::: "memory"); }
__device__ __forceinline__ void fence_release() { asm volatile("fence.release.gpu;" ::: "memory"); }
__device__ __forceinline__ void fence_async() {  asm volatile("fence.proxy.async.global;" ::: "memory"); }
__device__ __forceinline__ void fence_async_smem() { asm volatile("fence.proxy.async.shared::cta;" ::: "memory"); }
__device__ __forceinline__ void wait_count(const uint32_t* p, uint32_t target) {
    int n = 0;
    while ((int32_t)(ld_acquire(p) - target) < 0) { __nanosleep(POLL); if (++n > SPIN_LIMIT) spin_fault(); }
}
__device__ __forceinline__ void bar_sync(int id, int n) { asm volatile("bar.sync %0, %1;" ::"r"(id), "r"(n) : "memory"); }
__device__ __forceinline__ void bar_arrive(int id, int n) { asm volatile("bar.arrive %0, %1;" ::"r"(id), "r"(n) : "memory"); }
__device__ __forceinline__ bool bar_and(int id, bool v) {
    uint32_t r;
    asm volatile("{\n.reg .pred P, Q;\nsetp.ne.u32 Q, %2, 0;\nbar.red.and.pred P, %1, 128, Q;\nselp.u32 %0, 1, 0, P;\n}" : "=r"(r) : "r"(id), "r"((uint32_t)v) : "memory");
    return r;
}
__device__ __forceinline__ void lds128(uint32_t* v, uint32_t a) { asm volatile("ld.shared.v4.b32 {%0,%1,%2,%3}, [%4];" : "=r"(v[0]), "=r"(v[1]), "=r"(v[2]), "=r"(v[3]) : "r"(a) : "memory"); }
__device__ __forceinline__ uint32_t lds32(uint32_t a) { uint32_t v; asm volatile("ld.shared.b32 %0, [%1];" : "=r"(v) : "r"(a) : "memory"); return v; }
__device__ __forceinline__ void lds64f(float* v, uint32_t a) { asm volatile("ld.shared.v2.f32 {%0,%1}, [%2];" : "=f"(v[0]), "=f"(v[1]) : "r"(a) : "memory"); }
__device__ __forceinline__ void sts128(uint32_t a, const uint32_t* v) { asm volatile("st.shared.v4.b32 [%0], {%1,%2,%3,%4};" ::"r"(a), "r"(v[0]), "r"(v[1]), "r"(v[2]), "r"(v[3]) : "memory"); }
__device__ __forceinline__ void sts64(uint32_t a, uint32_t x, uint32_t y) { asm volatile("st.shared.v2.b32 [%0], {%1,%2};" ::"r"(a), "r"(x), "r"(y) : "memory"); }
__device__ __forceinline__ void sts32(uint32_t a, uint32_t x) { asm volatile("st.shared.b32 [%0], %1;" ::"r"(a), "r"(x) : "memory"); }
__device__ __forceinline__ bool mbar_try(uint32_t b, uint32_t par) {
    uint32_t ok;
    asm volatile("{\n.reg .pred P;\nmbarrier.try_wait.parity.shared::cta.b64 P, [%1], %2;\nselp.u32 %0, 1, 0, P;\n}" : "=r"(ok) : "r"(b), "r"(par) : "memory");
    return ok;
}
__device__ __forceinline__ bool mbar_test(uint32_t b, uint32_t par) {
    uint32_t ok;
    asm volatile("{\n.reg .pred P;\nmbarrier.test_wait.parity.shared::cta.b64 P, [%1], %2;\nselp.u32 %0, 1, 0, P;\n}" : "=r"(ok) : "r"(b), "r"(par) : "memory");
    return ok;
}
__device__ __forceinline__ void mbar_wait(uint32_t b, uint32_t par) { int n = 0; while (!mbar_try(b, par)) { if (++n > SPIN_LIMIT) spin_fault(); } }
__device__ __forceinline__ void mbar_init(uint32_t b, uint32_t n) { asm volatile("mbarrier.init.shared::cta.b64 [%0], %1;" ::"r"(b), "r"(n) : "memory"); }
__device__ __forceinline__ void mbar_expect(uint32_t b, uint32_t bytes) { asm volatile("mbarrier.arrive.expect_tx.shared::cta.b64 _, [%0], %1;" ::"r"(b), "r"(bytes) : "memory"); }
__device__ __forceinline__ void mbar_arrive(uint32_t b) { asm volatile("mbarrier.arrive.shared::cta.b64 _, [%0];" ::"r"(b) : "memory"); }
__device__ __forceinline__ void mbar_arrive_cluster(uint32_t b) { asm volatile("mbarrier.arrive.shared::cluster.b64 _, [%0];" ::"r"(b) : "memory"); }
__device__ __forceinline__ void st_async1(uint32_t a, uint32_t x, uint32_t bar) {
    asm volatile("st.async.weak.shared::cluster.mbarrier::complete_tx::bytes.b32 [%0], %1, [%2];" ::"r"(a), "r"(x), "r"(bar) : "memory");
}
__device__ __forceinline__ void st_async2(uint32_t a, uint32_t x, uint32_t y, uint32_t bar) {
    asm volatile("st.async.weak.shared::cluster.mbarrier::complete_tx::bytes.v2.b32 [%0], {%1,%2}, [%3];" ::"r"(a), "r"(x), "r"(y), "r"(bar) : "memory");
}
__device__ __forceinline__ void cluster_sync() { asm volatile("barrier.cluster.arrive.aligned;\nbarrier.cluster.wait.aligned;" ::: "memory"); }
constexpr uint64_t EVICT_FIRST = 0x12F0000000000000ull, EVICT_NORMAL = 0x1000000000000000ull;
__device__ __forceinline__ void tma2d(uint32_t dst, const CUtensorMap* m, int c0, int c1, uint32_t bar, uint64_t pol) {
    asm volatile("cp.async.bulk.tensor.2d.shared::cluster.global.mbarrier::complete_tx::bytes.L2::cache_hint [%0], [%1, {%2, %3}], [%4], %5;" ::"r"(dst), "l"(m), "r"(c0), "r"(c1), "r"(bar), "l"(pol) : "memory");
}
__device__ __forceinline__ void tma4d(uint32_t dst, const CUtensorMap* m, int c0, int c3, uint32_t bar, uint64_t pol) {
    asm volatile("cp.async.bulk.tensor.4d.shared::cluster.global.mbarrier::complete_tx::bytes.L2::cache_hint [%0], [%1, {%2, 0, 0, %3}], [%4], %5;" ::"r"(dst), "l"(m), "r"(c0), "r"(c3), "r"(bar), "l"(pol) : "memory");
}
__device__ __forceinline__ void tma3d(uint32_t dst, const CUtensorMap* m, int c0, int c1, int c2, uint32_t bar, uint64_t pol) {
    asm volatile("cp.async.bulk.tensor.3d.shared::cluster.global.mbarrier::complete_tx::bytes.L2::cache_hint [%0], [%1, {%2, %3, %4}], [%5], %6;" ::"r"(dst), "l"(m), "r"(c0), "r"(c1), "r"(c2), "r"(bar), "l"(pol) : "memory");
}
__device__ __forceinline__ void tma_store2d(const CUtensorMap* m, int c0, int c1, uint32_t src, uint64_t pol) {
    asm volatile("cp.async.bulk.tensor.2d.global.shared::cta.bulk_group.L2::cache_hint [%0, {%1, %2}], [%3], %4;" ::"l"(m), "r"(c0), "r"(c1), "r"(src), "l"(pol) : "memory");
}
#define EF 47
#define POL(bit) ((EF >> (bit)) & 1 ? EVICT_FIRST : EVICT_NORMAL)
__device__ __forceinline__ void tma2d_mc(uint32_t dst, const CUtensorMap* m, int c0, int c1, uint32_t bar, uint64_t pol) {
    asm volatile("cp.async.bulk.tensor.2d.shared::cluster.global.mbarrier::complete_tx::bytes.multicast::cluster.L2::cache_hint [%0], [%1, {%2, %3}], [%4], %5, %6;" ::"r"(dst), "l"(m), "r"(c0), "r"(c1), "r"(bar), "h"(pair_mask()), "l"(pol) : "memory");
}
__device__ __forceinline__ void tma3d_mc(uint32_t dst, const CUtensorMap* m, int c0, int c1, int c2, uint32_t bar, uint64_t pol) {
    asm volatile("cp.async.bulk.tensor.3d.shared::cluster.global.mbarrier::complete_tx::bytes.multicast::cluster.L2::cache_hint [%0], [%1, {%2, %3, %4}], [%5], %6, %7;" ::"r"(dst), "l"(m), "r"(c0), "r"(c1), "r"(c2), "r"(bar), "h"(pair_mask()), "l"(pol) : "memory");
}
__device__ __forceinline__ void tma4d_mc(uint32_t dst, const CUtensorMap* m, int c0, int c3, uint32_t bar, uint64_t pol) {
    asm volatile("cp.async.bulk.tensor.4d.shared::cluster.global.mbarrier::complete_tx::bytes.multicast::cluster.L2::cache_hint [%0], [%1, {%2, 0, 0, %3}], [%4], %5, %6;" ::"r"(dst), "l"(m), "r"(c0), "r"(c3), "r"(bar), "h"(pair_mask()), "l"(pol) : "memory");
}
__device__ __forceinline__ void map_prefetch(const CUtensorMap* m) { asm volatile("prefetch.tensormap [%0];" ::"l"(m) : "memory"); }
__device__ __forceinline__ void bulk_g2s(uint32_t dst, const void* src, uint32_t bytes, uint32_t bar) {
    asm volatile("cp.async.bulk.shared::cluster.global.mbarrier::complete_tx::bytes [%0], [%1], %2, [%3];" ::"r"(dst), "l"(src), "r"(bytes), "r"(bar) : "memory");
}
__device__ __forceinline__ void bulk_s2g(void* dst, uint32_t src, uint32_t bytes) {
    asm volatile("cp.async.bulk.global.shared::cta.bulk_group [%0], [%1], %2;" ::"l"(dst), "r"(src), "r"(bytes) : "memory");
}
__device__ __forceinline__ void bulk_commit() { asm volatile("cp.async.bulk.commit_group;" ::: "memory"); }
__device__ __forceinline__ void bulk_wait_read() { asm volatile("cp.async.bulk.wait_group.read 0;" ::: "memory"); }
__device__ __forceinline__ void bulk_wait_all() { asm volatile("cp.async.bulk.wait_group 0;" ::: "memory"); }
__device__ __forceinline__ uint64_t mkdesc(uint32_t addr, uint32_t lbo, uint32_t sbo, uint32_t swz) {
    return (uint64_t)((addr & 0x3FFFF) >> 4) | ((uint64_t)(lbo >> 4) << 16) | ((uint64_t)(sbo >> 4) << 32) | ((uint64_t)swz << 62);
}
__device__ __forceinline__ void wg_fence() { asm volatile("wgmma.fence.sync.aligned;" ::: "memory"); }
__device__ __forceinline__ void wg_commit() { asm volatile("wgmma.commit_group.sync.aligned;" ::: "memory"); }
template <int N> __device__ __forceinline__ void wg_wait() { asm volatile("wgmma.wait_group.sync.aligned %0;" ::"n"(N) : "memory"); }
template <typename T> __device__ __forceinline__ void pin_ptr(T*& p) { asm volatile("" : "+l"(p)); }
template <int N> __device__ __forceinline__ void pin(uint32_t* d) {
#pragma unroll
    for (int i = 0; i < N; i++) asm volatile("" : "+r"(d[i])::"memory");
}
template <int N> __device__ __forceinline__ void pin(float* d) {
#pragma unroll
    for (int i = 0; i < N; i++) asm volatile("" : "+f"(d[i])::"memory");
}

template <int TA, int TB>
__device__ __forceinline__ void wgmma_ss256(float* d, uint64_t da, uint64_t db) {
    asm volatile("wgmma.mma_async.sync.aligned.m64n256k16.f32.bf16.bf16 "
        "{%0, %1, %2, %3, %4, %5, %6, %7, %8, %9, %10, %11, %12, %13, %14, %15, %16, %17, %18, %19, %20, %21, %22, %23, %24, %25, %26, %27, %28, %29, %30, %31, %32, %33, %34, %35, %36, %37, %38, %39, %40, %41, %42, %43, %44, %45, %46, %47, %48, %49, %50, %51, %52, %53, %54, %55, %56, %57, %58, %59, %60, %61, %62, %63, %64, %65, %66, %67, %68, %69, %70, %71, %72, %73, %74, %75, %76, %77, %78, %79, %80, %81, %82, %83, %84, %85, %86, %87, %88, %89, %90, %91, %92, %93, %94, %95, %96, %97, %98, %99, %100, %101, %102, %103, %104, %105, %106, %107, %108, %109, %110, %111, %112, %113, %114, %115, %116, %117, %118, %119, %120, %121, %122, %123, %124, %125, %126, %127}, %128, %129, 1, 1, 1, %130, %131;"
        : "+f"(d[0]), "+f"(d[1]), "+f"(d[2]), "+f"(d[3]), "+f"(d[4]), "+f"(d[5]), "+f"(d[6]), "+f"(d[7]), "+f"(d[8]), "+f"(d[9]), "+f"(d[10]), "+f"(d[11]), "+f"(d[12]), "+f"(d[13]), "+f"(d[14]), "+f"(d[15]), "+f"(d[16]), "+f"(d[17]), "+f"(d[18]), "+f"(d[19]), "+f"(d[20]), "+f"(d[21]), "+f"(d[22]), "+f"(d[23]), "+f"(d[24]), "+f"(d[25]), "+f"(d[26]), "+f"(d[27]), "+f"(d[28]), "+f"(d[29]), "+f"(d[30]), "+f"(d[31]), "+f"(d[32]), "+f"(d[33]), "+f"(d[34]), "+f"(d[35]), "+f"(d[36]), "+f"(d[37]), "+f"(d[38]), "+f"(d[39]), "+f"(d[40]), "+f"(d[41]), "+f"(d[42]), "+f"(d[43]), "+f"(d[44]), "+f"(d[45]), "+f"(d[46]), "+f"(d[47]), "+f"(d[48]), "+f"(d[49]), "+f"(d[50]), "+f"(d[51]), "+f"(d[52]), "+f"(d[53]), "+f"(d[54]), "+f"(d[55]), "+f"(d[56]), "+f"(d[57]), "+f"(d[58]), "+f"(d[59]), "+f"(d[60]), "+f"(d[61]), "+f"(d[62]), "+f"(d[63]), "+f"(d[64]), "+f"(d[65]), "+f"(d[66]), "+f"(d[67]), "+f"(d[68]), "+f"(d[69]), "+f"(d[70]), "+f"(d[71]), "+f"(d[72]), "+f"(d[73]), "+f"(d[74]), "+f"(d[75]), "+f"(d[76]), "+f"(d[77]), "+f"(d[78]), "+f"(d[79]), "+f"(d[80]), "+f"(d[81]), "+f"(d[82]), "+f"(d[83]), "+f"(d[84]), "+f"(d[85]), "+f"(d[86]), "+f"(d[87]), "+f"(d[88]), "+f"(d[89]), "+f"(d[90]), "+f"(d[91]), "+f"(d[92]), "+f"(d[93]), "+f"(d[94]), "+f"(d[95]), "+f"(d[96]), "+f"(d[97]), "+f"(d[98]), "+f"(d[99]), "+f"(d[100]), "+f"(d[101]), "+f"(d[102]), "+f"(d[103]), "+f"(d[104]), "+f"(d[105]), "+f"(d[106]), "+f"(d[107]), "+f"(d[108]), "+f"(d[109]), "+f"(d[110]), "+f"(d[111]), "+f"(d[112]), "+f"(d[113]), "+f"(d[114]), "+f"(d[115]), "+f"(d[116]), "+f"(d[117]), "+f"(d[118]), "+f"(d[119]), "+f"(d[120]), "+f"(d[121]), "+f"(d[122]), "+f"(d[123]), "+f"(d[124]), "+f"(d[125]), "+f"(d[126]), "+f"(d[127])
        : "l"(da), "l"(db), "n"(TA), "n"(TB));
}
template <int TA, int TB>
__device__ __forceinline__ void wgmma_ss256_first(float* d, uint64_t da, uint64_t db) {
    asm volatile("wgmma.mma_async.sync.aligned.m64n256k16.f32.bf16.bf16 "
        "{%0, %1, %2, %3, %4, %5, %6, %7, %8, %9, %10, %11, %12, %13, %14, %15, %16, %17, %18, %19, %20, %21, %22, %23, %24, %25, %26, %27, %28, %29, %30, %31, %32, %33, %34, %35, %36, %37, %38, %39, %40, %41, %42, %43, %44, %45, %46, %47, %48, %49, %50, %51, %52, %53, %54, %55, %56, %57, %58, %59, %60, %61, %62, %63, %64, %65, %66, %67, %68, %69, %70, %71, %72, %73, %74, %75, %76, %77, %78, %79, %80, %81, %82, %83, %84, %85, %86, %87, %88, %89, %90, %91, %92, %93, %94, %95, %96, %97, %98, %99, %100, %101, %102, %103, %104, %105, %106, %107, %108, %109, %110, %111, %112, %113, %114, %115, %116, %117, %118, %119, %120, %121, %122, %123, %124, %125, %126, %127}, %128, %129, 0, 1, 1, %130, %131;"
        : "=f"(d[0]), "=f"(d[1]), "=f"(d[2]), "=f"(d[3]), "=f"(d[4]), "=f"(d[5]), "=f"(d[6]), "=f"(d[7]), "=f"(d[8]), "=f"(d[9]), "=f"(d[10]), "=f"(d[11]), "=f"(d[12]), "=f"(d[13]), "=f"(d[14]), "=f"(d[15]), "=f"(d[16]), "=f"(d[17]), "=f"(d[18]), "=f"(d[19]), "=f"(d[20]), "=f"(d[21]), "=f"(d[22]), "=f"(d[23]), "=f"(d[24]), "=f"(d[25]), "=f"(d[26]), "=f"(d[27]), "=f"(d[28]), "=f"(d[29]), "=f"(d[30]), "=f"(d[31]), "=f"(d[32]), "=f"(d[33]), "=f"(d[34]), "=f"(d[35]), "=f"(d[36]), "=f"(d[37]), "=f"(d[38]), "=f"(d[39]), "=f"(d[40]), "=f"(d[41]), "=f"(d[42]), "=f"(d[43]), "=f"(d[44]), "=f"(d[45]), "=f"(d[46]), "=f"(d[47]), "=f"(d[48]), "=f"(d[49]), "=f"(d[50]), "=f"(d[51]), "=f"(d[52]), "=f"(d[53]), "=f"(d[54]), "=f"(d[55]), "=f"(d[56]), "=f"(d[57]), "=f"(d[58]), "=f"(d[59]), "=f"(d[60]), "=f"(d[61]), "=f"(d[62]), "=f"(d[63]), "=f"(d[64]), "=f"(d[65]), "=f"(d[66]), "=f"(d[67]), "=f"(d[68]), "=f"(d[69]), "=f"(d[70]), "=f"(d[71]), "=f"(d[72]), "=f"(d[73]), "=f"(d[74]), "=f"(d[75]), "=f"(d[76]), "=f"(d[77]), "=f"(d[78]), "=f"(d[79]), "=f"(d[80]), "=f"(d[81]), "=f"(d[82]), "=f"(d[83]), "=f"(d[84]), "=f"(d[85]), "=f"(d[86]), "=f"(d[87]), "=f"(d[88]), "=f"(d[89]), "=f"(d[90]), "=f"(d[91]), "=f"(d[92]), "=f"(d[93]), "=f"(d[94]), "=f"(d[95]), "=f"(d[96]), "=f"(d[97]), "=f"(d[98]), "=f"(d[99]), "=f"(d[100]), "=f"(d[101]), "=f"(d[102]), "=f"(d[103]), "=f"(d[104]), "=f"(d[105]), "=f"(d[106]), "=f"(d[107]), "=f"(d[108]), "=f"(d[109]), "=f"(d[110]), "=f"(d[111]), "=f"(d[112]), "=f"(d[113]), "=f"(d[114]), "=f"(d[115]), "=f"(d[116]), "=f"(d[117]), "=f"(d[118]), "=f"(d[119]), "=f"(d[120]), "=f"(d[121]), "=f"(d[122]), "=f"(d[123]), "=f"(d[124]), "=f"(d[125]), "=f"(d[126]), "=f"(d[127])
        : "l"(da), "l"(db), "n"(TA), "n"(TB));
}
template <int TA, int TB>
__device__ __forceinline__ void wgmma_ss128(float* d, uint64_t da, uint64_t db) {
    asm volatile("wgmma.mma_async.sync.aligned.m64n128k16.f32.bf16.bf16 "
        "{%0, %1, %2, %3, %4, %5, %6, %7, %8, %9, %10, %11, %12, %13, %14, %15, %16, %17, %18, %19, %20, %21, %22, %23, %24, %25, %26, %27, %28, %29, %30, %31, %32, %33, %34, %35, %36, %37, %38, %39, %40, %41, %42, %43, %44, %45, %46, %47, %48, %49, %50, %51, %52, %53, %54, %55, %56, %57, %58, %59, %60, %61, %62, %63}, %64, %65, 1, 1, 1, %66, %67;"
        : "+f"(d[0]), "+f"(d[1]), "+f"(d[2]), "+f"(d[3]), "+f"(d[4]), "+f"(d[5]), "+f"(d[6]), "+f"(d[7]), "+f"(d[8]), "+f"(d[9]), "+f"(d[10]), "+f"(d[11]), "+f"(d[12]), "+f"(d[13]), "+f"(d[14]), "+f"(d[15]), "+f"(d[16]), "+f"(d[17]), "+f"(d[18]), "+f"(d[19]), "+f"(d[20]), "+f"(d[21]), "+f"(d[22]), "+f"(d[23]), "+f"(d[24]), "+f"(d[25]), "+f"(d[26]), "+f"(d[27]), "+f"(d[28]), "+f"(d[29]), "+f"(d[30]), "+f"(d[31]), "+f"(d[32]), "+f"(d[33]), "+f"(d[34]), "+f"(d[35]), "+f"(d[36]), "+f"(d[37]), "+f"(d[38]), "+f"(d[39]), "+f"(d[40]), "+f"(d[41]), "+f"(d[42]), "+f"(d[43]), "+f"(d[44]), "+f"(d[45]), "+f"(d[46]), "+f"(d[47]), "+f"(d[48]), "+f"(d[49]), "+f"(d[50]), "+f"(d[51]), "+f"(d[52]), "+f"(d[53]), "+f"(d[54]), "+f"(d[55]), "+f"(d[56]), "+f"(d[57]), "+f"(d[58]), "+f"(d[59]), "+f"(d[60]), "+f"(d[61]), "+f"(d[62]), "+f"(d[63])
        : "l"(da), "l"(db), "n"(TA), "n"(TB));
}
template <int TA, int TB>
__device__ __forceinline__ void wgmma_ss128_first(float* d, uint64_t da, uint64_t db) {
    asm volatile("wgmma.mma_async.sync.aligned.m64n128k16.f32.bf16.bf16 "
        "{%0, %1, %2, %3, %4, %5, %6, %7, %8, %9, %10, %11, %12, %13, %14, %15, %16, %17, %18, %19, %20, %21, %22, %23, %24, %25, %26, %27, %28, %29, %30, %31, %32, %33, %34, %35, %36, %37, %38, %39, %40, %41, %42, %43, %44, %45, %46, %47, %48, %49, %50, %51, %52, %53, %54, %55, %56, %57, %58, %59, %60, %61, %62, %63}, %64, %65, 0, 1, 1, %66, %67;"
        : "=f"(d[0]), "=f"(d[1]), "=f"(d[2]), "=f"(d[3]), "=f"(d[4]), "=f"(d[5]), "=f"(d[6]), "=f"(d[7]), "=f"(d[8]), "=f"(d[9]), "=f"(d[10]), "=f"(d[11]), "=f"(d[12]), "=f"(d[13]), "=f"(d[14]), "=f"(d[15]), "=f"(d[16]), "=f"(d[17]), "=f"(d[18]), "=f"(d[19]), "=f"(d[20]), "=f"(d[21]), "=f"(d[22]), "=f"(d[23]), "=f"(d[24]), "=f"(d[25]), "=f"(d[26]), "=f"(d[27]), "=f"(d[28]), "=f"(d[29]), "=f"(d[30]), "=f"(d[31]), "=f"(d[32]), "=f"(d[33]), "=f"(d[34]), "=f"(d[35]), "=f"(d[36]), "=f"(d[37]), "=f"(d[38]), "=f"(d[39]), "=f"(d[40]), "=f"(d[41]), "=f"(d[42]), "=f"(d[43]), "=f"(d[44]), "=f"(d[45]), "=f"(d[46]), "=f"(d[47]), "=f"(d[48]), "=f"(d[49]), "=f"(d[50]), "=f"(d[51]), "=f"(d[52]), "=f"(d[53]), "=f"(d[54]), "=f"(d[55]), "=f"(d[56]), "=f"(d[57]), "=f"(d[58]), "=f"(d[59]), "=f"(d[60]), "=f"(d[61]), "=f"(d[62]), "=f"(d[63])
        : "l"(da), "l"(db), "n"(TA), "n"(TB));
}
template <int TB>
__device__ __forceinline__ void wgmma_rs128(float* d, const uint32_t* a, uint64_t db, uint32_t acc) {
    asm volatile("{\n.reg .pred P;\nsetp.ne.u32 P, %69, 0;\nwgmma.mma_async.sync.aligned.m64n128k16.f32.bf16.bf16 "
        "{%0, %1, %2, %3, %4, %5, %6, %7, %8, %9, %10, %11, %12, %13, %14, %15, %16, %17, %18, %19, %20, %21, %22, %23, %24, %25, %26, %27, %28, %29, %30, %31, %32, %33, %34, %35, %36, %37, %38, %39, %40, %41, %42, %43, %44, %45, %46, %47, %48, %49, %50, %51, %52, %53, %54, %55, %56, %57, %58, %59, %60, %61, %62, %63}, {%64, %65, %66, %67}, %68, P, 1, 1, %70;\n}"
        : "+f"(d[0]), "+f"(d[1]), "+f"(d[2]), "+f"(d[3]), "+f"(d[4]), "+f"(d[5]), "+f"(d[6]), "+f"(d[7]), "+f"(d[8]), "+f"(d[9]), "+f"(d[10]), "+f"(d[11]), "+f"(d[12]), "+f"(d[13]), "+f"(d[14]), "+f"(d[15]), "+f"(d[16]), "+f"(d[17]), "+f"(d[18]), "+f"(d[19]), "+f"(d[20]), "+f"(d[21]), "+f"(d[22]), "+f"(d[23]), "+f"(d[24]), "+f"(d[25]), "+f"(d[26]), "+f"(d[27]), "+f"(d[28]), "+f"(d[29]), "+f"(d[30]), "+f"(d[31]), "+f"(d[32]), "+f"(d[33]), "+f"(d[34]), "+f"(d[35]), "+f"(d[36]), "+f"(d[37]), "+f"(d[38]), "+f"(d[39]), "+f"(d[40]), "+f"(d[41]), "+f"(d[42]), "+f"(d[43]), "+f"(d[44]), "+f"(d[45]), "+f"(d[46]), "+f"(d[47]), "+f"(d[48]), "+f"(d[49]), "+f"(d[50]), "+f"(d[51]), "+f"(d[52]), "+f"(d[53]), "+f"(d[54]), "+f"(d[55]), "+f"(d[56]), "+f"(d[57]), "+f"(d[58]), "+f"(d[59]), "+f"(d[60]), "+f"(d[61]), "+f"(d[62]), "+f"(d[63])
        : "r"(a[0]), "r"(a[1]), "r"(a[2]), "r"(a[3]), "l"(db), "r"(acc), "n"(TB));
}
template <int TB>
__device__ __forceinline__ void wgmma_rs64(float* d, const uint32_t* a, uint64_t db, uint32_t acc) {
    asm volatile("{\n.reg .pred P;\nsetp.ne.u32 P, %37, 0;\nwgmma.mma_async.sync.aligned.m64n64k16.f32.bf16.bf16 "
        "{%0, %1, %2, %3, %4, %5, %6, %7, %8, %9, %10, %11, %12, %13, %14, %15, %16, %17, %18, %19, %20, %21, %22, %23, %24, %25, %26, %27, %28, %29, %30, %31}, {%32, %33, %34, %35}, %36, P, 1, 1, %38;\n}"
        : "+f"(d[0]), "+f"(d[1]), "+f"(d[2]), "+f"(d[3]), "+f"(d[4]), "+f"(d[5]), "+f"(d[6]), "+f"(d[7]), "+f"(d[8]), "+f"(d[9]), "+f"(d[10]), "+f"(d[11]), "+f"(d[12]), "+f"(d[13]), "+f"(d[14]), "+f"(d[15]), "+f"(d[16]), "+f"(d[17]), "+f"(d[18]), "+f"(d[19]), "+f"(d[20]), "+f"(d[21]), "+f"(d[22]), "+f"(d[23]), "+f"(d[24]), "+f"(d[25]), "+f"(d[26]), "+f"(d[27]), "+f"(d[28]), "+f"(d[29]), "+f"(d[30]), "+f"(d[31])
        : "r"(a[0]), "r"(a[1]), "r"(a[2]), "r"(a[3]), "l"(db), "r"(acc), "n"(TB));
}
template <int TB>
__device__ __forceinline__ void wgmma_rs16(float* d, const uint32_t* a, uint64_t db, uint32_t acc) {
    asm volatile("{\n.reg .pred P;\nsetp.ne.u32 P, %13, 0;\nwgmma.mma_async.sync.aligned.m64n16k16.f32.bf16.bf16 "
        "{%0, %1, %2, %3, %4, %5, %6, %7}, {%8, %9, %10, %11}, %12, P, 1, 1, %14;\n}"
        : "+f"(d[0]), "+f"(d[1]), "+f"(d[2]), "+f"(d[3]), "+f"(d[4]), "+f"(d[5]), "+f"(d[6]), "+f"(d[7])
        : "r"(a[0]), "r"(a[1]), "r"(a[2]), "r"(a[3]), "l"(db), "r"(acc), "n"(TB));
}

__device__ __forceinline__ uint32_t delay_loop(int n, uint32_t x0) {
    uint32_t z;
    asm volatile("{\n.reg .pred P;\n.reg .u32 c, x;\nmov.u32 c, %1;\nmov.u32 x, %2;\nDL: mad.lo.u32 x, x, 1664525, 1013904223;\nadd.u32 c, c, -1;\nsetp.gt.s32 P, c, 0;\n@P bra DL;\n"
                 "setp.eq.u32 P, x, 0x7fffffff;\nselp.u32 %0, 16, 0, P;\n}" : "=r"(z) : "r"(n), "r"(x0) : "memory");
    return z;
}
__device__ __forceinline__ uint32_t gtime() { uint32_t t; asm volatile("mov.u32 %0, %%globaltimer_lo;" : "=r"(t)); return t; }
__device__ __forceinline__ void wait_time(uint32_t t, uint32_t sb) { while ((int32_t)(gtime() - t) < (int32_t)delay_loop(2, sb)) {} }
__device__ __forceinline__ uint32_t tpc_gpc(uint32_t t) { return t < 32 ? t & 7 : t < 60 ? (t - 32) % 7 + 1 : (t - 54) & 7; }
__device__ __forceinline__ uint32_t latest_stamp(const uint32_t* p, uint32_t seq, uint32_t ref, int backoff, uint32_t sb) {
    for (int n = 0;; n++) {
        uint32_t bad = 0; int32_t m = INT32_MIN;
#pragma unroll
        for (int i = 0; i < 3; i++) { const uint32_t v = ld_relaxed1(p + i * 256); bad |= (v ^ seq) & 31u; m = max(m, (int32_t)(v - (ref << 5)) >> 5); }
        if (__all_sync(0xffffffffu, bad == 0)) return ref + __reduce_max_sync(0xffffffffu, m);
        wait_time(gtime() + backoff, sb);
        if (n > SPIN_LIMIT) spin_fault();
    }
}
__device__ __forceinline__ void release_at(uint32_t t, uint32_t sb, uint32_t bar, int lane) {
    wait_time(t, sb);
    if (lane == 0) mbar_arrive(sb + bar);
}
__host__ __device__ constexpr int frag_word(int u, int f) { return (u == 0 ? 0 : u < 3 ? 3 * u - 1 : u == 3 ? 14 : 3 * u - 4) + f; }
__host__ __device__ constexpr int word_col(int e) { return ((0x32FED987CBA65410ull >> (4 * e)) & 14) * 64 + ((0x32FED987CBA65410ull >> (4 * e)) & 1) * 8; }

constexpr uint32_t CLEAR_LO = 0xFE000000u, CLEAR_HI = 0x5A7FEFEFu;
__device__ __forceinline__ void clear_slot(const Params& P, int slot, int cta, int lane) {
    const int i = cta * 2 + (lane >> 3), x = i & 63;
    if (lane < 16) st_relaxed4(P.gm + slot * M_SLOT + (x >> 1) * 1024 + (x & 1) * 256 + (i >> 7) * 512 + ((i >> 6) & 1) * 128 + (lane & 7) * 16, CLEAR_LO, CLEAR_HI, CLEAR_LO, CLEAR_HI);
    st_relaxed4(g_f + slot * F_SLOT + cta * 512 + lane * 16, 0, 0, 0, 0);
}
__device__ __forceinline__ void mem0_max(const Params& P, uint32_t sb, int tid) {
    uint32_t m = 0;
#pragma unroll
    for (int i = 0; i < 4; i++) {
        const uint4 x = __ldg((const uint4*)P.mem0 + i * 256 + tid);
        m = __vmaxu2(__vmaxu2(__vmaxu2(x.x & 0x7fff7fffu, x.y & 0x7fff7fffu), __vmaxu2(x.z & 0x7fff7fffu, x.w & 0x7fff7fffu)), m);
    }
    sts32(sb + S_COEF + (tid >> 5) * 4, __reduce_max_sync(0xffffffffu, max(m >> 16, m & 0xffffu)));
    bar_arrive(7, 288);
}
__device__ __forceinline__ uint32_t pack_mem0(const Params& P, uint32_t sb, int cta, int lane) {
    bar_sync(7, 288);
    const uint32_t e = __reduce_max_sync(0xffffffffu, lds32(sb + S_COEF + (lane & 7) * 4)) >> 7;
    if (e < 64 || e > 192) return 0x3F803F80u;
    const int i = cta * 2 + (lane >> 4), u = (i >> 5), x = i & 63, L = (i & 3) * 8 + ((lane & 15) >> 1);
    uint64_t w = 32;
#pragma unroll
    for (int f = 0; f < 3; f++) if (f < 2 || u % 3) {
        const float v = __bfloat162float(P.mem0[(L >> 2) * 1024 + word_col(frag_word(u, f)) + ((i >> 2) & 7) * 16 + (L & 3) * 2 + (lane & 1)]);
        w += (uint64_t)(int64_t)__float2int_rn(v * __uint_as_float((271 - e) << 23)) << (45 - 19 * f);
    }
    st_relaxed2(P.gm + 7 * M_SLOT + (x >> 1) * 1024 + (x & 1) * 256 + (i >> 7) * 512 + ((i >> 6) & 1) * 128 + (lane & 15) * 8, (uint32_t)w, (uint32_t)(w >> 32));
    return (e - 30) * 0x00800080u;
}
__device__ __forceinline__ void pacer(const Params& P, const uint32_t sb, const int lane) {
    constexpr uint32_t base = 2;
    int cta = lds32(sb + S_CTA);
#pragma unroll 1
    for (int i = 0; i < 8; i++) clear_slot(P, i, cta, lane);
    __syncwarp();
    if (lane == 0) { uint32_t smid; asm("mov.u32 %0, %%smid;" : "=r"(smid)); st_relaxed1(g_hint + 6144 + cta, smid >> 1); }
    sts32(sb + S_EPOCH + 4, pack_mem0(P, sb, cta, lane));
    fence_release();
    __syncwarp();
    float rate = 0.58f;
    uint32_t c0 = 0;
#pragma unroll 1
    for (int s = -1; s < 63; s++) {
        cta = lds32(sb + S_CTA);
        const int pair = cta >> 1;
        const uint32_t ahead = s > 0 ? (uint32_t)(rate * (float)(pair >= 32 ? P.dc - P.dv : P.dc)) : 0;
        mbar_wait(sb + B_GO, s & 1);
        SSTAMP(10, lane == 0 && s == 0)
        const uint32_t t0 = gtime();
        if (lane < 4) st_relaxed1(g_hint + ((s & 1) * 4 + lane) * 768 + (cta >> 5) * 256 + (cta & 31), (t0 + ahead + (lds32(sb + S_REDO) == s ? P.extra : 0)) << 5 | ((base + s) & 31u));
        wait_time(t0 + (s < 0 ? 2000 : s == 0 && pair >= 16 ? P.ds0 : P.ds), sb);
        const uint32_t t = latest_stamp(g_hint + ((s & 1) * 4 + (pair & 3)) * 768 + lane, base + s, t0, P.back, sb);
        if (s < 0) {
            fence_acquire();
            const uint32_t g = tpc_gpc(ld_relaxed1(g_hint + 6144 + (lane & 15) * 2));
            const uint32_t key = (__popc(__match_any_sync(0xffffffffu, g)) > 4 ? 0 : g + 1) * 16 + (lane & 15);
            const uint32_t tail = (pair & 48) + __popc(__ballot_sync(0xffffffffu, key < __shfl_sync(0xffffffffu, key, pair & 15))) / 2;
            mbar_wait(sb + B_INIT, 0);
            SSTAMP(4, lane == 0)
            sts32(sb + S_TAIL, tail);
            if (lane < 8) sts32(sb + S_SC + lane * 4, lds32(sb + S_EPOCH + 4));
            __syncwarp();
        }
        release_at(t + P.da, sb, B_RELA, lane);
        SSTAMP(11, lane == 0 && s == 0)
        release_at(t + P.db, sb, B_RELB, lane);
        {
            const uint32_t c1 = clock(), g1 = gtime();
            if (s > 1) rate += P.alpha * (__fdividef((float)(g1 - lds32(sb + S_EPOCH + 4)), (float)(c1 - c0)) - rate);
            __syncwarp();
            c0 = c1; sts32(sb + S_EPOCH + 4, g1);
        }
        if (s == 61) {
            sts32(sb + S_COEF, ITEM(ITEM_OFF(lds32(sb + S_TAIL)) + NPRE + 1) + (uint32_t)(uintptr_t)P.out);
            if (lane < M_CQ) map_prefetch(&P.tm[lane]);
        }
    }
}
__device__ __forceinline__ uint32_t xor_or(uint32_t a, uint32_t b, uint32_t t) { uint32_t d; asm("lop3.b32 %0, %1, %2, %3, 0x7E;" : "=r"(d) : "r"(a), "r"(b), "r"(t)); return d; }
__device__ __forceinline__ bool tags_ok(uint32_t bad) { return __all_sync(0xffffffffu, (bad & 1) == 0); }
#define RETRY(k)
#define RETRY_STAT(a, b)
#define UNIT_STAT(u0)
#define KE 0
#define ES 0
#define Q3 1
#define SFENCE() asm volatile("pmevent 1;" ::: "memory")
#define PF1 10
static_assert(NS == 24, "fragment residency");
__host__ __device__ constexpr bool in_smem(int n) { return n < 4 || n == 12 || n == 13; }
__host__ __device__ constexpr int unit_pos(int n) { return n < 4 ? n : n < 12 ? n - 4 : n < 14 ? n - 8 : n - 6; }

__host__ __device__ constexpr int fill_unit(int q) { return q < 4 ? q : q < 6 ? q + 8 : q < 14 ? q - 2 : q; }
__host__ __device__ constexpr int frag_off(int q) { return (q >> 2) * 16384 + ((q >> 1) & 1) * 8192 + (q & 1) * 512; }

constexpr uint32_t QBITS = 0x4B002000u;
constexpr uint64_t W_BIAS = ((uint64_t)QBITS << 45) + ((uint64_t)QBITS << 26) + (uint32_t)(QBITS << 7), W_CLEAR = 0 - 32 * W_BIAS;
static_assert(W_CLEAR == ((uint64_t)CLEAR_HI << 32 | CLEAR_LO), "clear value");
__host__ __device__ constexpr int unit_off(int u) { return (u & 1) * 16384 + (u >> 2) * 512 + ((u >> 1) & 1) * 128; }
__device__ __forceinline__ void red_add64(const uint8_t* p, uint64_t v) { asm volatile("red.relaxed.gpu.global.add.u64 [%0], %1;" ::"l"(p), "l"(v) : "memory"); }
template <int NF>
__device__ __forceinline__ uint64_t encode(const float* x, float S, uint32_t two26, uint32_t& bad) {
    uint32_t b[3];
#pragma unroll
    for (int i = 0; i < 3; i++) b[i] = i < NF ? __float_as_uint(fmaf(x[i], S, 8396800.f)) : QBITS;
    bad = xor_or(b[0], b[1], 0x4B000000u) | (NF == 3 ? b[2] ^ 0x4B000000u : 0);
    uint64_t w;
    asm("{\n.reg .b64 t;\nmov.b64 t, {%2, %3};\nmad.wide.u32 %0, %1, %4, t;\n}" : "=l"(w) : "r"(b[1]), "r"(b[2] << 7), "r"(b[0] << 13), "r"(two26));
    return w;
}
template <int NF>
__device__ __forceinline__ void emit(uint64_t* w, const float (*x)[3], const float* S, uint32_t two26, uint32_t lim, const uint8_t* p) {
    uint32_t bad[2];
    w[0] = encode<NF>(x[0], S[0], two26, bad[0]); w[1] = encode<NF>(x[1], S[1], two26, bad[1]);
    const bool ok = (bad[0] | bad[1]) < lim;
    w[0] |= ok; w[1] |= ok;
    red_add64(p, w[0]); red_add64(p + 1024, w[1]);
}
template <int NF>
__device__ __forceinline__ void repair(const uint64_t* w, const float (*x)[3], const float* S, const uint8_t* p, const uint8_t* pf) {
    if (!(w[0] & 1)) {
#pragma unroll
        for (int j = 0; j < 2; j++) {
            const float T = S[j] * 8192.f;
            asm volatile("red.relaxed.gpu.global.add.v4.f32 [%0], {%1,%2,%3,%4};" ::"l"(pf + j * 512), "f"(x[j][0] * T), "f"(x[j][1] * T), "f"(NF == 3 ? x[j][2] * T : 0.f), "f"(0.f) : "memory");
        }
        fence_release();
#pragma unroll
        for (int j = 0; j < 2; j++) {
            asm volatile("red.relaxed.gpu.global.or.b64 [%0], 64;" ::"l"(p + j * 1024) : "memory");
            red_add64(p + j * 1024, W_BIAS + 1 - w[j]);
        }
    }
    __syncwarp();
}
__device__ __forceinline__ void ld_words(uint32_t* v, const uint8_t* p) {
    asm volatile("{\n.reg .b64 a, b;\nld.relaxed.gpu.global.L1::no_allocate.v2.b64 {a, b}, [%4];\nmov.b64 {%0,%1}, a;\nmov.b64 {%2,%3}, b;\n}" : "=r"(v[0]), "=r"(v[1]), "=r"(v[2]), "=r"(v[3]) : "l"(p) : "memory");
}
__device__ __forceinline__ float field(const uint32_t* w, int f) { return __int2float_rn((int)(f == 0 ? w[1] : f == 1 ? __funnelshift_l(w[0], w[1], 19) : w[0] << 6)); }
template <int U>
__device__ __forceinline__ void decode(uint32_t* b, const uint32_t* v) {
#pragma unroll
    for (int f = 0; f < (U % 3 ? 3 : 2); f++) b[frag_word(U, f)] = pack2(field(v, f), field(v + 2, f));
}
__device__ __forceinline__ uint32_t status(const uint32_t (*v)[4], uint32_t c32) { return xor_or(v[0][0], v[0][2], c32) | xor_or(v[1][0], v[1][2], c32) | xor_or(v[2][0], v[2][2], c32); }
__device__ __forceinline__ void gather_slow(const Params& P, uint32_t* b, const uint8_t* pm, int s, int warp, uint32_t ln, uint32_t u2) {
    if (s == 0 && u2 == 0x3F803F80u) {
#pragma unroll
        for (int i = 0; i < 16; i++) b[i] = __ldg((const uint32_t*)(P.mem0 + (ln >> 2) * 1024 + word_col(i) + warp * 16 + (ln & 3) * 2));
        return;
    }
    uint32_t v[6][4], st;
    for (int n = 0;; n++) {
#pragma unroll
        for (int u = 0; u < 6; u++) ld_words(v[u], pm + unit_off(u));
        st = status(v, 32) | status(v + 3, 32);
        if (!__any_sync(0xffffffffu, st & 32)) break;
        __nanosleep(200);
        if (n > SPIN_LIMIT) spin_fault();
    }
    const bool side = __any_sync(0xffffffffu, st & 64);
    if (side) fence_acquire();
    const uint8_t* pf = g_f + ((s + 7) & 7) * F_SLOT + warp * 1024 + ln * 32;
#pragma unroll
    for (int u = 0; u < 6; u++) {
        float x[2][4] = {};
#pragma unroll
        for (int k = 0; k < 2; k++)
            asm volatile("{\n.reg .pred P;\nsetp.ne.u32 P, %5, 0;\n@P ld.relaxed.gpu.global.v4.f32 {%0,%1,%2,%3}, [%4];\n}"
                         : "+f"(x[k][0]), "+f"(x[k][1]), "+f"(x[k][2]), "+f"(x[k][3]) : "l"(pf + u * 8192 + k * 16), "r"((uint32_t)side) : "memory");
#pragma unroll
        for (int f = 0; f < (u % 3 ? 3 : 2); f++) b[frag_word(u, f)] = pack2(field(v[u], f) + x[0][f], field(v[u] + 2, f) + x[1][f]);
    }
}
__device__ __forceinline__ uint32_t max_abs2(uint32_t a, uint32_t b) { uint32_t d; asm("max.NaN.xorsign.abs.bf16x2 %0, %1, %2;" : "=r"(d) : "r"(a), "r"(b)); return d; }
__device__ __forceinline__ uint32_t max6(const uint32_t* b) {
    const uint32_t m = max_abs2(max_abs2(max_abs2(b[0], b[1]), max_abs2(b[2], b[3])), max_abs2(b[4], b[5]));
    return max(m & 0x7fff0000u, (m << 16) & 0x7fff0000u);
}

template <bool TR>
__device__ __forceinline__ void put_partials(uint32_t a, const float* x, const float* y) {
    if (TR) stsm4t(a, pack2(x[0], x[1]), pack2(x[2], x[3]), pack2(y[0], y[1]), pack2(y[2], y[3]));
    else stsm4(a, pack2(x[0], x[1]), pack2(x[2], x[3]), pack2(y[0], y[1]), pack2(y[2], y[3]));
}
__device__ __forceinline__ void reduce_load(uint32_t (*x)[4], uint32_t a) { ldsm4t(x[0], a); ldsm4t(x[1], a + 512); }
__device__ __forceinline__ uint32_t reduce8(const uint32_t (*x)[4], uint32_t l8, uint32_t u2) {
    uint32_t p[2];
#pragma unroll
    for (int i = 0; i < 2; i++) {
        float d[4] = {};
        mma16816(d, x[i][0], x[i][1], x[i][2], x[i][3], (l8 & 32) ? 0u : u2, (l8 & 32) ? u2 : 0u);
        p[i] = pack2((l8 & 8) ? d[2] : d[0], (l8 & 8) ? d[3] : d[1]);
    }
    return (l8 & 16) ? p[1] : p[0];
}
__device__ __forceinline__ void score_half(float (*a)[4], const uint32_t (*qa)[4], const uint32_t (*kf)[4]) {
#pragma unroll
    for (int w = 0; w < 2; w++) {
        mma16816(a[w], qa[w][0], qa[w][1], qa[w][2], qa[w][3], kf[w][0], kf[w][1]);
        mma16816(a[2 + w], qa[w][0], qa[w][1], qa[w][2], qa[w][3], kf[w][2], kf[w][3]);
    }
}
__device__ __forceinline__ void score_sum(float* S, const float (*a)[4]) {
    S[0] = (a[0][0] + a[1][0]) + (a[2][2] + a[3][2]);
    S[1] = (a[0][1] + a[1][1]) + (a[2][3] + a[3][3]);
}
__device__ __forceinline__ float quad_max(float m) {
    return fmaxf(fmaxf(m, __shfl_xor_sync(0xffffffffu, m, 1)), fmaxf(__shfl_xor_sync(0xffffffffu, m, 2), __shfl_xor_sync(0xffffffffu, m, 3)));
}

#define ISTAMP(i)
__device__ __forceinline__ float next_scale(uint32_t sb, int slot, int warp, uint32_t u2) {
    uint32_t x[2][4];
    lds128(x[0], sb + S_MX + slot * 32); lds128(x[1], sb + S_MX + slot * 32 + 16);
    const uint32_t mx = max(max(max(x[0][0], x[0][1]), max(x[0][2], x[0][3])), max(max(x[1][0], x[1][1]), max(x[1][2], x[1][3])));
    const float top = fminf(fmaxf(__uint_as_float(mx) * bf_hi(u2), 0x1p-40f), 0x1p40f) * (1.f / (12288.f * 8192.f));
    const uint32_t un = pack2(top, top);
    sts32(sb + S_SC + warp * 4, un);
    return rcp(bf_hi(un) * 8192.f);
}
#define NEARLY 1
#define U3POS 1
#define VPOS 1
#define ROT 0
#define BPOS 1
#define ONLINE 0
#define NBAR 1
#define ORD3 0
#define F2 1
#define EARLY 0
#define TK 0
#define OBN 4
#define CH4 1
#define RPOS 1
#define AF 0
#define AFENCE(i) if ((AF >> (i)) & 1) SFENCE();
#define FPOS 99
#define PACE 1
#define PF2 12
__host__ __device__ constexpr int w2_t(int i) { return i < 16 ? i & 1 : 2; }
__host__ __device__ constexpr int w2_k(int i) { return i < 16 ? i >> 1 : i - 16; }
template <typename G>
__device__ __forceinline__ void load_weights(uint32_t (*wr)[4], const uint32_t sb, const int warp, const int lane, G stores_read) {
    const uint32_t frag = sb + warp * 1024 + (lane >> 4) * 8192 + (lane & 7) * 128 + ((((lane >> 3) & 1) ^ (lane & 7)) << 4);
    const uint32_t rel = mapa(sb + B_EMPTY, cluster_rank() ^ (lane & 1));
#define RELEASE(st) { if ((st) >= 2) fence_async_smem(); __syncwarp(); if (lane < 2) mbar_arrive_cluster(rel + (st) * 8); }
    mbar_wait(sb + B_FULL, 0); mbar_wait(sb + B_FULL + 8, 0);
    RELEASE(0) RELEASE(1)
#pragma unroll
    for (int st = 2; st < 4; st++) {
        mbar_wait(sb + B_FULL + st * 8, 0);
        ISTAMP(st - 2)
#pragma unroll
        for (int f = 0; f < 12; f++) ldsm4t(wr[st * 12 - 24 + f], (frag ^ ((f & 3) << 5)) + st * STAGE + (f >> 2) * 16384);
        RELEASE(st)
    }
#pragma unroll 2
    for (int u = 0; u < 6; u++) {
        uint32_t x[4][4];
#pragma unroll
        for (int i = 0; i < 4; i++) lds128(x[i], (frag ^ (i << 5)) + u * 16384);
        __syncwarp();
#pragma unroll
        for (int i = 0; i < 4; i++) sts128(sb + warp * 1024 + lane * 16 + u * 16384 + frag_off(i), x[i]);
    }
    SSTAMP(0, threadIdx.x == 0)
    stores_read();
    SSTAMP(2, threadIdx.x == 0)
    mbar_wait(sb + B_FULL, 1); mbar_wait(sb + B_FULL + 8, 1);
    RELEASE(0) RELEASE(1)
#pragma unroll
    for (int st = 2; st < 4; st++) {
        mbar_wait(sb + B_FULL + st * 8, 1);
#pragma unroll
        for (int f = 0; f < (st == 2 ? 12 : 4); f++) ldsm4t(wr[st * 12 + f], (frag ^ ((f & 3) << 5)) + st * STAGE + (f >> 2) * 16384);
        RELEASE(st)
    }
    ISTAMP(2)
    bar_sync(1, 256);
    if (warp == 7 && lane < 3) mbar_arrive_cluster(mapa(sb + B_INIT, (cluster_rank() & 1) + lane * 2));
}
template <int ROLE>
__device__ __forceinline__ void chain_role(const Params& P, const uint32_t (*wr)[4], const uint32_t sb, const int h, const int warp, const int lane) {
    constexpr int NU = ROLE == 0 ? 2 : 3;
    const bool att = ROLE == 0 && warp < 4;
    uint32_t l8 = opq(sb + lane * 8, lane);
#define PERSIST() { mbar_wait(sb + B_KVGO, slot ^ 1); const uint32_t pa_ = ((l8 - sb) >> 1) + (sb + S_QX + warp * 128); sts32(pa_, r0); sts32(pa_ + 1024, r1); \
                    fence_async_smem(); __syncwarp(); if (l8 == sb) mbar_arrive(sb + B_PERS); }
    if (ROLE) sts32(sb + S_SX + warp * 128 + lane * 4, warp >= 2 ? 0 : (lane & 1) ? CLEAR_HI : CLEAR_LO);
    const uint32_t rdelta = __shfl_sync(0xffffffffu, mapa(sb, (cluster_rank() + (ROLE == 1 ? 4 : 2)) % 6) - sb, 0);
    const uint32_t vdelta = ROLE ? 0 : __shfl_sync(0xffffffffu, mapa(sb, (cluster_rank() + 4) % 6) - sb, 0);
    ISTAMP(3)
    __syncwarp();
#define GATHER_OFF(s) ((((s) + 7) & 7) * M_SLOT + warp * 2048 + (l8 & 56) * 2 + (l8 & 64) * 4 + (l8 & 128) * 8)
    uint32_t mo = GATHER_OFF(0);
    if (ROT) mbar_wait(sb + B_RELA, 0);
    for (int s = 0; s < (ROLE == 0 ? 63 : 64);) {
        const int slot = s & 1;
        l8 += s & P.zero;
        const uint32_t w1a = l8 * 2 + (S_W1 + warp * 1024 - sb);
        PROF(9)
        uint32_t u2, r0, r1, pld, pub, pbar, x[2][4];
        {
#define pm (P.gm + mo)
            uint32_t as[24][4], b[16], v[6][4];
            float acc[8][4];
#define W1LD(n) _Pragma("unroll") for (int i_ = 0; i_ < 4; i_++) ldsm4t(as[unit_pos(n) * 4 + i_], w1a + frag_off(unit_pos(n) * 4 + i_));
#define W1LD2(n, p) { const uint32_t wa_ = w1a + (as[unit_pos(p) * 4][0] & as[unit_pos(p) * 4 + 1][0] & as[unit_pos(p) * 4 + 2][0] & as[unit_pos(p) * 4 + 3][0] & P.zero); \
                      _Pragma("unroll") for (int i_ = 0; i_ < 4; i_++) ldsm4t(as[unit_pos(n) * 4 + i_], wa_ + frag_off(unit_pos(n) * 4 + i_)); }
#define W1MMA(n) _Pragma("unroll") for (int i_ = 0; i_ < 4; i_++) { const uint32_t* a_ = in_smem(n) ? as[unit_pos(n) * 4 + i_] : wr[unit_pos(n) * 4 + i_]; \
                                                                   mma16816(acc[((n) & 1) * 4 + i_], a_[0], a_[1], a_[2], a_[3], b[(n) & 14], b[(n) | 1]); }
#pragma unroll
            for (int T = 0; T < 8; T++) { acc[T][0] = acc[T][1] = acc[T][2] = acc[T][3] = 0.f; }
            if (!ROT) mbar_wait(sb + B_RELA, slot);
            PROF(12)
#pragma unroll
            for (int u = 0; u < 3; u++) ld_words(v[u], pm + unit_off(u));
            __syncwarp();
#pragma unroll
            for (int i = 0; i < PF1; i++) ldsm4t(as[i], w1a + frag_off(i));
            __syncwarp();
            mo += mbar_try(sb + B_RELB, slot) & P.zero;
            PROF(13)
#pragma unroll
            for (int u = 3; u < 6; u++) ld_words(v[u], pm + unit_off(u));
            uint32_t st = status(v, ((uint32_t)((uintptr_t)pm >> 32) & P.zero) + 32);
            pin<1>(&st);
            SFENCE();
            UNIT_STAT(0)
            PROF(0)
            decode<0>(b, v[0]); decode<1>(b, v[1]); decode<2>(b, v[2]);
#pragma unroll
            for (int i = PF1; i < 12; i++) ldsm4t(as[i], w1a + frag_off(i));
            W1MMA(0) W1MMA(1) W1MMA(2)
            if (TK & 1) W1LD2(3, 2) else { W1LD(3) }
            SFENCE();
            if (TK & 8) { W1MMA(5) W1MMA(4) W1MMA(3) W1MMA(6) } else { W1MMA(5) W1MMA(4) W1MMA(6) W1MMA(3) }
            if (U3POS == 0) W1MMA(7)
            if (TK & 2) W1LD2(12, 3) else { W1LD(12) }
            uint32_t mx = max6(b);
            pin<1>(&mx);
            SFENCE();
            PROF(10)
            if (U3POS == 1) W1MMA(7)
            const uint32_t mxa = sb + S_MX + slot * 32 + warp * 4;
            sts32(mxa, __reduce_max_sync(0xffffffffu, mx));
            UNIT_STAT(3)
            st |= status(v + 3, 32);
            const bool redo = __any_sync(0xffffffffu, st & 96);
            const bool kvok = ROLE || mbar_test(sb + B_KVFULL + slot * 8, (s >> 1) & 1);
            decode<4>(b, v[4]); decode<5>(b, v[5]); decode<3>(b, v[3]);
            u2 = lds32(sb + S_SC + warp * 4);
            W1MMA(8) W1MMA(10) if (ORD3) { W1MMA(14) W1MMA(12) } else { W1MMA(12) W1MMA(14) }
            if (TK & 4) W1LD2(13, 12) else { W1LD(13) }
            if (__builtin_expect(redo || !kvok, 0)) {
                if (redo) {
                    RETRY(3)
                    sts32(sb + S_REDO, s);
                    gather_slow(P, b, P.gm + GATHER_OFF(s), s, warp, (l8 - sb) >> 3, u2);
                    sts32(mxa, __reduce_max_sync(0xffffffffu, max6(b)));
#pragma unroll
                    for (int T = 0; T < 8; T++) { acc[T][0] = acc[T][1] = acc[T][2] = acc[T][3] = 0.f; }
#pragma unroll
                    for (int n = 0; n < 15; n += n < 8 ? 1 : 2) {
                        if (in_smem(n)) { W1LD(n) }
                        W1MMA(n)
                    }
                    W1LD(13)
                }
                if (ROLE == 0) mbar_wait(sb + B_KVFULL + slot * 8, (s >> 1) & 1);
            }
#undef pm
            SSTAMP(7, threadIdx.x == 0 && s == 0)
            PROF(14)
            const uint32_t pst = (l8 - sb) * 16 + ((warp * 16) ^ ((l8 * 2) & 112)) + (sb + S_P1);
            put_partials<ROLE == 2>(pst, acc[0], acc[1]); put_partials<ROLE == 2>(pst + 4096, acc[2], acc[3]);
            W1MMA(9)
            SFENCE();
            pld = (l8 & 64) * 4 + (l8 & 128) + (l8 & 56) * 2 + (sb + S_P1 + warp * 1024);
            const uint32_t rd = s == 63 ? 0 : rdelta;
            pub = ((l8 - sb) >> 1) + (ROLE ? sb + rd + (ROLE == 1 ? S_KL : S_VL) + warp * 128 : sb + S_QX + (warp & 4) * 128 + (warp & 1) * 256 + (warp & 2) * 64);
            pbar = sb + rd + (ROLE == 1 && s != 63 ? B_K : B_V);
#define PUBLISH0() { r0 = reduce8(x, l8, u2); if (ROLE) st_async1(pub, r0, KE && ROLE == 1 && s != 63 ? pbar + (B_PERS - B_K) : pbar); else sts32(pub, r0); }
            if (RPOS == 0) { bar_sync(1, 256); reduce_load(x, pld); SFENCE(); }
            W1MMA(11)
            if (RPOS == 1) { bar_sync(1, 256); reduce_load(x, pld); }
            if (RPOS != 2 || F2) SFENCE();
#define W1MMH(n, o) _Pragma("unroll") for (int i_ = o; i_ < o + 2; i_++) { const uint32_t* a_ = in_smem(n) ? as[unit_pos(n) * 4 + i_] : wr[unit_pos(n) * 4 + i_]; \
                                                                   mma16816(acc[((n) & 1) * 4 + i_], a_[0], a_[1], a_[2], a_[3], b[(n) & 14], b[(n) | 1]); }
            if (ES) { W1MMH(15, 0) W1MMH(15, 2) W1MMH(13, 0) } else W1MMA(15)
            if (RPOS == 0) PUBLISH0()
            if (RPOS == 2) { bar_sync(1, 256); reduce_load(x, pld); }
            if (RPOS != 1 || F2) SFENCE();
            if (ES) { W1MMH(13, 2) put_partials<ROLE == 2>(pst + 8192, acc[4], acc[5]); } else W1MMA(13)
            if (RPOS == 1) PUBLISH0()
            if (!ES) put_partials<ROLE == 2>(pst + 8192, acc[4], acc[5]);
            put_partials<ROLE == 2>(pst + 12288, acc[6], acc[7]);
            if (RPOS == 2) PUBLISH0()
        }
        SSTAMP(8, threadIdx.x == 0 && s == 0)
        PROF(1)
        if (ROLE) {
            bar_sync(1, 256);
            reduce_load(x, pld + 8192);
            r1 = reduce8(x, l8, u2);
            st_async1(pub + 1024, r1, pbar);
            if (s == 63) {
                PERSIST()
                mbar_wait(sb + B_V, 0);
                break;
            }
            PROF(2)
        }
        uint32_t ln, w2a, ro;
#define W2ADDR(late) { l8 += pub & P.zero; ln = (l8 - sb) >> 3; \
        w2a = sb + S_W2 + (ROLE ? (warp >> 2) * 16384 : late * 32768) + ((((ln & 7) + (ln >> 4) * 8) * 128 + ((((ln >> 3) & 1) ^ (ln & 7)) << 4)) ^ ((warp & 3) << 5)); \
        ro = (s & 7) * M_SLOT + (ROLE ? warp * 2048 + unit_off(ROLE) : (warp & 3) * 2048 + late * unit_off(3)) + (ln & 2) * 128 + (ln & 1) * 64 + (ln >> 2) * 8; }
        constexpr int RO2 = ROLE ? unit_off(ROLE + 3) - unit_off(ROLE) : 8192;
        float Sj[2];
        uint32_t w[24][4], ob[4][4];
        float S;
#define W2LD(i) ldsm4t(w[i], w2a + w2_t(i) * (ROLE ? 32768 : 16384) + (w2_k(i) & 1) * 8192 + (w2_k(i) >> 1) * 2048)
#define W2MMA(d, i) mma16816(d, w[i][0], w[i][1], w[i][2], w[i][3], ob[w2_k(i) >> 1][(w2_k(i) & 1) * 2], ob[w2_k(i) >> 1][(w2_k(i) & 1) * 2 + 1])
#define LEADER(wp) (l8 == sb + ((wp) - warp) * 256)
        if (att) {
            const float cs = 0.08838834764831845f * 1.4426950408889634f;
            uint32_t qa[4][4], kf[4][4], vf[4][4], vv[4];
            float T[5][2], sa[4][4] = {};
            const uint32_t l16 = l8 * 2 - sb;
            const uint32_t kaddr = (l8 & 56) * 16 + (((l8 >> 2) ^ (l8 * 2)) & 48) + ((l8 * 2) & 64) + (sb + S_KV + warp * 1024 + slot * 16384);
            bar_sync(1, 256);
            reduce_load(x, pld + 8192);
            __syncwarp();
#pragma unroll
            for (int i = 0; i < 2; i++) { ldsm4(qa[i], l16 + S_QX + i * 512); ldsm4(kf[i], kaddr ^ (i * 64)); }
            AFENCE(0)
            sts32(pub + 1024, reduce8(x, l8, u2));
            __syncwarp();
#pragma unroll
            for (int i = 2; i < 4; i++) ldsm4(kf[i], (kaddr ^ ((i & 1) * 64)) + 4096);
            score_half(sa, qa, kf);
            bar_sync(2, 256);
            PROF(2)
#pragma unroll
            for (int i = 2; i < 4; i++) ldsm4(qa[i], l16 + S_QX + i * 512);
            float sm[4][4] = {};
            const bool kearly = KE && mbar_try(sb + B_PERS, slot);
            score_half(sa, qa + 2, kf + 2);
            score_sum(T[0], sa);
            sts64(l8 + S_SX + warp * 256, __float_as_uint(T[0][0]), __float_as_uint(T[0][1]));
            PROF(4)
            if (KE) {
                if (!kearly) mbar_wait(sb + B_PERS, slot);
                ldsm4(kf[0], l16 + S_KL); ldsm4(kf[1], l16 + S_KL + 512);
                score_half(sm, qa, kf);
            }
            if (BPOS == 0) bar_sync(4, 128);
            mbar_wait(sb + B_K, slot);
            PROF(11)
#pragma unroll
            for (int i = KE ? 2 : 0; i < 4; i++) ldsm4(kf[i], l16 + S_KL + i * 512);
            if (BPOS == 1) bar_sync(4, 128); else __syncwarp();
#pragma unroll
            for (int n = 0; n < 4; n++) lds64f(T[n], l8 + S_SX + n * 256);
            if (!KE) score_half(sm, qa, kf);
            score_half(sm, qa + 2, kf + 2);
            const uint32_t vaddr = (l8 & 56) * 16 + (l8 & 128) * 8 + (((warp & 1) * 64 + ((l8 >> 2) & 16)) ^ ((l8 * 2) & 112)) + (sb + S_KV + 8192 + (warp >> 1) * 4096 + slot * 16384);
            float mx = fmaxf(fmaxf(fmaxf(T[0][0], T[0][1]), fmaxf(T[1][0], T[1][1])), fmaxf(fmaxf(T[2][0], T[2][1]), fmaxf(T[3][0], T[3][1])));
            score_sum(T[4], sm);
            float m = quad_max(fmaxf(mx, fmaxf(T[4][0], T[4][1])));
            if (VPOS == 0) {
#pragma unroll
                for (int i = 0; i < 4; i++) ldsm4t(vf[i], (vaddr ^ ((i & 1) << 5)) + (i >> 1) * 2048);
            }
            mbar_wait(sb + B_V, slot);
            if (VPOS == 1) {
#pragma unroll
                for (int i = 0; i < 4; i++) ldsm4t(vf[i], (vaddr ^ ((i & 1) << 5)) + (i >> 1) * 2048);
            }
            ldsm4(vv, l16 + S_VL + warp * 512);
            uint32_t pa[5];
            m *= cs;
#pragma unroll
            for (int n = 0; n < 5; n++) { T[n][0] = ex2(fmaf(T[n][0], cs, -m)); T[n][1] = ex2(fmaf(T[n][1], cs, -m)); pa[n] = pack2(T[n][0], T[n][1]); }
            float sum = (((T[0][0] + T[0][1]) + (T[1][0] + T[1][1])) + ((T[2][0] + T[2][1]) + (T[3][0] + T[3][1]))) + (T[4][0] + T[4][1]);
            PROF(3)
            W2ADDR(1)
            const uint32_t lo = sb + S_O + warp * 512 + (ln & 3) * 64 + (ln >> 2) * 8, ls = sb + S_SUM + (ln & 3) * 32 + (ln & 4) * 4 + (ln >> 3) * 4;
            const uint32_t sdelta = warp < 2 ? rdelta : vdelta;
            if (Q3 & 2) sum = (sum + __shfl_xor_sync(0xffffffffu, sum, 1)) + (__shfl_xor_sync(0xffffffffu, sum, 2) + __shfl_xor_sync(0xffffffffu, sum, 3));
            else { sum += __shfl_xor_sync(0xffffffffu, sum, 1); sum += __shfl_xor_sync(0xffffffffu, sum, 2); }
            float O[2][4];
#pragma unroll
            for (int i = 0; i < 2; i++) { O[i][0] = O[i][1] = O[i][2] = O[i][3] = 0.f; }
#pragma unroll
            for (int i = 0; i < 2; i++) {
                mma16816(O[0], vf[2 * i][0], vf[2 * i][1], vf[2 * i][2], vf[2 * i][3], pa[2 * i], pa[2 * i + 1]);
                mma16816(O[1], vf[2 * i + 1][0], vf[2 * i + 1][1], vf[2 * i + 1][2], vf[2 * i + 1][3], pa[2 * i], pa[2 * i + 1]);
            }
            mma1688(O[0], vv[0], vv[1], pa[4]);
            mma1688(O[1], vv[2], vv[3], pa[4]);
            uint32_t o[2][2];
#pragma unroll
            for (int j = 0; j < 2; j++) { o[j][0] = pack2(O[0][j], O[0][2 + j]); o[j][1] = pack2(O[1][j], O[1][2 + j]); }
#pragma unroll
            for (int j = 0; j < 2; j++) st_async2(lo + rdelta + j * 256, o[j][0], o[j][1], sb + rdelta + B_K);
            st_async1(ls + sdelta + (warp & 1) * 128, __float_as_uint(sum), sb + sdelta + B_K);
#pragma unroll
            for (int j = 0; j < 2; j++) st_async2(lo + vdelta + j * 256, o[j][0], o[j][1], sb + vdelta + B_K);
#pragma unroll
            for (int j = 0; j < 2; j++) sts64(lo + j * 256, o[j][0], o[j][1]);
            sts32(ls + warp * 128, __float_as_uint(sum));
            PROF(5)
            bar_sync(3, 256);
            if (LEADER(0)) { mbar_expect(sb + B_K, KE ? 1024 : 2048); if (KE) mbar_expect(sb + B_PERS, 1024); mbar_expect(sb + B_V, 2048); mbar_arrive(sb + B_KVGO + slot * 8); }
            S = next_scale(sb, slot, warp, u2);
            if (s == 0) mbar_wait(sb + B_WO, 0);
            pin<1>(&S);
            SFENCE();
#pragma unroll
            for (int j = 0; j < 4; j++) lds128(ob[j], l8 * 2 - sb + S_O + j * 512);
            lds64f(Sj, sb + S_SUM + (l8 & 24));
#pragma unroll
            for (int i = 0; i < PF2; i++) W2LD(i);
        } else {
            if (ROLE == 0) { bar_sync(1, 256); reduce_load(x, pld + 8192); sts32(pub + 1024, reduce8(x, l8, u2)); bar_arrive(2, 256); }
            if (LEADER(7)) { if (s) mbar_arrive(sb + B_GO); if (ROLE) mbar_expect(sb + B_K, 2304); }
            S = next_scale(sb, slot, warp, u2);
            if (s == 0) mbar_wait(sb + B_WO, 0);
            if (ROLE != 0) PERSIST()
            W2ADDR(0)
#pragma unroll
            for (int i = 0; i < PF2; i++) {
                W2LD(i);
                if (ROLE == 0 && (i & PACE) == PACE) w2a += w[i][0] & P.zero;
            }
            ro = opq(ro, ln);
            const uint32_t sa = opq(sb + S_SUM + (l8 & 24), ln), oa = opq(l8 * 2 - sb + S_O, ln);
            if (ROLE == 0) bar_sync(3, 256); else mbar_wait(sb + B_K, slot);
            if (OBN == 4 || !ROLE) lds64f(Sj, sa);
#pragma unroll
            for (int j = 0; j < 4; j++) { if (ROLE && j == OBN) SFENCE(); lds128(ob[j], oa + j * 512); }
            if (OBN < 4 && ROLE) lds64f(Sj, sa);
        }
        SSTAMP(9, threadIdx.x == 224 && s == 0)
        if (OBN == 4 || !ROLE) SFENCE();
        PROF(6)
        {
            const uint8_t* pr = P.gm + ro;
            float c[4][4];
            uint32_t lim = 0;
#pragma unroll
            for (int i = 0; i < 4; i++) { c[i][0] = c[i][1] = c[i][2] = c[i][3] = 0.f; }
#pragma unroll
            for (int i = 0; i < 16; i++) {
                W2MMA(c[i & (ROLE && !CH4 ? 1 : 3)], i);
                if (i + PF2 < (ROLE ? 16 + NEARLY : 16)) W2LD(i + PF2);
                if (i == 5) {
                    const uint32_t z = __float_as_uint(c[1][0]) & P.zero;
                    Sj[0] = S * rcp(__uint_as_float(__float_as_uint(Sj[0]) | z)); Sj[1] = S * rcp(__uint_as_float(__float_as_uint(Sj[1]) | z));
                }
                if (i == 5) lim = __any_sync(0xffffffffu, fmaxf(fmaxf(fabsf(c[0][0]), fabsf(c[0][2])), fmaxf(fabsf(c[1][0]), fabsf(c[1][2]))) * Sj[0] >= (ROLE && !CH4 ? 24.f : 20.f)) ? 16384 : 0;
                if (i == FPOS) { pin<1>(&lim); pin<2>(Sj); pin_ptr(pr); SFENCE(); }
            }
            if (ROLE == 0 || CH4) {
#pragma unroll
                for (int i = 0; i < 8; i++) { c[i >> 2][i & 3] += c[2 + (i >> 2)][i & 3]; c[2 + (i >> 2)][i & 3] = 0.f; }
            }
            const float xa[2][3] = {{c[0][0], c[0][2], c[1][0]}, {c[0][1], c[0][3], c[1][1]}};
            uint64_t wa[2], wb[2];
            emit<NU>(wa, xa, Sj, P.two26, lim, pr);
            PROF(7)
            mo = GATHER_OFF(s + 1);
            pin<1>(&mo);
            if (ROLE) {
                SFENCE();
#pragma unroll
                for (int i = 16 + NEARLY; i < 24; i++) { if (i == 16 + NBAR) bar_sync(2, 256); W2LD(i); __syncwarp(); }
                SFENCE();
#pragma unroll
                for (int i = 16; i < 24; i++) W2MMA(c[2 + (i & 1)], i);
#pragma unroll
                for (int i = 0; i < 4; i++) c[2][i] += c[3][i];
            }
            const float y[2][3] = {{ROLE ? c[1][2] : c[1][0], ROLE ? c[2][0] : c[1][2], c[2][2]}, {ROLE ? c[1][3] : c[1][1], ROLE ? c[2][1] : c[1][3], c[2][3]}};
            const bool released = !ROT || mbar_test(sb + B_RELA, slot ^ 1);
            emit<NU>(wb, y, Sj, P.two26, lim, pr + RO2);
            PROF(8)
            if (!__all_sync(0xffffffffu, (wa[0] & wb[0] & 1) && released && s)) {
                if (__builtin_expect(!__all_sync(0xffffffffu, wa[0] & wb[0] & 1), 0)) {
                    RETRY(5)
                    const uint8_t* pf = g_f + (s & 7) * F_SLOT + (ROLE ? ROLE * 8192 + warp * 1024 : (warp & 3) * 1024 + (att ? 24576 : 0)) + (ln & 3) * 128 + (ln >> 2) * 16;
                    repair<NU>(wa, xa, Sj, pr, pf);
                    repair<NU>(wb, y, Sj, pr + RO2, pf + (ROLE ? 24576 : 4096));
                }
                if (s == 0) { bar_sync(1, 256); if (LEADER(7)) mbar_arrive(sb + B_GO); }
                if (ROT) mbar_wait(sb + B_RELA, slot ^ 1);
            }
        }
        s++;
    }
}
struct Pipe { uint32_t stage, phase; };
struct Cons {
    uint32_t sb, rel;
    int wg, wq, lane, rank, pair;
    uint32_t nst;
    Pipe p;
};
__device__ __forceinline__ void pipe_next(Pipe& p) { p.stage = (p.stage + 1) & (NSTAGE - 1); p.phase ^= (p.stage == 0); }
__device__ __forceinline__ void release(const Cons& c, uint32_t stage) { if (c.lane < 2) mbar_arrive_cluster(c.rel + stage * 8); }

enum { PEND_NONE = 0, PEND_KVO = 1, PEND_HT = 2, PEND_OUT = 3, PEND_OUTH = 4 };
struct Pend { uint32_t pk[64]; int kind, row, col, cnt; };

__device__ __forceinline__ void staging_wait(const Cons& c) { if (c.nst) mbar_wait(c.sb + B_SFREE + c.wg * 8, (c.nst - 1) & 1); }
__device__ __forceinline__ void staging_post(Cons& c, int kind, int row, int col, int cnt) {
    __syncwarp();
    if (c.lane == 0) {
        if (c.wq == 0) { const uint32_t x[4] = {(uint32_t)kind, (uint32_t)row, (uint32_t)col, (uint32_t)cnt}; sts128(c.sb + S_DESC + c.wg * 16, x); }
        mbar_arrive(c.sb + B_SFULL + c.wg * 8);
    }
    c.nst++;
}
template <int HF, bool KVONLY = false>
__device__ __forceinline__ void drain(const Params& P, Cons& c, const Pend& d) {
    const uint32_t* pk = d.pk + HF * 32;
    if (!KVONLY && d.kind >= PEND_OUT) {
        if (HF == 1 && d.kind == PEND_OUTH) return;
        float* o = P.out + (size_t)(d.row + c.wq * 16 + (c.lane >> 2)) * 2048 + d.col + HF * 128 + (c.lane & 3) * 2;
#pragma unroll
        for (int j = 0; j < 16; j++) {
            st_stream2(o + j * 8, bf_lo(pk[j * 2]), bf_hi(pk[j * 2]));
            st_stream2(o + 8 * 2048 + j * 8, bf_lo(pk[j * 2 + 1]), bf_hi(pk[j * 2 + 1]));
        }
    } else if (d.kind != PEND_NONE) {
        const bool ht = !KVONLY && d.kind == PEND_HT;
        const int hi = (c.lane >> 3) & 1;
        const uint32_t base = c.sb + S_STG + c.wg * 16384 + ((ht ? hi * 32 + c.wq * 8 : c.wq * 16 + hi * 8) + (c.lane & 7)) * 128;
        staging_wait(c);
#pragma unroll
        for (int j = 0; j < 8; j++) {
            const int ch = (j & 3) * 2 + (c.lane >> 4);
            stsm4(base + (j >> 2) * 8192 + ((ch ^ (c.lane & 7)) << 4), pk[j * 4], pk[j * 4 + 1], pk[j * 4 + 2], pk[j * 4 + 3]);
        }
        fence_async_smem();
        staging_post(c, d.kind, d.row, d.col + HF * 128, HF ? d.cnt : -1);
    }
}
__device__ __forceinline__ void drain_all(const Params& P, Cons& c, Pend& d) { drain<0>(P, c, d); drain<1>(P, c, d); d.kind = PEND_NONE; }

__device__ __forceinline__ void store_warp(const Params& P, uint32_t sb, int wg) {
    const uint32_t stg = sb + S_STG + wg * 16384;
#pragma unroll 1
    for (uint32_t n = 0;; n++) {
        mbar_wait(sb + B_SFULL + wg * 8, n & 1);
        uint32_t x[4];
        lds128(x, sb + S_DESC + wg * 16);
        if (x[0] == PEND_NONE) break;
        const bool ht = x[0] == PEND_HT;
        const CUtensorMap* m = &P.tm[ht ? M_HTS : M_KVO];
#pragma unroll 1
        for (int i = 0; i < 4; i++) if (!(DBGF(128) && gridDim.x != 96)) tma_store2d(m, x[2] + (i >> 1) * 64, x[1] + (i & 1) * (ht ? 1024 : 32), stg + i * 4096, ht ? EVICT_NORMAL : x[1] < 4096 ? POL(4) : POL(5));
        bulk_commit();
        bulk_wait_read();
        mbar_arrive(sb + B_SFREE + wg * 8);
        if ((int)x[3] >= 0) {
            bulk_wait_all(); fence_async();
            asm volatile("red.relaxed.gpu.global.add.u32 [%0], 1;" ::"l"(&g_cnt(x[3])) : "memory");
        }
    }
}

template <int N, int TA, int TB, bool FIRST>
__device__ __forceinline__ void issue_ktile(float* acc, const Cons& c) {
    mbar_wait(c.sb + B_FULL + c.p.stage * 8, c.p.phase);
    const uint32_t a = c.sb + c.p.stage * STAGE + c.wg * 8192, b = c.sb + c.p.stage * STAGE + 16384;
    const uint64_t da = mkdesc(a, TA ? 8192 : 16, 1024, 1), db = mkdesc(b, TB ? 8192 : 16, 1024, 1);
    wg_fence();
#pragma unroll
    for (int k = 0; k < 4; k++) {
        const uint64_t x = da + (TA ? 128 : 2) * k, y = db + (TB ? 128 : 2) * k;
        if (N == 256) { if (FIRST && k == 0) wgmma_ss256_first<TA, TB>(acc, x, y); else wgmma_ss256<TA, TB>(acc, x, y); }
        else { if (FIRST && k == 0) wgmma_ss128_first<TA, TB>(acc, x, y); else wgmma_ss128<TA, TB>(acc, x, y); }
    }
    wg_commit();
}
template <int N, bool FIRST>
__device__ __forceinline__ void issue_any(float* acc, const Cons& c, int type) {
    if (N == 256 && type == T_A1) issue_ktile<N, 0, 0, FIRST>(acc, c);
    else if (type == (N == 256 ? T_A2 : T_A2H)) issue_ktile<N, 1, 0, FIRST>(acc, c);
    else issue_ktile<N, 0, 1, FIRST>(acc, c);
}
template <int N, bool KVONLY = false>
__device__ __forceinline__ void mainloop(float* acc, const Params& P, Cons& c, Pend& d, int type) {
    const int nk = (type == T_OP || type == T_OPH) ? 64 : (type == T_A2 || type == T_A2H) ? 32 : 16;
    issue_any<N, true>(acc, c, type);
    drain<0, KVONLY>(P, c, d);
    uint32_t prev = c.p.stage;
    pipe_next(c.p);
    const int hold = c.wg ? nk - (int)((P.lag >> (4 * type)) & 7) : -1;
    for (int kt = 1; kt < nk; kt++) {
        if (kt == hold) bar_sync(8, 256);
        issue_any<N, false>(acc, c, type);
        wg_wait<1>();
        release(c, prev);
        if (kt == 2) drain<1, KVONLY>(P, c, d);
        prev = c.p.stage;
        pipe_next(c.p);
    }
    if (c.wg == 0 && ((P.lag >> (4 * type)) & 7)) bar_arrive(8, 256);
    d.kind = PEND_NONE;
    wg_wait<0>();
    pin<N / 2>(acc);
    release(c, prev);
}
__device__ __forceinline__ void pack_half(uint32_t* pk, const float* a) {
#pragma unroll
    for (int i = 0; i < 32; i++) pk[i] = pack2(a[2 * i], a[2 * i + 1]);
}

__device__ __forceinline__ void epi_kv(const float* acc, const Cons& c, Pend& d, int mb, int nb) {
    pack_half(d.pk, acc); pack_half(d.pk + 32, acc + 64);
    d.kind = PEND_KVO; d.row = (nb >> 4) * 2048 + mb * 256 + c.rank * 128 + c.wg * 64; d.col = (nb & 15) * 256; d.cnt = C_KV + mb;
}

__device__ __forceinline__ void epi_qa(const float* acc, Cons& c, Pend& d, int mb, int nb) {
    uint32_t q[64];
    pack_half(q, acc);
    pack_half(q + 32, acc + 64);
#pragma unroll
    for (int i = 0; i < 32; i++) d.pk[32 + i] = 0;
    const int g = c.lane >> 2, t = c.lane & 3;
    const bool sg = c.wq >= 2;
    const int i0 = (c.wq & 1) * 16 + g;
#pragma unroll 1
    for (int hh = 0; hh < 2; hh++) {
        uint32_t pa[5][4];
        {
            float S[32] = {}, Sm[8] = {};
            mbar_wait(c.sb + B_FULL + c.p.stage * 8, c.p.phase);
            const uint32_t st = c.sb + c.p.stage * STAGE;
            const uint64_t dk = mkdesc(st + c.wg * 8192, 16, 1024, 1), dm = mkdesc(st + 32768 + c.wg * 4096, 128, 2048, 0);
            pin<32>(q); pin<32>(S); pin<8>(Sm);
            wg_fence();
#pragma unroll
            for (int i = 0; i < 8; i++) wgmma_rs64<0>(S, q + i * 4, dk + (i >> 2) * 1024 + (i & 3) * 2, i != 0);
#pragma unroll
            for (int i = 0; i < 8; i++) wgmma_rs16<0>(Sm, q + i * 4, dm + i * 16, i != 0);
            wg_commit();
            wg_wait<0>();
            pin<32>(S); pin<8>(Sm);
            release(c, c.p.stage);
            pipe_next(c.p);
            const float scale = 0.08838834764831845f, l2e = 1.4426950408889634f;
            float x[2][10];
#pragma unroll
            for (int r = 0; r < 2; r++) {
#pragma unroll
                for (int j = 0; j < 4; j++)
#pragma unroll
                    for (int e = 0; e < 2; e++) {
                        const float v = sg ? S[16 + j * 4 + r * 2 + e] : S[j * 4 + r * 2 + e];
                        x[r][j * 2 + e] = (j * 8 + 2 * t + e > i0 + r * 8) ? -1e9f : v * scale;
                    }
                x[r][8] = (sg ? Sm[4 + r * 2] : Sm[r * 2]) * scale;
                x[r][9] = (sg ? Sm[5 + r * 2] : Sm[1 + r * 2]) * scale;
                float m = x[r][0];
#pragma unroll
                for (int i = 1; i < 10; i++) m = fmaxf(m, x[r][i]);
                m = fmaxf(m, __shfl_xor_sync(0xffffffffu, m, 1));
                m = fmaxf(m, __shfl_xor_sync(0xffffffffu, m, 2));
                float sum = 0.f;
#pragma unroll
                for (int i = 0; i < 10; i++) { x[r][i] = ex2((x[r][i] - m) * l2e); sum += x[r][i]; }
                sum += __shfl_xor_sync(0xffffffffu, sum, 1);
                sum += __shfl_xor_sync(0xffffffffu, sum, 2);
                const float inv = rcp(sum);
#pragma unroll
                for (int i = 0; i < 10; i++) x[r][i] *= inv;
            }
#pragma unroll
            for (int ks = 0; ks < 2; ks++)
#pragma unroll
                for (int i = 0; i < 4; i++) {
                    const uint32_t p = pack2(x[i & 1][ks * 4 + (i >> 1) * 2], x[i & 1][ks * 4 + (i >> 1) * 2 + 1]);
                    pa[ks][i] = sg ? 0u : p;
                    pa[2 + ks][i] = sg ? p : 0u;
                }
#pragma unroll
            for (int r = 0; r < 2; r++) {
                const uint32_t p = pack2(x[r][8], x[r][9]);
                pa[4][r] = sg ? 0u : p;
                pa[4][2 + r] = sg ? p : 0u;
            }
        }
        float O[64] = {};
        mbar_wait(c.sb + B_FULL + c.p.stage * 8, c.p.phase);
        const uint32_t st = c.sb + c.p.stage * STAGE;
        const uint64_t dv = mkdesc(st + c.wg * 8192, 16384, 1024, 1), dm = mkdesc(st + 32768 + c.wg * 4096, 2048, 128, 0);
        pin<20>(&pa[0][0]); pin<64>(O);
        wg_fence();
#pragma unroll
        for (int ks = 0; ks < 4; ks++) wgmma_rs128<1>(O, pa[ks], dv + ks * 128, ks != 0);
        wgmma_rs128<0>(O, pa[4], dm, 1);
        wg_commit();
        wg_wait<0>();
        pin<64>(O);
        release(c, c.p.stage);
        pipe_next(c.p);
#pragma unroll
        for (int i = 0; i < 32; i++) { q[i] = q[32 + i]; q[32 + i] = d.pk[32 + i]; }
        pack_half(d.pk + 32, O);
    }
#pragma unroll
    for (int i = 0; i < 32; i++) d.pk[i] = q[32 + i];
    d.kind = PEND_KVO; d.row = 4096 + mb * 256 + c.rank * 128 + c.wg * 64; d.col = nb * 256; d.cnt = C_O + mb * 4 + (nb >> 2);
}

__device__ __forceinline__ void epi_op(const float* acc, const Cons& c, Pend& d, int mb, int nb) {
    pack_half(d.pk, acc); pack_half(d.pk + 32, acc + 64);
    d.kind = PEND_OUT; d.row = mb * 256 + c.rank * 128 + c.wg * 64; d.col = 1024 + nb * 256;
}

__device__ __forceinline__ void epi_oph(const float* acc, const Cons& c, Pend& d, int mb, int nb) {
    pack_half(d.pk, acc);
    d.kind = PEND_OUTH; d.row = mb * 256 + c.rank * 128 + c.wg * 64; d.col = 1024 + nb * 128;
}

template <int HF>
__device__ __forceinline__ void epi_a2_half(const float* acc, const Params& P, Cons& c, int mb, int col0) {
    const int g = c.lane >> 2, t = c.lane & 3;
    const int row = mb * 256 + (g >> 1) * 64 + (c.rank * 16 + c.wg * 8 + c.wq * 2) * 2 + (g & 1);
    float* o = P.out + (size_t)row * 2048 + col0 + HF * 128 + t * 2;
    mbar_wait(c.sb + B_FULL + c.p.stage * 8, c.p.phase);
    const uint32_t st = c.sb + c.p.stage * STAGE, da = st + 32768 + (c.lane >> 3) * 16;
    const uint32_t xa = st + (c.wg * 64 + c.wq * 16 + (c.lane & 15)) * 128 + (((c.lane >> 4) ^ (c.lane & 7)) << 4);
#pragma unroll
    for (int j4 = 0; j4 < 4; j4++) {
        uint32_t x[8], dv[4];
        ldsm4(dv, da + j4 * 64);
        ldsm4(x, (xa ^ ((j4 & 1) << 6)) + (j4 >> 1) * 16384);
        ldsm4(x + 4, (xa ^ ((j4 & 1) << 6) ^ 32) + (j4 >> 1) * 16384);
#pragma unroll
        for (int i = 0; i < 4; i++) {
            const int j = j4 * 4 + i;
            const float* a = acc + HF * 64 + j * 4;
            const uint32_t u0 = hmul2(x[2 * i], dv[i]), u1 = hmul2(x[2 * i + 1], dv[i]);
            st_stream2(o + j * 8, a[0] + bf_lo(u0), a[1] + bf_hi(u0));
            st_stream2(o + 2 * 2048 + j * 8, a[2] + bf_lo(u1), a[3] + bf_hi(u1));
        }
    }
    __syncwarp();
    release(c, c.p.stage);
    pipe_next(c.p);
}

#define TSTAMP(i)
__device__ __forceinline__ float2 cmul(float2 a, float2 b) { return make_float2(fmaf(a.x, b.x, -a.y * b.y), fmaf(a.x, b.y, a.y * b.x)); }
__device__ __forceinline__ float2 cfma(float2 a, float2 b, float2 u) { return make_float2(fmaf(a.x, b.x, fmaf(-a.y, b.y, u.x)), fmaf(a.x, b.y, fmaf(a.y, b.x, u.y))); }
__device__ __forceinline__ float4 ssm_coef(float lre, float lim, float logdt) {
    const float dt = __bfloat162float(__float2bfloat16(expf(logdt)));
    const float ea = expf(dt * lre);
    float sn, cn;
    sincosf(dt * lim, &sn, &cn);
    const float br = ea * cn, bi = ea * sn, nr = br - 1.f;
    float cr, ci;
    if (fabsf(lre) >= fabsf(lim)) { const float r = lim / lre, dn = lre + lim * r; cr = (nr + bi * r) / dn; ci = (bi - nr * r) / dn; }
    else { const float r = lre / lim, dn = lre * r + lim; cr = (nr * r + bi) / dn; ci = (bi * r - nr) / dn; }
    return make_float4(br, bi, cr, ci);
}
__device__ __forceinline__ void epi_a1(const float* acc, const Params& P, const Cons& c, Pend& d, int mb, int nb, uint32_t atag) {
    const int t = c.lane & 3;
    const int p = nb * 128 + c.rank * 64 + c.wg * 32 + c.wq * 8 + (c.lane >> 2);
    uint32_t cw[4];
    lds128(cw, c.sb + S_COEF + (p & 63) * 16);
    const float4 cf = make_float4(__uint_as_float(cw[0]), __uint_as_float(cw[1]), __uint_as_float(cw[2]), __uint_as_float(cw[3]));
    TSTAMP(1)
    const float2 lam = make_float2(cf.x, P.swap_ri ? -cf.y : cf.y);
    const float a0 = P.swap_ri ? -2.f * cf.w : 2.f * cf.z, a1 = P.swap_ri ? 2.f * cf.z : -2.f * cf.w;
    const float b0 = P.swap_ri ? -2.f * cf.z : -2.f * cf.w, b1 = P.swap_ri ? -2.f * cf.w : -2.f * cf.z;
    float2 h = make_float2(0.f, 0.f);
#pragma unroll
    for (int round = 0; round < 2; round++) {
#pragma unroll
        for (int j = 0; j < 32; j++) {
            h = cfma(lam, h, make_float2(acc[j * 4], acc[j * 4 + 2]));
            const float r0 = fmaf(a0, h.x, a1 * h.y), m0 = fmaf(b0, h.x, b1 * h.y);
            h = cfma(lam, h, make_float2(acc[j * 4 + 1], acc[j * 4 + 3]));
            d.pk[j * 2] = pack2(r0, fmaf(a0, h.x, a1 * h.y));
            d.pk[j * 2 + 1] = pack2(m0, fmaf(b0, h.x, b1 * h.y));
        }
        if (round) break;
        float2 l64 = lam;
#pragma unroll
        for (int i = 0; i < 6; i++) l64 = cmul(l64, l64);
        const float2 l128 = cmul(l64, l64), l256 = cmul(l128, l128);
        float2 o = make_float2(__shfl_up_sync(0xffffffffu, h.x, 1), __shfl_up_sync(0xffffffffu, h.y, 1));
        if (t >= 1) h = cfma(l64, o, h);
        o = make_float2(__shfl_up_sync(0xffffffffu, h.x, 2), __shfl_up_sync(0xffffffffu, h.y, 2));
        if (t >= 2) h = cfma(l128, o, h);
        TSTAMP(2)
        if (t == 3) st_relaxed2(&g_agg[mb * 1024 + p], (__float_as_uint(h.x) & ~1u) | atag, __float_as_uint(h.y));
        h = make_float2(__shfl_up_sync(0xffffffffu, h.x, 1), __shfl_up_sync(0xffffffffu, h.y, 1));
        if (t == 0) h = make_float2(0.f, 0.f);
        uint32_t ax[7], ay[7];
        int n = 0;
        while (true) {
            uint32_t bad = 0;
#pragma unroll
            for (int j = 0; j < 7; j++) { ax[j] = atag; ay[j] = 0; ld_relaxed2_if(ax[j], ay[j], &g_agg[j * 1024 + p], j < mb); }
#pragma unroll
            for (int j = 0; j < 7; j++) bad |= ax[j] ^ atag;
            if (tags_ok(bad)) break;
            __nanosleep(400);
            if (++n > SPIN_LIMIT) spin_fault();
        }
        float2 carry = make_float2(0.f, 0.f);
#pragma unroll
        for (int j = 0; j < 7; j++) if (j < mb) carry = cfma(l256, carry, make_float2(__uint_as_float(ax[j]), __uint_as_float(ay[j])));
        float2 w = (t & 1) ? l64 : make_float2(1.f, 0.f);
        if (t & 2) w = cmul(w, l128);
        h = cfma(w, carry, h);
        TSTAMP(3)
    }
    TSTAMP(4)
    d.kind = PEND_HT; d.row = nb * 128 + c.rank * 64 + c.wg * 32; d.col = mb * 256; d.cnt = C_HT + mb * 2 + (nb >> 2);
}

__device__ __forceinline__ uint32_t acquire_stage(uint32_t sb, Pipe& p, uint32_t bytes) {
    mbar_wait(sb + B_EMPTY + p.stage * 8, p.phase ^ 1);
    mbar_expect(sb + B_FULL + p.stage * 8, bytes);
    return p.stage;
}
#define EFS 40
#define AHEAD 1
__device__ __forceinline__ void watcher(const Params& P, const uint32_t sb, const int rank, const int lane) {
    const uint32_t epoch = ld_relaxed1(&g_cnt(C_EPOCH)), e1 = epoch + 1;
    sts32(sb + S_EPOCH, epoch);
    __syncwarp();
    if (lane == 0 && atomicInc(&g_cnt(C_DONE), (DBGF(32) ? 95 : NPAIR * 2 - 1) + (epoch & P.zero)) == (DBGF(32) ? 95 : NPAIR * 2 - 1)) atomicAdd(&g_cnt(C_EPOCH), 1);
    if (gridDim.x != 96) {
        uint32_t v;
        asm("mov.u32 %0, %%smid;" : "=r"(v));
        if (lane == 0 && rank == 0) st_relaxed1(g_hint + 6272 + (blockIdx.x >> 1), e1 << 8 | v >> 1);
        for (int k = 0;; k++) {
            __nanosleep(1000);
            v = ld_relaxed1(g_hint + 6272 + min(lane, 17));
            if (__all_sync(0xffffffffu, (v ^ e1 << 8) < 256)) break;
            if (k > SPIN_LIMIT) spin_fault();
        }
        const uint32_t key = ((v & 255) >= 62 ? 0 : tpc_gpc(v & 255)) * 32 + lane;
        sts32(sb + S_TAIL, 48 + __popc(__ballot_sync(0xffffffffu, key < __shfl_sync(0xffffffffu, key, blockIdx.x >> 1)) & 0x3ffff));
        __syncwarp();
    }
    uint32_t met = 1;
    if (lane == 0) asm volatile("st.release.cta.shared.u32 [%0], 1;" ::"r"(sb + S_DEP) : "memory");
    const int pair = lds32(sb + S_TAIL), first = ITEM_OFF(pair) + (pair < NCHAIN ? NPRE + 1 : 1);
#pragma unroll 1
    for (int it = first; it < ITEM_OFF(pair + 1); it++) {
        const int item = ITEM(it), type = item >> 8, mb = (item >> 5) & 7, nb = item & 31;
        const int n = (0x24021420 >> (type * 4)) & 7;
        for (int k = 0; it > first && (int)lds32(sb + S_CUR) < it - AHEAD; k++) { __nanosleep(200); if (k > SPIN_LIMIT) spin_fault(); }
#pragma unroll 1
        for (int i = 0; i < n; i++) {
            int idx = n == 4 ? C_O + mb * 4 + i : C_HT + mb * 2 + i;
            uint32_t target = e1 * 16;
            if (type == T_A1) { idx = C_COEF; target = e1 * 4; }
            if (type == T_QA) {
                idx = i ? C_FLAG + (lane & 1) * 32 + nb * 2 + ((lane >> 1) & 1) : C_KV + mb;
                target = i ? epoch * 64 + mb * 8 + rank * 4 + 4 : e1 * 128;
            }
            if (lane < 4) { wait_count(&g_cnt(idx), target); fence_async(); }
            __syncwarp();
            if (lane == 0) asm volatile("st.release.cta.shared.u32 [%0], %1;" ::"r"(sb + S_DEP), "r"(++met) : "memory");
        }
    }
}
__device__ __forceinline__ bool dep_met(uint32_t sb, uint32_t n) { uint32_t v; asm volatile("ld.acquire.cta.shared.u32 %0, [%1];" : "=r"(v) : "r"(sb + S_DEP) : "memory"); return v >= n; }
__device__ __forceinline__ void dep_wait(uint32_t sb, uint32_t n) { for (int k = 0; !dep_met(sb, n); k++) { __nanosleep(32); if (k > SPIN_LIMIT * 8) spin_fault(); } }
__device__ __forceinline__ void producer(const Params& P, const uint32_t sb, int pair, const int rank) {
    Pipe p = {0, 0};
    uint32_t dep = 1;
    for (int it = ITEM_OFF(pair); it < ITEM_OFF(pair + 1); it++) {
        const int item = ITEM(it), type = item >> 8, mb = (item >> 5) & 7, nb = item & 31;
        if (type == T_CHAIN) {
            sts32(sb + S_CUR, 0);
            const uint32_t epoch = ld_relaxed1(&g_cnt(C_EPOCH)), e1 = epoch + 1;
            const int role = pair >> 4, h = (pair & 15) * 2 + rank;
#pragma unroll 1
            for (int i = 0, q = 0; i < 8; i++) {
                const int n = (0x13003333 >> (i * 4)) & 3;
                const uint32_t st = acquire_stage(sb, p, n * 16384);
                SSTAMP(1, i == 6) SSTAMP(3, i == 7)
#pragma unroll 1
                for (int k = 0; k < 2 * n; k++, q++)
                    tma3d(sb + st * STAGE + k * 8192, &P.tm[M_CQ + role], h * 128 + (fill_unit(q >> 1) & 1) * 64, word_col((fill_unit(q >> 1) & 14) + (q & 1)) & 8, word_col((fill_unit(q >> 1) & 14) + (q & 1)) >> 4, sb + B_FULL + st * 8, role ? EVICT_NORMAL : POL(3));
                pipe_next(p);
                if (i == P.pf2) {
#pragma unroll 1
                    for (int k = 0; k < (role ? 12 : 8); k++)
                        asm volatile("cp.async.bulk.prefetch.tensor.4d.L2.global [%0, {%1, 0, 0, %2}];" ::"l"(&P.tm[M_CO + (k & 1)]), "r"((role == 0 ? 0 : role == 1 ? 256 : 640) + (k >> 1) * 64), "r"(h * 8) : "memory");
                }
            }
            if (role == 0 && !DBGF(1)) { wait_count(&g_cnt(C_KV), e1 * 128); fence_async(); }
            mbar_wait(sb + B_EMPTY + 16, 1); mbar_wait(sb + B_EMPTY + 24, 1);
            mbar_expect(sb + B_WO, role ? 98304 : 65536);
            if (role == 0) { mbar_expect(sb + B_KVFULL, 16384); mbar_expect(sb + B_KVFULL + 8, 16384); }
#pragma unroll 1
            for (int k = role ? 0 : -4; k < 12; k++) {
                const bool kv = role == 0 && (k & 8);
                const int sg = k > 0;
                tma4d(kv ? sb + S_KV + sg * 16384 + (k & 3) * 4096 : sb + S_W2 + k * 8192, &P.tm[kv ? M_KV4 : M_CO + (k & 1)],
                      kv ? h * 128 + (k & 1) * 64 : (role == 0 ? 0 : role == 1 ? 256 : 640) + (k >> 1) * 64, kv ? (k & 2) * 1024 + sg * 32 : h * 8, sb + (kv ? B_KVFULL + sg * 8 : B_WO), POL(2));
            }
            SSTAMP(5, true)
            if (pair < 16) {
#pragma unroll 1
                for (int s = 2; s < 63; s++) {
                    mbar_wait(sb + B_KVGO + (s & 1) * 8, ((s >> 1) + 1) & 1);
                    wait_time(gtime() + P.dk, sb);
                    SSTAMP(6, s == 2)
                    const uint32_t bar = sb + B_KVFULL + (s & 1) * 8, dst = sb + S_KV + (s & 1) * 16384;
                    if (DBGF(2)) { mbar_arrive(bar); continue; }
                    mbar_expect(bar, 16384);
#pragma unroll 1
                    for (int i = 0; i < 4; i++) tma2d(dst + i * 4096, &P.tm[M_KVO], (pair * 2 + rank) * 128 + (i & 1) * 64, (i >> 1) * 2048 + (DBGF(32 | 512) ? s & 7 : s) * 32, bar, s < EFS ? POL(1) : EVICT_NORMAL);
                    if ((s & 7) == 7 && !DBGF(1)) { wait_count(&g_cnt(C_KV + 1 + (s >> 3)), e1 * 128); fence_async(); }
                }
            } else {
                uint32_t* flag = &g_cnt(C_FLAG + pair * 2 + rank - 32);
                const int x = pair * 2 + rank - 32;
#pragma unroll 1
                for (int s = 0; s < 64; s++) {
                    mbar_wait(sb + B_PERS, s & 1);
                    if (s < 63) wait_time(gtime() + P.dp, sb);
                    if (!DBGF(4)) bulk_s2g((role == 1 ? g_km : g_vmt) + (s * 32 + h) * 512, sb + S_QX, 2048);
                    if (s < 57) {
                        uint8_t* m = P.gm + ((s + 6) & 7) * M_SLOT + (x >> 1) * 1024 + (x & 1) * 256;
                        bulk_s2g(m, sb + S_SX, 256); bulk_s2g(m + 512, sb + S_SX, 128);
                        bulk_s2g(g_f + ((s + 6) & 7) * F_SLOT + x * 768, sb + S_SX + 256, 768);
                    }
                    bulk_commit();
                    bulk_wait_read();
                    mbar_arrive(sb + B_KVGO);
                    bulk_wait_all();
                    fence_async();
                    if ((s & 3) == 3) st_relaxed1(flag, epoch * 64 + s + 1);
                }
            }
            mbar_wait(sb + B_RESUME, 0);
            pair = lds32(sb + S_TAIL);
            it = ITEM_OFF(pair) + NPRE;
            continue;
        }
        if (it == ITEM_OFF(pair) && pair >= NCHAIN) it = -1; else sts32(sb + S_CUR, it);
        const int m0 = mb * 256 + rank * 128;
        if (type <= T_OP) {
            const CUtensorMap* ma = &P.tm[type == T_OP ? M_OA : M_BX];
            const CUtensorMap* mw = &P.tm[type == T_OP ? M_WO : type == T_QA ? M_WQ : nb < 16 ? M_WK : M_WV];
            const int nk = type == T_OP ? 64 : 16, nc = (nb & 15) * 4 + rank * 2, ma0 = type == T_OP ? 4096 + m0 : m0;
#pragma unroll 1
            for (int kt = 0; kt < nk; kt++) {
                if (type == T_OP && (kt & 15) == 0) dep_wait(sb, ++dep);
                if (DBGF(256) && pair >= NCHAIN) { acquire_stage(sb, p, 0); pipe_next(p); continue; }
                const uint32_t st = acquire_stage(sb, p, STAGE), bar = sb + B_FULL + st * 8;
                tma2d(sb + st * STAGE, ma, kt * 64, ma0, bar, type == T_OP ? POL(6) : type == T_QA ? POL(12) : POL(13));
                tma3d_mc(sb + st * STAGE + 16384 + rank * 16384, mw, 0, kt * 64, nc, bar, type == T_KV && mb == 7 ? POL(9) : EVICT_NORMAL);
                pipe_next(p);
            }
            if (type == T_QA) {
                dep += 2;
                dep_wait(sb, dep);
#pragma unroll 1
                for (int e = 0; e < 4; e++) {
                    const uint32_t st = acquire_stage(sb, p, 40960), bar = sb + B_FULL + st * 8, dst = sb + st * STAGE;
                    tma2d(dst, &P.tm[M_OA], nb * 256 + (e >> 1) * 128, (e & 1) * 2048 + m0, bar, POL(0));
                    tma2d(dst + 16384, &P.tm[M_OA], nb * 256 + (e >> 1) * 128 + 64, (e & 1) * 2048 + m0, bar, POL(0));
                    const uint32_t* src = ((e & 1) ? g_vmt : g_km) + ((mb * 8 + rank * 4) * 32 + nb * 2 + (e >> 1)) * 512;
#pragma unroll 1
                    for (int i = 0; i < 4; i++) bulk_g2s(dst + 32768 + i * 2048, src + i * 32 * 512, 2048, bar);
                    pipe_next(p);
                }
            }
        } else if (type == T_OPH) {
#pragma unroll 1
            for (int kt = 0; kt < 64; kt++) {
                if ((kt & 15) == 0) dep_wait(sb, ++dep);
                const uint32_t st = acquire_stage(sb, p, 32768), bar = sb + B_FULL + st * 8;
                tma2d(sb + st * STAGE, &P.tm[M_OA], kt * 64, 4096 + m0, bar, POL(6));
                tma2d_mc(sb + st * STAGE + 16384 + rank * 8192, &P.tm[M_WOH], nb * 128 + rank * 64, kt * 64, bar, EVICT_NORMAL);
                pipe_next(p);
            }
        } else if (type == T_A1) {
#pragma unroll 1
            for (int kt = 0; kt < 16; kt++) {
                if (kt == 15) dep_wait(sb, ++dep);
                const uint32_t st = acquire_stage(sb, p, kt == 15 ? STAGE + 1024 : STAGE), bar = sb + B_FULL + st * 8;
                if (kt == 15) bulk_g2s(sb + S_COEF, g_coef + nb * 128 + rank * 64, 1024, bar);
                tma4d(sb + st * STAGE, &P.tm[M_AB], kt * 64, nb * 16 + rank * 8, bar, POL(10));
                tma4d_mc(sb + st * STAGE + 16384 + rank * 16384, &P.tm[M_AX], kt * 64, mb * 128 + rank * 16, bar, POL(10));
                pipe_next(p);
            }
        } else {
            const int hw = type == T_A2H ? 64 : 128;
            const CUtensorMap* mc = &P.tm[type == T_A2H ? M_CREH : M_CRE];
#pragma unroll 1
            for (int kt = 0; kt < 32; kt++) {
                if ((kt & 15) == 0) dep_wait(sb, ++dep);
                const uint32_t st = acquire_stage(sb, p, 16384 + hw * 256), bar = sb + B_FULL + st * 8;
                tma3d(sb + st * STAGE, &P.tm[M_HT], 0, (kt & 1) * 1024 + (kt >> 1) * 64, mb * 4 + rank * 2, bar, POL(7));
                tma2d_mc(sb + st * STAGE + 16384 + rank * hw * 128, mc + (kt & 1), (kt >> 1) * 64, (nb * 2 + rank) * hw, bar, POL(11));
                pipe_next(p);
            }
#pragma unroll 1
            for (int col = nb * 2 * hw; col < (nb + 1) * 2 * hw; col += 128) {
                const uint32_t st = acquire_stage(sb, p, 32768 + 256), bar = sb + B_FULL + st * 8;
                tma4d(sb + st * STAGE, &P.tm[M_AX], col, mb * 128 + rank * 16, bar, POL(8));
                tma4d(sb + st * STAGE + 16384, &P.tm[M_AX], col + 64, mb * 128 + rank * 16, bar, POL(8));
                bulk_g2s(sb + st * STAGE + 32768, P.Dskip + col, 256, bar);
                pipe_next(p);
            }
        }
        if (it < 0) { dep_wait(sb, 1); pair = lds32(sb + S_TAIL); it = ITEM_OFF(pair); }
    }
}

__device__ __forceinline__ uint32_t fresh_tid() { uint32_t t; asm volatile("mov.u32 %0, %%tid.x;" : "=r"(t)); return t; }
__device__ __forceinline__ uint32_t fresh_ctaid() { uint32_t t; asm volatile("mov.u32 %0, %%ctaid.x;" : "=r"(t)); return logical_cta(t); }
__device__ __forceinline__ void reset_state(Cons& c, Pend& d, uint32_t sb, bool resumed) {
    const uint32_t t = fresh_tid(), b = fresh_ctaid();
    const int w = __shfl_sync(0xffffffffu, t >> 5, 0);
    c.sb = sb; c.wg = w >> 2; c.wq = w & 3; c.lane = t & 31;
    c.rank = __shfl_sync(0xffffffffu, b & 1, 0); c.pair = __shfl_sync(0xffffffffu, resumed && b < NCHAIN * 2 ? lds32(sb + S_TAIL) : b >> 1, 0);
    c.rel = mapa(sb + B_EMPTY, cluster_rank() ^ (c.lane & 1));
    c.p.stage = 0; c.p.phase = 0;
    c.nst = resumed && c.pair < NCHAIN ? 2 * NPRE : 0;
    d = Pend{};
}
#define PROF_ITEM(i)
#define PROF_MAIN(i)

__global__ void __launch_bounds__(384, 1) fused_kernel(const __grid_constant__ Params P) {
    extern __shared__ __align__(1024) uint8_t smem[];
    const uint32_t sb = smem_u32(smem);
    asm volatile("griddepcontrol.launch_dependents;");
    const int tid = threadIdx.x, lane = tid & 31;
    const int warp = __shfl_sync(0xffffffffu, tid >> 5, 0);
    const int pair = __shfl_sync(0xffffffffu, logical_cta(blockIdx.x) >> 1, 0), rank = __shfl_sync(0xffffffffu, blockIdx.x & 1, 0);
    if (tid == 0) {
        if (sb & 1023) spin_fault();
        sts32(sb + S_DEP, 0); sts32(sb + S_CUR, 0); sts32(sb + S_TAIL, pair); sts32(sb + S_CTA, pair * 2 + rank);
        for (int i = 0; i < NSTAGE; i++) { mbar_init(sb + B_FULL + i * 8, 1); mbar_init(sb + B_EMPTY + i * 8, 16); }
        mbar_init(sb + B_RESUME, 2);
        mbar_init(sb + B_KVFULL, 1); mbar_init(sb + B_KVFULL + 8, 1);
        mbar_init(sb + B_GO, 1); mbar_init(sb + B_KVGO, 1); mbar_init(sb + B_KVGO + 8, 1); mbar_init(sb + B_K, 1); mbar_init(sb + B_V, 1); mbar_init(sb + B_PERS, pair < 16 ? 1 : 8); mbar_init(sb + B_INIT, 3);
        mbar_init(sb + B_WO, 1);
        for (int i = 0; i < 2; i++) { mbar_init(sb + B_SFULL + i * 8, 4); mbar_init(sb + B_SFREE + i * 8, 1); }
        mbar_init(sb + B_RELA, 1); mbar_init(sb + B_RELB, 1);
        asm volatile("fence.mbarrier_init.release.cluster;" ::: "memory");
        if (pair < 16) { mbar_expect(sb + B_K, KE ? 1024 : 2048); mbar_expect(sb + B_PERS, 1024); }
        mbar_expect(sb + B_V, 2048);
    }
    cluster_sync();
    if (warp >= 8) {
        asm volatile("setmaxnreg.dec.sync.aligned.u32 24;");
        if (warp == 10 && lane < M_COUNT) map_prefetch(&P.tm[lane]);
        if (warp == 11 && lane == 0 && pair < 16) {
            const uint32_t t0 = gtime();
#pragma unroll 1
            for (int i = 0; i < 32; i++) {
                wait_time(t0 + P.pf0 + i * P.pf1, sb);
                asm volatile("cp.async.bulk.prefetch.tensor.3d.L2.global [%0, {%1, %2, %3}];" ::"l"(&P.tm[M_CQ]), "r"((pair * 2 + rank) * 128 + (i & 1) * 64), "r"((i & 2) * 4), "r"((i >> 2) * 8) : "memory");
            }
        }
        if (warp == 9 && pair < NCHAIN) pacer(P, sb, lane);
        if (warp == 9) watcher(P, sb, rank, lane);
        if (warp >= 10 && lane == 0) store_warp(P, sb, warp - 10);
        if (warp == 8) {
            if (lane == 0) producer(P, sb, lds32(sb + S_CTA) >> 1, rank);
            __syncwarp();
            asm volatile("barrier.cluster.arrive.relaxed.aligned;\nbarrier.cluster.wait.aligned;" ::: "memory");
        }
    } else {
        asm volatile("setmaxnreg.inc.sync.aligned.u32 240;");
        Cons c;
        Pend d;
        if (pair < NCHAIN) {
            mem0_max(P, sb, tid);
            reset_state(c, d, sb, false);
#pragma unroll 1
            for (int i = 0; i < NPRE; i++) {
                PROF_ITEM(i)
                const int item = ITEM(ITEM_OFF(pair) + i);
                float acc[128];
                mainloop<256, true>(acc, P, c, d, T_KV);
                epi_kv(acc, c, d, (item >> 5) & 7, item & 31);
            }
            ISTAMP(4)
            drain<0, true>(P, c, d);
            drain<1, true>(P, c, d);
            PROF_ITEM(NPRE)
            uint32_t wr[NR][4];
            load_weights(wr, sb, warp, lane, [&]() { staging_wait(c); });
            const int h = (pair & 15) * 2 + rank;
            if (pair < 16) chain_role<0>(P, wr, sb, h, warp, lane);
            else if (pair < 32) chain_role<1>(P, wr, sb, h, warp, lane);
            else chain_role<2>(P, wr, sb, h, warp, lane);
            fence_async_smem();
            bar_sync(1, 256);
            const uint32_t t2 = fresh_tid();
            if (t2 < 2) mbar_arrive_cluster(mapa(sb + B_RESUME, cluster_rank() ^ t2));
        } else if (pair >= NPAIR - 2) {
            const int ch = (pair - (NPAIR - 2)) * 512 + rank * 256 + tid;
            g_coef[ch] = ssm_coef(__bfloat162float(P.Lre[ch]), __bfloat162float(P.Lim[ch]), __bfloat162float(P.logdt[ch]));
            bar_sync(1, 256);
            if (tid == 0) red_release(&g_cnt(C_COEF));
        }
        reset_state(c, d, sb, true);
        for (int it = ITEM_OFF(c.pair) + (c.pair < NCHAIN ? NPRE + 1 : 0);; it++) {
            const bool last = it == ITEM_OFF(c.pair + 1);
            if (d.kind != PEND_NONE && (last || !bar_and(5 + c.wg, mbar_test(sb + B_FULL + c.p.stage * 8, c.p.phase)))) drain_all(P, c, d);
            if (last) break;
            const int item = ITEM(it), type = item >> 8, mb = (item >> 5) & 7, nb = item & 31;
            PROF_ITEM(it - ITEM_OFF(c.pair))
            if (type >= T_OPH) {
                float acc[64];
                mainloop<128>(acc, P, c, d, type);
                PROF_MAIN(it - ITEM_OFF(c.pair))
                if (type == T_OPH) epi_oph(acc, c, d, mb, nb);
                else epi_a2_half<0>(acc, P, c, mb, nb * 128);
            } else {
                float acc[128];
                mainloop<256>(acc, P, c, d, type);
                PROF_MAIN(it - ITEM_OFF(c.pair))
                if (type == T_KV) epi_kv(acc, c, d, mb, nb);
                else if (type == T_QA) epi_qa(acc, c, d, mb, nb);
                else if (type == T_OP) epi_op(acc, c, d, mb, nb);
                else if (type == T_A1) epi_a1(acc, P, c, d, mb, nb, (lds32(sb + S_EPOCH) + 1) & 1);
                else { epi_a2_half<0>(acc, P, c, mb, nb * 256); epi_a2_half<1>(acc, P, c, mb, nb * 256); }
            }
            if (it == ITEM_OFF(c.pair)) { dep_wait(sb, 1); c.pair = __shfl_sync(0xffffffffu, lds32(sb + S_TAIL), 0); it = ITEM_OFF(c.pair); }
        }
        staging_wait(c);
        staging_post(c, PEND_NONE, 0, 0, 0);
        asm volatile("barrier.cluster.arrive.relaxed.aligned;\nbarrier.cluster.wait.aligned;" ::: "memory");
    }
}

typedef CUresult (*EncodeFn)(CUtensorMap*, CUtensorMapDataType, cuuint32_t, void*, const cuuint64_t*, const cuuint64_t*, const cuuint32_t*, const cuuint32_t*,
                             CUtensorMapInterleave, CUtensorMapSwizzle, CUtensorMapL2promotion, CUtensorMapFloatOOBfill);
void encode(EncodeFn fn, CUtensorMap* m, const void* base, int rank, const uint64_t* dims, const uint64_t* strides, const uint32_t* box, CUtensorMapSwizzle swz = CU_TENSOR_MAP_SWIZZLE_128B) {
    cuuint64_t d[5], s[5]; cuuint32_t b[5], e[5];
    for (int i = 0; i < rank; i++) { d[i] = dims[i]; b[i] = box[i]; e[i] = 1; if (i) s[i - 1] = strides[i - 1]; }
    fn(m, CU_TENSOR_MAP_DATA_TYPE_BFLOAT16, rank, (void*)base, d, s, b, e, CU_TENSOR_MAP_INTERLEAVE_NONE, swz,
       CU_TENSOR_MAP_L2_PROMOTION_L2_256B, CU_TENSOR_MAP_FLOAT_OOB_FILL_NONE);
}
void map_kmajor(EncodeFn fn, CUtensorMap* m, const void* base, uint64_t rows, uint64_t cols, uint32_t box_rows) {
    const uint64_t d[2] = {cols, rows}, s[1] = {cols * 2}; const uint32_t b[2] = {64, box_rows};
    encode(fn, m, base, 2, d, s, b);
}
void map_mnmajor(EncodeFn fn, CUtensorMap* m, const void* base, uint64_t krows, uint64_t cols) {
    const uint64_t d[3] = {64, krows, cols / 64}, s[2] = {cols * 2, 128}; const uint32_t b[3] = {64, 64, 2};
    encode(fn, m, base, 3, d, s, b);
}

}

extern "C" void kernel_launch(void* const* d_in, const int* in_sizes, int n_in, void* d_out, int out_size) {
    static Params P;
    static EncodeFn fn = nullptr;
    if (!fn) {
        cudaDriverEntryPointQueryResult q;
        cudaGetDriverEntryPoint("cuTensorMapEncodeTiled", (void**)&fn, cudaEnableDefault, &q);
        cudaFuncSetAttribute(fused_kernel, cudaFuncAttributeMaxDynamicSharedMemorySize, S_TOTAL);
    }
    const bf16* in[15];
    for (int i = 0; i < 15; i++) in[i] = (const bf16*)d_in[i];
    void *kvo, *ht, *gm;
    cudaGetSymbolAddress(&gm, g_m);
    P.gm = (uint8_t*)(((uintptr_t)gm + 32767) & ~(uintptr_t)32767);
    cudaGetSymbolAddress(&kvo, g_kvo);
    cudaGetSymbolAddress(&ht, g_ht);
    map_kmajor(fn, &P.tm[M_BX], in[9], 2048, 1024, 128);
    map_mnmajor(fn, &P.tm[M_WQ], in[11], 1024, 4096);
    map_mnmajor(fn, &P.tm[M_WK], in[12], 1024, 4096);
    map_mnmajor(fn, &P.tm[M_WV], in[13], 1024, 4096);
    map_mnmajor(fn, &P.tm[M_WO], in[14], 4096, 1024);
    map_kmajor(fn, &P.tm[M_OA], kvo, 3 * 2048, 4096, 128);
    P.swap_ri = in[4] < in[3];
    {
        const bf16* lo = P.swap_ri ? in[4] : in[3];
        const uint64_t diff = (uint64_t)((const char*)(P.swap_ri ? in[3] : in[4]) - (const char*)lo);
        const uint64_t d[4] = {1024, 8, 2, 128}, s[3] = {2048, diff, 16384}; const uint32_t b[4] = {64, 8, 2, 8};
        encode(fn, &P.tm[M_AB], lo, 4, d, s, b);
    }
    {
        const uint64_t d[4] = {1024, 2, 4, 1024}, s[3] = {2048, 64 * 2048, 4096}; const uint32_t b[4] = {64, 2, 4, 16};
        encode(fn, &P.tm[M_AX], in[0], 4, d, s, b);
    }
    map_mnmajor(fn, &P.tm[M_HT], ht, 2048, 2048);
    map_kmajor(fn, &P.tm[M_CRE], in[5], 1024, 1024, 128);
    map_kmajor(fn, &P.tm[M_CIM], in[6], 1024, 1024, 128);
    map_kmajor(fn, &P.tm[M_KVO], kvo, 3 * 2048, 4096, 32);
    map_kmajor(fn, &P.tm[M_HTS], ht, 2048, 2048, 32);
    map_kmajor(fn, &P.tm[M_WOH], in[14], 4096, 1024, 64);
    map_kmajor(fn, &P.tm[M_CREH], in[5], 1024, 1024, 64);
    map_kmajor(fn, &P.tm[M_CIMH], in[6], 1024, 1024, 64);
    for (int i = 0; i < 3; i++) {
        const uint64_t d[3] = {4096, 16, 64}, s[2] = {8192, 16 * 8192}; const uint32_t b[3] = {64, 8, 8};
        encode(fn, &P.tm[M_CQ + i], in[11 + i], 3, d, s, b);
    }
    {
        const uint64_t d[4] = {4096, 1, 1, 4096}, s[3] = {8192, 8192, 8192}; const uint32_t b[4] = {64, 1, 1, 32};
        encode(fn, &P.tm[M_KV4], kvo, 4, d, s, b);
    }
    for (int e = 0; e < 2; e++) {
        const uint64_t d[4] = {1024, 2, 4, 256}, s[3] = {8 * 2048, 2 * 2048, 16 * 2048}; const uint32_t b[4] = {64, 2, 4, 8};
        encode(fn, &P.tm[M_CO + e], in[14] + e * 1024, 4, d, s, b);
    }
    P.Wq = in[11]; P.Wk = in[12]; P.Wv = in[13]; P.Wo = in[14]; P.mem0 = in[10];
    P.Lre = in[1]; P.Lim = in[2]; P.logdt = in[7]; P.Dskip = in[8];
    P.out = (float*)d_out;
    P.two26 = 1u << 26;
    P.lag = 0x22023302;
    P.ds = 400; P.dc = 1600; P.alpha = 0.3f; P.extra = 200; P.da = 188; P.db = 428; P.dk = 800; P.dp = 1550; P.dv = 60; P.pf0 = 2000; P.pf1 = 250; P.pf2 = 7; P.back = 150; P.ds0 = 950;
    for (int i = 0; i < (DBGF(32) ? 1 : 2); i++) {
        cudaLaunchConfig_t cfg = {};
        cfg.gridDim = dim3(i ? 36 : 96); cfg.blockDim = dim3(384); cfg.dynamicSmemBytes = S_TOTAL; cfg.stream = cudaStreamPerThread;
        cudaLaunchAttribute at[2];
        at[0].id = cudaLaunchAttributeClusterDimension; at[0].val.clusterDim.x = i ? 2 : 6; at[0].val.clusterDim.y = at[0].val.clusterDim.z = 1;
        at[1].id = cudaLaunchAttributeProgrammaticStreamSerialization; at[1].val.programmaticStreamSerializationAllowed = 1;
        cfg.attrs = at; cfg.numAttrs = 1 + i;
        cudaLaunchKernelEx(&cfg, fused_kernel, P);
    }
}
```

```cpp
#include <cuda_runtime.h>
#include <cuda_bf16.h>
#include <cuda.h>
#include <stdint.h>
#include <string.h>

typedef __nv_bfloat16 bf16;

namespace {

#define POLL 200
constexpr int SPIN_LIMIT = 1 << 22;
constexpr int NPAIR = 66;
constexpr int NCHAIN = 48;
enum { T_KV = 0, T_QA = 1, T_OP = 2, T_A1 = 3, T_A2 = 4, T_CHAIN = 5, T_OPH = 6, T_A2H = 7 };
enum { M_BX = 0, M_WQ, M_WK, M_WV, M_WO, M_OA, M_AB, M_AX, M_HT, M_CRE, M_CIM, M_KVO, M_HTS, M_WOH, M_CREH, M_CIMH, M_CQ, M_CK, M_CV, M_CO, M_CO1, M_KV4, M_COUNT };
enum { C_KV = 0, C_HT = 8, C_DONE = 24, C_EPOCH = 25, C_COEF = 26, C_FLAG = 32, C_O = 96 };

struct Params {
    CUtensorMap tm[M_COUNT];
    const bf16 *Wq, *Wk, *Wv, *Wo, *mem0, *Lre, *Lim, *logdt, *Dskip;
    float* out;
    uint8_t* gm;
    int swap_ri, zero;
    uint32_t two26, lag;
    int ds, da, db, dk, dv, back, ds0, pf0, pf1, dc, extra, dp;
    float alpha;
#define DBGF(x) false
};

constexpr int NPRE = 1;
__constant__ uint16_t c_off[67] = {0, 5, 10, 15, 21, 25, 29, 35, 39, 43, 47, 51, 55, 59, 63, 67, 71, 76, 81, 86, 91, 95, 99, 103, 108, 112, 116, 120, 124, 128, 133, 137, 142, 147, 152, 157, 162, 166, 170, 175, 179, 183, 187, 191, 195, 200, 205, 209, 213, 232, 252, 272, 291, 311, 331, 349, 369, 389, 407, 427, 446, 466, 485, 505, 524, 543, 562};
__constant__ uint16_t c_items[640] = {
    32, 1280, 453, 492, 1056, 49, 1280, 485, 494, 1249, 34, 1280, 293, 301, 1120, 51, 1280, 458, 457, 428, 1959, 36, 1280, 896,
    642, 53, 1280, 898, 546, 38, 1280, 833, 961, 996, 1957, 55, 1280, 865, 578, 40, 1280, 495, 576, 57, 1280, 463, 579, 42,
    1280, 262, 675, 59, 1280, 264, 739, 44, 1280, 335, 608, 61, 1280, 897, 738, 46, 1280, 361, 707, 63, 1280, 265, 705, 0,
    1280, 388, 302, 1217, 1, 1280, 489, 493, 1248, 2, 1280, 391, 333, 1250, 3, 1280, 263, 459, 1088, 4, 1280, 866, 673, 5,
    1280, 931, 640, 6, 1280, 835, 737, 7, 1280, 899, 488, 1185, 8, 1280, 838, 643, 9, 1280, 839, 641, 10, 1280, 870, 672,
    11, 1280, 864, 515, 12, 1280, 871, 674, 13, 1280, 935, 933, 1219, 14, 1280, 772, 736, 15, 1280, 994, 964, 1091, 16, 1280,
    393, 332, 1216, 17, 1280, 484, 300, 1121, 18, 1280, 487, 364, 1058, 19, 1280, 423, 462, 1152, 20, 1280, 867, 544, 21, 1280,
    930, 545, 22, 1280, 900, 424, 1089, 23, 1280, 836, 577, 24, 1280, 903, 611, 25, 1280, 902, 609, 26, 1280, 928, 547, 27,
    1280, 869, 512, 28, 1280, 868, 901, 1251, 29, 1280, 932, 965, 1218, 30, 1280, 804, 704, 31, 1280, 962, 706, 33, 95, 94,
    127, 126, 159, 158, 255, 223, 191, 324, 352, 399, 422, 289, 425, 392, 490, 1024, 35, 93, 92, 125, 124, 157, 156, 189,
    221, 253, 252, 323, 254, 292, 418, 417, 386, 299, 365, 1956, 37, 91, 90, 123, 122, 155, 154, 187, 186, 251, 219, 250,
    334, 426, 366, 448, 449, 491, 430, 1123, 39, 89, 88, 121, 120, 153, 152, 185, 217, 184, 216, 218, 249, 248, 358, 288,
    321, 452, 514, 41, 87, 86, 119, 118, 151, 215, 247, 183, 214, 200, 199, 246, 325, 296, 420, 482, 268, 396, 1059, 43,
    85, 84, 117, 116, 149, 213, 181, 212, 180, 195, 193, 297, 363, 266, 326, 303, 455, 431, 1153, 45, 83, 82, 115, 114,
    147, 211, 179, 210, 178, 329, 243, 355, 356, 805, 837, 929, 610, 47, 81, 80, 113, 112, 145, 177, 176, 241, 190, 209,
    208, 240, 773, 832, 290, 480, 995, 966, 1057, 48, 79, 78, 111, 143, 142, 207, 175, 206, 174, 222, 192, 239, 256, 257,
    390, 389, 934, 997, 1090, 50, 77, 76, 109, 141, 140, 237, 173, 236, 234, 245, 205, 258, 771, 427, 421, 483, 513, 52,
    75, 74, 107, 139, 138, 171, 235, 170, 203, 202, 770, 774, 359, 775, 801, 963, 993, 397, 1958, 54, 73, 72, 105, 137,
    136, 169, 201, 233, 168, 362, 270, 394, 353, 807, 806, 960, 367, 1184, 56, 71, 103, 104, 135, 150, 167, 182, 231, 232,
    242, 238, 384, 224, 357, 387, 320, 486, 429, 1026, 58, 70, 102, 110, 134, 148, 166, 172, 230, 188, 267, 800, 244, 419,
    291, 295, 328, 269, 1027, 60, 69, 101, 108, 133, 146, 197, 165, 204, 198, 220, 322, 229, 398, 802, 803, 395, 454, 461,
    1155, 62, 68, 100, 106, 132, 144, 228, 164, 327, 196, 225, 768, 769, 260, 416, 481, 967, 999, 1122, 64, 67, 99, 97,
    131, 129, 163, 161, 271, 354, 259, 227, 261, 294, 450, 834, 992, 998, 1025, 65, 66, 98, 96, 130, 128, 162, 160, 298,
    226, 194, 385, 331, 330, 360, 451, 456, 460, 1154,
};
#define ITEM_OFF(p) c_off[p]
#define ITEM(i) c_items[i]

__device__ __align__(1024) bf16 g_kvo[3 * 2048 * 4096];
__device__ __align__(1024) bf16 g_ht[2048 * 2048];
__device__ __align__(1024) uint8_t g_m[9 * 32768];
__device__ __align__(1024) uint8_t g_f[8 * 49152];
__device__ __align__(1024) uint32_t g_km[64 * 32 * 512];
__device__ __align__(1024) uint32_t g_vmt[64 * 32 * 512];
__device__ __align__(1024) float2 g_agg[8 * 1024];
__device__ __align__(1024) float4 g_coef[1024];
__device__ __align__(1024) uint32_t g_cntl[128 * 32];
#define g_cnt(i) g_cntl[(i) * 32]
__device__ __align__(1024) uint32_t g_hint[6144 + 160];
#define SSTAMP(i, cond)
#define PROF(i)
#define GT_EDGE(o)
constexpr int M_SLOT = 32768, F_SLOT = 49152;

constexpr int STAGE = 49152, NSTAGE = 4;
constexpr int S_STG = NSTAGE * STAGE;
constexpr int S_BAR = S_STG + 32768;
constexpr int B_FULL = S_BAR, B_EMPTY = S_BAR + 32, B_RESUME = S_BAR + 64, B_KVFULL = S_BAR + 72, B_GO = S_BAR + 88, B_K = S_BAR + 96, B_PERS = S_BAR + 104, B_INIT = S_BAR + 112, B_RELA = S_BAR + 120, B_V = S_BAR + 128, B_WO = S_BAR + 136,
              B_SFULL = S_BAR + 144, B_SFREE = S_BAR + 160, S_DESC = S_BAR + 176, S_REDO = S_BAR + 256 + 512 + 64, S_EPOCH = S_BAR + 208, B_RELB = S_BAR + 216, B_KVGO = S_BAR + 224, S_DEP = S_BAR + 240, S_CUR = S_BAR + 244, S_TAIL = S_BAR + 248, S_CTA = S_BAR + 252;
constexpr int S_COEF = S_BAR + 256 + 512, S_TOTAL = S_COEF + 1024;
constexpr int S_W1 = 0;
constexpr int S_O = 24 * 4096, S_VL = S_O + 2048, S_MX = 25 * 4096, S_SC = S_MX + 64, S_SUM = S_MX + 128;
constexpr int S_KL = 26 * 4096;
constexpr int S_W2 = 27 * 4096;
constexpr int S_KV = S_W2 + 65536;
constexpr int S_P1 = S_W2 + 98304;
constexpr int S_QX = S_P1 + 16384;
constexpr int S_SX = S_QX + 2048;
static_assert(S_SX + 1280 <= S_BAR, "chain smem overlaps barriers");
constexpr int NR = 40, NS = 64 - NR;

__device__ __forceinline__ uint32_t logical_cta(uint32_t b) {
    const uint32_t c = b / 6, r = b - c * 6;
    return gridDim.x != 96 ? 96 + b : ((r >> 1) + (c >= 8) + (c >= 15)) % 3 * 32 + c * 2 + (r & 1);
}
__device__ __forceinline__ uint32_t cluster_rank() { uint32_t r; asm("mov.u32 %0, %%cluster_ctarank;" : "=r"(r)); return r; }
__device__ __forceinline__ uint16_t pair_mask() { return (uint16_t)(3u << (cluster_rank() & 6)); }
__device__ __forceinline__ void spin_fault() { asm volatile("st.global.u32 [%0], 0;" ::"l"(0ull) : "memory"); }
__device__ __forceinline__ uint32_t smem_u32(const void* p) { return (uint32_t)__cvta_generic_to_shared(p); }
__device__ __forceinline__ uint32_t opq(uint32_t x, int lane) { return __shfl_sync(0xffffffffu, x, lane); }
__device__ __forceinline__ uint32_t mapa(uint32_t a, uint32_t r) { uint32_t d; asm volatile("mapa.shared::cluster.u32 %0, %1, %2;" : "=r"(d) : "r"(a), "r"(r)); return d; }
__device__ __forceinline__ void mma16816(float* d, uint32_t a0, uint32_t a1, uint32_t a2, uint32_t a3, uint32_t b0, uint32_t b1) {
    asm("mma.sync.aligned.m16n8k16.row.col.f32.bf16.bf16.f32 {%0,%1,%2,%3}, {%4,%5,%6,%7}, {%8,%9}, {%0,%1,%2,%3};"
        : "+f"(d[0]), "+f"(d[1]), "+f"(d[2]), "+f"(d[3]) : "r"(a0), "r"(a1), "r"(a2), "r"(a3), "r"(b0), "r"(b1));
}
__device__ __forceinline__ void mma1688(float* d, uint32_t a0, uint32_t a1, uint32_t b0) {
    asm("mma.sync.aligned.m16n8k8.row.col.f32.bf16.bf16.f32 {%0,%1,%2,%3}, {%4,%5}, {%6}, {%0,%1,%2,%3};"
        : "+f"(d[0]), "+f"(d[1]), "+f"(d[2]), "+f"(d[3]) : "r"(a0), "r"(a1), "r"(b0));
}
__device__ __forceinline__ void ldsm4(uint32_t* r, uint32_t a) {
    asm volatile("ldmatrix.sync.aligned.m8n8.x4.shared.b16 {%0,%1,%2,%3}, [%4];" : "=r"(r[0]), "=r"(r[1]), "=r"(r[2]), "=r"(r[3]) : "r"(a));
}
__device__ __forceinline__ void ldsm4t(uint32_t* r, uint32_t a) {
    asm volatile("ldmatrix.sync.aligned.m8n8.x4.trans.shared.b16 {%0,%1,%2,%3}, [%4];" : "=r"(r[0]), "=r"(r[1]), "=r"(r[2]), "=r"(r[3]) : "r"(a));
}
__device__ __forceinline__ void stsm4(uint32_t a, uint32_t r0, uint32_t r1, uint32_t r2, uint32_t r3) {
    asm volatile("stmatrix.sync.aligned.m8n8.x4.shared.b16 [%0], {%1,%2,%3,%4};" ::"r"(a), "r"(r0), "r"(r1), "r"(r2), "r"(r3) : "memory");
}
__device__ __forceinline__ void stsm4t(uint32_t a, uint32_t r0, uint32_t r1, uint32_t r2, uint32_t r3) {
    asm volatile("stmatrix.sync.aligned.m8n8.x4.trans.shared.b16 [%0], {%1,%2,%3,%4};" ::"r"(a), "r"(r0), "r"(r1), "r"(r2), "r"(r3) : "memory");
}
__device__ __forceinline__ uint32_t pack2(float lo, float hi) { uint32_t d; asm("cvt.rn.bf16x2.f32 %0, %1, %2;" : "=r"(d) : "f"(hi), "f"(lo)); return d; }
__device__ __forceinline__ float bf_lo(uint32_t u) { return __uint_as_float(u << 16); }
__device__ __forceinline__ float bf_hi(uint32_t u) { return __uint_as_float(u & 0xffff0000u); }
__device__ __forceinline__ uint32_t hmul2(uint32_t a, uint32_t b) { uint32_t d; asm("mul.rn.bf16x2 %0, %1, %2;" : "=r"(d) : "r"(a), "r"(b)); return d; }
__device__ __forceinline__ float ex2(float x) { float y; asm("ex2.approx.ftz.f32 %0, %1;" : "=f"(y) : "f"(x)); return y; }
__device__ __forceinline__ float rcp(float x) { float y; asm("rcp.approx.ftz.f32 %0, %1;" : "=f"(y) : "f"(x)); return y; }
__device__ __forceinline__ void st_relaxed4(const void* p, uint32_t a, uint32_t b, uint32_t c, uint32_t d) {
    asm volatile("{\n.reg .b128 t;\nmov.b128 t, {%1,%2,%3,%4};\nst.relaxed.gpu.global.b128 [%0], t;\n}" ::"l"(p), "r"(a), "r"(b), "r"(c), "r"(d) : "memory");
}
__device__ __forceinline__ void st_relaxed2(const void* p, uint32_t a, uint32_t b) {
    asm volatile("{\n.reg .b64 t;\nmov.b64 t, {%1,%2};\nst.relaxed.gpu.global.b64 [%0], t;\n}" ::"l"(p), "r"(a), "r"(b) : "memory");
}
__device__ __forceinline__ void ld_relaxed2_if(uint32_t& a, uint32_t& b, const void* p, bool on) {
    asm volatile("{\n.reg .pred P;\n.reg .b64 t;\nsetp.ne.u32 P, %3, 0;\nmov.b64 t, {%0,%1};\n@P ld.relaxed.gpu.global.b64 t, [%2];\nmov.b64 {%0,%1}, t;\n}" : "+r"(a), "+r"(b) : "l"(p), "r"((uint32_t)on) : "memory");
}
__device__ __forceinline__ uint32_t ld_relaxed1(const void* p) { uint32_t v; asm volatile("ld.relaxed.gpu.global.u32 %0, [%1];" : "=r"(v) : "l"(p) : "memory"); return v; }
__device__ __forceinline__ void st_relaxed1(const void* p, uint32_t v) { asm volatile("st.relaxed.gpu.global.u32 [%0], %1;" ::"l"(p), "r"(v) : "memory"); }
__device__ __forceinline__ uint32_t ld_acquire(const void* p) { uint32_t v; asm volatile("ld.acquire.gpu.global.u32 %0, [%1];" : "=r"(v) : "l"(p) : "memory"); return v; }
__device__ __forceinline__ void red_release(void* p) { asm volatile("red.release.gpu.global.add.u32 [%0], 1;" ::"l"(p) : "memory"); }
__device__ __forceinline__ void st_stream2(float* p, float a, float b) { asm volatile("st.global.cs.v2.f32 [%0], {%1, %2};" ::"l"(p), "f"(a), "f"(b) : "memory"); }
__device__ __forceinline__ void fence_acquire() { asm volatile("fence.acquire.gpu;" ::: "memory"); }
__device__ __forceinline__ void fence_release() { asm volatile("fence.release.gpu;" ::: "memory"); }
__device__ __forceinline__ void fence_async() {  asm volatile("fence.proxy.async.global;" ::: "memory"); }
__device__ __forceinline__ void fence_async_smem() { asm volatile("fence.proxy.async.shared::cta;" ::: "memory"); }
__device__ __forceinline__ void wait_count(const uint32_t* p, uint32_t target) {
    int n = 0;
    while ((int32_t)(ld_acquire(p) - target) < 0) { __nanosleep(POLL); if (++n > SPIN_LIMIT) spin_fault(); }
}
__device__ __forceinline__ void bar_sync(int id, int n) { asm volatile("bar.sync %0, %1;" ::"r"(id), "r"(n) : "memory"); }
__device__ __forceinline__ void bar_arrive(int id, int n) { asm volatile("bar.arrive %0, %1;" ::"r"(id), "r"(n) : "memory"); }
__device__ __forceinline__ bool bar_and(int id, bool v) {
    uint32_t r;
    asm volatile("{\n.reg .pred P, Q;\nsetp.ne.u32 Q, %2, 0;\nbar.red.and.pred P, %1, 128, Q;\nselp.u32 %0, 1, 0, P;\n}" : "=r"(r) : "r"(id), "r"((uint32_t)v) : "memory");
    return r;
}
__device__ __forceinline__ void lds128(uint32_t* v, uint32_t a) { asm volatile("ld.shared.v4.b32 {%0,%1,%2,%3}, [%4];" : "=r"(v[0]), "=r"(v[1]), "=r"(v[2]), "=r"(v[3]) : "r"(a) : "memory"); }
__device__ __forceinline__ uint32_t lds32(uint32_t a) { uint32_t v; asm volatile("ld.shared.b32 %0, [%1];" : "=r"(v) : "r"(a) : "memory"); return v; }
__device__ __forceinline__ void lds64f(float* v, uint32_t a) { asm volatile("ld.shared.v2.f32 {%0,%1}, [%2];" : "=f"(v[0]), "=f"(v[1]) : "r"(a) : "memory"); }
__device__ __forceinline__ void sts128(uint32_t a, const uint32_t* v) { asm volatile("st.shared.v4.b32 [%0], {%1,%2,%3,%4};" ::"r"(a), "r"(v[0]), "r"(v[1]), "r"(v[2]), "r"(v[3]) : "memory"); }
__device__ __forceinline__ void sts64(uint32_t a, uint32_t x, uint32_t y) { asm volatile("st.shared.v2.b32 [%0], {%1,%2};" ::"r"(a), "r"(x), "r"(y) : "memory"); }
__device__ __forceinline__ void sts32(uint32_t a, uint32_t x) { asm volatile("st.shared.b32 [%0], %1;" ::"r"(a), "r"(x) : "memory"); }
__device__ __forceinline__ bool mbar_try(uint32_t b, uint32_t par) {
    uint32_t ok;
    asm volatile("{\n.reg .pred P;\nmbarrier.try_wait.parity.shared::cta.b64 P, [%1], %2;\nselp.u32 %0, 1, 0, P;\n}" : "=r"(ok) : "r"(b), "r"(par) : "memory");
    return ok;
}
__device__ __forceinline__ bool mbar_test(uint32_t b, uint32_t par) {
    uint32_t ok;
    asm volatile("{\n.reg .pred P;\nmbarrier.test_wait.parity.shared::cta.b64 P, [%1], %2;\nselp.u32 %0, 1, 0, P;\n}" : "=r"(ok) : "r"(b), "r"(par) : "memory");
    return ok;
}
__device__ __forceinline__ void mbar_wait(uint32_t b, uint32_t par) { int n = 0; while (!mbar_try(b, par)) { if (++n > SPIN_LIMIT) spin_fault(); } }
__device__ __forceinline__ void mbar_init(uint32_t b, uint32_t n) { asm volatile("mbarrier.init.shared::cta.b64 [%0], %1;" ::"r"(b), "r"(n) : "memory"); }
__device__ __forceinline__ void mbar_expect(uint32_t b, uint32_t bytes) { asm volatile("mbarrier.arrive.expect_tx.shared::cta.b64 _, [%0], %1;" ::"r"(b), "r"(bytes) : "memory"); }
__device__ __forceinline__ void mbar_arrive(uint32_t b) { asm volatile("mbarrier.arrive.shared::cta.b64 _, [%0];" ::"r"(b) : "memory"); }
__device__ __forceinline__ void mbar_arrive_cluster(uint32_t b) { asm volatile("mbarrier.arrive.shared::cluster.b64 _, [%0];" ::"r"(b) : "memory"); }
__device__ __forceinline__ void st_async1(uint32_t a, uint32_t x, uint32_t bar) {
    asm volatile("st.async.weak.shared::cluster.mbarrier::complete_tx::bytes.b32 [%0], %1, [%2];" ::"r"(a), "r"(x), "r"(bar) : "memory");
}
__device__ __forceinline__ void st_async2(uint32_t a, uint32_t x, uint32_t y, uint32_t bar) {
    asm volatile("st.async.weak.shared::cluster.mbarrier::complete_tx::bytes.v2.b32 [%0], {%1,%2}, [%3];" ::"r"(a), "r"(x), "r"(y), "r"(bar) : "memory");
}
__device__ __forceinline__ void cluster_sync() { asm volatile("barrier.cluster.arrive.aligned;\nbarrier.cluster.wait.aligned;" ::: "memory"); }
constexpr uint64_t EVICT_FIRST = 0x12F0000000000000ull, EVICT_NORMAL = 0x1000000000000000ull;
__device__ __forceinline__ void tma2d(uint32_t dst, const CUtensorMap* m, int c0, int c1, uint32_t bar, uint64_t pol) {
    asm volatile("cp.async.bulk.tensor.2d.shared::cluster.global.mbarrier::complete_tx::bytes.L2::cache_hint [%0], [%1, {%2, %3}], [%4], %5;" ::"r"(dst), "l"(m), "r"(c0), "r"(c1), "r"(bar), "l"(pol) : "memory");
}
__device__ __forceinline__ void tma4d(uint32_t dst, const CUtensorMap* m, int c0, int c3, uint32_t bar, uint64_t pol) {
    asm volatile("cp.async.bulk.tensor.4d.shared::cluster.global.mbarrier::complete_tx::bytes.L2::cache_hint [%0], [%1, {%2, 0, 0, %3}], [%4], %5;" ::"r"(dst), "l"(m), "r"(c0), "r"(c3), "r"(bar), "l"(pol) : "memory");
}
__device__ __forceinline__ void tma3d(uint32_t dst, const CUtensorMap* m, int c0, int c1, int c2, uint32_t bar, uint64_t pol) {
    asm volatile("cp.async.bulk.tensor.3d.shared::cluster.global.mbarrier::complete_tx::bytes.L2::cache_hint [%0], [%1, {%2, %3, %4}], [%5], %6;" ::"r"(dst), "l"(m), "r"(c0), "r"(c1), "r"(c2), "r"(bar), "l"(pol) : "memory");
}
__device__ __forceinline__ void tma_store2d(const CUtensorMap* m, int c0, int c1, uint32_t src, uint64_t pol) {
    asm volatile("cp.async.bulk.tensor.2d.global.shared::cta.bulk_group.L2::cache_hint [%0, {%1, %2}], [%3], %4;" ::"l"(m), "r"(c0), "r"(c1), "r"(src), "l"(pol) : "memory");
}
#define EF 63
#define POL(bit) ((EF >> (bit)) & 1 ? EVICT_FIRST : EVICT_NORMAL)
__device__ __forceinline__ void tma2d_mc(uint32_t dst, const CUtensorMap* m, int c0, int c1, uint32_t bar, uint64_t pol) {
    asm volatile("cp.async.bulk.tensor.2d.shared::cluster.global.mbarrier::complete_tx::bytes.multicast::cluster.L2::cache_hint [%0], [%1, {%2, %3}], [%4], %5, %6;" ::"r"(dst), "l"(m), "r"(c0), "r"(c1), "r"(bar), "h"(pair_mask()), "l"(pol) : "memory");
}
__device__ __forceinline__ void tma3d_mc(uint32_t dst, const CUtensorMap* m, int c0, int c1, int c2, uint32_t bar, uint64_t pol) {
    asm volatile("cp.async.bulk.tensor.3d.shared::cluster.global.mbarrier::complete_tx::bytes.multicast::cluster.L2::cache_hint [%0], [%1, {%2, %3, %4}], [%5], %6, %7;" ::"r"(dst), "l"(m), "r"(c0), "r"(c1), "r"(c2), "r"(bar), "h"(pair_mask()), "l"(pol) : "memory");
}
__device__ __forceinline__ void tma4d_mc(uint32_t dst, const CUtensorMap* m, int c0, int c3, uint32_t bar, uint64_t pol) {
    asm volatile("cp.async.bulk.tensor.4d.shared::cluster.global.mbarrier::complete_tx::bytes.multicast::cluster.L2::cache_hint [%0], [%1, {%2, 0, 0, %3}], [%4], %5, %6;" ::"r"(dst), "l"(m), "r"(c0), "r"(c3), "r"(bar), "h"(pair_mask()), "l"(pol) : "memory");
}
__device__ __forceinline__ void map_prefetch(const CUtensorMap* m) { asm volatile("prefetch.tensormap [%0];" ::"l"(m) : "memory"); }
__device__ __forceinline__ void bulk_g2s(uint32_t dst, const void* src, uint32_t bytes, uint32_t bar) {
    asm volatile("cp.async.bulk.shared::cluster.global.mbarrier::complete_tx::bytes [%0], [%1], %2, [%3];" ::"r"(dst), "l"(src), "r"(bytes), "r"(bar) : "memory");
}
__device__ __forceinline__ void bulk_s2g(void* dst, uint32_t src, uint32_t bytes) {
    asm volatile("cp.async.bulk.global.shared::cta.bulk_group [%0], [%1], %2;" ::"l"(dst), "r"(src), "r"(bytes) : "memory");
}
__device__ __forceinline__ void bulk_commit() { asm volatile("cp.async.bulk.commit_group;" ::: "memory"); }
__device__ __forceinline__ void bulk_wait_read() { asm volatile("cp.async.bulk.wait_group.read 0;" ::: "memory"); }
__device__ __forceinline__ void bulk_wait_all() { asm volatile("cp.async.bulk.wait_group 0;" ::: "memory"); }
__device__ __forceinline__ uint64_t mkdesc(uint32_t addr, uint32_t lbo, uint32_t sbo, uint32_t swz) {
    return (uint64_t)((addr & 0x3FFFF) >> 4) | ((uint64_t)(lbo >> 4) << 16) | ((uint64_t)(sbo >> 4) << 32) | ((uint64_t)swz << 62);
}
__device__ __forceinline__ void wg_fence() { asm volatile("wgmma.fence.sync.aligned;" ::: "memory"); }
__device__ __forceinline__ void wg_commit() { asm volatile("wgmma.commit_group.sync.aligned;" ::: "memory"); }
template <int N> __device__ __forceinline__ void wg_wait() { asm volatile("wgmma.wait_group.sync.aligned %0;" ::"n"(N) : "memory"); }
template <typename T> __device__ __forceinline__ void pin_ptr(T*& p) { asm volatile("" : "+l"(p)); }
template <int N> __device__ __forceinline__ void pin(uint32_t* d) {
#pragma unroll
    for (int i = 0; i < N; i++) asm volatile("" : "+r"(d[i])::"memory");
}
template <int N> __device__ __forceinline__ void pin(float* d) {
#pragma unroll
    for (int i = 0; i < N; i++) asm volatile("" : "+f"(d[i])::"memory");
}

template <int TA, int TB>
__device__ __forceinline__ void wgmma_ss256(float* d, uint64_t da, uint64_t db) {
    asm volatile("wgmma.mma_async.sync.aligned.m64n256k16.f32.bf16.bf16 "
        "{%0, %1, %2, %3, %4, %5, %6, %7, %8, %9, %10, %11, %12, %13, %14, %15, %16, %17, %18, %19, %20, %21, %22, %23, %24, %25, %26, %27, %28, %29, %30, %31, %32, %33, %34, %35, %36, %37, %38, %39, %40, %41, %42, %43, %44, %45, %46, %47, %48, %49, %50, %51, %52, %53, %54, %55, %56, %57, %58, %59, %60, %61, %62, %63, %64, %65, %66, %67, %68, %69, %70, %71, %72, %73, %74, %75, %76, %77, %78, %79, %80, %81, %82, %83, %84, %85, %86, %87, %88, %89, %90, %91, %92, %93, %94, %95, %96, %97, %98, %99, %100, %101, %102, %103, %104, %105, %106, %107, %108, %109, %110, %111, %112, %113, %114, %115, %116, %117, %118, %119, %120, %121, %122, %123, %124, %125, %126, %127}, %128, %129, 1, 1, 1, %130, %131;"
        : "+f"(d[0]), "+f"(d[1]), "+f"(d[2]), "+f"(d[3]), "+f"(d[4]), "+f"(d[5]), "+f"(d[6]), "+f"(d[7]), "+f"(d[8]), "+f"(d[9]), "+f"(d[10]), "+f"(d[11]), "+f"(d[12]), "+f"(d[13]), "+f"(d[14]), "+f"(d[15]), "+f"(d[16]), "+f"(d[17]), "+f"(d[18]), "+f"(d[19]), "+f"(d[20]), "+f"(d[21]), "+f"(d[22]), "+f"(d[23]), "+f"(d[24]), "+f"(d[25]), "+f"(d[26]), "+f"(d[27]), "+f"(d[28]), "+f"(d[29]), "+f"(d[30]), "+f"(d[31]), "+f"(d[32]), "+f"(d[33]), "+f"(d[34]), "+f"(d[35]), "+f"(d[36]), "+f"(d[37]), "+f"(d[38]), "+f"(d[39]), "+f"(d[40]), "+f"(d[41]), "+f"(d[42]), "+f"(d[43]), "+f"(d[44]), "+f"(d[45]), "+f"(d[46]), "+f"(d[47]), "+f"(d[48]), "+f"(d[49]), "+f"(d[50]), "+f"(d[51]), "+f"(d[52]), "+f"(d[53]), "+f"(d[54]), "+f"(d[55]), "+f"(d[56]), "+f"(d[57]), "+f"(d[58]), "+f"(d[59]), "+f"(d[60]), "+f"(d[61]), "+f"(d[62]), "+f"(d[63]), "+f"(d[64]), "+f"(d[65]), "+f"(d[66]), "+f"(d[67]), "+f"(d[68]), "+f"(d[69]), "+f"(d[70]), "+f"(d[71]), "+f"(d[72]), "+f"(d[73]), "+f"(d[74]), "+f"(d[75]), "+f"(d[76]), "+f"(d[77]), "+f"(d[78]), "+f"(d[79]), "+f"(d[80]), "+f"(d[81]), "+f"(d[82]), "+f"(d[83]), "+f"(d[84]), "+f"(d[85]), "+f"(d[86]), "+f"(d[87]), "+f"(d[88]), "+f"(d[89]), "+f"(d[90]), "+f"(d[91]), "+f"(d[92]), "+f"(d[93]), "+f"(d[94]), "+f"(d[95]), "+f"(d[96]), "+f"(d[97]), "+f"(d[98]), "+f"(d[99]), "+f"(d[100]), "+f"(d[101]), "+f"(d[102]), "+f"(d[103]), "+f"(d[104]), "+f"(d[105]), "+f"(d[106]), "+f"(d[107]), "+f"(d[108]), "+f"(d[109]), "+f"(d[110]), "+f"(d[111]), "+f"(d[112]), "+f"(d[113]), "+f"(d[114]), "+f"(d[115]), "+f"(d[116]), "+f"(d[117]), "+f"(d[118]), "+f"(d[119]), "+f"(d[120]), "+f"(d[121]), "+f"(d[122]), "+f"(d[123]), "+f"(d[124]), "+f"(d[125]), "+f"(d[126]), "+f"(d[127])
        : "l"(da), "l"(db), "n"(TA), "n"(TB));
}
template <int TA, int TB>
__device__ __forceinline__ void wgmma_ss256_first(float* d, uint64_t da, uint64_t db) {
    asm volatile("wgmma.mma_async.sync.aligned.m64n256k16.f32.bf16.bf16 "
        "{%0, %1, %2, %3, %4, %5, %6, %7, %8, %9, %10, %11, %12, %13, %14, %15, %16, %17, %18, %19, %20, %21, %22, %23, %24, %25, %26, %27, %28, %29, %30, %31, %32, %33, %34, %35, %36, %37, %38, %39, %40, %41, %42, %43, %44, %45, %46, %47, %48, %49, %50, %51, %52, %53, %54, %55, %56, %57, %58, %59, %60, %61, %62, %63, %64, %65, %66, %67, %68, %69, %70, %71, %72, %73, %74, %75, %76, %77, %78, %79, %80, %81, %82, %83, %84, %85, %86, %87, %88, %89, %90, %91, %92, %93, %94, %95, %96, %97, %98, %99, %100, %101, %102, %103, %104, %105, %106, %107, %108, %109, %110, %111, %112, %113, %114, %115, %116, %117, %118, %119, %120, %121, %122, %123, %124, %125, %126, %127}, %128, %129, 0, 1, 1, %130, %131;"
        : "=f"(d[0]), "=f"(d[1]), "=f"(d[2]), "=f"(d[3]), "=f"(d[4]), "=f"(d[5]), "=f"(d[6]), "=f"(d[7]), "=f"(d[8]), "=f"(d[9]), "=f"(d[10]), "=f"(d[11]), "=f"(d[12]), "=f"(d[13]), "=f"(d[14]), "=f"(d[15]), "=f"(d[16]), "=f"(d[17]), "=f"(d[18]), "=f"(d[19]), "=f"(d[20]), "=f"(d[21]), "=f"(d[22]), "=f"(d[23]), "=f"(d[24]), "=f"(d[25]), "=f"(d[26]), "=f"(d[27]), "=f"(d[28]), "=f"(d[29]), "=f"(d[30]), "=f"(d[31]), "=f"(d[32]), "=f"(d[33]), "=f"(d[34]), "=f"(d[35]), "=f"(d[36]), "=f"(d[37]), "=f"(d[38]), "=f"(d[39]), "=f"(d[40]), "=f"(d[41]), "=f"(d[42]), "=f"(d[43]), "=f"(d[44]), "=f"(d[45]), "=f"(d[46]), "=f"(d[47]), "=f"(d[48]), "=f"(d[49]), "=f"(d[50]), "=f"(d[51]), "=f"(d[52]), "=f"(d[53]), "=f"(d[54]), "=f"(d[55]), "=f"(d[56]), "=f"(d[57]), "=f"(d[58]), "=f"(d[59]), "=f"(d[60]), "=f"(d[61]), "=f"(d[62]), "=f"(d[63]), "=f"(d[64]), "=f"(d[65]), "=f"(d[66]), "=f"(d[67]), "=f"(d[68]), "=f"(d[69]), "=f"(d[70]), "=f"(d[71]), "=f"(d[72]), "=f"(d[73]), "=f"(d[74]), "=f"(d[75]), "=f"(d[76]), "=f"(d[77]), "=f"(d[78]), "=f"(d[79]), "=f"(d[80]), "=f"(d[81]), "=f"(d[82]), "=f"(d[83]), "=f"(d[84]), "=f"(d[85]), "=f"(d[86]), "=f"(d[87]), "=f"(d[88]), "=f"(d[89]), "=f"(d[90]), "=f"(d[91]), "=f"(d[92]), "=f"(d[93]), "=f"(d[94]), "=f"(d[95]), "=f"(d[96]), "=f"(d[97]), "=f"(d[98]), "=f"(d[99]), "=f"(d[100]), "=f"(d[101]), "=f"(d[102]), "=f"(d[103]), "=f"(d[104]), "=f"(d[105]), "=f"(d[106]), "=f"(d[107]), "=f"(d[108]), "=f"(d[109]), "=f"(d[110]), "=f"(d[111]), "=f"(d[112]), "=f"(d[113]), "=f"(d[114]), "=f"(d[115]), "=f"(d[116]), "=f"(d[117]), "=f"(d[118]), "=f"(d[119]), "=f"(d[120]), "=f"(d[121]), "=f"(d[122]), "=f"(d[123]), "=f"(d[124]), "=f"(d[125]), "=f"(d[126]), "=f"(d[127])
        : "l"(da), "l"(db), "n"(TA), "n"(TB));
}
template <int TA, int TB>
__device__ __forceinline__ void wgmma_ss128(float* d, uint64_t da, uint64_t db) {
    asm volatile("wgmma.mma_async.sync.aligned.m64n128k16.f32.bf16.bf16 "
        "{%0, %1, %2, %3, %4, %5, %6, %7, %8, %9, %10, %11, %12, %13, %14, %15, %16, %17, %18, %19, %20, %21, %22, %23, %24, %25, %26, %27, %28, %29, %30, %31, %32, %33, %34, %35, %36, %37, %38, %39, %40, %41, %42, %43, %44, %45, %46, %47, %48, %49, %50, %51, %52, %53, %54, %55, %56, %57, %58, %59, %60, %61, %62, %63}, %64, %65, 1, 1, 1, %66, %67;"
        : "+f"(d[0]), "+f"(d[1]), "+f"(d[2]), "+f"(d[3]), "+f"(d[4]), "+f"(d[5]), "+f"(d[6]), "+f"(d[7]), "+f"(d[8]), "+f"(d[9]), "+f"(d[10]), "+f"(d[11]), "+f"(d[12]), "+f"(d[13]), "+f"(d[14]), "+f"(d[15]), "+f"(d[16]), "+f"(d[17]), "+f"(d[18]), "+f"(d[19]), "+f"(d[20]), "+f"(d[21]), "+f"(d[22]), "+f"(d[23]), "+f"(d[24]), "+f"(d[25]), "+f"(d[26]), "+f"(d[27]), "+f"(d[28]), "+f"(d[29]), "+f"(d[30]), "+f"(d[31]), "+f"(d[32]), "+f"(d[33]), "+f"(d[34]), "+f"(d[35]), "+f"(d[36]), "+f"(d[37]), "+f"(d[38]), "+f"(d[39]), "+f"(d[40]), "+f"(d[41]), "+f"(d[42]), "+f"(d[43]), "+f"(d[44]), "+f"(d[45]), "+f"(d[46]), "+f"(d[47]), "+f"(d[48]), "+f"(d[49]), "+f"(d[50]), "+f"(d[51]), "+f"(d[52]), "+f"(d[53]), "+f"(d[54]), "+f"(d[55]), "+f"(d[56]), "+f"(d[57]), "+f"(d[58]), "+f"(d[59]), "+f"(d[60]), "+f"(d[61]), "+f"(d[62]), "+f"(d[63])
        : "l"(da), "l"(db), "n"(TA), "n"(TB));
}
template <int TA, int TB>
__device__ __forceinline__ void wgmma_ss128_first(float* d, uint64_t da, uint64_t db) {
    asm volatile("wgmma.mma_async.sync.aligned.m64n128k16.f32.bf16.bf16 "
        "{%0, %1, %2, %3, %4, %5, %6, %7, %8, %9, %10, %11, %12, %13, %14, %15, %16, %17, %18, %19, %20, %21, %22, %23, %24, %25, %26, %27, %28, %29, %30, %31, %32, %33, %34, %35, %36, %37, %38, %39, %40, %41, %42, %43, %44, %45, %46, %47, %48, %49, %50, %51, %52, %53, %54, %55, %56, %57, %58, %59, %60, %61, %62, %63}, %64, %65, 0, 1, 1, %66, %67;"
        : "=f"(d[0]), "=f"(d[1]), "=f"(d[2]), "=f"(d[3]), "=f"(d[4]), "=f"(d[5]), "=f"(d[6]), "=f"(d[7]), "=f"(d[8]), "=f"(d[9]), "=f"(d[10]), "=f"(d[11]), "=f"(d[12]), "=f"(d[13]), "=f"(d[14]), "=f"(d[15]), "=f"(d[16]), "=f"(d[17]), "=f"(d[18]), "=f"(d[19]), "=f"(d[20]), "=f"(d[21]), "=f"(d[22]), "=f"(d[23]), "=f"(d[24]), "=f"(d[25]), "=f"(d[26]), "=f"(d[27]), "=f"(d[28]), "=f"(d[29]), "=f"(d[30]), "=f"(d[31]), "=f"(d[32]), "=f"(d[33]), "=f"(d[34]), "=f"(d[35]), "=f"(d[36]), "=f"(d[37]), "=f"(d[38]), "=f"(d[39]), "=f"(d[40]), "=f"(d[41]), "=f"(d[42]), "=f"(d[43]), "=f"(d[44]), "=f"(d[45]), "=f"(d[46]), "=f"(d[47]), "=f"(d[48]), "=f"(d[49]), "=f"(d[50]), "=f"(d[51]), "=f"(d[52]), "=f"(d[53]), "=f"(d[54]), "=f"(d[55]), "=f"(d[56]), "=f"(d[57]), "=f"(d[58]), "=f"(d[59]), "=f"(d[60]), "=f"(d[61]), "=f"(d[62]), "=f"(d[63])
        : "l"(da), "l"(db), "n"(TA), "n"(TB));
}
template <int TB>
__device__ __forceinline__ void wgmma_rs128(float* d, const uint32_t* a, uint64_t db, uint32_t acc) {
    asm volatile("{\n.reg .pred P;\nsetp.ne.u32 P, %69, 0;\nwgmma.mma_async.sync.aligned.m64n128k16.f32.bf16.bf16 "
        "{%0, %1, %2, %3, %4, %5, %6, %7, %8, %9, %10, %11, %12, %13, %14, %15, %16, %17, %18, %19, %20, %21, %22, %23, %24, %25, %26, %27, %28, %29, %30, %31, %32, %33, %34, %35, %36, %37, %38, %39, %40, %41, %42, %43, %44, %45, %46, %47, %48, %49, %50, %51, %52, %53, %54, %55, %56, %57, %58, %59, %60, %61, %62, %63}, {%64, %65, %66, %67}, %68, P, 1, 1, %70;\n}"
        : "+f"(d[0]), "+f"(d[1]), "+f"(d[2]), "+f"(d[3]), "+f"(d[4]), "+f"(d[5]), "+f"(d[6]), "+f"(d[7]), "+f"(d[8]), "+f"(d[9]), "+f"(d[10]), "+f"(d[11]), "+f"(d[12]), "+f"(d[13]), "+f"(d[14]), "+f"(d[15]), "+f"(d[16]), "+f"(d[17]), "+f"(d[18]), "+f"(d[19]), "+f"(d[20]), "+f"(d[21]), "+f"(d[22]), "+f"(d[23]), "+f"(d[24]), "+f"(d[25]), "+f"(d[26]), "+f"(d[27]), "+f"(d[28]), "+f"(d[29]), "+f"(d[30]), "+f"(d[31]), "+f"(d[32]), "+f"(d[33]), "+f"(d[34]), "+f"(d[35]), "+f"(d[36]), "+f"(d[37]), "+f"(d[38]), "+f"(d[39]), "+f"(d[40]), "+f"(d[41]), "+f"(d[42]), "+f"(d[43]), "+f"(d[44]), "+f"(d[45]), "+f"(d[46]), "+f"(d[47]), "+f"(d[48]), "+f"(d[49]), "+f"(d[50]), "+f"(d[51]), "+f"(d[52]), "+f"(d[53]), "+f"(d[54]), "+f"(d[55]), "+f"(d[56]), "+f"(d[57]), "+f"(d[58]), "+f"(d[59]), "+f"(d[60]), "+f"(d[61]), "+f"(d[62]), "+f"(d[63])
        : "r"(a[0]), "r"(a[1]), "r"(a[2]), "r"(a[3]), "l"(db), "r"(acc), "n"(TB));
}
template <int TB>
__device__ __forceinline__ void wgmma_rs64(float* d, const uint32_t* a, uint64_t db, uint32_t acc) {
    asm volatile("{\n.reg .pred P;\nsetp.ne.u32 P, %37, 0;\nwgmma.mma_async.sync.aligned.m64n64k16.f32.bf16.bf16 "
        "{%0, %1, %2, %3, %4, %5, %6, %7, %8, %9, %10, %11, %12, %13, %14, %15, %16, %17, %18, %19, %20, %21, %22, %23, %24, %25, %26, %27, %28, %29, %30, %31}, {%32, %33, %34, %35}, %36, P, 1, 1, %38;\n}"
        : "+f"(d[0]), "+f"(d[1]), "+f"(d[2]), "+f"(d[3]), "+f"(d[4]), "+f"(d[5]), "+f"(d[6]), "+f"(d[7]), "+f"(d[8]), "+f"(d[9]), "+f"(d[10]), "+f"(d[11]), "+f"(d[12]), "+f"(d[13]), "+f"(d[14]), "+f"(d[15]), "+f"(d[16]), "+f"(d[17]), "+f"(d[18]), "+f"(d[19]), "+f"(d[20]), "+f"(d[21]), "+f"(d[22]), "+f"(d[23]), "+f"(d[24]), "+f"(d[25]), "+f"(d[26]), "+f"(d[27]), "+f"(d[28]), "+f"(d[29]), "+f"(d[30]), "+f"(d[31])
        : "r"(a[0]), "r"(a[1]), "r"(a[2]), "r"(a[3]), "l"(db), "r"(acc), "n"(TB));
}
template <int TB>
__device__ __forceinline__ void wgmma_rs16(float* d, const uint32_t* a, uint64_t db, uint32_t acc) {
    asm volatile("{\n.reg .pred P;\nsetp.ne.u32 P, %13, 0;\nwgmma.mma_async.sync.aligned.m64n16k16.f32.bf16.bf16 "
        "{%0, %1, %2, %3, %4, %5, %6, %7}, {%8, %9, %10, %11}, %12, P, 1, 1, %14;\n}"
        : "+f"(d[0]), "+f"(d[1]), "+f"(d[2]), "+f"(d[3]), "+f"(d[4]), "+f"(d[5]), "+f"(d[6]), "+f"(d[7])
        : "r"(a[0]), "r"(a[1]), "r"(a[2]), "r"(a[3]), "l"(db), "r"(acc), "n"(TB));
}

__device__ __forceinline__ uint32_t delay_loop(int n, uint32_t x0) {
    uint32_t z;
    asm volatile("{\n.reg .pred P;\n.reg .u32 c, x;\nmov.u32 c, %1;\nmov.u32 x, %2;\nDL: mad.lo.u32 x, x, 1664525, 1013904223;\nadd.u32 c, c, -1;\nsetp.gt.s32 P, c, 0;\n@P bra DL;\n"
                 "setp.eq.u32 P, x, 0x7fffffff;\nselp.u32 %0, 16, 0, P;\n}" : "=r"(z) : "r"(n), "r"(x0) : "memory");
    return z;
}
__device__ __forceinline__ uint32_t gtime() { uint32_t t; asm volatile("mov.u32 %0, %%globaltimer_lo;" : "=r"(t)); return t; }
__device__ __forceinline__ void wait_time(uint32_t t, uint32_t sb) { while ((int32_t)(gtime() - t) < (int32_t)delay_loop(2, sb)) {} }
__device__ __forceinline__ uint32_t tpc_gpc(uint32_t t) { return t < 32 ? t & 7 : t < 60 ? (t - 32) % 7 + 1 : (t - 54) & 7; }
__device__ __forceinline__ uint32_t latest_stamp(const uint32_t* p, uint32_t seq, uint32_t ref, int backoff, uint32_t sb) {
    for (int n = 0;; n++) {
        uint32_t bad = 0; int32_t m = INT32_MIN;
#pragma unroll
        for (int i = 0; i < 3; i++) { const uint32_t v = ld_relaxed1(p + i * 256); bad |= (v ^ seq) & 31u; m = max(m, (int32_t)(v - (ref << 5)) >> 5); }
        if (__all_sync(0xffffffffu, bad == 0)) return ref + __reduce_max_sync(0xffffffffu, m);
        wait_time(gtime() + backoff, sb);
        if (n > SPIN_LIMIT) spin_fault();
    }
}
__device__ __forceinline__ void release_at(uint32_t t, uint32_t sb, uint32_t bar, int lane) {
    wait_time(t, sb);
    if (lane == 0) mbar_arrive(sb + bar);
}
__host__ __device__ constexpr int frag_word(int u, int f) { return (u == 0 ? 0 : u < 3 ? 3 * u - 1 : u == 3 ? 14 : 3 * u - 4) + f; }
__host__ __device__ constexpr int word_col(int e) { return ((0x32FED987CBA65410ull >> (4 * e)) & 14) * 64 + ((0x32FED987CBA65410ull >> (4 * e)) & 1) * 8; }

constexpr uint32_t CLEAR_LO = 0xFE000000u, CLEAR_HI = 0x5A7FEFEFu;
__device__ __forceinline__ void clear_slot(const Params& P, int slot, int cta, int lane) {
    const int i = cta * 2 + (lane >> 3), x = i & 63;
    if (lane < 16) st_relaxed4(P.gm + slot * M_SLOT + (x >> 1) * 1024 + (x & 1) * 256 + (i >> 7) * 512 + ((i >> 6) & 1) * 128 + (lane & 7) * 16, CLEAR_LO, CLEAR_HI, CLEAR_LO, CLEAR_HI);
    st_relaxed4(g_f + slot * F_SLOT + cta * 512 + lane * 16, 0, 0, 0, 0);
}
__device__ __forceinline__ void mem0_max(const Params& P, uint32_t sb, int tid) {
    uint32_t m = 0;
#pragma unroll
    for (int i = 0; i < 4; i++) {
        const uint4 x = __ldg((const uint4*)P.mem0 + i * 256 + tid);
        m = __vmaxu2(__vmaxu2(__vmaxu2(x.x & 0x7fff7fffu, x.y & 0x7fff7fffu), __vmaxu2(x.z & 0x7fff7fffu, x.w & 0x7fff7fffu)), m);
    }
    sts32(sb + S_COEF + (tid >> 5) * 4, __reduce_max_sync(0xffffffffu, max(m >> 16, m & 0xffffu)));
    bar_arrive(7, 288);
}
__device__ __forceinline__ uint32_t pack_mem0(const Params& P, uint32_t sb, int cta, int lane) {
    bar_sync(7, 288);
    const uint32_t e = __reduce_max_sync(0xffffffffu, lds32(sb + S_COEF + (lane & 7) * 4)) >> 7;
    if (e < 64 || e > 192) return 0x3F803F80u;
    const int i = cta * 2 + (lane >> 4), u = (i >> 5), x = i & 63, L = (i & 3) * 8 + ((lane & 15) >> 1);
    uint64_t w = 32;
#pragma unroll
    for (int f = 0; f < 3; f++) if (f < 2 || u % 3) {
        const float v = __bfloat162float(P.mem0[(L >> 2) * 1024 + word_col(frag_word(u, f)) + ((i >> 2) & 7) * 16 + (L & 3) * 2 + (lane & 1)]);
        w += (uint64_t)(int64_t)__float2int_rn(v * __uint_as_float((271 - e) << 23)) << (45 - 19 * f);
    }
    st_relaxed2(P.gm + 7 * M_SLOT + (x >> 1) * 1024 + (x & 1) * 256 + (i >> 7) * 512 + ((i >> 6) & 1) * 128 + (lane & 15) * 8, (uint32_t)w, (uint32_t)(w >> 32));
    return (e - 30) * 0x00800080u;
}
__device__ __forceinline__ void pacer(const Params& P, const uint32_t sb, const int lane) {
    constexpr uint32_t base = 2;
    int cta = lds32(sb + S_CTA);
#pragma unroll 1
    for (int i = 0; i < 8; i++) clear_slot(P, i, cta, lane);
    __syncwarp();
    if (lane == 0) { uint32_t smid; asm("mov.u32 %0, %%smid;" : "=r"(smid)); st_relaxed1(g_hint + 6144 + cta, smid >> 1); }
    sts32(sb + S_EPOCH + 4, pack_mem0(P, sb, cta, lane));
    fence_release();
    __syncwarp();
    float rate = 0.58f;
    uint32_t c0 = 0;
#pragma unroll 1
    for (int s = -1; s < 63; s++) {
        cta = lds32(sb + S_CTA);
        const int pair = cta >> 1;
        const uint32_t ahead = s > 0 ? (uint32_t)(rate * (float)(pair >= 32 ? P.dc - P.dv : P.dc)) : 0;
        mbar_wait(sb + B_GO, s & 1);
        SSTAMP(10, lane == 0 && s == 0)
        const uint32_t t0 = gtime();
        if (lane < 4) st_relaxed1(g_hint + ((s & 1) * 4 + lane) * 768 + (cta >> 5) * 256 + (cta & 31), (t0 + ahead + (lds32(sb + S_REDO) == s ? P.extra : 0)) << 5 | ((base + s) & 31u));
        wait_time(t0 + (s < 0 ? 2000 : s == 0 && pair >= 16 ? P.ds0 : P.ds), sb);
        const uint32_t t = latest_stamp(g_hint + ((s & 1) * 4 + (pair & 3)) * 768 + lane, base + s, t0, P.back, sb);
        if (s < 0) {
            fence_acquire();
            const uint32_t g = tpc_gpc(ld_relaxed1(g_hint + 6144 + (lane & 15) * 2));
            const uint32_t key = (__popc(__match_any_sync(0xffffffffu, g)) > 4 ? 0 : g + 1) * 16 + (lane & 15);
            const uint32_t tail = (pair & 48) + __popc(__ballot_sync(0xffffffffu, key < __shfl_sync(0xffffffffu, key, pair & 15))) / 2;
            mbar_wait(sb + B_INIT, 0);
            SSTAMP(4, lane == 0)
            sts32(sb + S_TAIL, tail);
            if (lane < 8) sts32(sb + S_SC + lane * 4, lds32(sb + S_EPOCH + 4));
            __syncwarp();
        }
        release_at(t + P.da, sb, B_RELA, lane);
        SSTAMP(11, lane == 0 && s == 0)
        release_at(t + P.db, sb, B_RELB, lane);
        {
            const uint32_t c1 = clock(), g1 = gtime();
            if (s > 1) rate += P.alpha * (__fdividef((float)(g1 - lds32(sb + S_EPOCH + 4)), (float)(c1 - c0)) - rate);
            __syncwarp();
            c0 = c1; sts32(sb + S_EPOCH + 4, g1);
        }
        if (s == 61) {
            sts32(sb + S_COEF, ITEM(ITEM_OFF(lds32(sb + S_TAIL)) + NPRE + 1) + (uint32_t)(uintptr_t)P.out);
            if (lane < M_CQ) map_prefetch(&P.tm[lane]);
        }
    }
}
__device__ __forceinline__ uint32_t xor_or(uint32_t a, uint32_t b, uint32_t t) { uint32_t d; asm("lop3.b32 %0, %1, %2, %3, 0x7E;" : "=r"(d) : "r"(a), "r"(b), "r"(t)); return d; }
__device__ __forceinline__ bool tags_ok(uint32_t bad) { return __all_sync(0xffffffffu, (bad & 1) == 0); }
#define RETRY(k)
#define RETRY_STAT(a, b)
#define UNIT_STAT(u0)
#define KE 0
#define ES 0
#define Q3 1
#define SFENCE() asm volatile("pmevent 1;" ::: "memory")
#define PF1 10
static_assert(NS == 24, "fragment residency");
__host__ __device__ constexpr bool in_smem(int n) { return n < 4 || n == 12 || n == 13; }
__host__ __device__ constexpr int unit_pos(int n) { return n < 4 ? n : n < 12 ? n - 4 : n < 14 ? n - 8 : n - 6; }

__host__ __device__ constexpr int fill_unit(int q) { return q < 4 ? q : q < 6 ? q + 8 : q < 14 ? q - 2 : q; }
__host__ __device__ constexpr int frag_off(int q) { return (q >> 2) * 16384 + ((q >> 1) & 1) * 8192 + (q & 1) * 512; }

constexpr uint32_t QBITS = 0x4B002000u;
constexpr uint64_t W_BIAS = ((uint64_t)QBITS << 45) + ((uint64_t)QBITS << 26) + (uint32_t)(QBITS << 7), W_CLEAR = 0 - 32 * W_BIAS;
static_assert(W_CLEAR == ((uint64_t)CLEAR_HI << 32 | CLEAR_LO), "clear value");
__host__ __device__ constexpr int unit_off(int u) { return (u & 1) * 16384 + (u >> 2) * 512 + ((u >> 1) & 1) * 128; }
__device__ __forceinline__ void red_add64(const uint8_t* p, uint64_t v) { asm volatile("red.relaxed.gpu.global.add.u64 [%0], %1;" ::"l"(p), "l"(v) : "memory"); }
template <int NF>
__device__ __forceinline__ uint64_t encode(const float* x, float S, uint32_t two26, uint32_t& bad) {
    uint32_t b[3];
#pragma unroll
    for (int i = 0; i < 3; i++) b[i] = i < NF ? __float_as_uint(fmaf(x[i], S, 8396800.f)) : QBITS;
    bad = xor_or(b[0], b[1], 0x4B000000u) | (NF == 3 ? b[2] ^ 0x4B000000u : 0);
    uint64_t w;
    asm("{\n.reg .b64 t;\nmov.b64 t, {%2, %3};\nmad.wide.u32 %0, %1, %4, t;\n}" : "=l"(w) : "r"(b[1]), "r"(b[2] << 7), "r"(b[0] << 13), "r"(two26));
    return w;
}
template <int NF>
__device__ __forceinline__ void emit(uint64_t* w, const float (*x)[3], const float* S, uint32_t two26, uint32_t lim, const uint8_t* p) {
    uint32_t bad[2];
    w[0] = encode<NF>(x[0], S[0], two26, bad[0]); w[1] = encode<NF>(x[1], S[1], two26, bad[1]);
    const bool ok = (bad[0] | bad[1]) < lim;
    w[0] |= ok; w[1] |= ok;
    red_add64(p, w[0]); red_add64(p + 1024, w[1]);
}
template <int NF>
__device__ __forceinline__ void repair(const uint64_t* w, const float (*x)[3], const float* S, const uint8_t* p, const uint8_t* pf) {
    if (!(w[0] & 1)) {
#pragma unroll
        for (int j = 0; j < 2; j++) {
            const float T = S[j] * 8192.f;
            asm volatile("red.relaxed.gpu.global.add.v4.f32 [%0], {%1,%2,%3,%4};" ::"l"(pf + j * 512), "f"(x[j][0] * T), "f"(x[j][1] * T), "f"(NF == 3 ? x[j][2] * T : 0.f), "f"(0.f) : "memory");
        }
        fence_release();
#pragma unroll
        for (int j = 0; j < 2; j++) {
            asm volatile("red.relaxed.gpu.global.or.b64 [%0], 64;" ::"l"(p + j * 1024) : "memory");
            red_add64(p + j * 1024, W_BIAS + 1 - w[j]);
        }
    }
    __syncwarp();
}
__device__ __forceinline__ void ld_words(uint32_t* v, const uint8_t* p) {
    asm volatile("{\n.reg .b64 a, b;\nld.relaxed.gpu.global.L1::no_allocate.v2.b64 {a, b}, [%4];\nmov.b64 {%0,%1}, a;\nmov.b64 {%2,%3}, b;\n}" : "=r"(v[0]), "=r"(v[1]), "=r"(v[2]), "=r"(v[3]) : "l"(p) : "memory");
}
__device__ __forceinline__ float field(const uint32_t* w, int f) { return __int2float_rn((int)(f == 0 ? w[1] : f == 1 ? __funnelshift_l(w[0], w[1], 19) : w[0] << 6)); }
template <int U>
__device__ __forceinline__ void decode(uint32_t* b, const uint32_t* v) {
#pragma unroll
    for (int f = 0; f < (U % 3 ? 3 : 2); f++) b[frag_word(U, f)] = pack2(field(v, f), field(v + 2, f));
}
__device__ __forceinline__ uint32_t status(const uint32_t (*v)[4], uint32_t c32) { return xor_or(v[0][0], v[0][2], c32) | xor_or(v[1][0], v[1][2], c32) | xor_or(v[2][0], v[2][2], c32); }
__device__ __forceinline__ void gather_slow(const Params& P, uint32_t* b, const uint8_t* pm, int s, int warp, uint32_t ln, uint32_t u2) {
    if (s == 0 && u2 == 0x3F803F80u) {
#pragma unroll
        for (int i = 0; i < 16; i++) b[i] = __ldg((const uint32_t*)(P.mem0 + (ln >> 2) * 1024 + word_col(i) + warp * 16 + (ln & 3) * 2));
        return;
    }
    uint32_t v[6][4], st;
    for (int n = 0;; n++) {
#pragma unroll
        for (int u = 0; u < 6; u++) ld_words(v[u], pm + unit_off(u));
        st = status(v, 32) | status(v + 3, 32);
        if (!__any_sync(0xffffffffu, st & 32)) break;
        __nanosleep(200);
        if (n > SPIN_LIMIT) spin_fault();
    }
    const bool side = __any_sync(0xffffffffu, st & 64);
    if (side) fence_acquire();
    const uint8_t* pf = g_f + ((s + 7) & 7) * F_SLOT + warp * 1024 + ln * 32;
#pragma unroll
    for (int u = 0; u < 6; u++) {
        float x[2][4] = {};
#pragma unroll
        for (int k = 0; k < 2; k++)
            asm volatile("{\n.reg .pred P;\nsetp.ne.u32 P, %5, 0;\n@P ld.relaxed.gpu.global.v4.f32 {%0,%1,%2,%3}, [%4];\n}"
                         : "+f"(x[k][0]), "+f"(x[k][1]), "+f"(x[k][2]), "+f"(x[k][3]) : "l"(pf + u * 8192 + k * 16), "r"((uint32_t)side) : "memory");
#pragma unroll
        for (int f = 0; f < (u % 3 ? 3 : 2); f++) b[frag_word(u, f)] = pack2(field(v[u], f) + x[0][f], field(v[u] + 2, f) + x[1][f]);
    }
}
__device__ __forceinline__ uint32_t max_abs2(uint32_t a, uint32_t b) { uint32_t d; asm("max.NaN.xorsign.abs.bf16x2 %0, %1, %2;" : "=r"(d) : "r"(a), "r"(b)); return d; }
__device__ __forceinline__ uint32_t max6(const uint32_t* b) {
    const uint32_t m = max_abs2(max_abs2(max_abs2(b[0], b[1]), max_abs2(b[2], b[3])), max_abs2(b[4], b[5]));
    return max(m & 0x7fff0000u, (m << 16) & 0x7fff0000u);
}

template <bool TR>
__device__ __forceinline__ void put_partials(uint32_t a, const float* x, const float* y) {
    if (TR) stsm4t(a, pack2(x[0], x[1]), pack2(x[2], x[3]), pack2(y[0], y[1]), pack2(y[2], y[3]));
    else stsm4(a, pack2(x[0], x[1]), pack2(x[2], x[3]), pack2(y[0], y[1]), pack2(y[2], y[3]));
}
__device__ __forceinline__ void reduce_load(uint32_t (*x)[4], uint32_t a) { ldsm4t(x[0], a); ldsm4t(x[1], a + 512); }
__device__ __forceinline__ uint32_t reduce8(const uint32_t (*x)[4], uint32_t l8, uint32_t u2) {
    uint32_t p[2];
#pragma unroll
    for (int i = 0; i < 2; i++) {
        float d[4] = {};
        mma16816(d, x[i][0], x[i][1], x[i][2], x[i][3], (l8 & 32) ? 0u : u2, (l8 & 32) ? u2 : 0u);
        p[i] = pack2((l8 & 8) ? d[2] : d[0], (l8 & 8) ? d[3] : d[1]);
    }
    return (l8 & 16) ? p[1] : p[0];
}
__device__ __forceinline__ void score_half(float (*a)[4], const uint32_t (*qa)[4], const uint32_t (*kf)[4]) {
#pragma unroll
    for (int w = 0; w < 2; w++) {
        mma16816(a[w], qa[w][0], qa[w][1], qa[w][2], qa[w][3], kf[w][0], kf[w][1]);
        mma16816(a[2 + w], qa[w][0], qa[w][1], qa[w][2], qa[w][3], kf[w][2], kf[w][3]);
    }
}
__device__ __forceinline__ void score_sum(float* S, const float (*a)[4]) {
    S[0] = (a[0][0] + a[1][0]) + (a[2][2] + a[3][2]);
    S[1] = (a[0][1] + a[1][1]) + (a[2][3] + a[3][3]);
}
__device__ __forceinline__ float quad_max(float m) {
    return fmaxf(fmaxf(m, __shfl_xor_sync(0xffffffffu, m, 1)), fmaxf(__shfl_xor_sync(0xffffffffu, m, 2), __shfl_xor_sync(0xffffffffu, m, 3)));
}

#define ISTAMP(i)
__device__ __forceinline__ float next_scale(uint32_t sb, int slot, int warp, uint32_t u2) {
    uint32_t x[2][4];
    lds128(x[0], sb + S_MX + slot * 32); lds128(x[1], sb + S_MX + slot * 32 + 16);
    const uint32_t mx = max(max(max(x[0][0], x[0][1]), max(x[0][2], x[0][3])), max(max(x[1][0], x[1][1]), max(x[1][2], x[1][3])));
    const float top = fminf(fmaxf(__uint_as_float(mx) * bf_hi(u2), 0x1p-40f), 0x1p40f) * (1.f / (12288.f * 8192.f));
    const uint32_t un = pack2(top, top);
    sts32(sb + S_SC + warp * 4, un);
    return rcp(bf_hi(un) * 8192.f);
}
#define NEARLY 1
#define U3POS 1
#define VPOS 1
#define ROT 0
#define BPOS 1
#define ONLINE 0
#define NBAR 1
#define ORD3 0
#define F2 1
#define EARLY 0
#define TK 0
#define OBN 4
#define CH4 1
#define RPOS 1
#define AF 0
#define AFENCE(i) if ((AF >> (i)) & 1) SFENCE();
#define FPOS 99
#define PACE 1
#define PF2 12
__host__ __device__ constexpr int w2_t(int i) { return i < 16 ? i & 1 : 2; }
__host__ __device__ constexpr int w2_k(int i) { return i < 16 ? i >> 1 : i - 16; }
template <typename G>
__device__ __forceinline__ void load_weights(uint32_t (*wr)[4], const uint32_t sb, const int warp, const int lane, G stores_read) {
    const uint32_t frag = sb + warp * 1024 + (lane >> 4) * 8192 + (lane & 7) * 128 + ((((lane >> 3) & 1) ^ (lane & 7)) << 4);
    const uint32_t rel = mapa(sb + B_EMPTY, cluster_rank() ^ (lane & 1));
#define RELEASE(st) { if ((st) >= 2) fence_async_smem(); __syncwarp(); if (lane < 2) mbar_arrive_cluster(rel + (st) * 8); }
    mbar_wait(sb + B_FULL, 0); mbar_wait(sb + B_FULL + 8, 0);
    RELEASE(0) RELEASE(1)
#pragma unroll
    for (int st = 2; st < 4; st++) {
        mbar_wait(sb + B_FULL + st * 8, 0);
        ISTAMP(st - 2)
#pragma unroll
        for (int f = 0; f < 12; f++) ldsm4t(wr[st * 12 - 24 + f], (frag ^ ((f & 3) << 5)) + st * STAGE + (f >> 2) * 16384);
        RELEASE(st)
    }
#pragma unroll 2
    for (int u = 0; u < 6; u++) {
        uint32_t x[4][4];
#pragma unroll
        for (int i = 0; i < 4; i++) lds128(x[i], (frag ^ (i << 5)) + u * 16384);
        __syncwarp();
#pragma unroll
        for (int i = 0; i < 4; i++) sts128(sb + warp * 1024 + lane * 16 + u * 16384 + frag_off(i), x[i]);
    }
    SSTAMP(0, threadIdx.x == 0)
    stores_read();
    SSTAMP(2, threadIdx.x == 0)
    mbar_wait(sb + B_FULL, 1); mbar_wait(sb + B_FULL + 8, 1);
    RELEASE(0) RELEASE(1)
#pragma unroll
    for (int st = 2; st < 4; st++) {
        mbar_wait(sb + B_FULL + st * 8, 1);
#pragma unroll
        for (int f = 0; f < (st == 2 ? 12 : 4); f++) ldsm4t(wr[st * 12 + f], (frag ^ ((f & 3) << 5)) + st * STAGE + (f >> 2) * 16384);
        RELEASE(st)
    }
    ISTAMP(2)
    bar_sync(1, 256);
    if (warp == 7 && lane < 3) mbar_arrive_cluster(mapa(sb + B_INIT, (cluster_rank() & 1) + lane * 2));
}
template <int ROLE>
__device__ __forceinline__ void chain_role(const Params& P, const uint32_t (*wr)[4], const uint32_t sb, const int h, const int warp, const int lane) {
    constexpr int NU = ROLE == 0 ? 2 : 3;
    const bool att = ROLE == 0 && warp < 4;
    uint32_t l8 = opq(sb + lane * 8, lane);
#define PERSIST() { mbar_wait(sb + B_KVGO, slot ^ 1); const uint32_t pa_ = ((l8 - sb) >> 1) + (sb + S_QX + warp * 128); sts32(pa_, r0); sts32(pa_ + 1024, r1); \
                    fence_async_smem(); __syncwarp(); if (l8 == sb) mbar_arrive(sb + B_PERS); }
    if (ROLE) sts32(sb + S_SX + warp * 128 + lane * 4, warp >= 2 ? 0 : (lane & 1) ? CLEAR_HI : CLEAR_LO);
    const uint32_t rdelta = __shfl_sync(0xffffffffu, mapa(sb, (cluster_rank() + (ROLE == 1 ? 4 : 2)) % 6) - sb, 0);
    const uint32_t vdelta = ROLE ? 0 : __shfl_sync(0xffffffffu, mapa(sb, (cluster_rank() + 4) % 6) - sb, 0);
    ISTAMP(3)
    __syncwarp();
#define GATHER_OFF(s) ((((s) + 7) & 7) * M_SLOT + warp * 2048 + (l8 & 56) * 2 + (l8 & 64) * 4 + (l8 & 128) * 8)
    uint32_t mo = GATHER_OFF(0);
    if (ROT) mbar_wait(sb + B_RELA, 0);
    for (int s = 0; s < (ROLE == 0 ? 63 : 64);) {
        const int slot = s & 1;
        l8 += s & P.zero;
        const uint32_t w1a = l8 * 2 + (S_W1 + warp * 1024 - sb);
        PROF(9)
        uint32_t u2, r0, r1, pld, pub, pbar, x[2][4];
        {
#define pm (P.gm + mo)
            uint32_t as[24][4], b[16], v[6][4];
            float acc[8][4];
#define W1LD(n) _Pragma("unroll") for (int i_ = 0; i_ < 4; i_++) ldsm4t(as[unit_pos(n) * 4 + i_], w1a + frag_off(unit_pos(n) * 4 + i_));
#define W1LD2(n, p) { const uint32_t wa_ = w1a + (as[unit_pos(p) * 4][0] & as[unit_pos(p) * 4 + 1][0] & as[unit_pos(p) * 4 + 2][0] & as[unit_pos(p) * 4 + 3][0] & P.zero); \
                      _Pragma("unroll") for (int i_ = 0; i_ < 4; i_++) ldsm4t(as[unit_pos(n) * 4 + i_], wa_ + frag_off(unit_pos(n) * 4 + i_)); }
#define W1MMA(n) _Pragma("unroll") for (int i_ = 0; i_ < 4; i_++) { const uint32_t* a_ = in_smem(n) ? as[unit_pos(n) * 4 + i_] : wr[unit_pos(n) * 4 + i_]; \
                                                                   mma16816(acc[((n) & 1) * 4 + i_], a_[0], a_[1], a_[2], a_[3], b[(n) & 14], b[(n) | 1]); }
#pragma unroll
            for (int T = 0; T < 8; T++) { acc[T][0] = acc[T][1] = acc[T][2] = acc[T][3] = 0.f; }
            if (!ROT) mbar_wait(sb + B_RELA, slot);
            PROF(12)
#pragma unroll
            for (int u = 0; u < 3; u++) ld_words(v[u], pm + unit_off(u));
            __syncwarp();
#pragma unroll
            for (int i = 0; i < PF1; i++) ldsm4t(as[i], w1a + frag_off(i));
            __syncwarp();
            mo += mbar_try(sb + B_RELB, slot) & P.zero;
            PROF(13)
#pragma unroll
            for (int u = 3; u < 6; u++) ld_words(v[u], pm + unit_off(u));
            uint32_t st = status(v, ((uint32_t)((uintptr_t)pm >> 32) & P.zero) + 32);
            pin<1>(&st);
            SFENCE();
            UNIT_STAT(0)
            PROF(0)
            decode<0>(b, v[0]); decode<1>(b, v[1]); decode<2>(b, v[2]);
#pragma unroll
            for (int i = PF1; i < 12; i++) ldsm4t(as[i], w1a + frag_off(i));
            W1MMA(0) W1MMA(1) W1MMA(2)
            if (TK & 1) W1LD2(3, 2) else { W1LD(3) }
            SFENCE();
            if (TK & 8) { W1MMA(5) W1MMA(4) W1MMA(3) W1MMA(6) } else { W1MMA(5) W1MMA(4) W1MMA(6) W1MMA(3) }
            if (U3POS == 0) W1MMA(7)
            if (TK & 2) W1LD2(12, 3) else { W1LD(12) }
            uint32_t mx = max6(b);
            pin<1>(&mx);
            SFENCE();
            PROF(10)
            if (U3POS == 1) W1MMA(7)
            const uint32_t mxa = sb + S_MX + slot * 32 + warp * 4;
            sts32(mxa, __reduce_max_sync(0xffffffffu, mx));
            UNIT_STAT(3)
            st |= status(v + 3, 32);
            const bool redo = __any_sync(0xffffffffu, st & 96);
            const bool kvok = ROLE || mbar_test(sb + B_KVFULL + slot * 8, (s >> 1) & 1);
            decode<4>(b, v[4]); decode<5>(b, v[5]); decode<3>(b, v[3]);
            u2 = lds32(sb + S_SC + warp * 4);
            W1MMA(8) W1MMA(10) if (ORD3) { W1MMA(14) W1MMA(12) } else { W1MMA(12) W1MMA(14) }
            if (TK & 4) W1LD2(13, 12) else { W1LD(13) }
            if (__builtin_expect(redo || !kvok, 0)) {
                if (redo) {
                    RETRY(3)
                    sts32(sb + S_REDO, s);
                    gather_slow(P, b, P.gm + GATHER_OFF(s), s, warp, (l8 - sb) >> 3, u2);
                    sts32(mxa, __reduce_max_sync(0xffffffffu, max6(b)));
#pragma unroll
                    for (int T = 0; T < 8; T++) { acc[T][0] = acc[T][1] = acc[T][2] = acc[T][3] = 0.f; }
#pragma unroll
                    for (int n = 0; n < 15; n += n < 8 ? 1 : 2) {
                        if (in_smem(n)) { W1LD(n) }
                        W1MMA(n)
                    }
                    W1LD(13)
                }
                if (ROLE == 0) mbar_wait(sb + B_KVFULL + slot * 8, (s >> 1) & 1);
            }
#undef pm
            SSTAMP(7, threadIdx.x == 0 && s == 0)
            PROF(14)
            const uint32_t pst = (l8 - sb) * 16 + ((warp * 16) ^ ((l8 * 2) & 112)) + (sb + S_P1);
            put_partials<ROLE == 2>(pst, acc[0], acc[1]); put_partials<ROLE == 2>(pst + 4096, acc[2], acc[3]);
            W1MMA(9)
            SFENCE();
            pld = (l8 & 64) * 4 + (l8 & 128) + (l8 & 56) * 2 + (sb + S_P1 + warp * 1024);
            const uint32_t rd = s == 63 ? 0 : rdelta;
            pub = ((l8 - sb) >> 1) + (ROLE ? sb + rd + (ROLE == 1 ? S_KL : S_VL) + warp * 128 : sb + S_QX + (warp & 4) * 128 + (warp & 1) * 256 + (warp & 2) * 64);
            pbar = sb + rd + (ROLE == 1 && s != 63 ? B_K : B_V);
#define PUBLISH0() { r0 = reduce8(x, l8, u2); if (ROLE) st_async1(pub, r0, KE && ROLE == 1 && s != 63 ? pbar + (B_PERS - B_K) : pbar); else sts32(pub, r0); }
            if (RPOS == 0) { bar_sync(1, 256); reduce_load(x, pld); SFENCE(); }
            W1MMA(11)
            if (RPOS == 1) { bar_sync(1, 256); reduce_load(x, pld); }
            if (RPOS != 2 || F2) SFENCE();
#define W1MMH(n, o) _Pragma("unroll") for (int i_ = o; i_ < o + 2; i_++) { const uint32_t* a_ = in_smem(n) ? as[unit_pos(n) * 4 + i_] : wr[unit_pos(n) * 4 + i_]; \
                                                                   mma16816(acc[((n) & 1) * 4 + i_], a_[0], a_[1], a_[2], a_[3], b[(n) & 14], b[(n) | 1]); }
            if (ES) { W1MMH(15, 0) W1MMH(15, 2) W1MMH(13, 0) } else W1MMA(15)
            if (RPOS == 0) PUBLISH0()
            if (RPOS == 2) { bar_sync(1, 256); reduce_load(x, pld); }
            if (RPOS != 1 || F2) SFENCE();
            if (ES) { W1MMH(13, 2) put_partials<ROLE == 2>(pst + 8192, acc[4], acc[5]); } else W1MMA(13)
            if (RPOS == 1) PUBLISH0()
            if (!ES) put_partials<ROLE == 2>(pst + 8192, acc[4], acc[5]);
            put_partials<ROLE == 2>(pst + 12288, acc[6], acc[7]);
            if (RPOS == 2) PUBLISH0()
        }
        SSTAMP(8, threadIdx.x == 0 && s == 0)
        PROF(1)
        if (ROLE) {
            bar_sync(1, 256);
            reduce_load(x, pld + 8192);
            r1 = reduce8(x, l8, u2);
            st_async1(pub + 1024, r1, pbar);
            if (s == 63) {
                PERSIST()
                mbar_wait(sb + B_V, 0);
                break;
            }
            PROF(2)
        }
        uint32_t ln, w2a, ro;
#define W2ADDR(late) { l8 += pub & P.zero; ln = (l8 - sb) >> 3; \
        w2a = sb + S_W2 + (ROLE ? (warp >> 2) * 16384 : late * 32768) + ((((ln & 7) + (ln >> 4) * 8) * 128 + ((((ln >> 3) & 1) ^ (ln & 7)) << 4)) ^ ((warp & 3) << 5)); \
        ro = (s & 7) * M_SLOT + (ROLE ? warp * 2048 + unit_off(ROLE) : (warp & 3) * 2048 + late * unit_off(3)) + (ln & 2) * 128 + (ln & 1) * 64 + (ln >> 2) * 8; }
        constexpr int RO2 = ROLE ? unit_off(ROLE + 3) - unit_off(ROLE) : 8192;
        float Sj[2];
        uint32_t w[24][4], ob[4][4];
        float S;
#define W2LD(i) ldsm4t(w[i], w2a + w2_t(i) * (ROLE ? 32768 : 16384) + (w2_k(i) & 1) * 8192 + (w2_k(i) >> 1) * 2048)
#define W2MMA(d, i) mma16816(d, w[i][0], w[i][1], w[i][2], w[i][3], ob[w2_k(i) >> 1][(w2_k(i) & 1) * 2], ob[w2_k(i) >> 1][(w2_k(i) & 1) * 2 + 1])
#define LEADER(wp) (l8 == sb + ((wp) - warp) * 256)
        if (att) {
            const float cs = 0.08838834764831845f * 1.4426950408889634f;
            uint32_t qa[4][4], kf[4][4], vf[4][4], vv[4];
            float T[5][2], sa[4][4] = {};
            const uint32_t l16 = l8 * 2 - sb;
            const uint32_t kaddr = (l8 & 56) * 16 + (((l8 >> 2) ^ (l8 * 2)) & 48) + ((l8 * 2) & 64) + (sb + S_KV + warp * 1024 + slot * 16384);
            bar_sync(1, 256);
            reduce_load(x, pld + 8192);
            __syncwarp();
#pragma unroll
            for (int i = 0; i < 2; i++) { ldsm4(qa[i], l16 + S_QX + i * 512); ldsm4(kf[i], kaddr ^ (i * 64)); }
            AFENCE(0)
            sts32(pub + 1024, reduce8(x, l8, u2));
            __syncwarp();
#pragma unroll
            for (int i = 2; i < 4; i++) ldsm4(kf[i], (kaddr ^ ((i & 1) * 64)) + 4096);
            score_half(sa, qa, kf);
            bar_sync(2, 256);
            PROF(2)
#pragma unroll
            for (int i = 2; i < 4; i++) ldsm4(qa[i], l16 + S_QX + i * 512);
            float sm[4][4] = {};
            const bool kearly = KE && mbar_try(sb + B_PERS, slot);
            score_half(sa, qa + 2, kf + 2);
            score_sum(T[0], sa);
            sts64(l8 + S_SX + warp * 256, __float_as_uint(T[0][0]), __float_as_uint(T[0][1]));
            PROF(4)
            if (KE) {
                if (!kearly) mbar_wait(sb + B_PERS, slot);
                ldsm4(kf[0], l16 + S_KL); ldsm4(kf[1], l16 + S_KL + 512);
                score_half(sm, qa, kf);
            }
            if (BPOS == 0) bar_sync(4, 128);
            mbar_wait(sb + B_K, slot);
            PROF(11)
#pragma unroll
            for (int i = KE ? 2 : 0; i < 4; i++) ldsm4(kf[i], l16 + S_KL + i * 512);
            if (BPOS == 1) bar_sync(4, 128); else __syncwarp();
#pragma unroll
            for (int n = 0; n < 4; n++) lds64f(T[n], l8 + S_SX + n * 256);
            if (!KE) score_half(sm, qa, kf);
            score_half(sm, qa + 2, kf + 2);
            const uint32_t vaddr = (l8 & 56) * 16 + (l8 & 128) * 8 + (((warp & 1) * 64 + ((l8 >> 2) & 16)) ^ ((l8 * 2) & 112)) + (sb + S_KV + 8192 + (warp >> 1) * 4096 + slot * 16384);
            float mx = fmaxf(fmaxf(fmaxf(T[0][0], T[0][1]), fmaxf(T[1][0], T[1][1])), fmaxf(fmaxf(T[2][0], T[2][1]), fmaxf(T[3][0], T[3][1])));
            score_sum(T[4], sm);
            float m = quad_max(fmaxf(mx, fmaxf(T[4][0], T[4][1])));
            if (VPOS == 0) {
#pragma unroll
                for (int i = 0; i < 4; i++) ldsm4t(vf[i], (vaddr ^ ((i & 1) << 5)) + (i >> 1) * 2048);
            }
            mbar_wait(sb + B_V, slot);
            if (VPOS == 1) {
#pragma unroll
                for (int i = 0; i < 4; i++) ldsm4t(vf[i], (vaddr ^ ((i & 1) << 5)) + (i >> 1) * 2048);
            }
            ldsm4(vv, l16 + S_VL + warp * 512);
            uint32_t pa[5];
            m *= cs;
#pragma unroll
            for (int n = 0; n < 5; n++) { T[n][0] = ex2(fmaf(T[n][0], cs, -m)); T[n][1] = ex2(fmaf(T[n][1], cs, -m)); pa[n] = pack2(T[n][0], T[n][1]); }
            float sum = (((T[0][0] + T[0][1]) + (T[1][0] + T[1][1])) + ((T[2][0] + T[2][1]) + (T[3][0] + T[3][1]))) + (T[4][0] + T[4][1]);
            PROF(3)
            W2ADDR(1)
            const uint32_t lo = sb + S_O + warp * 512 + (ln & 3) * 64 + (ln >> 2) * 8, ls = sb + S_SUM + (ln & 3) * 32 + (ln & 4) * 4 + (ln >> 3) * 4;
            const uint32_t sdelta = warp < 2 ? rdelta : vdelta;
            if (Q3 & 2) sum = (sum + __shfl_xor_sync(0xffffffffu, sum, 1)) + (__shfl_xor_sync(0xffffffffu, sum, 2) + __shfl_xor_sync(0xffffffffu, sum, 3));
            else { sum += __shfl_xor_sync(0xffffffffu, sum, 1); sum += __shfl_xor_sync(0xffffffffu, sum, 2); }
            float O[2][4];
#pragma unroll
            for (int i = 0; i < 2; i++) { O[i][0] = O[i][1] = O[i][2] = O[i][3] = 0.f; }
#pragma unroll
            for (int i = 0; i < 2; i++) {
                mma16816(O[0], vf[2 * i][0], vf[2 * i][1], vf[2 * i][2], vf[2 * i][3], pa[2 * i], pa[2 * i + 1]);
                mma16816(O[1], vf[2 * i + 1][0], vf[2 * i + 1][1], vf[2 * i + 1][2], vf[2 * i + 1][3], pa[2 * i], pa[2 * i + 1]);
            }
            mma1688(O[0], vv[0], vv[1], pa[4]);
            mma1688(O[1], vv[2], vv[3], pa[4]);
            uint32_t o[2][2];
#pragma unroll
            for (int j = 0; j < 2; j++) { o[j][0] = pack2(O[0][j], O[0][2 + j]); o[j][1] = pack2(O[1][j], O[1][2 + j]); }
#pragma unroll
            for (int j = 0; j < 2; j++) st_async2(lo + rdelta + j * 256, o[j][0], o[j][1], sb + rdelta + B_K);
            st_async1(ls + sdelta + (warp & 1) * 128, __float_as_uint(sum), sb + sdelta + B_K);
#pragma unroll
            for (int j = 0; j < 2; j++) st_async2(lo + vdelta + j * 256, o[j][0], o[j][1], sb + vdelta + B_K);
#pragma unroll
            for (int j = 0; j < 2; j++) sts64(lo + j * 256, o[j][0], o[j][1]);
            sts32(ls + warp * 128, __float_as_uint(sum));
            PROF(5)
            bar_sync(3, 256);
            if (LEADER(0)) { mbar_expect(sb + B_K, KE ? 1024 : 2048); if (KE) mbar_expect(sb + B_PERS, 1024); mbar_expect(sb + B_V, 2048); mbar_arrive(sb + B_KVGO + slot * 8); }
            S = next_scale(sb, slot, warp, u2);
            if (s == 0) mbar_wait(sb + B_WO, 0);
            pin<1>(&S);
            SFENCE();
#pragma unroll
            for (int j = 0; j < 4; j++) lds128(ob[j], l8 * 2 - sb + S_O + j * 512);
            lds64f(Sj, sb + S_SUM + (l8 & 24));
#pragma unroll
            for (int i = 0; i < PF2; i++) W2LD(i);
        } else {
            if (ROLE == 0) { bar_sync(1, 256); reduce_load(x, pld + 8192); sts32(pub + 1024, reduce8(x, l8, u2)); bar_arrive(2, 256); }
            if (LEADER(7)) { if (s) mbar_arrive(sb + B_GO); if (ROLE) mbar_expect(sb + B_K, 2304); }
            S = next_scale(sb, slot, warp, u2);
            if (s == 0) mbar_wait(sb + B_WO, 0);
            if (ROLE != 0) PERSIST()
            W2ADDR(0)
#pragma unroll
            for (int i = 0; i < PF2; i++) {
                W2LD(i);
                if (ROLE == 0 && (i & PACE) == PACE) w2a += w[i][0] & P.zero;
            }
            ro = opq(ro, ln);
            const uint32_t sa = opq(sb + S_SUM + (l8 & 24), ln), oa = opq(l8 * 2 - sb + S_O, ln);
            if (ROLE == 0) bar_sync(3, 256); else mbar_wait(sb + B_K, slot);
            if (OBN == 4 || !ROLE) lds64f(Sj, sa);
#pragma unroll
            for (int j = 0; j < 4; j++) { if (ROLE && j == OBN) SFENCE(); lds128(ob[j], oa + j * 512); }
            if (OBN < 4 && ROLE) lds64f(Sj, sa);
        }
        SSTAMP(9, threadIdx.x == 224 && s == 0)
        if (OBN == 4 || !ROLE) SFENCE();
        PROF(6)
        {
            const uint8_t* pr = P.gm + ro;
            float c[4][4];
            uint32_t lim = 0;
#pragma unroll
            for (int i = 0; i < 4; i++) { c[i][0] = c[i][1] = c[i][2] = c[i][3] = 0.f; }
#pragma unroll
            for (int i = 0; i < 16; i++) {
                W2MMA(c[i & (ROLE && !CH4 ? 1 : 3)], i);
                if (i + PF2 < (ROLE ? 16 + NEARLY : 16)) W2LD(i + PF2);
                if (i == 5) {
                    const uint32_t z = __float_as_uint(c[1][0]) & P.zero;
                    Sj[0] = S * rcp(__uint_as_float(__float_as_uint(Sj[0]) | z)); Sj[1] = S * rcp(__uint_as_float(__float_as_uint(Sj[1]) | z));
                }
                if (i == 5) lim = __any_sync(0xffffffffu, fmaxf(fmaxf(fabsf(c[0][0]), fabsf(c[0][2])), fmaxf(fabsf(c[1][0]), fabsf(c[1][2]))) * Sj[0] >= (ROLE && !CH4 ? 24.f : 20.f)) ? 16384 : 0;
                if (i == FPOS) { pin<1>(&lim); pin<2>(Sj); pin_ptr(pr); SFENCE(); }
            }
            if (ROLE == 0 || CH4) {
#pragma unroll
                for (int i = 0; i < 8; i++) { c[i >> 2][i & 3] += c[2 + (i >> 2)][i & 3]; c[2 + (i >> 2)][i & 3] = 0.f; }
            }
            const float xa[2][3] = {{c[0][0], c[0][2], c[1][0]}, {c[0][1], c[0][3], c[1][1]}};
            uint64_t wa[2], wb[2];
            emit<NU>(wa, xa, Sj, P.two26, lim, pr);
            PROF(7)
            mo = GATHER_OFF(s + 1);
            pin<1>(&mo);
            if (ROLE) {
                SFENCE();
#pragma unroll
                for (int i = 16 + NEARLY; i < 24; i++) { if (i == 16 + NBAR) bar_sync(2, 256); W2LD(i); __syncwarp(); }
                SFENCE();
#pragma unroll
                for (int i = 16; i < 24; i++) W2MMA(c[2 + (i & 1)], i);
#pragma unroll
                for (int i = 0; i < 4; i++) c[2][i] += c[3][i];
            }
            const float y[2][3] = {{ROLE ? c[1][2] : c[1][0], ROLE ? c[2][0] : c[1][2], c[2][2]}, {ROLE ? c[1][3] : c[1][1], ROLE ? c[2][1] : c[1][3], c[2][3]}};
            const bool released = !ROT || mbar_test(sb + B_RELA, slot ^ 1);
            emit<NU>(wb, y, Sj, P.two26, lim, pr + RO2);
            PROF(8)
            if (!__all_sync(0xffffffffu, (wa[0] & wb[0] & 1) && released && s)) {
                if (__builtin_expect(!__all_sync(0xffffffffu, wa[0] & wb[0] & 1), 0)) {
                    RETRY(5)
                    const uint8_t* pf = g_f + (s & 7) * F_SLOT + (ROLE ? ROLE * 8192 + warp * 1024 : (warp & 3) * 1024 + (att ? 24576 : 0)) + (ln & 3) * 128 + (ln >> 2) * 16;
                    repair<NU>(wa, xa, Sj, pr, pf);
                    repair<NU>(wb, y, Sj, pr + RO2, pf + (ROLE ? 24576 : 4096));
                }
                if (s == 0) { bar_sync(1, 256); if (LEADER(7)) mbar_arrive(sb + B_GO); }
                if (ROT) mbar_wait(sb + B_RELA, slot ^ 1);
            }
        }
        s++;
    }
}
struct Pipe { uint32_t stage, phase; };
struct Cons {
    uint32_t sb, rel;
    int wg, wq, lane, rank, pair;
    uint32_t nst;
    Pipe p;
};
__device__ __forceinline__ void pipe_next(Pipe& p) { p.stage = (p.stage + 1) & (NSTAGE - 1); p.phase ^= (p.stage == 0); }
__device__ __forceinline__ void release(const Cons& c, uint32_t stage) { if (c.lane < 2) mbar_arrive_cluster(c.rel + stage * 8); }

enum { PEND_NONE = 0, PEND_KVO = 1, PEND_HT = 2, PEND_OUT = 3, PEND_OUTH = 4 };
struct Pend { uint32_t pk[64]; int kind, row, col, cnt; };

__device__ __forceinline__ void staging_wait(const Cons& c) { if (c.nst) mbar_wait(c.sb + B_SFREE + c.wg * 8, (c.nst - 1) & 1); }
__device__ __forceinline__ void staging_post(Cons& c, int kind, int row, int col, int cnt) {
    __syncwarp();
    if (c.lane == 0) {
        if (c.wq == 0) { const uint32_t x[4] = {(uint32_t)kind, (uint32_t)row, (uint32_t)col, (uint32_t)cnt}; sts128(c.sb + S_DESC + c.wg * 16, x); }
        mbar_arrive(c.sb + B_SFULL + c.wg * 8);
    }
    c.nst++;
}
template <int HF, bool KVONLY = false>
__device__ __forceinline__ void drain(const Params& P, Cons& c, const Pend& d) {
    const uint32_t* pk = d.pk + HF * 32;
    if (!KVONLY && d.kind >= PEND_OUT) {
        if (HF == 1 && d.kind == PEND_OUTH) return;
        float* o = P.out + (size_t)(d.row + c.wq * 16 + (c.lane >> 2)) * 2048 + d.col + HF * 128 + (c.lane & 3) * 2;
#pragma unroll
        for (int j = 0; j < 16; j++) {
            st_stream2(o + j * 8, bf_lo(pk[j * 2]), bf_hi(pk[j * 2]));
            st_stream2(o + 8 * 2048 + j * 8, bf_lo(pk[j * 2 + 1]), bf_hi(pk[j * 2 + 1]));
        }
    } else if (d.kind != PEND_NONE) {
        const bool ht = !KVONLY && d.kind == PEND_HT;
        const int hi = (c.lane >> 3) & 1;
        const uint32_t base = c.sb + S_STG + c.wg * 16384 + ((ht ? hi * 32 + c.wq * 8 : c.wq * 16 + hi * 8) + (c.lane & 7)) * 128;
        staging_wait(c);
#pragma unroll
        for (int j = 0; j < 8; j++) {
            const int ch = (j & 3) * 2 + (c.lane >> 4);
            stsm4(base + (j >> 2) * 8192 + ((ch ^ (c.lane & 7)) << 4), pk[j * 4], pk[j * 4 + 1], pk[j * 4 + 2], pk[j * 4 + 3]);
        }
        fence_async_smem();
        staging_post(c, d.kind, d.row, d.col + HF * 128, HF ? d.cnt : -1);
    }
}
__device__ __forceinline__ void drain_all(const Params& P, Cons& c, Pend& d) { drain<0>(P, c, d); drain<1>(P, c, d); d.kind = PEND_NONE; }

__device__ __forceinline__ void store_warp(const Params& P, uint32_t sb, int wg) {
    const uint32_t stg = sb + S_STG + wg * 16384;
#pragma unroll 1
    for (uint32_t n = 0;; n++) {
        mbar_wait(sb + B_SFULL + wg * 8, n & 1);
        uint32_t x[4];
        lds128(x, sb + S_DESC + wg * 16);
        if (x[0] == PEND_NONE) break;
        const bool ht = x[0] == PEND_HT;
        const CUtensorMap* m = &P.tm[ht ? M_HTS : M_KVO];
#pragma unroll 1
        for (int i = 0; i < 4; i++) if (!(DBGF(128) && gridDim.x != 96)) tma_store2d(m, x[2] + (i >> 1) * 64, x[1] + (i & 1) * (ht ? 1024 : 32), stg + i * 4096, ht ? EVICT_NORMAL : x[1] < 4096 ? POL(4) : POL(5));
        bulk_commit();
        bulk_wait_read();
        mbar_arrive(sb + B_SFREE + wg * 8);
        if ((int)x[3] >= 0) {
            bulk_wait_all(); fence_async();
            asm volatile("red.relaxed.gpu.global.add.u32 [%0], 1;" ::"l"(&g_cnt(x[3])) : "memory");
        }
    }
}

template <int N, int TA, int TB, bool FIRST>
__device__ __forceinline__ void issue_ktile(float* acc, const Cons& c) {
    mbar_wait(c.sb + B_FULL + c.p.stage * 8, c.p.phase);
    const uint32_t a = c.sb + c.p.stage * STAGE + c.wg * 8192, b = c.sb + c.p.stage * STAGE + 16384;
    const uint64_t da = mkdesc(a, TA ? 8192 : 16, 1024, 1), db = mkdesc(b, TB ? 8192 : 16, 1024, 1);
    wg_fence();
#pragma unroll
    for (int k = 0; k < 4; k++) {
        const uint64_t x = da + (TA ? 128 : 2) * k, y = db + (TB ? 128 : 2) * k;
        if (N == 256) { if (FIRST && k == 0) wgmma_ss256_first<TA, TB>(acc, x, y); else wgmma_ss256<TA, TB>(acc, x, y); }
        else { if (FIRST && k == 0) wgmma_ss128_first<TA, TB>(acc, x, y); else wgmma_ss128<TA, TB>(acc, x, y); }
    }
    wg_commit();
}
template <int N, bool FIRST>
__device__ __forceinline__ void issue_any(float* acc, const Cons& c, int type) {
    if (N == 256 && type == T_A1) issue_ktile<N, 0, 0, FIRST>(acc, c);
    else if (type == (N == 256 ? T_A2 : T_A2H)) issue_ktile<N, 1, 0, FIRST>(acc, c);
    else issue_ktile<N, 0, 1, FIRST>(acc, c);
}
template <int N, bool KVONLY = false>
__device__ __forceinline__ void mainloop(float* acc, const Params& P, Cons& c, Pend& d, int type) {
    const int nk = (type == T_OP || type == T_OPH) ? 64 : (type == T_A2 || type == T_A2H) ? 32 : 16;
    issue_any<N, true>(acc, c, type);
    drain<0, KVONLY>(P, c, d);
    uint32_t prev = c.p.stage;
    pipe_next(c.p);
    const int hold = c.wg ? nk - (int)((P.lag >> (4 * type)) & 7) : -1;
    for (int kt = 1; kt < nk; kt++) {
        if (kt == hold) bar_sync(8, 256);
        issue_any<N, false>(acc, c, type);
        wg_wait<1>();
        release(c, prev);
        if (kt == 2) drain<1, KVONLY>(P, c, d);
        prev = c.p.stage;
        pipe_next(c.p);
    }
    if (c.wg == 0 && ((P.lag >> (4 * type)) & 7)) bar_arrive(8, 256);
    d.kind = PEND_NONE;
    wg_wait<0>();
    pin<N / 2>(acc);
    release(c, prev);
}
__device__ __forceinline__ void pack_half(uint32_t* pk, const float* a) {
#pragma unroll
    for (int i = 0; i < 32; i++) pk[i] = pack2(a[2 * i], a[2 * i + 1]);
}

__device__ __forceinline__ void epi_kv(const float* acc, const Cons& c, Pend& d, int mb, int nb) {
    pack_half(d.pk, acc); pack_half(d.pk + 32, acc + 64);
    d.kind = PEND_KVO; d.row = (nb >> 4) * 2048 + mb * 256 + c.rank * 128 + c.wg * 64; d.col = (nb & 15) * 256; d.cnt = C_KV + mb;
}

__device__ __forceinline__ void epi_qa(const float* acc, Cons& c, Pend& d, int mb, int nb) {
    uint32_t q[64];
    pack_half(q, acc);
    pack_half(q + 32, acc + 64);
#pragma unroll
    for (int i = 0; i < 32; i++) d.pk[32 + i] = 0;
    const int g = c.lane >> 2, t = c.lane & 3;
    const bool sg = c.wq >= 2;
    const int i0 = (c.wq & 1) * 16 + g;
#pragma unroll 1
    for (int hh = 0; hh < 2; hh++) {
        uint32_t pa[5][4];
        {
            float S[32] = {}, Sm[8] = {};
            mbar_wait(c.sb + B_FULL + c.p.stage * 8, c.p.phase);
            const uint32_t st = c.sb + c.p.stage * STAGE;
            const uint64_t dk = mkdesc(st + c.wg * 8192, 16, 1024, 1), dm = mkdesc(st + 32768 + c.wg * 4096, 128, 2048, 0);
            pin<32>(q); pin<32>(S); pin<8>(Sm);
            wg_fence();
#pragma unroll
            for (int i = 0; i < 8; i++) wgmma_rs64<0>(S, q + i * 4, dk + (i >> 2) * 1024 + (i & 3) * 2, i != 0);
#pragma unroll
            for (int i = 0; i < 8; i++) wgmma_rs16<0>(Sm, q + i * 4, dm + i * 16, i != 0);
            wg_commit();
            wg_wait<0>();
            pin<32>(S); pin<8>(Sm);
            release(c, c.p.stage);
            pipe_next(c.p);
            const float scale = 0.08838834764831845f, l2e = 1.4426950408889634f;
            float x[2][10];
#pragma unroll
            for (int r = 0; r < 2; r++) {
#pragma unroll
                for (int j = 0; j < 4; j++)
#pragma unroll
                    for (int e = 0; e < 2; e++) {
                        const float v = sg ? S[16 + j * 4 + r * 2 + e] : S[j * 4 + r * 2 + e];
                        x[r][j * 2 + e] = (j * 8 + 2 * t + e > i0 + r * 8) ? -1e9f : v * scale;
                    }
                x[r][8] = (sg ? Sm[4 + r * 2] : Sm[r * 2]) * scale;
                x[r][9] = (sg ? Sm[5 + r * 2] : Sm[1 + r * 2]) * scale;
                float m = x[r][0];
#pragma unroll
                for (int i = 1; i < 10; i++) m = fmaxf(m, x[r][i]);
                m = fmaxf(m, __shfl_xor_sync(0xffffffffu, m, 1));
                m = fmaxf(m, __shfl_xor_sync(0xffffffffu, m, 2));
                float sum = 0.f;
#pragma unroll
                for (int i = 0; i < 10; i++) { x[r][i] = ex2((x[r][i] - m) * l2e); sum += x[r][i]; }
                sum += __shfl_xor_sync(0xffffffffu, sum, 1);
                sum += __shfl_xor_sync(0xffffffffu, sum, 2);
                const float inv = rcp(sum);
#pragma unroll
                for (int i = 0; i < 10; i++) x[r][i] *= inv;
            }
#pragma unroll
            for (int ks = 0; ks < 2; ks++)
#pragma unroll
                for (int i = 0; i < 4; i++) {
                    const uint32_t p = pack2(x[i & 1][ks * 4 + (i >> 1) * 2], x[i & 1][ks * 4 + (i >> 1) * 2 + 1]);
                    pa[ks][i] = sg ? 0u : p;
                    pa[2 + ks][i] = sg ? p : 0u;
                }
#pragma unroll
            for (int r = 0; r < 2; r++) {
                const uint32_t p = pack2(x[r][8], x[r][9]);
                pa[4][r] = sg ? 0u : p;
                pa[4][2 + r] = sg ? p : 0u;
            }
        }
        float O[64] = {};
        mbar_wait(c.sb + B_FULL + c.p.stage * 8, c.p.phase);
        const uint32_t st = c.sb + c.p.stage * STAGE;
        const uint64_t dv = mkdesc(st + c.wg * 8192, 16384, 1024, 1), dm = mkdesc(st + 32768 + c.wg * 4096, 2048, 128, 0);
        pin<20>(&pa[0][0]); pin<64>(O);
        wg_fence();
#pragma unroll
        for (int ks = 0; ks < 4; ks++) wgmma_rs128<1>(O, pa[ks], dv + ks * 128, ks != 0);
        wgmma_rs128<0>(O, pa[4], dm, 1);
        wg_commit();
        wg_wait<0>();
        pin<64>(O);
        release(c, c.p.stage);
        pipe_next(c.p);
#pragma unroll
        for (int i = 0; i < 32; i++) { q[i] = q[32 + i]; q[32 + i] = d.pk[32 + i]; }
        pack_half(d.pk + 32, O);
    }
#pragma unroll
    for (int i = 0; i < 32; i++) d.pk[i] = q[32 + i];
    d.kind = PEND_KVO; d.row = 4096 + mb * 256 + c.rank * 128 + c.wg * 64; d.col = nb * 256; d.cnt = C_O + mb * 4 + (nb >> 2);
}

__device__ __forceinline__ void epi_op(const float* acc, const Cons& c, Pend& d, int mb, int nb) {
    pack_half(d.pk, acc); pack_half(d.pk + 32, acc + 64);
    d.kind = PEND_OUT; d.row = mb * 256 + c.rank * 128 + c.wg * 64; d.col = 1024 + nb * 256;
}

__device__ __forceinline__ void epi_oph(const float* acc, const Cons& c, Pend& d, int mb, int nb) {
    pack_half(d.pk, acc);
    d.kind = PEND_OUTH; d.row = mb * 256 + c.rank * 128 + c.wg * 64; d.col = 1024 + nb * 128;
}

template <int HF>
__device__ __forceinline__ void epi_a2_half(const float* acc, const Params& P, Cons& c, int mb, int col0) {
    const int g = c.lane >> 2, t = c.lane & 3;
    const int row = mb * 256 + (g >> 1) * 64 + (c.rank * 16 + c.wg * 8 + c.wq * 2) * 2 + (g & 1);
    float* o = P.out + (size_t)row * 2048 + col0 + HF * 128 + t * 2;
    mbar_wait(c.sb + B_FULL + c.p.stage * 8, c.p.phase);
    const uint32_t st = c.sb + c.p.stage * STAGE, da = st + 32768 + (c.lane >> 3) * 16;
    const uint32_t xa = st + (c.wg * 64 + c.wq * 16 + (c.lane & 15)) * 128 + (((c.lane >> 4) ^ (c.lane & 7)) << 4);
#pragma unroll
    for (int j4 = 0; j4 < 4; j4++) {
        uint32_t x[8], dv[4];
        ldsm4(dv, da + j4 * 64);
        ldsm4(x, (xa ^ ((j4 & 1) << 6)) + (j4 >> 1) * 16384);
        ldsm4(x + 4, (xa ^ ((j4 & 1) << 6) ^ 32) + (j4 >> 1) * 16384);
#pragma unroll
        for (int i = 0; i < 4; i++) {
            const int j = j4 * 4 + i;
            const float* a = acc + HF * 64 + j * 4;
            const uint32_t u0 = hmul2(x[2 * i], dv[i]), u1 = hmul2(x[2 * i + 1], dv[i]);
            st_stream2(o + j * 8, a[0] + bf_lo(u0), a[1] + bf_hi(u0));
            st_stream2(o + 2 * 2048 + j * 8, a[2] + bf_lo(u1), a[3] + bf_hi(u1));
        }
    }
    __syncwarp();
    release(c, c.p.stage);
    pipe_next(c.p);
}

#define TSTAMP(i)
__device__ __forceinline__ float2 cmul(float2 a, float2 b) { return make_float2(fmaf(a.x, b.x, -a.y * b.y), fmaf(a.x, b.y, a.y * b.x)); }
__device__ __forceinline__ float2 cfma(float2 a, float2 b, float2 u) { return make_float2(fmaf(a.x, b.x, fmaf(-a.y, b.y, u.x)), fmaf(a.x, b.y, fmaf(a.y, b.x, u.y))); }
__device__ __forceinline__ float4 ssm_coef(float lre, float lim, float logdt) {
    const float dt = __bfloat162float(__float2bfloat16(expf(logdt)));
    const float ea = expf(dt * lre);
    float sn, cn;
    sincosf(dt * lim, &sn, &cn);
    const float br = ea * cn, bi = ea * sn, nr = br - 1.f;
    float cr, ci;
    if (fabsf(lre) >= fabsf(lim)) { const float r = lim / lre, dn = lre + lim * r; cr = (nr + bi * r) / dn; ci = (bi - nr * r) / dn; }
    else { const float r = lre / lim, dn = lre * r + lim; cr = (nr * r + bi) / dn; ci = (bi * r - nr) / dn; }
    return make_float4(br, bi, cr, ci);
}
__device__ __forceinline__ void epi_a1(const float* acc, const Params& P, const Cons& c, Pend& d, int mb, int nb, uint32_t atag) {
    const int t = c.lane & 3;
    const int p = nb * 128 + c.rank * 64 + c.wg * 32 + c.wq * 8 + (c.lane >> 2);
    uint32_t cw[4];
    lds128(cw, c.sb + S_COEF + (p & 63) * 16);
    const float4 cf = make_float4(__uint_as_float(cw[0]), __uint_as_float(cw[1]), __uint_as_float(cw[2]), __uint_as_float(cw[3]));
    TSTAMP(1)
    const float2 lam = make_float2(cf.x, P.swap_ri ? -cf.y : cf.y);
    const float a0 = P.swap_ri ? -2.f * cf.w : 2.f * cf.z, a1 = P.swap_ri ? 2.f * cf.z : -2.f * cf.w;
    const float b0 = P.swap_ri ? -2.f * cf.z : -2.f * cf.w, b1 = P.swap_ri ? -2.f * cf.w : -2.f * cf.z;
    float2 h = make_float2(0.f, 0.f);
#pragma unroll
    for (int round = 0; round < 2; round++) {
#pragma unroll
        for (int j = 0; j < 32; j++) {
            h = cfma(lam, h, make_float2(acc[j * 4], acc[j * 4 + 2]));
            const float r0 = fmaf(a0, h.x, a1 * h.y), m0 = fmaf(b0, h.x, b1 * h.y);
            h = cfma(lam, h, make_float2(acc[j * 4 + 1], acc[j * 4 + 3]));
            d.pk[j * 2] = pack2(r0, fmaf(a0, h.x, a1 * h.y));
            d.pk[j * 2 + 1] = pack2(m0, fmaf(b0, h.x, b1 * h.y));
        }
        if (round) break;
        float2 l64 = lam;
#pragma unroll
        for (int i = 0; i < 6; i++) l64 = cmul(l64, l64);
        const float2 l128 = cmul(l64, l64), l256 = cmul(l128, l128);
        float2 o = make_float2(__shfl_up_sync(0xffffffffu, h.x, 1), __shfl_up_sync(0xffffffffu, h.y, 1));
        if (t >= 1) h = cfma(l64, o, h);
        o = make_float2(__shfl_up_sync(0xffffffffu, h.x, 2), __shfl_up_sync(0xffffffffu, h.y, 2));
        if (t >= 2) h = cfma(l128, o, h);
        TSTAMP(2)
        if (t == 3) st_relaxed2(&g_agg[mb * 1024 + p], (__float_as_uint(h.x) & ~1u) | atag, __float_as_uint(h.y));
        h = make_float2(__shfl_up_sync(0xffffffffu, h.x, 1), __shfl_up_sync(0xffffffffu, h.y, 1));
        if (t == 0) h = make_float2(0.f, 0.f);
        uint32_t ax[7], ay[7];
        int n = 0;
        while (true) {
            uint32_t bad = 0;
#pragma unroll
            for (int j = 0; j < 7; j++) { ax[j] = atag; ay[j] = 0; ld_relaxed2_if(ax[j], ay[j], &g_agg[j * 1024 + p], j < mb); }
#pragma unroll
            for (int j = 0; j < 7; j++) bad |= ax[j] ^ atag;
            if (tags_ok(bad)) break;
            __nanosleep(400);
            if (++n > SPIN_LIMIT) spin_fault();
        }
        float2 carry = make_float2(0.f, 0.f);
#pragma unroll
        for (int j = 0; j < 7; j++) if (j < mb) carry = cfma(l256, carry, make_float2(__uint_as_float(ax[j]), __uint_as_float(ay[j])));
        float2 w = (t & 1) ? l64 : make_float2(1.f, 0.f);
        if (t & 2) w = cmul(w, l128);
        h = cfma(w, carry, h);
        TSTAMP(3)
    }
    TSTAMP(4)
    d.kind = PEND_HT; d.row = nb * 128 + c.rank * 64 + c.wg * 32; d.col = mb * 256; d.cnt = C_HT + mb * 2 + (nb >> 2);
}

__device__ __forceinline__ uint32_t acquire_stage(uint32_t sb, Pipe& p, uint32_t bytes) {
    mbar_wait(sb + B_EMPTY + p.stage * 8, p.phase ^ 1);
    mbar_expect(sb + B_FULL + p.stage * 8, bytes);
    return p.stage;
}
#define AHEAD 1
__device__ __forceinline__ void watcher(const Params& P, const uint32_t sb, const int rank, const int lane) {
    const uint32_t epoch = ld_relaxed1(&g_cnt(C_EPOCH)), e1 = epoch + 1;
    sts32(sb + S_EPOCH, epoch);
    __syncwarp();
    if (lane == 0 && atomicInc(&g_cnt(C_DONE), (DBGF(32) ? 95 : NPAIR * 2 - 1) + (epoch & P.zero)) == (DBGF(32) ? 95 : NPAIR * 2 - 1)) atomicAdd(&g_cnt(C_EPOCH), 1);
    if (gridDim.x != 96) {
        uint32_t v;
        asm("mov.u32 %0, %%smid;" : "=r"(v));
        if (lane == 0 && rank == 0) st_relaxed1(g_hint + 6272 + (blockIdx.x >> 1), e1 << 8 | v >> 1);
        for (int k = 0;; k++) {
            __nanosleep(1000);
            v = ld_relaxed1(g_hint + 6272 + min(lane, 17));
            if (__all_sync(0xffffffffu, (v ^ e1 << 8) < 256)) break;
            if (k > SPIN_LIMIT) spin_fault();
        }
        const uint32_t key = ((v & 255) >= 62 ? 0 : tpc_gpc(v & 255)) * 32 + lane;
        sts32(sb + S_TAIL, 48 + __popc(__ballot_sync(0xffffffffu, key < __shfl_sync(0xffffffffu, key, blockIdx.x >> 1)) & 0x3ffff));
        __syncwarp();
    }
    uint32_t met = 1;
    if (lane == 0) asm volatile("st.release.cta.shared.u32 [%0], 1;" ::"r"(sb + S_DEP) : "memory");
    const int pair = lds32(sb + S_TAIL), first = ITEM_OFF(pair) + (pair < NCHAIN ? NPRE + 1 : 1);
#pragma unroll 1
    for (int it = first; it < ITEM_OFF(pair + 1); it++) {
        const int item = ITEM(it), type = item >> 8, mb = (item >> 5) & 7, nb = item & 31;
        const int n = (0x24021420 >> (type * 4)) & 7;
        for (int k = 0; it > first && (int)lds32(sb + S_CUR) < it - AHEAD; k++) { __nanosleep(200); if (k > SPIN_LIMIT) spin_fault(); }
#pragma unroll 1
        for (int i = 0; i < n; i++) {
            int idx = n == 4 ? C_O + mb * 4 + i : C_HT + mb * 2 + i;
            uint32_t target = e1 * 16;
            if (type == T_A1) { idx = C_COEF; target = e1 * 4; }
            if (type == T_QA) {
                idx = i ? C_FLAG + (lane & 1) * 32 + nb * 2 + ((lane >> 1) & 1) : C_KV + mb;
                target = i ? epoch * 64 + mb * 8 + rank * 4 + 4 : e1 * 128;
            }
            if (lane < 4) { wait_count(&g_cnt(idx), target); fence_async(); }
            __syncwarp();
            if (lane == 0) asm volatile("st.release.cta.shared.u32 [%0], %1;" ::"r"(sb + S_DEP), "r"(++met) : "memory");
        }
    }
}
__device__ __forceinline__ bool dep_met(uint32_t sb, uint32_t n) { uint32_t v; asm volatile("ld.acquire.cta.shared.u32 %0, [%1];" : "=r"(v) : "r"(sb + S_DEP) : "memory"); return v >= n; }
__device__ __forceinline__ void dep_wait(uint32_t sb, uint32_t n) { for (int k = 0; !dep_met(sb, n); k++) { __nanosleep(32); if (k > SPIN_LIMIT * 8) spin_fault(); } }
__device__ __forceinline__ void producer(const Params& P, const uint32_t sb, int pair, const int rank) {
    Pipe p = {0, 0};
    uint32_t dep = 1;
    for (int it = ITEM_OFF(pair); it < ITEM_OFF(pair + 1); it++) {
        const int item = ITEM(it), type = item >> 8, mb = (item >> 5) & 7, nb = item & 31;
        if (type == T_CHAIN) {
            sts32(sb + S_CUR, 0);
            const uint32_t epoch = ld_relaxed1(&g_cnt(C_EPOCH)), e1 = epoch + 1;
            const int role = pair >> 4, h = (pair & 15) * 2 + rank;
#pragma unroll 1
            for (int i = 0, q = 0; i < 8; i++) {
                const int n = (0x13003333 >> (i * 4)) & 3;
                const uint32_t st = acquire_stage(sb, p, n * 16384);
                SSTAMP(1, i == 6) SSTAMP(3, i == 7)
#pragma unroll 1
                for (int k = 0; k < 2 * n; k++, q++)
                    tma3d(sb + st * STAGE + k * 8192, &P.tm[M_CQ + role], h * 128 + (fill_unit(q >> 1) & 1) * 64, word_col((fill_unit(q >> 1) & 14) + (q & 1)) & 8, word_col((fill_unit(q >> 1) & 14) + (q & 1)) >> 4, sb + B_FULL + st * 8, role ? EVICT_NORMAL : POL(3));
                pipe_next(p);
            }
            if (role == 0 && !DBGF(1)) { wait_count(&g_cnt(C_KV), e1 * 128); fence_async(); }
            mbar_wait(sb + B_EMPTY + 16, 1); mbar_wait(sb + B_EMPTY + 24, 1);
            mbar_expect(sb + B_WO, role ? 98304 : 65536);
            if (role == 0) { mbar_expect(sb + B_KVFULL, 16384); mbar_expect(sb + B_KVFULL + 8, 16384); }
#pragma unroll 1
            for (int k = role ? 0 : -4; k < 12; k++) {
                const bool kv = role == 0 && (k & 8);
                const int sg = k > 0;
                tma4d(kv ? sb + S_KV + sg * 16384 + (k & 3) * 4096 : sb + S_W2 + k * 8192, &P.tm[kv ? M_KV4 : M_CO + (k & 1)],
                      kv ? h * 128 + (k & 1) * 64 : (role == 0 ? 0 : role == 1 ? 256 : 640) + (k >> 1) * 64, kv ? (k & 2) * 1024 + sg * 32 : h * 8, sb + (kv ? B_KVFULL + sg * 8 : B_WO), POL(2));
            }
            SSTAMP(5, true)
            if (pair < 16) {
#pragma unroll 1
                for (int s = 2; s < 63; s++) {
                    mbar_wait(sb + B_KVGO + (s & 1) * 8, ((s >> 1) + 1) & 1);
                    wait_time(gtime() + P.dk, sb);
                    SSTAMP(6, s == 2)
                    const uint32_t bar = sb + B_KVFULL + (s & 1) * 8, dst = sb + S_KV + (s & 1) * 16384;
                    if (DBGF(2)) { mbar_arrive(bar); continue; }
                    mbar_expect(bar, 16384);
#pragma unroll 1
                    for (int i = 0; i < 4; i++) tma2d(dst + i * 4096, &P.tm[M_KVO], (pair * 2 + rank) * 128 + (i & 1) * 64, (i >> 1) * 2048 + (DBGF(32 | 512) ? s & 7 : s) * 32, bar, POL(1));
                    if ((s & 7) == 7 && !DBGF(1)) { wait_count(&g_cnt(C_KV + 1 + (s >> 3)), e1 * 128); fence_async(); }
                }
            } else {
                uint32_t* flag = &g_cnt(C_FLAG + pair * 2 + rank - 32);
                const int x = pair * 2 + rank - 32;
#pragma unroll 1
                for (int s = 0; s < 64; s++) {
                    mbar_wait(sb + B_PERS, s & 1);
                    if (s < 63) wait_time(gtime() + P.dp, sb);
                    if (!DBGF(4)) bulk_s2g((role == 1 ? g_km : g_vmt) + (s * 32 + h) * 512, sb + S_QX, 2048);
                    if (s < 57) {
                        uint8_t* m = P.gm + ((s + 6) & 7) * M_SLOT + (x >> 1) * 1024 + (x & 1) * 256;
                        bulk_s2g(m, sb + S_SX, 256); bulk_s2g(m + 512, sb + S_SX, 128);
                        bulk_s2g(g_f + ((s + 6) & 7) * F_SLOT + x * 768, sb + S_SX + 256, 768);
                    }
                    bulk_commit();
                    bulk_wait_read();
                    mbar_arrive(sb + B_KVGO);
                    bulk_wait_all();
                    fence_async();
                    if ((s & 3) == 3) st_relaxed1(flag, epoch * 64 + s + 1);
                }
            }
            mbar_wait(sb + B_RESUME, 0);
            pair = lds32(sb + S_TAIL);
            it = ITEM_OFF(pair) + NPRE;
            continue;
        }
        if (it == ITEM_OFF(pair) && pair >= NCHAIN) it = -1; else sts32(sb + S_CUR, it);
        const int m0 = mb * 256 + rank * 128;
        if (type <= T_OP) {
            const CUtensorMap* ma = &P.tm[type == T_OP ? M_OA : M_BX];
            const CUtensorMap* mw = &P.tm[type == T_OP ? M_WO : type == T_QA ? M_WQ : nb < 16 ? M_WK : M_WV];
            const int nk = type == T_OP ? 64 : 16, nc = (nb & 15) * 4 + rank * 2, ma0 = type == T_OP ? 4096 + m0 : m0;
#pragma unroll 1
            for (int kt = 0; kt < nk; kt++) {
                if (type == T_OP && (kt & 15) == 0) dep_wait(sb, ++dep);
                if (DBGF(256) && pair >= NCHAIN) { acquire_stage(sb, p, 0); pipe_next(p); continue; }
                const uint32_t st = acquire_stage(sb, p, STAGE), bar = sb + B_FULL + st * 8;
                tma2d(sb + st * STAGE, ma, kt * 64, ma0, bar, type == T_OP ? POL(6) : type == T_QA ? POL(12) : POL(13));
                tma3d_mc(sb + st * STAGE + 16384 + rank * 16384, mw, 0, kt * 64, nc, bar, type == T_KV && mb == 7 ? POL(9) : EVICT_NORMAL);
                pipe_next(p);
            }
            if (type == T_QA) {
                dep += 2;
                dep_wait(sb, dep);
#pragma unroll 1
                for (int e = 0; e < 4; e++) {
                    const uint32_t st = acquire_stage(sb, p, 40960), bar = sb + B_FULL + st * 8, dst = sb + st * STAGE;
                    tma2d(dst, &P.tm[M_OA], nb * 256 + (e >> 1) * 128, (e & 1) * 2048 + m0, bar, POL(0));
                    tma2d(dst + 16384, &P.tm[M_OA], nb * 256 + (e >> 1) * 128 + 64, (e & 1) * 2048 + m0, bar, POL(0));
                    const uint32_t* src = ((e & 1) ? g_vmt : g_km) + ((mb * 8 + rank * 4) * 32 + nb * 2 + (e >> 1)) * 512;
#pragma unroll 1
                    for (int i = 0; i < 4; i++) bulk_g2s(dst + 32768 + i * 2048, src + i * 32 * 512, 2048, bar);
                    pipe_next(p);
                }
            }
        } else if (type == T_OPH) {
#pragma unroll 1
            for (int kt = 0; kt < 64; kt++) {
                if ((kt & 15) == 0) dep_wait(sb, ++dep);
                const uint32_t st = acquire_stage(sb, p, 32768), bar = sb + B_FULL + st * 8;
                tma2d(sb + st * STAGE, &P.tm[M_OA], kt * 64, 4096 + m0, bar, POL(6));
                tma2d_mc(sb + st * STAGE + 16384 + rank * 8192, &P.tm[M_WOH], nb * 128 + rank * 64, kt * 64, bar, EVICT_NORMAL);
                pipe_next(p);
            }
        } else if (type == T_A1) {
#pragma unroll 1
            for (int kt = 0; kt < 16; kt++) {
                if (kt == 15) dep_wait(sb, ++dep);
                const uint32_t st = acquire_stage(sb, p, kt == 15 ? STAGE + 1024 : STAGE), bar = sb + B_FULL + st * 8;
                if (kt == 15) bulk_g2s(sb + S_COEF, g_coef + nb * 128 + rank * 64, 1024, bar);
                tma4d(sb + st * STAGE, &P.tm[M_AB], kt * 64, nb * 16 + rank * 8, bar, POL(10));
                tma4d_mc(sb + st * STAGE + 16384 + rank * 16384, &P.tm[M_AX], kt * 64, mb * 128 + rank * 16, bar, POL(10));
                pipe_next(p);
            }
        } else {
            const int hw = type == T_A2H ? 64 : 128;
            const CUtensorMap* mc = &P.tm[type == T_A2H ? M_CREH : M_CRE];
#pragma unroll 1
            for (int kt = 0; kt < 32; kt++) {
                if ((kt & 15) == 0) dep_wait(sb, ++dep);
                const uint32_t st = acquire_stage(sb, p, 16384 + hw * 256), bar = sb + B_FULL + st * 8;
                tma3d(sb + st * STAGE, &P.tm[M_HT], 0, (kt & 1) * 1024 + (kt >> 1) * 64, mb * 4 + rank * 2, bar, POL(7));
                tma2d_mc(sb + st * STAGE + 16384 + rank * hw * 128, mc + (kt & 1), (kt >> 1) * 64, (nb * 2 + rank) * hw, bar, POL(11));
                pipe_next(p);
            }
#pragma unroll 1
            for (int col = nb * 2 * hw; col < (nb + 1) * 2 * hw; col += 128) {
                const uint32_t st = acquire_stage(sb, p, 32768 + 256), bar = sb + B_FULL + st * 8;
                tma4d(sb + st * STAGE, &P.tm[M_AX], col, mb * 128 + rank * 16, bar, POL(8));
                tma4d(sb + st * STAGE + 16384, &P.tm[M_AX], col + 64, mb * 128 + rank * 16, bar, POL(8));
                bulk_g2s(sb + st * STAGE + 32768, P.Dskip + col, 256, bar);
                pipe_next(p);
            }
        }
        if (it < 0) { dep_wait(sb, 1); pair = lds32(sb + S_TAIL); it = ITEM_OFF(pair); }
    }
}

__device__ __forceinline__ uint32_t fresh_tid() { uint32_t t; asm volatile("mov.u32 %0, %%tid.x;" : "=r"(t)); return t; }
__device__ __forceinline__ uint32_t fresh_ctaid() { uint32_t t; asm volatile("mov.u32 %0, %%ctaid.x;" : "=r"(t)); return logical_cta(t); }
__device__ __forceinline__ void reset_state(Cons& c, Pend& d, uint32_t sb, bool resumed) {
    const uint32_t t = fresh_tid(), b = fresh_ctaid();
    const int w = __shfl_sync(0xffffffffu, t >> 5, 0);
    c.sb = sb; c.wg = w >> 2; c.wq = w & 3; c.lane = t & 31;
    c.rank = __shfl_sync(0xffffffffu, b & 1, 0); c.pair = __shfl_sync(0xffffffffu, resumed && b < NCHAIN * 2 ? lds32(sb + S_TAIL) : b >> 1, 0);
    c.rel = mapa(sb + B_EMPTY, cluster_rank() ^ (c.lane & 1));
    c.p.stage = 0; c.p.phase = 0;
    c.nst = resumed && c.pair < NCHAIN ? 2 * NPRE : 0;
    d = Pend{};
}
#define PROF_ITEM(i)
#define PROF_MAIN(i)

__global__ void __launch_bounds__(384, 1) fused_kernel(const __grid_constant__ Params P) {
    extern __shared__ __align__(1024) uint8_t smem[];
    const uint32_t sb = smem_u32(smem);
    asm volatile("griddepcontrol.launch_dependents;");
    const int tid = threadIdx.x, lane = tid & 31;
    const int warp = __shfl_sync(0xffffffffu, tid >> 5, 0);
    const int pair = __shfl_sync(0xffffffffu, logical_cta(blockIdx.x) >> 1, 0), rank = __shfl_sync(0xffffffffu, blockIdx.x & 1, 0);
    if (tid == 0) {
        if (sb & 1023) spin_fault();
        sts32(sb + S_DEP, 0); sts32(sb + S_CUR, 0); sts32(sb + S_TAIL, pair); sts32(sb + S_CTA, pair * 2 + rank);
        for (int i = 0; i < NSTAGE; i++) { mbar_init(sb + B_FULL + i * 8, 1); mbar_init(sb + B_EMPTY + i * 8, 16); }
        mbar_init(sb + B_RESUME, 2);
        mbar_init(sb + B_KVFULL, 1); mbar_init(sb + B_KVFULL + 8, 1);
        mbar_init(sb + B_GO, 1); mbar_init(sb + B_KVGO, 1); mbar_init(sb + B_KVGO + 8, 1); mbar_init(sb + B_K, 1); mbar_init(sb + B_V, 1); mbar_init(sb + B_PERS, pair < 16 ? 1 : 8); mbar_init(sb + B_INIT, 3);
        mbar_init(sb + B_WO, 1);
        for (int i = 0; i < 2; i++) { mbar_init(sb + B_SFULL + i * 8, 4); mbar_init(sb + B_SFREE + i * 8, 1); }
        mbar_init(sb + B_RELA, 1); mbar_init(sb + B_RELB, 1);
        asm volatile("fence.mbarrier_init.release.cluster;" ::: "memory");
        if (pair < 16) { mbar_expect(sb + B_K, KE ? 1024 : 2048); mbar_expect(sb + B_PERS, 1024); }
        mbar_expect(sb + B_V, 2048);
    }
    cluster_sync();
    if (warp >= 8) {
        asm volatile("setmaxnreg.dec.sync.aligned.u32 24;");
        if (warp == 10 && lane < M_COUNT) map_prefetch(&P.tm[lane]);
        if (warp == 11 && lane == 0 && pair < 16) {
            const uint32_t t0 = gtime();
#pragma unroll 1
            for (int i = 0; i < 32; i++) {
                wait_time(t0 + P.pf0 + i * P.pf1, sb);
                asm volatile("cp.async.bulk.prefetch.tensor.3d.L2.global [%0, {%1, %2, %3}];" ::"l"(&P.tm[M_CQ]), "r"((pair * 2 + rank) * 128 + (i & 1) * 64), "r"((i & 2) * 4), "r"((i >> 2) * 8) : "memory");
            }
        }
        if (warp == 9 && pair < NCHAIN) pacer(P, sb, lane);
        if (warp == 9) watcher(P, sb, rank, lane);
        if (warp >= 10 && lane == 0) store_warp(P, sb, warp - 10);
        if (warp == 8) {
            if (lane == 0) producer(P, sb, lds32(sb + S_CTA) >> 1, rank);
            __syncwarp();
            asm volatile("barrier.cluster.arrive.relaxed.aligned;\nbarrier.cluster.wait.aligned;" ::: "memory");
        }
    } else {
        asm volatile("setmaxnreg.inc.sync.aligned.u32 240;");
        Cons c;
        Pend d;
        if (pair < NCHAIN) {
            mem0_max(P, sb, tid);
            reset_state(c, d, sb, false);
#pragma unroll 1
            for (int i = 0; i < NPRE; i++) {
                PROF_ITEM(i)
                const int item = ITEM(ITEM_OFF(pair) + i);
                float acc[128];
                mainloop<256, true>(acc, P, c, d, T_KV);
                epi_kv(acc, c, d, (item >> 5) & 7, item & 31);
            }
            ISTAMP(4)
            drain<0, true>(P, c, d);
            drain<1, true>(P, c, d);
            PROF_ITEM(NPRE)
            uint32_t wr[NR][4];
            load_weights(wr, sb, warp, lane, [&]() { staging_wait(c); });
            const int h = (pair & 15) * 2 + rank;
            if (pair < 16) chain_role<0>(P, wr, sb, h, warp, lane);
            else if (pair < 32) chain_role<1>(P, wr, sb, h, warp, lane);
            else chain_role<2>(P, wr, sb, h, warp, lane);
            fence_async_smem();
            bar_sync(1, 256);
            const uint32_t t2 = fresh_tid();
            if (t2 < 2) mbar_arrive_cluster(mapa(sb + B_RESUME, cluster_rank() ^ t2));
        } else if (pair >= NPAIR - 2) {
            const int ch = (pair - (NPAIR - 2)) * 512 + rank * 256 + tid;
            g_coef[ch] = ssm_coef(__bfloat162float(P.Lre[ch]), __bfloat162float(P.Lim[ch]), __bfloat162float(P.logdt[ch]));
            bar_sync(1, 256);
            if (tid == 0) red_release(&g_cnt(C_COEF));
        }
        reset_state(c, d, sb, true);
        for (int it = ITEM_OFF(c.pair) + (c.pair < NCHAIN ? NPRE + 1 : 0);; it++) {
            const bool last = it == ITEM_OFF(c.pair + 1);
            if (d.kind != PEND_NONE && (last || !bar_and(5 + c.wg, mbar_test(sb + B_FULL + c.p.stage * 8, c.p.phase)))) drain_all(P, c, d);
            if (last) break;
            const int item = ITEM(it), type = item >> 8, mb = (item >> 5) & 7, nb = item & 31;
            PROF_ITEM(it - ITEM_OFF(c.pair))
            if (type >= T_OPH) {
                float acc[64];
                mainloop<128>(acc, P, c, d, type);
                PROF_MAIN(it - ITEM_OFF(c.pair))
                if (type == T_OPH) epi_oph(acc, c, d, mb, nb);
                else epi_a2_half<0>(acc, P, c, mb, nb * 128);
            } else {
                float acc[128];
                mainloop<256>(acc, P, c, d, type);
                PROF_MAIN(it - ITEM_OFF(c.pair))
                if (type == T_KV) epi_kv(acc, c, d, mb, nb);
                else if (type == T_QA) epi_qa(acc, c, d, mb, nb);
                else if (type == T_OP) epi_op(acc, c, d, mb, nb);
                else if (type == T_A1) epi_a1(acc, P, c, d, mb, nb, (lds32(sb + S_EPOCH) + 1) & 1);
                else { epi_a2_half<0>(acc, P, c, mb, nb * 256); epi_a2_half<1>(acc, P, c, mb, nb * 256); }
            }
            if (it == ITEM_OFF(c.pair)) { dep_wait(sb, 1); c.pair = __shfl_sync(0xffffffffu, lds32(sb + S_TAIL), 0); it = ITEM_OFF(c.pair); }
        }
        staging_wait(c);
        staging_post(c, PEND_NONE, 0, 0, 0);
        asm volatile("barrier.cluster.arrive.relaxed.aligned;\nbarrier.cluster.wait.aligned;" ::: "memory");
    }
}

typedef CUresult (*EncodeFn)(CUtensorMap*, CUtensorMapDataType, cuuint32_t, void*, const cuuint64_t*, const cuuint64_t*, const cuuint32_t*, const cuuint32_t*,
                             CUtensorMapInterleave, CUtensorMapSwizzle, CUtensorMapL2promotion, CUtensorMapFloatOOBfill);
void encode(EncodeFn fn, CUtensorMap* m, const void* base, int rank, const uint64_t* dims, const uint64_t* strides, const uint32_t* box, CUtensorMapSwizzle swz = CU_TENSOR_MAP_SWIZZLE_128B) {
    cuuint64_t d[5], s[5]; cuuint32_t b[5], e[5];
    for (int i = 0; i < rank; i++) { d[i] = dims[i]; b[i] = box[i]; e[i] = 1; if (i) s[i - 1] = strides[i - 1]; }
    fn(m, CU_TENSOR_MAP_DATA_TYPE_BFLOAT16, rank, (void*)base, d, s, b, e, CU_TENSOR_MAP_INTERLEAVE_NONE, swz,
       CU_TENSOR_MAP_L2_PROMOTION_L2_256B, CU_TENSOR_MAP_FLOAT_OOB_FILL_NONE);
}
void map_kmajor(EncodeFn fn, CUtensorMap* m, const void* base, uint64_t rows, uint64_t cols, uint32_t box_rows) {
    const uint64_t d[2] = {cols, rows}, s[1] = {cols * 2}; const uint32_t b[2] = {64, box_rows};
    encode(fn, m, base, 2, d, s, b);
}
void map_mnmajor(EncodeFn fn, CUtensorMap* m, const void* base, uint64_t krows, uint64_t cols) {
    const uint64_t d[3] = {64, krows, cols / 64}, s[2] = {cols * 2, 128}; const uint32_t b[3] = {64, 64, 2};
    encode(fn, m, base, 3, d, s, b);
}

}

extern "C" void kernel_launch(void* const* d_in, const int* in_sizes, int n_in, void* d_out, int out_size) {
    static Params P;
    static EncodeFn fn = nullptr;
    if (!fn) {
        cudaDriverEntryPointQueryResult q;
        cudaGetDriverEntryPoint("cuTensorMapEncodeTiled", (void**)&fn, cudaEnableDefault, &q);
        cudaFuncSetAttribute(fused_kernel, cudaFuncAttributeMaxDynamicSharedMemorySize, S_TOTAL);
    }
    const bf16* in[15];
    for (int i = 0; i < 15; i++) in[i] = (const bf16*)d_in[i];
    void *kvo, *ht, *gm;
    cudaGetSymbolAddress(&gm, g_m);
    P.gm = (uint8_t*)(((uintptr_t)gm + 32767) & ~(uintptr_t)32767);
    cudaGetSymbolAddress(&kvo, g_kvo);
    cudaGetSymbolAddress(&ht, g_ht);
    map_kmajor(fn, &P.tm[M_BX], in[9], 2048, 1024, 128);
    map_mnmajor(fn, &P.tm[M_WQ], in[11], 1024, 4096);
    map_mnmajor(fn, &P.tm[M_WK], in[12], 1024, 4096);
    map_mnmajor(fn, &P.tm[M_WV], in[13], 1024, 4096);
    map_mnmajor(fn, &P.tm[M_WO], in[14], 4096, 1024);
    map_kmajor(fn, &P.tm[M_OA], kvo, 3 * 2048, 4096, 128);
    P.swap_ri = in[4] < in[3];
    {
        const bf16* lo = P.swap_ri ? in[4] : in[3];
        const uint64_t diff = (uint64_t)((const char*)(P.swap_ri ? in[3] : in[4]) - (const char*)lo);
        const uint64_t d[4] = {1024, 8, 2, 128}, s[3] = {2048, diff, 16384}; const uint32_t b[4] = {64, 8, 2, 8};
        encode(fn, &P.tm[M_AB], lo, 4, d, s, b);
    }
    {
        const uint64_t d[4] = {1024, 2, 4, 1024}, s[3] = {2048, 64 * 2048, 4096}; const uint32_t b[4] = {64, 2, 4, 16};
        encode(fn, &P.tm[M_AX], in[0], 4, d, s, b);
    }
    map_mnmajor(fn, &P.tm[M_HT], ht, 2048, 2048);
    map_kmajor(fn, &P.tm[M_CRE], in[5], 1024, 1024, 128);
    map_kmajor(fn, &P.tm[M_CIM], in[6], 1024, 1024, 128);
    map_kmajor(fn, &P.tm[M_KVO], kvo, 3 * 2048, 4096, 32);
    map_kmajor(fn, &P.tm[M_HTS], ht, 2048, 2048, 32);
    map_kmajor(fn, &P.tm[M_WOH], in[14], 4096, 1024, 64);
    map_kmajor(fn, &P.tm[M_CREH], in[5], 1024, 1024, 64);
    map_kmajor(fn, &P.tm[M_CIMH], in[6], 1024, 1024, 64);
    for (int i = 0; i < 3; i++) {
        const uint64_t d[3] = {4096, 16, 64}, s[2] = {8192, 16 * 8192}; const uint32_t b[3] = {64, 8, 8};
        encode(fn, &P.tm[M_CQ + i], in[11 + i], 3, d, s, b);
    }
    {
        const uint64_t d[4] = {4096, 1, 1, 4096}, s[3] = {8192, 8192, 8192}; const uint32_t b[4] = {64, 1, 1, 32};
        encode(fn, &P.tm[M_KV4], kvo, 4, d, s, b);
    }
    for (int e = 0; e < 2; e++) {
        const uint64_t d[4] = {1024, 2, 4, 256}, s[3] = {8 * 2048, 2 * 2048, 16 * 2048}; const uint32_t b[4] = {64, 2, 4, 8};
        encode(fn, &P.tm[M_CO + e], in[14] + e * 1024, 4, d, s, b);
    }
    P.Wq = in[11]; P.Wk = in[12]; P.Wv = in[13]; P.Wo = in[14]; P.mem0 = in[10];
    P.Lre = in[1]; P.Lim = in[2]; P.logdt = in[7]; P.Dskip = in[8];
    P.out = (float*)d_out;
    P.two26 = 1u << 26;
    P.lag = 0x22023302;
    P.ds = 400; P.dc = 1600; P.alpha = 0.3f; P.extra = 200; P.da = 180; P.db = 420; P.dk = 750; P.dp = 1500; P.dv = 60; P.pf0 = 2000; P.pf1 = 250; P.back = 150; P.ds0 = 950;
    for (int i = 0; i < (DBGF(32) ? 1 : 2); i++) {
        cudaLaunchConfig_t cfg = {};
        cfg.gridDim = dim3(i ? 36 : 96); cfg.blockDim = dim3(384); cfg.dynamicSmemBytes = S_TOTAL; cfg.stream = cudaStreamPerThread;
        cudaLaunchAttribute at[2];
        at[0].id = cudaLaunchAttributeClusterDimension; at[0].val.clusterDim.x = i ? 2 : 6; at[0].val.clusterDim.y = at[0].val.clusterDim.z = 1;
        at[1].id = cudaLaunchAttributeProgrammaticStreamSerialization; at[1].val.programmaticStreamSerializationAllowed = 1;
        cfg.attrs = at; cfg.numAttrs = 1 + i;
        cudaLaunchKernelEx(&cfg, fused_kernel, P);
    }
}
```

```cpp
#include <cuda_runtime.h>
#include <cuda_bf16.h>
#include <cuda.h>
#include <stdint.h>
#include <string.h>

typedef __nv_bfloat16 bf16;

namespace {

#define POLL 200
constexpr int SPIN_LIMIT = 1 << 22;
constexpr int NPAIR = 66;
constexpr int NCHAIN = 48;
enum { T_KV = 0, T_QA = 1, T_OP = 2, T_A1 = 3, T_A2 = 4, T_CHAIN = 5, T_OPH = 6, T_A2H = 7 };
enum { M_BX = 0, M_WQ, M_WK, M_WV, M_WO, M_OA, M_AB, M_AX, M_HT, M_CRE, M_CIM, M_KVO, M_HTS, M_WOH, M_CREH, M_CIMH, M_CQ, M_CK, M_CV, M_CO, M_CO1, M_KV4, M_COUNT };
enum { C_KV = 0, C_HT = 8, C_DONE = 24, C_EPOCH = 25, C_COEF = 26, C_FLAG = 32, C_O = 96 };

struct Params {
    CUtensorMap tm[M_COUNT];
    const bf16 *Wq, *Wk, *Wv, *Wo, *mem0, *Lre, *Lim, *logdt, *Dskip;
    float* out;
    uint8_t* gm;
    int swap_ri, zero;
    uint32_t two26, lag;
    int ds, da, db, dk, dv, back, ds0, pf0, pf1, dc, extra, dp;
    float alpha;
#define DBGF(x) false
};

constexpr int NPRE = 1;
__constant__ uint16_t c_off[67] = {0, 5, 10, 15, 21, 25, 29, 35, 39, 43, 47, 51, 55, 59, 63, 67, 71, 76, 81, 86, 91, 95, 99, 103, 108, 112, 116, 120, 124, 128, 133, 137, 142, 147, 152, 157, 162, 166, 170, 175, 179, 183, 187, 191, 195, 200, 205, 209, 213, 232, 252, 272, 291, 311, 331, 349, 369, 389, 407, 427, 446, 466, 485, 505, 524, 543, 562};
__constant__ uint16_t c_items[640] = {
    32, 1280, 453, 492, 1056, 49, 1280, 485, 494, 1249, 34, 1280, 293, 301, 1120, 51, 1280, 458, 457, 428, 1959, 36, 1280, 896,
    642, 53, 1280, 898, 546, 38, 1280, 833, 961, 996, 1957, 55, 1280, 865, 578, 40, 1280, 495, 576, 57, 1280, 463, 579, 42,
    1280, 262, 675, 59, 1280, 264, 739, 44, 1280, 335, 608, 61, 1280, 897, 738, 46, 1280, 361, 707, 63, 1280, 265, 705, 0,
    1280, 388, 302, 1217, 1, 1280, 489, 493, 1248, 2, 1280, 391, 333, 1250, 3, 1280, 263, 459, 1088, 4, 1280, 866, 673, 5,
    1280, 931, 640, 6, 1280, 835, 737, 7, 1280, 899, 488, 1185, 8, 1280, 838, 643, 9, 1280, 839, 641, 10, 1280, 870, 672,
    11, 1280, 864, 515, 12, 1280, 871, 674, 13, 1280, 935, 933, 1219, 14, 1280, 772, 736, 15, 1280, 994, 964, 1091, 16, 1280,
    393, 332, 1216, 17, 1280, 484, 300, 1121, 18, 1280, 487, 364, 1058, 19, 1280, 423, 462, 1152, 20, 1280, 867, 544, 21, 1280,
    930, 545, 22, 1280, 900, 424, 1089, 23, 1280, 836, 577, 24, 1280, 903, 611, 25, 1280, 902, 609, 26, 1280, 928, 547, 27,
    1280, 869, 512, 28, 1280, 868, 901, 1251, 29, 1280, 932, 965, 1218, 30, 1280, 804, 704, 31, 1280, 962, 706, 33, 95, 94,
    127, 126, 159, 158, 255, 223, 191, 324, 352, 399, 422, 289, 425, 392, 490, 1024, 35, 93, 92, 125, 124, 157, 156, 189,
    221, 253, 252, 323, 254, 292, 418, 417, 386, 299, 365, 1956, 37, 91, 90, 123, 122, 155, 154, 187, 186, 251, 219, 250,
    334, 426, 366, 448, 449, 491, 430, 1123, 39, 89, 88, 121, 120, 153, 152, 185, 217, 184, 216, 218, 249, 248, 358, 288,
    321, 452, 514, 41, 87, 86, 119, 118, 151, 215, 247, 183, 214, 200, 199, 246, 325, 296, 420, 482, 268, 396, 1059, 43,
    85, 84, 117, 116, 149, 213, 181, 212, 180, 195, 193, 297, 363, 266, 326, 303, 455, 431, 1153, 45, 83, 82, 115, 114,
    147, 211, 179, 210, 178, 329, 243, 355, 356, 805, 837, 929, 610, 47, 81, 80, 113, 112, 145, 177, 176, 241, 190, 209,
    208, 240, 773, 832, 290, 480, 995, 966, 1057, 48, 79, 78, 111, 143, 142, 207, 175, 206, 174, 222, 192, 239, 256, 257,
    390, 389, 934, 997, 1090, 50, 77, 76, 109, 141, 140, 237, 173, 236, 234, 245, 205, 258, 771, 427, 421, 483, 513, 52,
    75, 74, 107, 139, 138, 171, 235, 170, 203, 202, 770, 774, 359, 775, 801, 963, 993, 397, 1958, 54, 73, 72, 105, 137,
    136, 169, 201, 233, 168, 362, 270, 394, 353, 807, 806, 960, 367, 1184, 56, 71, 103, 104, 135, 150, 167, 182, 231, 232,
    242, 238, 384, 224, 357, 387, 320, 486, 429, 1026, 58, 70, 102, 110, 134, 148, 166, 172, 230, 188, 267, 800, 244, 419,
    291, 295, 328, 269, 1027, 60, 69, 101, 108, 133, 146, 197, 165, 204, 198, 220, 322, 229, 398, 802, 803, 395, 454, 461,
    1155, 62, 68, 100, 106, 132, 144, 228, 164, 327, 196, 225, 768, 769, 260, 416, 481, 967, 999, 1122, 64, 67, 99, 97,
    131, 129, 163, 161, 271, 354, 259, 227, 261, 294, 450, 834, 992, 998, 1025, 65, 66, 98, 96, 130, 128, 162, 160, 298,
    226, 194, 385, 331, 330, 360, 451, 456, 460, 1154,
};
#define ITEM_OFF(p) c_off[p]
#define ITEM(i) c_items[i]

__device__ __align__(1024) bf16 g_kvo[3 * 2048 * 4096];
__device__ __align__(1024) bf16 g_ht[2048 * 2048];
__device__ __align__(1024) uint8_t g_m[9 * 32768];
__device__ __align__(1024) uint8_t g_f[8 * 49152];
__device__ __align__(1024) uint32_t g_km[64 * 32 * 512];
__device__ __align__(1024) uint32_t g_vmt[64 * 32 * 512];
__device__ __align__(1024) float2 g_agg[8 * 1024];
__device__ __align__(1024) float4 g_coef[1024];
__device__ __align__(1024) uint32_t g_cntl[128 * 32];
#define g_cnt(i) g_cntl[(i) * 32]
__device__ __align__(1024) uint32_t g_hint[6144 + 160];
#define SSTAMP(i, cond)
#define PROF(i)
#define GT_EDGE(o)
constexpr int M_SLOT = 32768, F_SLOT = 49152;

constexpr int STAGE = 49152, NSTAGE = 4;
constexpr int S_STG = NSTAGE * STAGE;
constexpr int S_BAR = S_STG + 32768;
constexpr int B_FULL = S_BAR, B_EMPTY = S_BAR + 32, B_RESUME = S_BAR + 64, B_KVFULL = S_BAR + 72, B_GO = S_BAR + 88, B_K = S_BAR + 96, B_PERS = S_BAR + 104, B_INIT = S_BAR + 112, B_RELA = S_BAR + 120, B_V = S_BAR + 128, B_WO = S_BAR + 136,
              B_SFULL = S_BAR + 144, B_SFREE = S_BAR + 160, S_DESC = S_BAR + 176, S_REDO = S_BAR + 256 + 512 + 64, S_EPOCH = S_BAR + 208, B_RELB = S_BAR + 216, B_KVGO = S_BAR + 224, S_DEP = S_BAR + 240, S_CUR = S_BAR + 244, S_TAIL = S_BAR + 248, S_CTA = S_BAR + 252;
constexpr int S_COEF = S_BAR + 256 + 512, S_TOTAL = S_COEF + 1024;
constexpr int S_W1 = 0;
constexpr int S_O = 24 * 4096, S_VL = S_O + 2048, S_MX = 25 * 4096, S_SC = S_MX + 64, S_SUM = S_MX + 128;
constexpr int S_KL = 26 * 4096;
constexpr int S_W2 = 27 * 4096;
constexpr int S_KV = S_W2 + 65536;
constexpr int S_P1 = S_W2 + 98304;
constexpr int S_QX = S_P1 + 16384;
constexpr int S_SX = S_QX + 2048;
static_assert(S_SX + 1280 <= S_BAR, "chain smem overlaps barriers");
constexpr int NR = 40, NS = 64 - NR;

__device__ __forceinline__ uint32_t logical_cta(uint32_t b) {
    const uint32_t c = b / 6, r = b - c * 6;
    return gridDim.x != 96 ? 96 + b : ((r >> 1) + (c >= 8) + (c >= 15)) % 3 * 32 + c * 2 + (r & 1);
}
__device__ __forceinline__ uint32_t cluster_rank() { uint32_t r; asm("mov.u32 %0, %%cluster_ctarank;" : "=r"(r)); return r; }
__device__ __forceinline__ uint16_t pair_mask() { return (uint16_t)(3u << (cluster_rank() & 6)); }
__device__ __forceinline__ void spin_fault() { asm volatile("st.global.u32 [%0], 0;" ::"l"(0ull) : "memory"); }
__device__ __forceinline__ uint32_t smem_u32(const void* p) { return (uint32_t)__cvta_generic_to_shared(p); }
__device__ __forceinline__ uint32_t opq(uint32_t x, int lane) { return __shfl_sync(0xffffffffu, x, lane); }
__device__ __forceinline__ uint32_t mapa(uint32_t a, uint32_t r) { uint32_t d; asm volatile("mapa.shared::cluster.u32 %0, %1, %2;" : "=r"(d) : "r"(a), "r"(r)); return d; }
__device__ __forceinline__ void mma16816(float* d, uint32_t a0, uint32_t a1, uint32_t a2, uint32_t a3, uint32_t b0, uint32_t b1) {
    asm("mma.sync.aligned.m16n8k16.row.col.f32.bf16.bf16.f32 {%0,%1,%2,%3}, {%4,%5,%6,%7}, {%8,%9}, {%0,%1,%2,%3};"
        : "+f"(d[0]), "+f"(d[1]), "+f"(d[2]), "+f"(d[3]) : "r"(a0), "r"(a1), "r"(a2), "r"(a3), "r"(b0), "r"(b1));
}
__device__ __forceinline__ void mma1688(float* d, uint32_t a0, uint32_t a1, uint32_t b0) {
    asm("mma.sync.aligned.m16n8k8.row.col.f32.bf16.bf16.f32 {%0,%1,%2,%3}, {%4,%5}, {%6}, {%0,%1,%2,%3};"
        : "+f"(d[0]), "+f"(d[1]), "+f"(d[2]), "+f"(d[3]) : "r"(a0), "r"(a1), "r"(b0));
}
__device__ __forceinline__ void ldsm4(uint32_t* r, uint32_t a) {
    asm volatile("ldmatrix.sync.aligned.m8n8.x4.shared.b16 {%0,%1,%2,%3}, [%4];" : "=r"(r[0]), "=r"(r[1]), "=r"(r[2]), "=r"(r[3]) : "r"(a));
}
__device__ __forceinline__ void ldsm4t(uint32_t* r, uint32_t a) {
    asm volatile("ldmatrix.sync.aligned.m8n8.x4.trans.shared.b16 {%0,%1,%2,%3}, [%4];" : "=r"(r[0]), "=r"(r[1]), "=r"(r[2]), "=r"(r[3]) : "r"(a));
}
__device__ __forceinline__ void stsm4(uint32_t a, uint32_t r0, uint32_t r1, uint32_t r2, uint32_t r3) {
    asm volatile("stmatrix.sync.aligned.m8n8.x4.shared.b16 [%0], {%1,%2,%3,%4};" ::"r"(a), "r"(r0), "r"(r1), "r"(r2), "r"(r3) : "memory");
}
__device__ __forceinline__ void stsm4t(uint32_t a, uint32_t r0, uint32_t r1, uint32_t r2, uint32_t r3) {
    asm volatile("stmatrix.sync.aligned.m8n8.x4.trans.shared.b16 [%0], {%1,%2,%3,%4};" ::"r"(a), "r"(r0), "r"(r1), "r"(r2), "r"(r3) : "memory");
}
__device__ __forceinline__ uint32_t pack2(float lo, float hi) { uint32_t d; asm("cvt.rn.bf16x2.f32 %0, %1, %2;" : "=r"(d) : "f"(hi), "f"(lo)); return d; }
__device__ __forceinline__ float bf_lo(uint32_t u) { return __uint_as_float(u << 16); }
__device__ __forceinline__ float bf_hi(uint32_t u) { return __uint_as_float(u & 0xffff0000u); }
__device__ __forceinline__ uint32_t hmul2(uint32_t a, uint32_t b) { uint32_t d; asm("mul.rn.bf16x2 %0, %1, %2;" : "=r"(d) : "r"(a), "r"(b)); return d; }
__device__ __forceinline__ float ex2(float x) { float y; asm("ex2.approx.ftz.f32 %0, %1;" : "=f"(y) : "f"(x)); return y; }
__device__ __forceinline__ float rcp(float x) { float y; asm("rcp.approx.ftz.f32 %0, %1;" : "=f"(y) : "f"(x)); return y; }
__device__ __forceinline__ void st_relaxed4(const void* p, uint32_t a, uint32_t b, uint32_t c, uint32_t d) {
    asm volatile("{\n.reg .b128 t;\nmov.b128 t, {%1,%2,%3,%4};\nst.relaxed.gpu.global.b128 [%0], t;\n}" ::"l"(p), "r"(a), "r"(b), "r"(c), "r"(d) : "memory");
}
__device__ __forceinline__ void st_relaxed2(const void* p, uint32_t a, uint32_t b) {
    asm volatile("{\n.reg .b64 t;\nmov.b64 t, {%1,%2};\nst.relaxed.gpu.global.b64 [%0], t;\n}" ::"l"(p), "r"(a), "r"(b) : "memory");
}
__device__ __forceinline__ void ld_relaxed2_if(uint32_t& a, uint32_t& b, const void* p, bool on) {
    asm volatile("{\n.reg .pred P;\n.reg .b64 t;\nsetp.ne.u32 P, %3, 0;\nmov.b64 t, {%0,%1};\n@P ld.relaxed.gpu.global.b64 t, [%2];\nmov.b64 {%0,%1}, t;\n}" : "+r"(a), "+r"(b) : "l"(p), "r"((uint32_t)on) : "memory");
}
__device__ __forceinline__ uint32_t ld_relaxed1(const void* p) { uint32_t v; asm volatile("ld.relaxed.gpu.global.u32 %0, [%1];" : "=r"(v) : "l"(p) : "memory"); return v; }
__device__ __forceinline__ void st_relaxed1(const void* p, uint32_t v) { asm volatile("st.relaxed.gpu.global.u32 [%0], %1;" ::"l"(p), "r"(v) : "memory"); }
__device__ __forceinline__ uint32_t ld_acquire(const void* p) { uint32_t v; asm volatile("ld.acquire.gpu.global.u32 %0, [%1];" : "=r"(v) : "l"(p) : "memory"); return v; }
__device__ __forceinline__ void red_release(void* p) { asm volatile("red.release.gpu.global.add.u32 [%0], 1;" ::"l"(p) : "memory"); }
__device__ __forceinline__ void st_stream2(float* p, float a, float b) { asm volatile("st.global.cs.v2.f32 [%0], {%1, %2};" ::"l"(p), "f"(a), "f"(b) : "memory"); }
__device__ __forceinline__ void fence_acquire() { asm volatile("fence.acquire.gpu;" ::: "memory"); }
__device__ __forceinline__ void fence_release() { asm volatile("fence.release.gpu;" ::: "memory"); }
__device__ __forceinline__ void fence_async() {  asm volatile("fence.proxy.async.global;" ::: "memory"); }
__device__ __forceinline__ void fence_async_smem() { asm volatile("fence.proxy.async.shared::cta;" ::: "memory"); }
__device__ __forceinline__ void wait_count(const uint32_t* p, uint32_t target) {
    int n = 0;
    while ((int32_t)(ld_acquire(p) - target) < 0) { __nanosleep(POLL); if (++n > SPIN_LIMIT) spin_fault(); }
}
__device__ __forceinline__ void bar_sync(int id, int n) { asm volatile("bar.sync %0, %1;" ::"r"(id), "r"(n) : "memory"); }
__device__ __forceinline__ void bar_arrive(int id, int n) { asm volatile("bar.arrive %0, %1;" ::"r"(id), "r"(n) : "memory"); }
__device__ __forceinline__ bool bar_and(int id, bool v) {
    uint32_t r;
    asm volatile("{\n.reg .pred P, Q;\nsetp.ne.u32 Q, %2, 0;\nbar.red.and.pred P, %1, 128, Q;\nselp.u32 %0, 1, 0, P;\n}" : "=r"(r) : "r"(id), "r"((uint32_t)v) : "memory");
    return r;
}
__device__ __forceinline__ void lds128(uint32_t* v, uint32_t a) { asm volatile("ld.shared.v4.b32 {%0,%1,%2,%3}, [%4];" : "=r"(v[0]), "=r"(v[1]), "=r"(v[2]), "=r"(v[3]) : "r"(a) : "memory"); }
__device__ __forceinline__ uint32_t lds32(uint32_t a) { uint32_t v; asm volatile("ld.shared.b32 %0, [%1];" : "=r"(v) : "r"(a) : "memory"); return v; }
__device__ __forceinline__ void lds64f(float* v, uint32_t a) { asm volatile("ld.shared.v2.f32 {%0,%1}, [%2];" : "=f"(v[0]), "=f"(v[1]) : "r"(a) : "memory"); }
__device__ __forceinline__ void sts128(uint32_t a, const uint32_t* v) { asm volatile("st.shared.v4.b32 [%0], {%1,%2,%3,%4};" ::"r"(a), "r"(v[0]), "r"(v[1]), "r"(v[2]), "r"(v[3]) : "memory"); }
__device__ __forceinline__ void sts64(uint32_t a, uint32_t x, uint32_t y) { asm volatile("st.shared.v2.b32 [%0], {%1,%2};" ::"r"(a), "r"(x), "r"(y) : "memory"); }
__device__ __forceinline__ void sts32(uint32_t a, uint32_t x) { asm volatile("st.shared.b32 [%0], %1;" ::"r"(a), "r"(x) : "memory"); }
__device__ __forceinline__ bool mbar_try(uint32_t b, uint32_t par) {
    uint32_t ok;
    asm volatile("{\n.reg .pred P;\nmbarrier.try_wait.parity.shared::cta.b64 P, [%1], %2;\nselp.u32 %0, 1, 0, P;\n}" : "=r"(ok) : "r"(b), "r"(par) : "memory");
    return ok;
}
__device__ __forceinline__ bool mbar_test(uint32_t b, uint32_t par) {
    uint32_t ok;
    asm volatile("{\n.reg .pred P;\nmbarrier.test_wait.parity.shared::cta.b64 P, [%1], %2;\nselp.u32 %0, 1, 0, P;\n}" : "=r"(ok) : "r"(b), "r"(par) : "memory");
    return ok;
}
__device__ __forceinline__ void mbar_wait(uint32_t b, uint32_t par) { int n = 0; while (!mbar_try(b, par)) { if (++n > SPIN_LIMIT) spin_fault(); } }
__device__ __forceinline__ void mbar_init(uint32_t b, uint32_t n) { asm volatile("mbarrier.init.shared::cta.b64 [%0], %1;" ::"r"(b), "r"(n) : "memory"); }
__device__ __forceinline__ void mbar_expect(uint32_t b, uint32_t bytes) { asm volatile("mbarrier.arrive.expect_tx.shared::cta.b64 _, [%0], %1;" ::"r"(b), "r"(bytes) : "memory"); }
__device__ __forceinline__ void mbar_arrive(uint32_t b) { asm volatile("mbarrier.arrive.shared::cta.b64 _, [%0];" ::"r"(b) : "memory"); }
__device__ __forceinline__ void mbar_arrive_cluster(uint32_t b) { asm volatile("mbarrier.arrive.shared::cluster.b64 _, [%0];" ::"r"(b) : "memory"); }
__device__ __forceinline__ void st_async1(uint32_t a, uint32_t x, uint32_t bar) {
    asm volatile("st.async.weak.shared::cluster.mbarrier::complete_tx::bytes.b32 [%0], %1, [%2];" ::"r"(a), "r"(x), "r"(bar) : "memory");
}
__device__ __forceinline__ void st_async2(uint32_t a, uint32_t x, uint32_t y, uint32_t bar) {
    asm volatile("st.async.weak.shared::cluster.mbarrier::complete_tx::bytes.v2.b32 [%0], {%1,%2}, [%3];" ::"r"(a), "r"(x), "r"(y), "r"(bar) : "memory");
}
__device__ __forceinline__ void cluster_arrive() { asm volatile("barrier.cluster.arrive.relaxed.aligned;" ::: "memory"); }
__device__ __forceinline__ void cluster_wait() { asm volatile("barrier.cluster.wait.aligned;" ::: "memory"); }
constexpr uint64_t EVICT_FIRST = 0x12F0000000000000ull, EVICT_NORMAL = 0x1000000000000000ull;
__device__ __forceinline__ void tma2d(uint32_t dst, const CUtensorMap* m, int c0, int c1, uint32_t bar, uint64_t pol) {
    asm volatile("cp.async.bulk.tensor.2d.shared::cluster.global.mbarrier::complete_tx::bytes.L2::cache_hint [%0], [%1, {%2, %3}], [%4], %5;" ::"r"(dst), "l"(m), "r"(c0), "r"(c1), "r"(bar), "l"(pol) : "memory");
}
__device__ __forceinline__ void tma4d(uint32_t dst, const CUtensorMap* m, int c0, int c3, uint32_t bar, uint64_t pol) {
    asm volatile("cp.async.bulk.tensor.4d.shared::cluster.global.mbarrier::complete_tx::bytes.L2::cache_hint [%0], [%1, {%2, 0, 0, %3}], [%4], %5;" ::"r"(dst), "l"(m), "r"(c0), "r"(c3), "r"(bar), "l"(pol) : "memory");
}
__device__ __forceinline__ void tma3d(uint32_t dst, const CUtensorMap* m, int c0, int c1, int c2, uint32_t bar, uint64_t pol) {
    asm volatile("cp.async.bulk.tensor.3d.shared::cluster.global.mbarrier::complete_tx::bytes.L2::cache_hint [%0], [%1, {%2, %3, %4}], [%5], %6;" ::"r"(dst), "l"(m), "r"(c0), "r"(c1), "r"(c2), "r"(bar), "l"(pol) : "memory");
}
__device__ __forceinline__ void tma_store2d(const CUtensorMap* m, int c0, int c1, uint32_t src, uint64_t pol) {
    asm volatile("cp.async.bulk.tensor.2d.global.shared::cta.bulk_group.L2::cache_hint [%0, {%1, %2}], [%3], %4;" ::"l"(m), "r"(c0), "r"(c1), "r"(src), "l"(pol) : "memory");
}
#define EF 63
#define POL(bit) ((EF >> (bit)) & 1 ? EVICT_FIRST : EVICT_NORMAL)
__device__ __forceinline__ void tma2d_mc(uint32_t dst, const CUtensorMap* m, int c0, int c1, uint32_t bar, uint64_t pol) {
    asm volatile("cp.async.bulk.tensor.2d.shared::cluster.global.mbarrier::complete_tx::bytes.multicast::cluster.L2::cache_hint [%0], [%1, {%2, %3}], [%4], %5, %6;" ::"r"(dst), "l"(m), "r"(c0), "r"(c1), "r"(bar), "h"(pair_mask()), "l"(pol) : "memory");
}
__device__ __forceinline__ void tma3d_mc(uint32_t dst, const CUtensorMap* m, int c0, int c1, int c2, uint32_t bar, uint64_t pol) {
    asm volatile("cp.async.bulk.tensor.3d.shared::cluster.global.mbarrier::complete_tx::bytes.multicast::cluster.L2::cache_hint [%0], [%1, {%2, %3, %4}], [%5], %6, %7;" ::"r"(dst), "l"(m), "r"(c0), "r"(c1), "r"(c2), "r"(bar), "h"(pair_mask()), "l"(pol) : "memory");
}
__device__ __forceinline__ void tma4d_mc(uint32_t dst, const CUtensorMap* m, int c0, int c3, uint32_t bar, uint64_t pol) {
    asm volatile("cp.async.bulk.tensor.4d.shared::cluster.global.mbarrier::complete_tx::bytes.multicast::cluster.L2::cache_hint [%0], [%1, {%2, 0, 0, %3}], [%4], %5, %6;" ::"r"(dst), "l"(m), "r"(c0), "r"(c3), "r"(bar), "h"(pair_mask()), "l"(pol) : "memory");
}
__device__ __forceinline__ void map_prefetch(const CUtensorMap* m) { asm volatile("prefetch.tensormap [%0];" ::"l"(m) : "memory"); }
__device__ __forceinline__ void bulk_g2s(uint32_t dst, const void* src, uint32_t bytes, uint32_t bar) {
    asm volatile("cp.async.bulk.shared::cluster.global.mbarrier::complete_tx::bytes [%0], [%1], %2, [%3];" ::"r"(dst), "l"(src), "r"(bytes), "r"(bar) : "memory");
}
__device__ __forceinline__ void bulk_s2g(void* dst, uint32_t src, uint32_t bytes) {
    asm volatile("cp.async.bulk.global.shared::cta.bulk_group [%0], [%1], %2;" ::"l"(dst), "r"(src), "r"(bytes) : "memory");
}
__device__ __forceinline__ void bulk_commit() { asm volatile("cp.async.bulk.commit_group;" ::: "memory"); }
__device__ __forceinline__ void bulk_wait_read() { asm volatile("cp.async.bulk.wait_group.read 0;" ::: "memory"); }
__device__ __forceinline__ void bulk_wait_all() { asm volatile("cp.async.bulk.wait_group 0;" ::: "memory"); }
__device__ __forceinline__ uint64_t mkdesc(uint32_t addr, uint32_t lbo, uint32_t sbo, uint32_t swz) {
    return (uint64_t)((addr & 0x3FFFF) >> 4) | ((uint64_t)(lbo >> 4) << 16) | ((uint64_t)(sbo >> 4) << 32) | ((uint64_t)swz << 62);
}
__device__ __forceinline__ void wg_fence() { asm volatile("wgmma.fence.sync.aligned;" ::: "memory"); }
__device__ __forceinline__ void wg_commit() { asm volatile("wgmma.commit_group.sync.aligned;" ::: "memory"); }
template <int N> __device__ __forceinline__ void wg_wait() { asm volatile("wgmma.wait_group.sync.aligned %0;" ::"n"(N) : "memory"); }
template <typename T> __device__ __forceinline__ void pin_ptr(T*& p) { asm volatile("" : "+l"(p)); }
template <int N> __device__ __forceinline__ void pin(uint32_t* d) {
#pragma unroll
    for (int i = 0; i < N; i++) asm volatile("" : "+r"(d[i])::"memory");
}
template <int N> __device__ __forceinline__ void pin(float* d) {
#pragma unroll
    for (int i = 0; i < N; i++) asm volatile("" : "+f"(d[i])::"memory");
}

template <int TA, int TB>
__device__ __forceinline__ void wgmma_ss256(float* d, uint64_t da, uint64_t db) {
    asm volatile("wgmma.mma_async.sync.aligned.m64n256k16.f32.bf16.bf16 "
        "{%0, %1, %2, %3, %4, %5, %6, %7, %8, %9, %10, %11, %12, %13, %14, %15, %16, %17, %18, %19, %20, %21, %22, %23, %24, %25, %26, %27, %28, %29, %30, %31, %32, %33, %34, %35, %36, %37, %38, %39, %40, %41, %42, %43, %44, %45, %46, %47, %48, %49, %50, %51, %52, %53, %54, %55, %56, %57, %58, %59, %60, %61, %62, %63, %64, %65, %66, %67, %68, %69, %70, %71, %72, %73, %74, %75, %76, %77, %78, %79, %80, %81, %82, %83, %84, %85, %86, %87, %88, %89, %90, %91, %92, %93, %94, %95, %96, %97, %98, %99, %100, %101, %102, %103, %104, %105, %106, %107, %108, %109, %110, %111, %112, %113, %114, %115, %116, %117, %118, %119, %120, %121, %122, %123, %124, %125, %126, %127}, %128, %129, 1, 1, 1, %130, %131;"
        : "+f"(d[0]), "+f"(d[1]), "+f"(d[2]), "+f"(d[3]), "+f"(d[4]), "+f"(d[5]), "+f"(d[6]), "+f"(d[7]), "+f"(d[8]), "+f"(d[9]), "+f"(d[10]), "+f"(d[11]), "+f"(d[12]), "+f"(d[13]), "+f"(d[14]), "+f"(d[15]), "+f"(d[16]), "+f"(d[17]), "+f"(d[18]), "+f"(d[19]), "+f"(d[20]), "+f"(d[21]), "+f"(d[22]), "+f"(d[23]), "+f"(d[24]), "+f"(d[25]), "+f"(d[26]), "+f"(d[27]), "+f"(d[28]), "+f"(d[29]), "+f"(d[30]), "+f"(d[31]), "+f"(d[32]), "+f"(d[33]), "+f"(d[34]), "+f"(d[35]), "+f"(d[36]), "+f"(d[37]), "+f"(d[38]), "+f"(d[39]), "+f"(d[40]), "+f"(d[41]), "+f"(d[42]), "+f"(d[43]), "+f"(d[44]), "+f"(d[45]), "+f"(d[46]), "+f"(d[47]), "+f"(d[48]), "+f"(d[49]), "+f"(d[50]), "+f"(d[51]), "+f"(d[52]), "+f"(d[53]), "+f"(d[54]), "+f"(d[55]), "+f"(d[56]), "+f"(d[57]), "+f"(d[58]), "+f"(d[59]), "+f"(d[60]), "+f"(d[61]), "+f"(d[62]), "+f"(d[63]), "+f"(d[64]), "+f"(d[65]), "+f"(d[66]), "+f"(d[67]), "+f"(d[68]), "+f"(d[69]), "+f"(d[70]), "+f"(d[71]), "+f"(d[72]), "+f"(d[73]), "+f"(d[74]), "+f"(d[75]), "+f"(d[76]), "+f"(d[77]), "+f"(d[78]), "+f"(d[79]), "+f"(d[80]), "+f"(d[81]), "+f"(d[82]), "+f"(d[83]), "+f"(d[84]), "+f"(d[85]), "+f"(d[86]), "+f"(d[87]), "+f"(d[88]), "+f"(d[89]), "+f"(d[90]), "+f"(d[91]), "+f"(d[92]), "+f"(d[93]), "+f"(d[94]), "+f"(d[95]), "+f"(d[96]), "+f"(d[97]), "+f"(d[98]), "+f"(d[99]), "+f"(d[100]), "+f"(d[101]), "+f"(d[102]), "+f"(d[103]), "+f"(d[104]), "+f"(d[105]), "+f"(d[106]), "+f"(d[107]), "+f"(d[108]), "+f"(d[109]), "+f"(d[110]), "+f"(d[111]), "+f"(d[112]), "+f"(d[113]), "+f"(d[114]), "+f"(d[115]), "+f"(d[116]), "+f"(d[117]), "+f"(d[118]), "+f"(d[119]), "+f"(d[120]), "+f"(d[121]), "+f"(d[122]), "+f"(d[123]), "+f"(d[124]), "+f"(d[125]), "+f"(d[126]), "+f"(d[127])
        : "l"(da), "l"(db), "n"(TA), "n"(TB));
}
template <int TA, int TB>
__device__ __forceinline__ void wgmma_ss256_first(float* d, uint64_t da, uint64_t db) {
    asm volatile("wgmma.mma_async.sync.aligned.m64n256k16.f32.bf16.bf16 "
        "{%0, %1, %2, %3, %4, %5, %6, %7, %8, %9, %10, %11, %12, %13, %14, %15, %16, %17, %18, %19, %20, %21, %22, %23, %24, %25, %26, %27, %28, %29, %30, %31, %32, %33, %34, %35, %36, %37, %38, %39, %40, %41, %42, %43, %44, %45, %46, %47, %48, %49, %50, %51, %52, %53, %54, %55, %56, %57, %58, %59, %60, %61, %62, %63, %64, %65, %66, %67, %68, %69, %70, %71, %72, %73, %74, %75, %76, %77, %78, %79, %80, %81, %82, %83, %84, %85, %86, %87, %88, %89, %90, %91, %92, %93, %94, %95, %96, %97, %98, %99, %100, %101, %102, %103, %104, %105, %106, %107, %108, %109, %110, %111, %112, %113, %114, %115, %116, %117, %118, %119, %120, %121, %122, %123, %124, %125, %126, %127}, %128, %129, 0, 1, 1, %130, %131;"
        : "=f"(d[0]), "=f"(d[1]), "=f"(d[2]), "=f"(d[3]), "=f"(d[4]), "=f"(d[5]), "=f"(d[6]), "=f"(d[7]), "=f"(d[8]), "=f"(d[9]), "=f"(d[10]), "=f"(d[11]), "=f"(d[12]), "=f"(d[13]), "=f"(d[14]), "=f"(d[15]), "=f"(d[16]), "=f"(d[17]), "=f"(d[18]), "=f"(d[19]), "=f"(d[20]), "=f"(d[21]), "=f"(d[22]), "=f"(d[23]), "=f"(d[24]), "=f"(d[25]), "=f"(d[26]), "=f"(d[27]), "=f"(d[28]), "=f"(d[29]), "=f"(d[30]), "=f"(d[31]), "=f"(d[32]), "=f"(d[33]), "=f"(d[34]), "=f"(d[35]), "=f"(d[36]), "=f"(d[37]), "=f"(d[38]), "=f"(d[39]), "=f"(d[40]), "=f"(d[41]), "=f"(d[42]), "=f"(d[43]), "=f"(d[44]), "=f"(d[45]), "=f"(d[46]), "=f"(d[47]), "=f"(d[48]), "=f"(d[49]), "=f"(d[50]), "=f"(d[51]), "=f"(d[52]), "=f"(d[53]), "=f"(d[54]), "=f"(d[55]), "=f"(d[56]), "=f"(d[57]), "=f"(d[58]), "=f"(d[59]), "=f"(d[60]), "=f"(d[61]), "=f"(d[62]), "=f"(d[63]), "=f"(d[64]), "=f"(d[65]), "=f"(d[66]), "=f"(d[67]), "=f"(d[68]), "=f"(d[69]), "=f"(d[70]), "=f"(d[71]), "=f"(d[72]), "=f"(d[73]), "=f"(d[74]), "=f"(d[75]), "=f"(d[76]), "=f"(d[77]), "=f"(d[78]), "=f"(d[79]), "=f"(d[80]), "=f"(d[81]), "=f"(d[82]), "=f"(d[83]), "=f"(d[84]), "=f"(d[85]), "=f"(d[86]), "=f"(d[87]), "=f"(d[88]), "=f"(d[89]), "=f"(d[90]), "=f"(d[91]), "=f"(d[92]), "=f"(d[93]), "=f"(d[94]), "=f"(d[95]), "=f"(d[96]), "=f"(d[97]), "=f"(d[98]), "=f"(d[99]), "=f"(d[100]), "=f"(d[101]), "=f"(d[102]), "=f"(d[103]), "=f"(d[104]), "=f"(d[105]), "=f"(d[106]), "=f"(d[107]), "=f"(d[108]), "=f"(d[109]), "=f"(d[110]), "=f"(d[111]), "=f"(d[112]), "=f"(d[113]), "=f"(d[114]), "=f"(d[115]), "=f"(d[116]), "=f"(d[117]), "=f"(d[118]), "=f"(d[119]), "=f"(d[120]), "=f"(d[121]), "=f"(d[122]), "=f"(d[123]), "=f"(d[124]), "=f"(d[125]), "=f"(d[126]), "=f"(d[127])
        : "l"(da), "l"(db), "n"(TA), "n"(TB));
}
template <int TA, int TB>
__device__ __forceinline__ void wgmma_ss128(float* d, uint64_t da, uint64_t db) {
    asm volatile("wgmma.mma_async.sync.aligned.m64n128k16.f32.bf16.bf16 "
        "{%0, %1, %2, %3, %4, %5, %6, %7, %8, %9, %10, %11, %12, %13, %14, %15, %16, %17, %18, %19, %20, %21, %22, %23, %24, %25, %26, %27, %28, %29, %30, %31, %32, %33, %34, %35, %36, %37, %38, %39, %40, %41, %42, %43, %44, %45, %46, %47, %48, %49, %50, %51, %52, %53, %54, %55, %56, %57, %58, %59, %60, %61, %62, %63}, %64, %65, 1, 1, 1, %66, %67;"
        : "+f"(d[0]), "+f"(d[1]), "+f"(d[2]), "+f"(d[3]), "+f"(d[4]), "+f"(d[5]), "+f"(d[6]), "+f"(d[7]), "+f"(d[8]), "+f"(d[9]), "+f"(d[10]), "+f"(d[11]), "+f"(d[12]), "+f"(d[13]), "+f"(d[14]), "+f"(d[15]), "+f"(d[16]), "+f"(d[17]), "+f"(d[18]), "+f"(d[19]), "+f"(d[20]), "+f"(d[21]), "+f"(d[22]), "+f"(d[23]), "+f"(d[24]), "+f"(d[25]), "+f"(d[26]), "+f"(d[27]), "+f"(d[28]), "+f"(d[29]), "+f"(d[30]), "+f"(d[31]), "+f"(d[32]), "+f"(d[33]), "+f"(d[34]), "+f"(d[35]), "+f"(d[36]), "+f"(d[37]), "+f"(d[38]), "+f"(d[39]), "+f"(d[40]), "+f"(d[41]), "+f"(d[42]), "+f"(d[43]), "+f"(d[44]), "+f"(d[45]), "+f"(d[46]), "+f"(d[47]), "+f"(d[48]), "+f"(d[49]), "+f"(d[50]), "+f"(d[51]), "+f"(d[52]), "+f"(d[53]), "+f"(d[54]), "+f"(d[55]), "+f"(d[56]), "+f"(d[57]), "+f"(d[58]), "+f"(d[59]), "+f"(d[60]), "+f"(d[61]), "+f"(d[62]), "+f"(d[63])
        : "l"(da), "l"(db), "n"(TA), "n"(TB));
}
template <int TA, int TB>
__device__ __forceinline__ void wgmma_ss128_first(float* d, uint64_t da, uint64_t db) {
    asm volatile("wgmma.mma_async.sync.aligned.m64n128k16.f32.bf16.bf16 "
        "{%0, %1, %2, %3, %4, %5, %6, %7, %8, %9, %10, %11, %12, %13, %14, %15, %16, %17, %18, %19, %20, %21, %22, %23, %24, %25, %26, %27, %28, %29, %30, %31, %32, %33, %34, %35, %36, %37, %38, %39, %40, %41, %42, %43, %44, %45, %46, %47, %48, %49, %50, %51, %52, %53, %54, %55, %56, %57, %58, %59, %60, %61, %62, %63}, %64, %65, 0, 1, 1, %66, %67;"
        : "=f"(d[0]), "=f"(d[1]), "=f"(d[2]), "=f"(d[3]), "=f"(d[4]), "=f"(d[5]), "=f"(d[6]), "=f"(d[7]), "=f"(d[8]), "=f"(d[9]), "=f"(d[10]), "=f"(d[11]), "=f"(d[12]), "=f"(d[13]), "=f"(d[14]), "=f"(d[15]), "=f"(d[16]), "=f"(d[17]), "=f"(d[18]), "=f"(d[19]), "=f"(d[20]), "=f"(d[21]), "=f"(d[22]), "=f"(d[23]), "=f"(d[24]), "=f"(d[25]), "=f"(d[26]), "=f"(d[27]), "=f"(d[28]), "=f"(d[29]), "=f"(d[30]), "=f"(d[31]), "=f"(d[32]), "=f"(d[33]), "=f"(d[34]), "=f"(d[35]), "=f"(d[36]), "=f"(d[37]), "=f"(d[38]), "=f"(d[39]), "=f"(d[40]), "=f"(d[41]), "=f"(d[42]), "=f"(d[43]), "=f"(d[44]), "=f"(d[45]), "=f"(d[46]), "=f"(d[47]), "=f"(d[48]), "=f"(d[49]), "=f"(d[50]), "=f"(d[51]), "=f"(d[52]), "=f"(d[53]), "=f"(d[54]), "=f"(d[55]), "=f"(d[56]), "=f"(d[57]), "=f"(d[58]), "=f"(d[59]), "=f"(d[60]), "=f"(d[61]), "=f"(d[62]), "=f"(d[63])
        : "l"(da), "l"(db), "n"(TA), "n"(TB));
}
template <int TB>
__device__ __forceinline__ void wgmma_rs128(float* d, const uint32_t* a, uint64_t db, uint32_t acc) {
    asm volatile("{\n.reg .pred P;\nsetp.ne.u32 P, %69, 0;\nwgmma.mma_async.sync.aligned.m64n128k16.f32.bf16.bf16 "
        "{%0, %1, %2, %3, %4, %5, %6, %7, %8, %9, %10, %11, %12, %13, %14, %15, %16, %17, %18, %19, %20, %21, %22, %23, %24, %25, %26, %27, %28, %29, %30, %31, %32, %33, %34, %35, %36, %37, %38, %39, %40, %41, %42, %43, %44, %45, %46, %47, %48, %49, %50, %51, %52, %53, %54, %55, %56, %57, %58, %59, %60, %61, %62, %63}, {%64, %65, %66, %67}, %68, P, 1, 1, %70;\n}"
        : "+f"(d[0]), "+f"(d[1]), "+f"(d[2]), "+f"(d[3]), "+f"(d[4]), "+f"(d[5]), "+f"(d[6]), "+f"(d[7]), "+f"(d[8]), "+f"(d[9]), "+f"(d[10]), "+f"(d[11]), "+f"(d[12]), "+f"(d[13]), "+f"(d[14]), "+f"(d[15]), "+f"(d[16]), "+f"(d[17]), "+f"(d[18]), "+f"(d[19]), "+f"(d[20]), "+f"(d[21]), "+f"(d[22]), "+f"(d[23]), "+f"(d[24]), "+f"(d[25]), "+f"(d[26]), "+f"(d[27]), "+f"(d[28]), "+f"(d[29]), "+f"(d[30]), "+f"(d[31]), "+f"(d[32]), "+f"(d[33]), "+f"(d[34]), "+f"(d[35]), "+f"(d[36]), "+f"(d[37]), "+f"(d[38]), "+f"(d[39]), "+f"(d[40]), "+f"(d[41]), "+f"(d[42]), "+f"(d[43]), "+f"(d[44]), "+f"(d[45]), "+f"(d[46]), "+f"(d[47]), "+f"(d[48]), "+f"(d[49]), "+f"(d[50]), "+f"(d[51]), "+f"(d[52]), "+f"(d[53]), "+f"(d[54]), "+f"(d[55]), "+f"(d[56]), "+f"(d[57]), "+f"(d[58]), "+f"(d[59]), "+f"(d[60]), "+f"(d[61]), "+f"(d[62]), "+f"(d[63])
        : "r"(a[0]), "r"(a[1]), "r"(a[2]), "r"(a[3]), "l"(db), "r"(acc), "n"(TB));
}
template <int TB>
__device__ __forceinline__ void wgmma_rs64(float* d, const uint32_t* a, uint64_t db, uint32_t acc) {
    asm volatile("{\n.reg .pred P;\nsetp.ne.u32 P, %37, 0;\nwgmma.mma_async.sync.aligned.m64n64k16.f32.bf16.bf16 "
        "{%0, %1, %2, %3, %4, %5, %6, %7, %8, %9, %10, %11, %12, %13, %14, %15, %16, %17, %18, %19, %20, %21, %22, %23, %24, %25, %26, %27, %28, %29, %30, %31}, {%32, %33, %34, %35}, %36, P, 1, 1, %38;\n}"
        : "+f"(d[0]), "+f"(d[1]), "+f"(d[2]), "+f"(d[3]), "+f"(d[4]), "+f"(d[5]), "+f"(d[6]), "+f"(d[7]), "+f"(d[8]), "+f"(d[9]), "+f"(d[10]), "+f"(d[11]), "+f"(d[12]), "+f"(d[13]), "+f"(d[14]), "+f"(d[15]), "+f"(d[16]), "+f"(d[17]), "+f"(d[18]), "+f"(d[19]), "+f"(d[20]), "+f"(d[21]), "+f"(d[22]), "+f"(d[23]), "+f"(d[24]), "+f"(d[25]), "+f"(d[26]), "+f"(d[27]), "+f"(d[28]), "+f"(d[29]), "+f"(d[30]), "+f"(d[31])
        : "r"(a[0]), "r"(a[1]), "r"(a[2]), "r"(a[3]), "l"(db), "r"(acc), "n"(TB));
}
template <int TB>
__device__ __forceinline__ void wgmma_rs16(float* d, const uint32_t* a, uint64_t db, uint32_t acc) {
    asm volatile("{\n.reg .pred P;\nsetp.ne.u32 P, %13, 0;\nwgmma.mma_async.sync.aligned.m64n16k16.f32.bf16.bf16 "
        "{%0, %1, %2, %3, %4, %5, %6, %7}, {%8, %9, %10, %11}, %12, P, 1, 1, %14;\n}"
        : "+f"(d[0]), "+f"(d[1]), "+f"(d[2]), "+f"(d[3]), "+f"(d[4]), "+f"(d[5]), "+f"(d[6]), "+f"(d[7])
        : "r"(a[0]), "r"(a[1]), "r"(a[2]), "r"(a[3]), "l"(db), "r"(acc), "n"(TB));
}

__device__ __forceinline__ uint32_t delay_loop(int n, uint32_t x0) {
    uint32_t z;
    asm volatile("{\n.reg .pred P;\n.reg .u32 c, x;\nmov.u32 c, %1;\nmov.u32 x, %2;\nDL: mad.lo.u32 x, x, 1664525, 1013904223;\nadd.u32 c, c, -1;\nsetp.gt.s32 P, c, 0;\n@P bra DL;\n"
                 "setp.eq.u32 P, x, 0x7fffffff;\nselp.u32 %0, 16, 0, P;\n}" : "=r"(z) : "r"(n), "r"(x0) : "memory");
    return z;
}
__device__ __forceinline__ uint32_t gtime() { uint32_t t; asm volatile("mov.u32 %0, %%globaltimer_lo;" : "=r"(t)); return t; }
__device__ __forceinline__ void wait_time(uint32_t t, uint32_t sb) { while ((int32_t)(gtime() - t) < (int32_t)delay_loop(2, sb)) {} }
__device__ __forceinline__ uint32_t tpc_gpc(uint32_t t) { return t < 32 ? t & 7 : t < 60 ? (t - 32) % 7 + 1 : (t - 54) & 7; }
__device__ __forceinline__ uint32_t latest_stamp(const uint32_t* p, uint32_t seq, uint32_t ref, int backoff, uint32_t sb) {
    for (int n = 0;; n++) {
        uint32_t bad = 0; int32_t m = INT32_MIN;
#pragma unroll
        for (int i = 0; i < 3; i++) { const uint32_t v = ld_relaxed1(p + i * 256); bad |= (v ^ seq) & 31u; m = max(m, (int32_t)(v - (ref << 5)) >> 5); }
        if (__all_sync(0xffffffffu, bad == 0)) return ref + __reduce_max_sync(0xffffffffu, m);
        wait_time(gtime() + backoff, sb);
        if (n > SPIN_LIMIT) spin_fault();
    }
}
__device__ __forceinline__ void release_at(uint32_t t, uint32_t sb, uint32_t bar, int lane) {
    wait_time(t, sb);
    if (lane == 0) mbar_arrive(sb + bar);
}
__host__ __device__ constexpr int frag_word(int u, int f) { return (u == 0 ? 0 : u < 3 ? 3 * u - 1 : u == 3 ? 14 : 3 * u - 4) + f; }
__host__ __device__ constexpr int word_col(int e) { return ((0x32FED987CBA65410ull >> (4 * e)) & 14) * 64 + ((0x32FED987CBA65410ull >> (4 * e)) & 1) * 8; }

constexpr uint32_t CLEAR_LO = 0xFE000000u, CLEAR_HI = 0x5A7FEFEFu;
__device__ __forceinline__ void clear_slot(const Params& P, int slot, int cta, int lane) {
    const int i = cta * 2 + (lane >> 3), x = i & 63;
    if (lane < 16) st_relaxed4(P.gm + slot * M_SLOT + (x >> 1) * 1024 + (x & 1) * 256 + (i >> 7) * 512 + ((i >> 6) & 1) * 128 + (lane & 7) * 16, CLEAR_LO, CLEAR_HI, CLEAR_LO, CLEAR_HI);
    st_relaxed4(g_f + slot * F_SLOT + cta * 512 + lane * 16, 0, 0, 0, 0);
}
__device__ __forceinline__ void mem0_max(const Params& P, uint32_t sb, int tid) {
    uint32_t m = 0;
#pragma unroll
    for (int i = 0; i < 4; i++) {
        const uint4 x = __ldg((const uint4*)P.mem0 + i * 256 + tid);
        m = __vmaxu2(__vmaxu2(__vmaxu2(x.x & 0x7fff7fffu, x.y & 0x7fff7fffu), __vmaxu2(x.z & 0x7fff7fffu, x.w & 0x7fff7fffu)), m);
    }
    sts32(sb + S_COEF + (tid >> 5) * 4, __reduce_max_sync(0xffffffffu, max(m >> 16, m & 0xffffu)));
    bar_arrive(7, 288);
}
__device__ __forceinline__ uint32_t pack_mem0(const Params& P, uint32_t sb, int cta, int lane) {
    bar_sync(7, 288);
    const uint32_t e = __reduce_max_sync(0xffffffffu, lds32(sb + S_COEF + (lane & 7) * 4)) >> 7;
    if (e < 64 || e > 192) return 0x3F803F80u;
    const int i = cta * 2 + (lane >> 4), u = (i >> 5), x = i & 63, L = (i & 3) * 8 + ((lane & 15) >> 1);
    uint64_t w = 32;
#pragma unroll
    for (int f = 0; f < 3; f++) if (f < 2 || u % 3) {
        const float v = __bfloat162float(P.mem0[(L >> 2) * 1024 + word_col(frag_word(u, f)) + ((i >> 2) & 7) * 16 + (L & 3) * 2 + (lane & 1)]);
        w += (uint64_t)(int64_t)__float2int_rn(v * __uint_as_float((271 - e) << 23)) << (45 - 19 * f);
    }
    st_relaxed2(P.gm + 7 * M_SLOT + (x >> 1) * 1024 + (x & 1) * 256 + (i >> 7) * 512 + ((i >> 6) & 1) * 128 + (lane & 15) * 8, (uint32_t)w, (uint32_t)(w >> 32));
    return (e - 30) * 0x00800080u;
}
__device__ __forceinline__ void pacer(const Params& P, const uint32_t sb, const int lane) {
    constexpr uint32_t base = 2;
    int cta = lds32(sb + S_CTA);
#pragma unroll 1
    for (int i = 0; i < 8; i++) clear_slot(P, i, cta, lane);
    __syncwarp();
    if (lane == 0) { uint32_t smid; asm("mov.u32 %0, %%smid;" : "=r"(smid)); st_relaxed1(g_hint + 6144 + cta, smid >> 1); }
    sts32(sb + S_EPOCH + 4, pack_mem0(P, sb, cta, lane));
    fence_release();
    __syncwarp();
    float rate = 0.58f;
    uint32_t c0 = 0;
#pragma unroll 1
    for (int s = -1; s < 63; s++) {
        cta = lds32(sb + S_CTA);
        const int pair = cta >> 1;
        const uint32_t ahead = s > 0 ? (uint32_t)(rate * (float)(pair >= 32 ? P.dc - P.dv : P.dc)) : 0;
        mbar_wait(sb + B_GO, s & 1);
        SSTAMP(10, lane == 0 && s == 0)
        const uint32_t t0 = gtime();
        if (lane < 4) st_relaxed1(g_hint + ((s & 1) * 4 + lane) * 768 + (cta >> 5) * 256 + (cta & 31), (t0 + ahead + (lds32(sb + S_REDO) == s ? P.extra : 0)) << 5 | ((base + s) & 31u));
        wait_time(t0 + (s < 0 ? 2000 : s == 0 && pair >= 16 ? P.ds0 : P.ds), sb);
        const uint32_t t = latest_stamp(g_hint + ((s & 1) * 4 + (pair & 3)) * 768 + lane, base + s, t0, P.back, sb);
        if (s < 0) {
            fence_acquire();
            const uint32_t g = tpc_gpc(ld_relaxed1(g_hint + 6144 + (lane & 15) * 2));
            const uint32_t key = (__popc(__match_any_sync(0xffffffffu, g)) > 4 ? 0 : g + 1) * 16 + (lane & 15);
            const uint32_t tail = (pair & 48) + __popc(__ballot_sync(0xffffffffu, key < __shfl_sync(0xffffffffu, key, pair & 15))) / 2;
            mbar_wait(sb + B_INIT, 0);
            SSTAMP(4, lane == 0)
            sts32(sb + S_TAIL, tail);
            if (lane < 8) sts32(sb + S_SC + lane * 4, lds32(sb + S_EPOCH + 4));
            __syncwarp();
        }
        release_at(t + P.da, sb, B_RELA, lane);
        SSTAMP(11, lane == 0 && s == 0)
        release_at(t + P.db, sb, B_RELB, lane);
        {
            const uint32_t c1 = clock(), g1 = gtime();
            if (s > 1) rate += P.alpha * (__fdividef((float)(g1 - lds32(sb + S_EPOCH + 4)), (float)(c1 - c0)) - rate);
            __syncwarp();
            c0 = c1; sts32(sb + S_EPOCH + 4, g1);
        }
        if (s == 61) {
            sts32(sb + S_COEF, ITEM(ITEM_OFF(lds32(sb + S_TAIL)) + NPRE + 1) + (uint32_t)(uintptr_t)P.out);
            if (lane < M_CQ) map_prefetch(&P.tm[lane]);
        }
    }
}
__device__ __forceinline__ uint32_t xor_or(uint32_t a, uint32_t b, uint32_t t) { uint32_t d; asm("lop3.b32 %0, %1, %2, %3, 0x7E;" : "=r"(d) : "r"(a), "r"(b), "r"(t)); return d; }
__device__ __forceinline__ bool tags_ok(uint32_t bad) { return __all_sync(0xffffffffu, (bad & 1) == 0); }
#define RETRY(k)
#define RETRY_STAT(a, b)
#define UNIT_STAT(u0)
#define KE 0
#define ES 0
#define Q3 1
#define SFENCE() asm volatile("pmevent 1;" ::: "memory")
#define PF1 10
static_assert(NS == 24, "fragment residency");
__host__ __device__ constexpr bool in_smem(int n) { return n < 4 || n == 12 || n == 13; }
__host__ __device__ constexpr int unit_pos(int n) { return n < 4 ? n : n < 12 ? n - 4 : n < 14 ? n - 8 : n - 6; }

__host__ __device__ constexpr int fill_unit(int q) { return q < 4 ? q : q < 6 ? q + 8 : q < 14 ? q - 2 : q; }
__host__ __device__ constexpr int frag_off(int q) { return (q >> 2) * 16384 + ((q >> 1) & 1) * 8192 + (q & 1) * 512; }

constexpr uint32_t QBITS = 0x4B002000u;
constexpr uint64_t W_BIAS = ((uint64_t)QBITS << 45) + ((uint64_t)QBITS << 26) + (uint32_t)(QBITS << 7), W_CLEAR = 0 - 32 * W_BIAS;
static_assert(W_CLEAR == ((uint64_t)CLEAR_HI << 32 | CLEAR_LO), "clear value");
__host__ __device__ constexpr int unit_off(int u) { return (u & 1) * 16384 + (u >> 2) * 512 + ((u >> 1) & 1) * 128; }
__device__ __forceinline__ void red_add64(const uint8_t* p, uint64_t v) { asm volatile("red.relaxed.gpu.global.add.u64 [%0], %1;" ::"l"(p), "l"(v) : "memory"); }
template <int NF>
__device__ __forceinline__ uint64_t encode(const float* x, float S, uint32_t two26, uint32_t& bad) {
    uint32_t b[3];
#pragma unroll
    for (int i = 0; i < 3; i++) b[i] = i < NF ? __float_as_uint(fmaf(x[i], S, 8396800.f)) : QBITS;
    bad = xor_or(b[0], b[1], 0x4B000000u) | (NF == 3 ? b[2] ^ 0x4B000000u : 0);
    uint64_t w;
    asm("{\n.reg .b64 t;\nmov.b64 t, {%2, %3};\nmad.wide.u32 %0, %1, %4, t;\n}" : "=l"(w) : "r"(b[1]), "r"(b[2] << 7), "r"(b[0] << 13), "r"(two26));
    return w;
}
template <int NF>
__device__ __forceinline__ void emit(uint64_t* w, const float (*x)[3], const float* S, uint32_t two26, uint32_t lim, const uint8_t* p) {
    uint32_t bad[2];
    w[0] = encode<NF>(x[0], S[0], two26, bad[0]); w[1] = encode<NF>(x[1], S[1], two26, bad[1]);
    const bool ok = (bad[0] | bad[1]) < lim;
    w[0] |= ok; w[1] |= ok;
    red_add64(p, w[0]); red_add64(p + 1024, w[1]);
}
template <int NF>
__device__ __forceinline__ void repair(const uint64_t* w, const float (*x)[3], const float* S, const uint8_t* p, const uint8_t* pf) {
    if (!(w[0] & 1)) {
#pragma unroll
        for (int j = 0; j < 2; j++) {
            const float T = S[j] * 8192.f;
            asm volatile("red.relaxed.gpu.global.add.v4.f32 [%0], {%1,%2,%3,%4};" ::"l"(pf + j * 512), "f"(x[j][0] * T), "f"(x[j][1] * T), "f"(NF == 3 ? x[j][2] * T : 0.f), "f"(0.f) : "memory");
        }
        fence_release();
#pragma unroll
        for (int j = 0; j < 2; j++) {
            asm volatile("red.relaxed.gpu.global.or.b64 [%0], 64;" ::"l"(p + j * 1024) : "memory");
            red_add64(p + j * 1024, W_BIAS + 1 - w[j]);
        }
    }
    __syncwarp();
}
__device__ __forceinline__ void ld_words(uint32_t* v, const uint8_t* p) {
    asm volatile("{\n.reg .b64 a, b;\nld.relaxed.gpu.global.L1::no_allocate.v2.b64 {a, b}, [%4];\nmov.b64 {%0,%1}, a;\nmov.b64 {%2,%3}, b;\n}" : "=r"(v[0]), "=r"(v[1]), "=r"(v[2]), "=r"(v[3]) : "l"(p) : "memory");
}
__device__ __forceinline__ float field(const uint32_t* w, int f) { return __int2float_rn((int)(f == 0 ? w[1] : f == 1 ? __funnelshift_l(w[0], w[1], 19) : w[0] << 6)); }
template <int U>
__device__ __forceinline__ void decode(uint32_t* b, const uint32_t* v) {
#pragma unroll
    for (int f = 0; f < (U % 3 ? 3 : 2); f++) b[frag_word(U, f)] = pack2(field(v, f), field(v + 2, f));
}
__device__ __forceinline__ uint32_t status(const uint32_t (*v)[4], uint32_t c32) { return xor_or(v[0][0], v[0][2], c32) | xor_or(v[1][0], v[1][2], c32) | xor_or(v[2][0], v[2][2], c32); }
__device__ __forceinline__ void gather_slow(const Params& P, uint32_t* b, const uint8_t* pm, int s, int warp, uint32_t ln, uint32_t u2) {
    if (s == 0 && u2 == 0x3F803F80u) {
#pragma unroll
        for (int i = 0; i < 16; i++) b[i] = __ldg((const uint32_t*)(P.mem0 + (ln >> 2) * 1024 + word_col(i) + warp * 16 + (ln & 3) * 2));
        return;
    }
    uint32_t v[6][4], st;
    for (int n = 0;; n++) {
#pragma unroll
        for (int u = 0; u < 6; u++) ld_words(v[u], pm + unit_off(u));
        st = status(v, 32) | status(v + 3, 32);
        if (!__any_sync(0xffffffffu, st & 32)) break;
        __nanosleep(200);
        if (n > SPIN_LIMIT) spin_fault();
    }
    const bool side = __any_sync(0xffffffffu, st & 64);
    if (side) fence_acquire();
    const uint8_t* pf = g_f + ((s + 7) & 7) * F_SLOT + warp * 1024 + ln * 32;
#pragma unroll
    for (int u = 0; u < 6; u++) {
        float x[2][4] = {};
#pragma unroll
        for (int k = 0; k < 2; k++)
            asm volatile("{\n.reg .pred P;\nsetp.ne.u32 P, %5, 0;\n@P ld.relaxed.gpu.global.v4.f32 {%0,%1,%2,%3}, [%4];\n}"
                         : "+f"(x[k][0]), "+f"(x[k][1]), "+f"(x[k][2]), "+f"(x[k][3]) : "l"(pf + u * 8192 + k * 16), "r"((uint32_t)side) : "memory");
#pragma unroll
        for (int f = 0; f < (u % 3 ? 3 : 2); f++) b[frag_word(u, f)] = pack2(field(v[u], f) + x[0][f], field(v[u] + 2, f) + x[1][f]);
    }
}
__device__ __forceinline__ uint32_t max_abs2(uint32_t a, uint32_t b) { uint32_t d; asm("max.NaN.xorsign.abs.bf16x2 %0, %1, %2;" : "=r"(d) : "r"(a), "r"(b)); return d; }
__device__ __forceinline__ uint32_t max6(const uint32_t* b) {
    const uint32_t m = max_abs2(max_abs2(max_abs2(b[0], b[1]), max_abs2(b[2], b[3])), max_abs2(b[4], b[5]));
    return max(m & 0x7fff0000u, (m << 16) & 0x7fff0000u);
}

template <bool TR>
__device__ __forceinline__ void put_partials(uint32_t a, const float* x, const float* y) {
    if (TR) stsm4t(a, pack2(x[0], x[1]), pack2(x[2], x[3]), pack2(y[0], y[1]), pack2(y[2], y[3]));
    else stsm4(a, pack2(x[0], x[1]), pack2(x[2], x[3]), pack2(y[0], y[1]), pack2(y[2], y[3]));
}
__device__ __forceinline__ void reduce_load(uint32_t (*x)[4], uint32_t a) { ldsm4t(x[0], a); ldsm4t(x[1], a + 512); }
__device__ __forceinline__ uint32_t reduce8(const uint32_t (*x)[4], uint32_t l8, uint32_t u2) {
    uint32_t p[2];
#pragma unroll
    for (int i = 0; i < 2; i++) {
        float d[4] = {};
        mma16816(d, x[i][0], x[i][1], x[i][2], x[i][3], (l8 & 32) ? 0u : u2, (l8 & 32) ? u2 : 0u);
        p[i] = pack2((l8 & 8) ? d[2] : d[0], (l8 & 8) ? d[3] : d[1]);
    }
    return (l8 & 16) ? p[1] : p[0];
}
__device__ __forceinline__ void score_half(float (*a)[4], const uint32_t (*qa)[4], const uint32_t (*kf)[4]) {
#pragma unroll
    for (int w = 0; w < 2; w++) {
        mma16816(a[w], qa[w][0], qa[w][1], qa[w][2], qa[w][3], kf[w][0], kf[w][1]);
        mma16816(a[2 + w], qa[w][0], qa[w][1], qa[w][2], qa[w][3], kf[w][2], kf[w][3]);
    }
}
__device__ __forceinline__ void score_sum(float* S, const float (*a)[4]) {
    S[0] = (a[0][0] + a[1][0]) + (a[2][2] + a[3][2]);
    S[1] = (a[0][1] + a[1][1]) + (a[2][3] + a[3][3]);
}
__device__ __forceinline__ float quad_max(float m) {
    return fmaxf(fmaxf(m, __shfl_xor_sync(0xffffffffu, m, 1)), fmaxf(__shfl_xor_sync(0xffffffffu, m, 2), __shfl_xor_sync(0xffffffffu, m, 3)));
}

#define ISTAMP(i)
__device__ __forceinline__ float next_scale(uint32_t sb, int slot, int warp, uint32_t u2) {
    uint32_t x[2][4];
    lds128(x[0], sb + S_MX + slot * 32); lds128(x[1], sb + S_MX + slot * 32 + 16);
    const uint32_t mx = max(max(max(x[0][0], x[0][1]), max(x[0][2], x[0][3])), max(max(x[1][0], x[1][1]), max(x[1][2], x[1][3])));
    const float top = fminf(fmaxf(__uint_as_float(mx) * bf_hi(u2), 0x1p-40f), 0x1p40f) * (1.f / (12288.f * 8192.f));
    const uint32_t un = pack2(top, top);
    sts32(sb + S_SC + warp * 4, un);
    return rcp(bf_hi(un) * 8192.f);
}
#define NEARLY 1
#define U3POS 1
#define VPOS 1
#define ROT 0
#define BPOS 1
#define ONLINE 0
#define NBAR 1
#define ORD3 0
#define F2 1
#define EARLY 0
#define TK 0
#define OBN 4
#define CH4 1
#define RPOS 1
#define AF 0
#define AFENCE(i) if ((AF >> (i)) & 1) SFENCE();
#define FPOS 99
#define PACE 1
#define PF2 12
__host__ __device__ constexpr int w2_t(int i) { return i < 16 ? i & 1 : 2; }
__host__ __device__ constexpr int w2_k(int i) { return i < 16 ? i >> 1 : i - 16; }
template <typename G>
__device__ __forceinline__ void load_weights(uint32_t (*wr)[4], const uint32_t sb, const int warp, const int lane, G stores_read) {
    const uint32_t frag = sb + warp * 1024 + (lane >> 4) * 8192 + (lane & 7) * 128 + ((((lane >> 3) & 1) ^ (lane & 7)) << 4);
    const uint32_t rel = mapa(sb + B_EMPTY, cluster_rank() ^ (lane & 1));
#define RELEASE(st) { if ((st) >= 2) fence_async_smem(); __syncwarp(); if (lane < 2) mbar_arrive_cluster(rel + (st) * 8); }
    mbar_wait(sb + B_FULL, 0); mbar_wait(sb + B_FULL + 8, 0);
    RELEASE(0) RELEASE(1)
#pragma unroll
    for (int st = 2; st < 4; st++) {
        mbar_wait(sb + B_FULL + st * 8, 0);
        ISTAMP(st - 2)
#pragma unroll
        for (int f = 0; f < 12; f++) ldsm4t(wr[st * 12 - 24 + f], (frag ^ ((f & 3) << 5)) + st * STAGE + (f >> 2) * 16384);
        RELEASE(st)
    }
#pragma unroll 2
    for (int u = 0; u < 6; u++) {
        uint32_t x[4][4];
#pragma unroll
        for (int i = 0; i < 4; i++) lds128(x[i], (frag ^ (i << 5)) + u * 16384);
        __syncwarp();
#pragma unroll
        for (int i = 0; i < 4; i++) sts128(sb + warp * 1024 + lane * 16 + u * 16384 + frag_off(i), x[i]);
    }
    SSTAMP(0, threadIdx.x == 0)
    stores_read();
    SSTAMP(2, threadIdx.x == 0)
    mbar_wait(sb + B_FULL, 1); mbar_wait(sb + B_FULL + 8, 1);
    RELEASE(0) RELEASE(1)
#pragma unroll
    for (int st = 2; st < 4; st++) {
        mbar_wait(sb + B_FULL + st * 8, 1);
#pragma unroll
        for (int f = 0; f < (st == 2 ? 12 : 4); f++) ldsm4t(wr[st * 12 + f], (frag ^ ((f & 3) << 5)) + st * STAGE + (f >> 2) * 16384);
        RELEASE(st)
    }
    ISTAMP(2)
    bar_sync(1, 256);
    if (warp == 7 && lane < 3) mbar_arrive_cluster(mapa(sb + B_INIT, (cluster_rank() & 1) + lane * 2));
}
template <int ROLE>
__device__ __forceinline__ void chain_role(const Params& P, const uint32_t (*wr)[4], const uint32_t sb, const int h, const int warp, const int lane) {
    constexpr int NU = ROLE == 0 ? 2 : 3;
    const bool att = ROLE == 0 && warp < 4;
    uint32_t l8 = opq(sb + lane * 8, lane);
#define PERSIST() { mbar_wait(sb + B_KVGO, slot ^ 1); const uint32_t pa_ = ((l8 - sb) >> 1) + (sb + S_QX + warp * 128); sts32(pa_, r0); sts32(pa_ + 1024, r1); \
                    fence_async_smem(); __syncwarp(); if (l8 == sb) mbar_arrive(sb + B_PERS); }
    if (ROLE) sts32(sb + S_SX + warp * 128 + lane * 4, warp >= 2 ? 0 : (lane & 1) ? CLEAR_HI : CLEAR_LO);
    const uint32_t rdelta = __shfl_sync(0xffffffffu, mapa(sb, (cluster_rank() + (ROLE == 1 ? 4 : 2)) % 6) - sb, 0);
    const uint32_t vdelta = ROLE ? 0 : __shfl_sync(0xffffffffu, mapa(sb, (cluster_rank() + 4) % 6) - sb, 0);
    ISTAMP(3)
    __syncwarp();
#define GATHER_OFF(s) ((((s) + 7) & 7) * M_SLOT + warp * 2048 + (l8 & 56) * 2 + (l8 & 64) * 4 + (l8 & 128) * 8)
    uint32_t mo = GATHER_OFF(0);
    if (ROT) mbar_wait(sb + B_RELA, 0);
    for (int s = 0; s < (ROLE == 0 ? 63 : 64);) {
        const int slot = s & 1;
        l8 += s & P.zero;
        const uint32_t w1a = l8 * 2 + (S_W1 + warp * 1024 - sb);
        PROF(9)
        uint32_t u2, r0, r1, pld, pub, pbar, x[2][4];
        {
#define pm (P.gm + mo)
            uint32_t as[24][4], b[16], v[6][4];
            float acc[8][4];
#define W1LD(n) _Pragma("unroll") for (int i_ = 0; i_ < 4; i_++) ldsm4t(as[unit_pos(n) * 4 + i_], w1a + frag_off(unit_pos(n) * 4 + i_));
#define W1LD2(n, p) { const uint32_t wa_ = w1a + (as[unit_pos(p) * 4][0] & as[unit_pos(p) * 4 + 1][0] & as[unit_pos(p) * 4 + 2][0] & as[unit_pos(p) * 4 + 3][0] & P.zero); \
                      _Pragma("unroll") for (int i_ = 0; i_ < 4; i_++) ldsm4t(as[unit_pos(n) * 4 + i_], wa_ + frag_off(unit_pos(n) * 4 + i_)); }
#define W1MMA(n) _Pragma("unroll") for (int i_ = 0; i_ < 4; i_++) { const uint32_t* a_ = in_smem(n) ? as[unit_pos(n) * 4 + i_] : wr[unit_pos(n) * 4 + i_]; \
                                                                   mma16816(acc[((n) & 1) * 4 + i_], a_[0], a_[1], a_[2], a_[3], b[(n) & 14], b[(n) | 1]); }
#pragma unroll
            for (int T = 0; T < 8; T++) { acc[T][0] = acc[T][1] = acc[T][2] = acc[T][3] = 0.f; }
            if (!ROT) mbar_wait(sb + B_RELA, slot);
            PROF(12)
#pragma unroll
            for (int u = 0; u < 3; u++) ld_words(v[u], pm + unit_off(u));
            __syncwarp();
#pragma unroll
            for (int i = 0; i < PF1; i++) ldsm4t(as[i], w1a + frag_off(i));
            __syncwarp();
            mo += mbar_try(sb + B_RELB, slot) & P.zero;
            PROF(13)
#pragma unroll
            for (int u = 3; u < 6; u++) ld_words(v[u], pm + unit_off(u));
            uint32_t st = status(v, ((uint32_t)((uintptr_t)pm >> 32) & P.zero) + 32);
            pin<1>(&st);
            SFENCE();
            UNIT_STAT(0)
            PROF(0)
            decode<0>(b, v[0]); decode<1>(b, v[1]); decode<2>(b, v[2]);
#pragma unroll
            for (int i = PF1; i < 12; i++) ldsm4t(as[i], w1a + frag_off(i));
            W1MMA(0) W1MMA(1) W1MMA(2)
            if (TK & 1) W1LD2(3, 2) else { W1LD(3) }
            SFENCE();
            if (TK & 8) { W1MMA(5) W1MMA(4) W1MMA(3) W1MMA(6) } else { W1MMA(5) W1MMA(4) W1MMA(6) W1MMA(3) }
            if (U3POS == 0) W1MMA(7)
            if (TK & 2) W1LD2(12, 3) else { W1LD(12) }
            uint32_t mx = max6(b);
            pin<1>(&mx);
            SFENCE();
            PROF(10)
            if (U3POS == 1) W1MMA(7)
            const uint32_t mxa = sb + S_MX + slot * 32 + warp * 4;
            sts32(mxa, __reduce_max_sync(0xffffffffu, mx));
            UNIT_STAT(3)
            st |= status(v + 3, 32);
            const bool redo = __any_sync(0xffffffffu, st & 96);
            const bool kvok = ROLE || mbar_test(sb + B_KVFULL + slot * 8, (s >> 1) & 1);
            decode<4>(b, v[4]); decode<5>(b, v[5]); decode<3>(b, v[3]);
            u2 = lds32(sb + S_SC + warp * 4);
            W1MMA(8) W1MMA(10) if (ORD3) { W1MMA(14) W1MMA(12) } else { W1MMA(12) W1MMA(14) }
            if (TK & 4) W1LD2(13, 12) else { W1LD(13) }
            if (__builtin_expect(redo || !kvok, 0)) {
                if (redo) {
                    RETRY(3)
                    sts32(sb + S_REDO, s);
                    gather_slow(P, b, P.gm + GATHER_OFF(s), s, warp, (l8 - sb) >> 3, u2);
                    sts32(mxa, __reduce_max_sync(0xffffffffu, max6(b)));
#pragma unroll
                    for (int T = 0; T < 8; T++) { acc[T][0] = acc[T][1] = acc[T][2] = acc[T][3] = 0.f; }
#pragma unroll
                    for (int n = 0; n < 15; n += n < 8 ? 1 : 2) {
                        if (in_smem(n)) { W1LD(n) }
                        W1MMA(n)
                    }
                    W1LD(13)
                }
                if (ROLE == 0) mbar_wait(sb + B_KVFULL + slot * 8, (s >> 1) & 1);
            }
#undef pm
            SSTAMP(7, threadIdx.x == 0 && s == 0)
            PROF(14)
            const uint32_t pst = (l8 - sb) * 16 + ((warp * 16) ^ ((l8 * 2) & 112)) + (sb + S_P1);
            put_partials<ROLE == 2>(pst, acc[0], acc[1]); put_partials<ROLE == 2>(pst + 4096, acc[2], acc[3]);
            W1MMA(9)
            SFENCE();
            pld = (l8 & 64) * 4 + (l8 & 128) + (l8 & 56) * 2 + (sb + S_P1 + warp * 1024);
            const uint32_t rd = s == 63 ? 0 : rdelta;
            pub = ((l8 - sb) >> 1) + (ROLE ? sb + rd + (ROLE == 1 ? S_KL : S_VL) + warp * 128 : sb + S_QX + (warp & 4) * 128 + (warp & 1) * 256 + (warp & 2) * 64);
            pbar = sb + rd + (ROLE == 1 && s != 63 ? B_K : B_V);
#define PUBLISH0() { r0 = reduce8(x, l8, u2); if (ROLE) st_async1(pub, r0, KE && ROLE == 1 && s != 63 ? pbar + (B_PERS - B_K) : pbar); else sts32(pub, r0); }
            if (RPOS == 0) { bar_sync(1, 256); reduce_load(x, pld); SFENCE(); }
            W1MMA(11)
            if (RPOS == 1) { bar_sync(1, 256); reduce_load(x, pld); }
            if (RPOS != 2 || F2) SFENCE();
#define W1MMH(n, o) _Pragma("unroll") for (int i_ = o; i_ < o + 2; i_++) { const uint32_t* a_ = in_smem(n) ? as[unit_pos(n) * 4 + i_] : wr[unit_pos(n) * 4 + i_]; \
                                                                   mma16816(acc[((n) & 1) * 4 + i_], a_[0], a_[1], a_[2], a_[3], b[(n) & 14], b[(n) | 1]); }
            if (ES) { W1MMH(15, 0) W1MMH(15, 2) W1MMH(13, 0) } else W1MMA(15)
            if (RPOS == 0) PUBLISH0()
            if (RPOS == 2) { bar_sync(1, 256); reduce_load(x, pld); }
            if (RPOS != 1 || F2) SFENCE();
            if (ES) { W1MMH(13, 2) put_partials<ROLE == 2>(pst + 8192, acc[4], acc[5]); } else W1MMA(13)
            if (RPOS == 1) PUBLISH0()
            if (!ES) put_partials<ROLE == 2>(pst + 8192, acc[4], acc[5]);
            put_partials<ROLE == 2>(pst + 12288, acc[6], acc[7]);
            if (RPOS == 2) PUBLISH0()
        }
        SSTAMP(8, threadIdx.x == 0 && s == 0)
        PROF(1)
        if (ROLE) {
            bar_sync(1, 256);
            reduce_load(x, pld + 8192);
            r1 = reduce8(x, l8, u2);
            st_async1(pub + 1024, r1, pbar);
            if (s == 63) {
                PERSIST()
                mbar_wait(sb + B_V, 0);
                break;
            }
            PROF(2)
        }
        uint32_t ln, w2a, ro;
#define W2ADDR(late) { l8 += pub & P.zero; ln = (l8 - sb) >> 3; \
        w2a = sb + S_W2 + (ROLE ? (warp >> 2) * 16384 : late * 32768) + ((((ln & 7) + (ln >> 4) * 8) * 128 + ((((ln >> 3) & 1) ^ (ln & 7)) << 4)) ^ ((warp & 3) << 5)); \
        ro = (s & 7) * M_SLOT + (ROLE ? warp * 2048 + unit_off(ROLE) : (warp & 3) * 2048 + late * unit_off(3)) + (ln & 2) * 128 + (ln & 1) * 64 + (ln >> 2) * 8; }
        constexpr int RO2 = ROLE ? unit_off(ROLE + 3) - unit_off(ROLE) : 8192;
        float Sj[2];
        uint32_t w[24][4], ob[4][4];
        float S;
#define W2LD(i) ldsm4t(w[i], w2a + w2_t(i) * (ROLE ? 32768 : 16384) + (w2_k(i) & 1) * 8192 + (w2_k(i) >> 1) * 2048)
#define W2MMA(d, i) mma16816(d, w[i][0], w[i][1], w[i][2], w[i][3], ob[w2_k(i) >> 1][(w2_k(i) & 1) * 2], ob[w2_k(i) >> 1][(w2_k(i) & 1) * 2 + 1])
#define LEADER(wp) (l8 == sb + ((wp) - warp) * 256)
        if (att) {
            const float cs = 0.08838834764831845f * 1.4426950408889634f;
            uint32_t qa[4][4], kf[4][4], vf[4][4], vv[4];
            float T[5][2], sa[4][4] = {};
            const uint32_t l16 = l8 * 2 - sb;
            const uint32_t kaddr = (l8 & 56) * 16 + (((l8 >> 2) ^ (l8 * 2)) & 48) + ((l8 * 2) & 64) + (sb + S_KV + warp * 1024 + slot * 16384);
            bar_sync(1, 256);
            reduce_load(x, pld + 8192);
            __syncwarp();
#pragma unroll
            for (int i = 0; i < 2; i++) { ldsm4(qa[i], l16 + S_QX + i * 512); ldsm4(kf[i], kaddr ^ (i * 64)); }
            AFENCE(0)
            sts32(pub + 1024, reduce8(x, l8, u2));
            __syncwarp();
#pragma unroll
            for (int i = 2; i < 4; i++) ldsm4(kf[i], (kaddr ^ ((i & 1) * 64)) + 4096);
            score_half(sa, qa, kf);
            bar_sync(2, 256);
            PROF(2)
#pragma unroll
            for (int i = 2; i < 4; i++) ldsm4(qa[i], l16 + S_QX + i * 512);
            float sm[4][4] = {};
            const bool kearly = KE && mbar_try(sb + B_PERS, slot);
            score_half(sa, qa + 2, kf + 2);
            score_sum(T[0], sa);
            sts64(l8 + S_SX + warp * 256, __float_as_uint(T[0][0]), __float_as_uint(T[0][1]));
            PROF(4)
            if (KE) {
                if (!kearly) mbar_wait(sb + B_PERS, slot);
                ldsm4(kf[0], l16 + S_KL); ldsm4(kf[1], l16 + S_KL + 512);
                score_half(sm, qa, kf);
            }
            if (BPOS == 0) bar_sync(4, 128);
            mbar_wait(sb + B_K, slot);
            PROF(11)
#pragma unroll
            for (int i = KE ? 2 : 0; i < 4; i++) ldsm4(kf[i], l16 + S_KL + i * 512);
            if (BPOS == 1) bar_sync(4, 128); else __syncwarp();
#pragma unroll
            for (int n = 0; n < 4; n++) lds64f(T[n], l8 + S_SX + n * 256);
            if (!KE) score_half(sm, qa, kf);
            score_half(sm, qa + 2, kf + 2);
            const uint32_t vaddr = (l8 & 56) * 16 + (l8 & 128) * 8 + (((warp & 1) * 64 + ((l8 >> 2) & 16)) ^ ((l8 * 2) & 112)) + (sb + S_KV + 8192 + (warp >> 1) * 4096 + slot * 16384);
            float mx = fmaxf(fmaxf(fmaxf(T[0][0], T[0][1]), fmaxf(T[1][0], T[1][1])), fmaxf(fmaxf(T[2][0], T[2][1]), fmaxf(T[3][0], T[3][1])));
            score_sum(T[4], sm);
            float m = quad_max(fmaxf(mx, fmaxf(T[4][0], T[4][1])));
            if (VPOS == 0) {
#pragma unroll
                for (int i = 0; i < 4; i++) ldsm4t(vf[i], (vaddr ^ ((i & 1) << 5)) + (i >> 1) * 2048);
            }
            mbar_wait(sb + B_V, slot);
            if (VPOS == 1) {
#pragma unroll
                for (int i = 0; i < 4; i++) ldsm4t(vf[i], (vaddr ^ ((i & 1) << 5)) + (i >> 1) * 2048);
            }
            ldsm4(vv, l16 + S_VL + warp * 512);
            uint32_t pa[5];
            m *= cs;
#pragma unroll
            for (int n = 0; n < 5; n++) { T[n][0] = ex2(fmaf(T[n][0], cs, -m)); T[n][1] = ex2(fmaf(T[n][1], cs, -m)); pa[n] = pack2(T[n][0], T[n][1]); }
            float sum = (((T[0][0] + T[0][1]) + (T[1][0] + T[1][1])) + ((T[2][0] + T[2][1]) + (T[3][0] + T[3][1]))) + (T[4][0] + T[4][1]);
            PROF(3)
            W2ADDR(1)
            const uint32_t lo = sb + S_O + warp * 512 + (ln & 3) * 64 + (ln >> 2) * 8, ls = sb + S_SUM + (ln & 3) * 32 + (ln & 4) * 4 + (ln >> 3) * 4;
            const uint32_t sdelta = warp < 2 ? rdelta : vdelta;
            if (Q3 & 2) sum = (sum + __shfl_xor_sync(0xffffffffu, sum, 1)) + (__shfl_xor_sync(0xffffffffu, sum, 2) + __shfl_xor_sync(0xffffffffu, sum, 3));
            else { sum += __shfl_xor_sync(0xffffffffu, sum, 1); sum += __shfl_xor_sync(0xffffffffu, sum, 2); }
            float O[2][4];
#pragma unroll
            for (int i = 0; i < 2; i++) { O[i][0] = O[i][1] = O[i][2] = O[i][3] = 0.f; }
#pragma unroll
            for (int i = 0; i < 2; i++) {
                mma16816(O[0], vf[2 * i][0], vf[2 * i][1], vf[2 * i][2], vf[2 * i][3], pa[2 * i], pa[2 * i + 1]);
                mma16816(O[1], vf[2 * i + 1][0], vf[2 * i + 1][1], vf[2 * i + 1][2], vf[2 * i + 1][3], pa[2 * i], pa[2 * i + 1]);
            }
            mma1688(O[0], vv[0], vv[1], pa[4]);
            mma1688(O[1], vv[2], vv[3], pa[4]);
            uint32_t o[2][2];
#pragma unroll
            for (int j = 0; j < 2; j++) { o[j][0] = pack2(O[0][j], O[0][2 + j]); o[j][1] = pack2(O[1][j], O[1][2 + j]); }
#pragma unroll
            for (int j = 0; j < 2; j++) st_async2(lo + rdelta + j * 256, o[j][0], o[j][1], sb + rdelta + B_K);
            st_async1(ls + sdelta + (warp & 1) * 128, __float_as_uint(sum), sb + sdelta + B_K);
#pragma unroll
            for (int j = 0; j < 2; j++) st_async2(lo + vdelta + j * 256, o[j][0], o[j][1], sb + vdelta + B_K);
#pragma unroll
            for (int j = 0; j < 2; j++) sts64(lo + j * 256, o[j][0], o[j][1]);
            sts32(ls + warp * 128, __float_as_uint(sum));
            PROF(5)
            bar_sync(3, 256);
            if (LEADER(0)) { mbar_expect(sb + B_K, KE ? 1024 : 2048); if (KE) mbar_expect(sb + B_PERS, 1024); mbar_expect(sb + B_V, 2048); mbar_arrive(sb + B_KVGO + slot * 8); }
            S = next_scale(sb, slot, warp, u2);
            if (s == 0) mbar_wait(sb + B_WO, 0);
            pin<1>(&S);
            SFENCE();
#pragma unroll
            for (int j = 0; j < 4; j++) lds128(ob[j], l8 * 2 - sb + S_O + j * 512);
            lds64f(Sj, sb + S_SUM + (l8 & 24));
#pragma unroll
            for (int i = 0; i < PF2; i++) W2LD(i);
        } else {
            if (ROLE == 0) { bar_sync(1, 256); reduce_load(x, pld + 8192); sts32(pub + 1024, reduce8(x, l8, u2)); bar_arrive(2, 256); }
            if (LEADER(7)) { if (s) mbar_arrive(sb + B_GO); if (ROLE) mbar_expect(sb + B_K, 2304); }
            S = next_scale(sb, slot, warp, u2);
            if (s == 0) mbar_wait(sb + B_WO, 0);
            if (ROLE != 0) PERSIST()
            W2ADDR(0)
#pragma unroll
            for (int i = 0; i < PF2; i++) {
                W2LD(i);
                if (ROLE == 0 && (i & PACE) == PACE) w2a += w[i][0] & P.zero;
            }
            ro = opq(ro, ln);
            const uint32_t sa = opq(sb + S_SUM + (l8 & 24), ln), oa = opq(l8 * 2 - sb + S_O, ln);
            if (ROLE == 0) bar_sync(3, 256); else mbar_wait(sb + B_K, slot);
            if (OBN == 4 || !ROLE) lds64f(Sj, sa);
#pragma unroll
            for (int j = 0; j < 4; j++) { if (ROLE && j == OBN) SFENCE(); lds128(ob[j], oa + j * 512); }
            if (OBN < 4 && ROLE) lds64f(Sj, sa);
        }
        SSTAMP(9, threadIdx.x == 224 && s == 0)
        if (OBN == 4 || !ROLE) SFENCE();
        PROF(6)
        {
            const uint8_t* pr = P.gm + ro;
            float c[4][4];
            uint32_t lim = 0;
#pragma unroll
            for (int i = 0; i < 4; i++) { c[i][0] = c[i][1] = c[i][2] = c[i][3] = 0.f; }
#pragma unroll
            for (int i = 0; i < 16; i++) {
                W2MMA(c[i & (ROLE && !CH4 ? 1 : 3)], i);
                if (i + PF2 < (ROLE ? 16 + NEARLY : 16)) W2LD(i + PF2);
                if (i == 5) {
                    const uint32_t z = __float_as_uint(c[1][0]) & P.zero;
                    Sj[0] = S * rcp(__uint_as_float(__float_as_uint(Sj[0]) | z)); Sj[1] = S * rcp(__uint_as_float(__float_as_uint(Sj[1]) | z));
                }
                if (i == 5) lim = __any_sync(0xffffffffu, fmaxf(fmaxf(fabsf(c[0][0]), fabsf(c[0][2])), fmaxf(fabsf(c[1][0]), fabsf(c[1][2]))) * Sj[0] >= (ROLE && !CH4 ? 24.f : 20.f)) ? 16384 : 0;
                if (i == FPOS) { pin<1>(&lim); pin<2>(Sj); pin_ptr(pr); SFENCE(); }
            }
            if (ROLE == 0 || CH4) {
#pragma unroll
                for (int i = 0; i < 8; i++) { c[i >> 2][i & 3] += c[2 + (i >> 2)][i & 3]; c[2 + (i >> 2)][i & 3] = 0.f; }
            }
            const float xa[2][3] = {{c[0][0], c[0][2], c[1][0]}, {c[0][1], c[0][3], c[1][1]}};
            uint64_t wa[2], wb[2];
            emit<NU>(wa, xa, Sj, P.two26, lim, pr);
            PROF(7)
            mo = GATHER_OFF(s + 1);
            pin<1>(&mo);
            if (ROLE) {
                SFENCE();
#pragma unroll
                for (int i = 16 + NEARLY; i < 24; i++) { if (i == 16 + NBAR) bar_sync(2, 256); W2LD(i); __syncwarp(); }
                SFENCE();
#pragma unroll
                for (int i = 16; i < 24; i++) W2MMA(c[2 + (i & 1)], i);
#pragma unroll
                for (int i = 0; i < 4; i++) c[2][i] += c[3][i];
            }
            const float y[2][3] = {{ROLE ? c[1][2] : c[1][0], ROLE ? c[2][0] : c[1][2], c[2][2]}, {ROLE ? c[1][3] : c[1][1], ROLE ? c[2][1] : c[1][3], c[2][3]}};
            const bool released = !ROT || mbar_test(sb + B_RELA, slot ^ 1);
            emit<NU>(wb, y, Sj, P.two26, lim, pr + RO2);
            PROF(8)
            if (!__all_sync(0xffffffffu, (wa[0] & wb[0] & 1) && released && s)) {
                if (__builtin_expect(!__all_sync(0xffffffffu, wa[0] & wb[0] & 1), 0)) {
                    RETRY(5)
                    const uint8_t* pf = g_f + (s & 7) * F_SLOT + (ROLE ? ROLE * 8192 + warp * 1024 : (warp & 3) * 1024 + (att ? 24576 : 0)) + (ln & 3) * 128 + (ln >> 2) * 16;
                    repair<NU>(wa, xa, Sj, pr, pf);
                    repair<NU>(wb, y, Sj, pr + RO2, pf + (ROLE ? 24576 : 4096));
                }
                if (s == 0) { bar_sync(1, 256); if (LEADER(7)) mbar_arrive(sb + B_GO); }
                if (ROT) mbar_wait(sb + B_RELA, slot ^ 1);
            }
        }
        s++;
    }
}
struct Pipe { uint32_t stage, phase; };
struct Cons {
    uint32_t sb, rel;
    int wg, wq, lane, rank, pair;
    uint32_t nst;
    Pipe p;
};
__device__ __forceinline__ void pipe_next(Pipe& p) { p.stage = (p.stage + 1) & (NSTAGE - 1); p.phase ^= (p.stage == 0); }
__device__ __forceinline__ void release(const Cons& c, uint32_t stage) { if (c.lane < 2) mbar_arrive_cluster(c.rel + stage * 8); }

enum { PEND_NONE = 0, PEND_KVO = 1, PEND_HT = 2, PEND_OUT = 3, PEND_OUTH = 4 };
struct Pend { uint32_t pk[64]; int kind, row, col, cnt; };

__device__ __forceinline__ void staging_wait(const Cons& c) { if (c.nst) mbar_wait(c.sb + B_SFREE + c.wg * 8, (c.nst - 1) & 1); }
__device__ __forceinline__ void staging_post(Cons& c, int kind, int row, int col, int cnt) {
    __syncwarp();
    if (c.lane == 0) {
        if (c.wq == 0) { const uint32_t x[4] = {(uint32_t)kind, (uint32_t)row, (uint32_t)col, (uint32_t)cnt}; sts128(c.sb + S_DESC + c.wg * 16, x); }
        mbar_arrive(c.sb + B_SFULL + c.wg * 8);
    }
    c.nst++;
}
template <int HF, bool KVONLY = false>
__device__ __forceinline__ void drain(const Params& P, Cons& c, const Pend& d) {
    const uint32_t* pk = d.pk + HF * 32;
    if (!KVONLY && d.kind >= PEND_OUT) {
        if (HF == 1 && d.kind == PEND_OUTH) return;
        float* o = P.out + (size_t)(d.row + c.wq * 16 + (c.lane >> 2)) * 2048 + d.col + HF * 128 + (c.lane & 3) * 2;
#pragma unroll
        for (int j = 0; j < 16; j++) {
            st_stream2(o + j * 8, bf_lo(pk[j * 2]), bf_hi(pk[j * 2]));
            st_stream2(o + 8 * 2048 + j * 8, bf_lo(pk[j * 2 + 1]), bf_hi(pk[j * 2 + 1]));
        }
    } else if (d.kind != PEND_NONE) {
        const bool ht = !KVONLY && d.kind == PEND_HT;
        const int hi = (c.lane >> 3) & 1;
        const uint32_t base = c.sb + S_STG + c.wg * 16384 + ((ht ? hi * 32 + c.wq * 8 : c.wq * 16 + hi * 8) + (c.lane & 7)) * 128;
        staging_wait(c);
#pragma unroll
        for (int j = 0; j < 8; j++) {
            const int ch = (j & 3) * 2 + (c.lane >> 4);
            stsm4(base + (j >> 2) * 8192 + ((ch ^ (c.lane & 7)) << 4), pk[j * 4], pk[j * 4 + 1], pk[j * 4 + 2], pk[j * 4 + 3]);
        }
        fence_async_smem();
        staging_post(c, d.kind, d.row, d.col + HF * 128, HF ? d.cnt : -1);
    }
}
__device__ __forceinline__ void drain_all(const Params& P, Cons& c, Pend& d) { drain<0>(P, c, d); drain<1>(P, c, d); d.kind = PEND_NONE; }

__device__ __forceinline__ void store_warp(const Params& P, uint32_t sb, int wg) {
    const uint32_t stg = sb + S_STG + wg * 16384;
#pragma unroll 1
    for (uint32_t n = 0;; n++) {
        mbar_wait(sb + B_SFULL + wg * 8, n & 1);
        uint32_t x[4];
        lds128(x, sb + S_DESC + wg * 16);
        if (x[0] == PEND_NONE) break;
        const bool ht = x[0] == PEND_HT;
        const CUtensorMap* m = &P.tm[ht ? M_HTS : M_KVO];
#pragma unroll 1
        for (int i = 0; i < 4; i++) if (!(DBGF(128) && gridDim.x != 96)) tma_store2d(m, x[2] + (i >> 1) * 64, x[1] + (i & 1) * (ht ? 1024 : 32), stg + i * 4096, ht ? EVICT_NORMAL : x[1] < 4096 ? POL(4) : POL(5));
        bulk_commit();
        bulk_wait_read();
        mbar_arrive(sb + B_SFREE + wg * 8);
        if ((int)x[3] >= 0) {
            bulk_wait_all(); fence_async();
            asm volatile("red.relaxed.gpu.global.add.u32 [%0], 1;" ::"l"(&g_cnt(x[3])) : "memory");
        }
    }
}

template <int N, int TA, int TB, bool FIRST>
__device__ __forceinline__ void issue_ktile(float* acc, const Cons& c) {
    mbar_wait(c.sb + B_FULL + c.p.stage * 8, c.p.phase);
    const uint32_t a = c.sb + c.p.stage * STAGE + c.wg * 8192, b = c.sb + c.p.stage * STAGE + 16384;
    const uint64_t da = mkdesc(a, TA ? 8192 : 16, 1024, 1), db = mkdesc(b, TB ? 8192 : 16, 1024, 1);
    wg_fence();
#pragma unroll
    for (int k = 0; k < 4; k++) {
        const uint64_t x = da + (TA ? 128 : 2) * k, y = db + (TB ? 128 : 2) * k;
        if (N == 256) { if (FIRST && k == 0) wgmma_ss256_first<TA, TB>(acc, x, y); else wgmma_ss256<TA, TB>(acc, x, y); }
        else { if (FIRST && k == 0) wgmma_ss128_first<TA, TB>(acc, x, y); else wgmma_ss128<TA, TB>(acc, x, y); }
    }
    wg_commit();
}
template <int N, bool FIRST>
__device__ __forceinline__ void issue_any(float* acc, const Cons& c, int type) {
    if (N == 256 && type == T_A1) issue_ktile<N, 0, 0, FIRST>(acc, c);
    else if (type == (N == 256 ? T_A2 : T_A2H)) issue_ktile<N, 1, 0, FIRST>(acc, c);
    else issue_ktile<N, 0, 1, FIRST>(acc, c);
}
template <int N, bool KVONLY = false>
__device__ __forceinline__ void mainloop(float* acc, const Params& P, Cons& c, Pend& d, int type) {
    const int nk = (type == T_OP || type == T_OPH) ? 64 : (type == T_A2 || type == T_A2H) ? 32 : 16;
    issue_any<N, true>(acc, c, type);
    drain<0, KVONLY>(P, c, d);
    uint32_t prev = c.p.stage;
    pipe_next(c.p);
    const int hold = c.wg ? nk - (int)((P.lag >> (4 * type)) & 7) : -1;
    for (int kt = 1; kt < nk; kt++) {
        if (kt == hold) bar_sync(8, 256);
        issue_any<N, false>(acc, c, type);
        wg_wait<1>();
        release(c, prev);
        if (kt == 2) drain<1, KVONLY>(P, c, d);
        prev = c.p.stage;
        pipe_next(c.p);
    }
    if (c.wg == 0 && ((P.lag >> (4 * type)) & 7)) bar_arrive(8, 256);
    d.kind = PEND_NONE;
    wg_wait<0>();
    pin<N / 2>(acc);
    release(c, prev);
}
__device__ __forceinline__ void pack_half(uint32_t* pk, const float* a) {
#pragma unroll
    for (int i = 0; i < 32; i++) pk[i] = pack2(a[2 * i], a[2 * i + 1]);
}

__device__ __forceinline__ void epi_kv(const float* acc, const Cons& c, Pend& d, int mb, int nb) {
    pack_half(d.pk, acc); pack_half(d.pk + 32, acc + 64);
    d.kind = PEND_KVO; d.row = (nb >> 4) * 2048 + mb * 256 + c.rank * 128 + c.wg * 64; d.col = (nb & 15) * 256; d.cnt = C_KV + mb;
}

__device__ __forceinline__ void epi_qa(const float* acc, Cons& c, Pend& d, int mb, int nb) {
    uint32_t* q = d.pk;
    pack_half(q, acc);
    pack_half(q + 32, acc + 64);
    const int g = c.lane >> 2, t = c.lane & 3;
    const bool sg = c.wq >= 2;
    const int i0 = (c.wq & 1) * 16 + g;
#pragma unroll 1
    for (int hh = 0; hh < 2; hh++) {
        uint32_t pa[5][4];
        {
            float S[32] = {}, Sm[8] = {};
            mbar_wait(c.sb + B_FULL + c.p.stage * 8, c.p.phase);
            const uint32_t st = c.sb + c.p.stage * STAGE;
            const uint64_t dk = mkdesc(st + c.wg * 8192, 16, 1024, 1), dm = mkdesc(st + 32768 + c.wg * 4096, 128, 2048, 0);
            pin<32>(q); pin<32>(S); pin<8>(Sm);
            wg_fence();
#pragma unroll
            for (int i = 0; i < 8; i++) wgmma_rs64<0>(S, q + i * 4, dk + (i >> 2) * 1024 + (i & 3) * 2, i != 0);
#pragma unroll
            for (int i = 0; i < 8; i++) wgmma_rs16<0>(Sm, q + i * 4, dm + i * 16, i != 0);
            wg_commit();
            wg_wait<0>();
            pin<32>(S); pin<8>(Sm);
            release(c, c.p.stage);
            pipe_next(c.p);
            const float cs = 0.08838834764831845f * 1.4426950408889634f, masked = -1e9f / 0.08838834764831845f;
            float x[2][10];
#pragma unroll
            for (int r = 0; r < 2; r++) {
#pragma unroll
                for (int j = 0; j < 4; j++)
#pragma unroll
                    for (int e = 0; e < 2; e++) {
                        const float v = sg ? S[16 + j * 4 + r * 2 + e] : S[j * 4 + r * 2 + e];
                        x[r][j * 2 + e] = (j * 8 + 2 * t + e > i0 + r * 8) ? masked : v;
                    }
                x[r][8] = sg ? Sm[4 + r * 2] : Sm[r * 2];
                x[r][9] = sg ? Sm[5 + r * 2] : Sm[1 + r * 2];
                float m = x[r][0];
#pragma unroll
                for (int i = 1; i < 10; i++) m = fmaxf(m, x[r][i]);
                m = fmaxf(m, __shfl_xor_sync(0xffffffffu, m, 1));
                m = cs * fmaxf(m, __shfl_xor_sync(0xffffffffu, m, 2));
                float sum = 0.f;
#pragma unroll
                for (int i = 0; i < 10; i++) { x[r][i] = ex2(fmaf(x[r][i], cs, -m)); sum += x[r][i]; }
                sum += __shfl_xor_sync(0xffffffffu, sum, 1);
                sum += __shfl_xor_sync(0xffffffffu, sum, 2);
                const float inv = rcp(sum);
#pragma unroll
                for (int i = 0; i < 10; i++) x[r][i] *= inv;
            }
#pragma unroll
            for (int ks = 0; ks < 2; ks++)
#pragma unroll
                for (int i = 0; i < 4; i++) {
                    const uint32_t p = pack2(x[i & 1][ks * 4 + (i >> 1) * 2], x[i & 1][ks * 4 + (i >> 1) * 2 + 1]);
                    pa[ks][i] = sg ? 0u : p;
                    pa[2 + ks][i] = sg ? p : 0u;
                }
#pragma unroll
            for (int r = 0; r < 2; r++) {
                const uint32_t p = pack2(x[r][8], x[r][9]);
                pa[4][r] = sg ? 0u : p;
                pa[4][2 + r] = sg ? p : 0u;
            }
        }
        float O[64] = {};
        mbar_wait(c.sb + B_FULL + c.p.stage * 8, c.p.phase);
        const uint32_t st = c.sb + c.p.stage * STAGE;
        const uint64_t dv = mkdesc(st + c.wg * 8192, 16384, 1024, 1), dm = mkdesc(st + 32768 + c.wg * 4096, 2048, 128, 0);
        pin<20>(&pa[0][0]); pin<64>(O);
        wg_fence();
#pragma unroll
        for (int ks = 0; ks < 4; ks++) wgmma_rs128<1>(O, pa[ks], dv + ks * 128, ks != 0);
        wgmma_rs128<0>(O, pa[4], dm, 1);
        wg_commit();
#pragma unroll
        for (int i = 0; i < 32; i++) q[i] = q[32 + i];
        pin<32>(q);
        wg_wait<0>();
        pin<64>(O);
        release(c, c.p.stage);
        pipe_next(c.p);
        pack_half(q + 32, O);
    }
    d.kind = PEND_KVO; d.row = 4096 + mb * 256 + c.rank * 128 + c.wg * 64; d.col = nb * 256; d.cnt = C_O + mb * 4 + (nb >> 2);
}

__device__ __forceinline__ void epi_op(const float* acc, const Cons& c, Pend& d, int mb, int nb) {
    pack_half(d.pk, acc); pack_half(d.pk + 32, acc + 64);
    d.kind = PEND_OUT; d.row = mb * 256 + c.rank * 128 + c.wg * 64; d.col = 1024 + nb * 256;
}

__device__ __forceinline__ void epi_oph(const float* acc, const Cons& c, Pend& d, int mb, int nb) {
    pack_half(d.pk, acc);
    d.kind = PEND_OUTH; d.row = mb * 256 + c.rank * 128 + c.wg * 64; d.col = 1024 + nb * 128;
}

template <int HF>
__device__ __forceinline__ void epi_a2_half(const float* acc, const Params& P, Cons& c, int mb, int col0) {
    const int g = c.lane >> 2, t = c.lane & 3;
    const int row = mb * 256 + (g >> 1) * 64 + (c.rank * 16 + c.wg * 8 + c.wq * 2) * 2 + (g & 1);
    float* o = P.out + (size_t)row * 2048 + col0 + HF * 128 + t * 2;
    mbar_wait(c.sb + B_FULL + c.p.stage * 8, c.p.phase);
    const uint32_t st = c.sb + c.p.stage * STAGE, da = st + 32768 + (c.lane >> 3) * 16;
    const uint32_t xa = st + (c.wg * 64 + c.wq * 16 + (c.lane & 15)) * 128 + (((c.lane >> 4) ^ (c.lane & 7)) << 4);
#pragma unroll
    for (int j4 = 0; j4 < 4; j4++) {
        uint32_t x[8], dv[4];
        ldsm4(dv, da + j4 * 64);
        ldsm4(x, (xa ^ ((j4 & 1) << 6)) + (j4 >> 1) * 16384);
        ldsm4(x + 4, (xa ^ ((j4 & 1) << 6) ^ 32) + (j4 >> 1) * 16384);
#pragma unroll
        for (int i = 0; i < 4; i++) {
            const int j = j4 * 4 + i;
            const float* a = acc + HF * 64 + j * 4;
            const uint32_t u0 = hmul2(x[2 * i], dv[i]), u1 = hmul2(x[2 * i + 1], dv[i]);
            st_stream2(o + j * 8, a[0] + bf_lo(u0), a[1] + bf_hi(u0));
            st_stream2(o + 2 * 2048 + j * 8, a[2] + bf_lo(u1), a[3] + bf_hi(u1));
        }
    }
    __syncwarp();
    release(c, c.p.stage);
    pipe_next(c.p);
}

#define TSTAMP(i)
__device__ __forceinline__ float2 cmul(float2 a, float2 b) { return make_float2(fmaf(a.x, b.x, -a.y * b.y), fmaf(a.x, b.y, a.y * b.x)); }
__device__ __forceinline__ float2 cfma(float2 a, float2 b, float2 u) { return make_float2(fmaf(a.x, b.x, fmaf(-a.y, b.y, u.x)), fmaf(a.x, b.y, fmaf(a.y, b.x, u.y))); }
__device__ __forceinline__ float4 ssm_coef(float lre, float lim, float logdt) {
    const float dt = __bfloat162float(__float2bfloat16(expf(logdt)));
    const float ea = expf(dt * lre);
    float sn, cn;
    sincosf(dt * lim, &sn, &cn);
    const float br = ea * cn, bi = ea * sn, nr = br - 1.f;
    float cr, ci;
    if (fabsf(lre) >= fabsf(lim)) { const float r = lim / lre, dn = lre + lim * r; cr = (nr + bi * r) / dn; ci = (bi - nr * r) / dn; }
    else { const float r = lre / lim, dn = lre * r + lim; cr = (nr * r + bi) / dn; ci = (bi * r - nr) / dn; }
    return make_float4(br, bi, cr, ci);
}
__device__ __forceinline__ void epi_a1(const float* acc, const Params& P, const Cons& c, Pend& d, int mb, int nb, uint32_t atag) {
    const int t = c.lane & 3;
    const int p = nb * 128 + c.rank * 64 + c.wg * 32 + c.wq * 8 + (c.lane >> 2);
    uint32_t cw[4];
    lds128(cw, c.sb + S_COEF + (p & 63) * 16);
    const float4 cf = make_float4(__uint_as_float(cw[0]), __uint_as_float(cw[1]), __uint_as_float(cw[2]), __uint_as_float(cw[3]));
    TSTAMP(1)
    const float2 lam = make_float2(cf.x, P.swap_ri ? -cf.y : cf.y);
    const float a0 = P.swap_ri ? -2.f * cf.w : 2.f * cf.z, a1 = P.swap_ri ? 2.f * cf.z : -2.f * cf.w;
    const float b0 = P.swap_ri ? -2.f * cf.z : -2.f * cf.w, b1 = P.swap_ri ? -2.f * cf.w : -2.f * cf.z;
    float2 h = make_float2(0.f, 0.f);
#pragma unroll
    for (int round = 0; round < 2; round++) {
#pragma unroll
        for (int j = 0; j < 32; j++) {
            h = cfma(lam, h, make_float2(acc[j * 4], acc[j * 4 + 2]));
            const float r0 = fmaf(a0, h.x, a1 * h.y), m0 = fmaf(b0, h.x, b1 * h.y);
            h = cfma(lam, h, make_float2(acc[j * 4 + 1], acc[j * 4 + 3]));
            d.pk[j * 2] = pack2(r0, fmaf(a0, h.x, a1 * h.y));
            d.pk[j * 2 + 1] = pack2(m0, fmaf(b0, h.x, b1 * h.y));
        }
        if (round) break;
        float2 l64 = lam;
#pragma unroll
        for (int i = 0; i < 6; i++) l64 = cmul(l64, l64);
        const float2 l128 = cmul(l64, l64), l256 = cmul(l128, l128);
        float2 o = make_float2(__shfl_up_sync(0xffffffffu, h.x, 1), __shfl_up_sync(0xffffffffu, h.y, 1));
        if (t >= 1) h = cfma(l64, o, h);
        o = make_float2(__shfl_up_sync(0xffffffffu, h.x, 2), __shfl_up_sync(0xffffffffu, h.y, 2));
        if (t >= 2) h = cfma(l128, o, h);
        TSTAMP(2)
        if (t == 3) st_relaxed2(&g_agg[mb * 1024 + p], (__float_as_uint(h.x) & ~1u) | atag, __float_as_uint(h.y));
        h = make_float2(__shfl_up_sync(0xffffffffu, h.x, 1), __shfl_up_sync(0xffffffffu, h.y, 1));
        if (t == 0) h = make_float2(0.f, 0.f);
        uint32_t ax[7], ay[7];
        int n = 0;
        while (true) {
            uint32_t bad = 0;
#pragma unroll
            for (int j = 0; j < 7; j++) { ax[j] = atag; ay[j] = 0; ld_relaxed2_if(ax[j], ay[j], &g_agg[j * 1024 + p], j < mb); }
#pragma unroll
            for (int j = 0; j < 7; j++) bad |= ax[j] ^ atag;
            if (tags_ok(bad)) break;
            __nanosleep(400);
            if (++n > SPIN_LIMIT) spin_fault();
        }
        float2 carry = make_float2(0.f, 0.f);
#pragma unroll
        for (int j = 0; j < 7; j++) if (j < mb) carry = cfma(l256, carry, make_float2(__uint_as_float(ax[j]), __uint_as_float(ay[j])));
        float2 w = (t & 1) ? l64 : make_float2(1.f, 0.f);
        if (t & 2) w = cmul(w, l128);
        h = cfma(w, carry, h);
        TSTAMP(3)
    }
    TSTAMP(4)
    d.kind = PEND_HT; d.row = nb * 128 + c.rank * 64 + c.wg * 32; d.col = mb * 256; d.cnt = C_HT + mb * 2 + (nb >> 2);
}

__device__ __forceinline__ uint32_t acquire_stage(uint32_t sb, Pipe& p, uint32_t bytes) {
    mbar_wait(sb + B_EMPTY + p.stage * 8, p.phase ^ 1);
    mbar_expect(sb + B_FULL + p.stage * 8, bytes);
    return p.stage;
}
#define AHEAD 1
__device__ __forceinline__ void watcher(const Params& P, const uint32_t sb, const int rank, const int lane) {
    const uint32_t epoch = ld_relaxed1(&g_cnt(C_EPOCH)), e1 = epoch + 1;
    sts32(sb + S_EPOCH, epoch);
    __syncwarp();
    if (lane == 0 && atomicInc(&g_cnt(C_DONE), (DBGF(32) ? 95 : NPAIR * 2 - 1) + (epoch & P.zero)) == (DBGF(32) ? 95 : NPAIR * 2 - 1)) atomicAdd(&g_cnt(C_EPOCH), 1);
    if (gridDim.x != 96) {
        uint32_t v;
        asm("mov.u32 %0, %%smid;" : "=r"(v));
        if (lane == 0 && rank == 0) st_relaxed1(g_hint + 6272 + (blockIdx.x >> 1), e1 << 8 | v >> 1);
        for (int k = 0;; k++) {
            __nanosleep(1000);
            v = ld_relaxed1(g_hint + 6272 + min(lane, 17));
            if (__all_sync(0xffffffffu, (v ^ e1 << 8) < 256)) break;
            if (k > SPIN_LIMIT) spin_fault();
        }
        const uint32_t key = ((v & 255) >= 62 ? 0 : tpc_gpc(v & 255)) * 32 + lane;
        sts32(sb + S_TAIL, 48 + __popc(__ballot_sync(0xffffffffu, key < __shfl_sync(0xffffffffu, key, blockIdx.x >> 1)) & 0x3ffff));
        __syncwarp();
    }
    uint32_t met = 1;
    if (lane == 0) asm volatile("st.release.cta.shared.u32 [%0], 1;" ::"r"(sb + S_DEP) : "memory");
    const int pair = lds32(sb + S_TAIL), first = ITEM_OFF(pair) + (pair < NCHAIN ? NPRE + 1 : 1);
#pragma unroll 1
    for (int it = first; it < ITEM_OFF(pair + 1); it++) {
        const int item = ITEM(it), type = item >> 8, mb = (item >> 5) & 7, nb = item & 31;
        const int n = (0x24021420 >> (type * 4)) & 7;
        for (int k = 0; it > first && (int)lds32(sb + S_CUR) < it - AHEAD; k++) { __nanosleep(200); if (k > SPIN_LIMIT) spin_fault(); }
#pragma unroll 1
        for (int i = 0; i < n; i++) {
            int idx = n == 4 ? C_O + mb * 4 + i : C_HT + mb * 2 + i;
            uint32_t target = e1 * 16;
            if (type == T_A1) { idx = C_COEF; target = e1 * 4; }
            if (type == T_QA) {
                idx = i ? C_FLAG + (lane & 1) * 32 + nb * 2 + ((lane >> 1) & 1) : C_KV + mb;
                target = i ? epoch * 64 + mb * 8 + rank * 4 + 4 : e1 * 128;
            }
            if (lane < 4) { wait_count(&g_cnt(idx), target); fence_async(); }
            __syncwarp();
            if (lane == 0) asm volatile("st.release.cta.shared.u32 [%0], %1;" ::"r"(sb + S_DEP), "r"(++met) : "memory");
        }
    }
}
__device__ __forceinline__ bool dep_met(uint32_t sb, uint32_t n) { uint32_t v; asm volatile("ld.acquire.cta.shared.u32 %0, [%1];" : "=r"(v) : "r"(sb + S_DEP) : "memory"); return v >= n; }
__device__ __forceinline__ void dep_wait(uint32_t sb, uint32_t n) { for (int k = 0; !dep_met(sb, n); k++) { __nanosleep(32); if (k > SPIN_LIMIT * 8) spin_fault(); } }
__device__ __forceinline__ void producer(const Params& P, const uint32_t sb, int pair, const int rank) {
    Pipe p = {0, 0};
    uint32_t dep = 1;
    for (int it = ITEM_OFF(pair); it < ITEM_OFF(pair + 1); it++) {
        const int item = ITEM(it), type = item >> 8, mb = (item >> 5) & 7, nb = item & 31;
        if (type == T_CHAIN) {
            sts32(sb + S_CUR, 0);
            const uint32_t epoch = ld_relaxed1(&g_cnt(C_EPOCH)), e1 = epoch + 1;
            const int role = pair >> 4, h = (pair & 15) * 2 + rank;
#pragma unroll 1
            for (int i = 0, q = 0; i < 8; i++) {
                const int n = (0x13003333 >> (i * 4)) & 3;
                const uint32_t st = acquire_stage(sb, p, n * 16384);
                SSTAMP(1, i == 6) SSTAMP(3, i == 7)
#pragma unroll 1
                for (int k = 0; k < 2 * n; k++, q++)
                    tma3d(sb + st * STAGE + k * 8192, &P.tm[M_CQ + role], h * 128 + (fill_unit(q >> 1) & 1) * 64, word_col((fill_unit(q >> 1) & 14) + (q & 1)) & 8, word_col((fill_unit(q >> 1) & 14) + (q & 1)) >> 4, sb + B_FULL + st * 8, role ? EVICT_NORMAL : POL(3));
                pipe_next(p);
            }
            if (role == 0 && !DBGF(1)) { wait_count(&g_cnt(C_KV), e1 * 128); fence_async(); }
            mbar_wait(sb + B_EMPTY + 16, 1); mbar_wait(sb + B_EMPTY + 24, 1);
            mbar_expect(sb + B_WO, role ? 98304 : 65536);
            if (role == 0) { mbar_expect(sb + B_KVFULL, 16384); mbar_expect(sb + B_KVFULL + 8, 16384); }
#pragma unroll 1
            for (int k = role ? 0 : -4; k < 12; k++) {
                const bool kv = role == 0 && (k & 8);
                const int sg = k > 0;
                tma4d(kv ? sb + S_KV + sg * 16384 + (k & 3) * 4096 : sb + S_W2 + k * 8192, &P.tm[kv ? M_KV4 : M_CO + (k & 1)],
                      kv ? h * 128 + (k & 1) * 64 : (role == 0 ? 0 : role == 1 ? 256 : 640) + (k >> 1) * 64, kv ? (k & 2) * 1024 + sg * 32 : h * 8, sb + (kv ? B_KVFULL + sg * 8 : B_WO), POL(2));
            }
            SSTAMP(5, true)
            if (pair < 16) {
#pragma unroll 1
                for (int s = 2; s < 63; s++) {
                    mbar_wait(sb + B_KVGO + (s & 1) * 8, ((s >> 1) + 1) & 1);
                    wait_time(gtime() + P.dk, sb);
                    SSTAMP(6, s == 2)
                    const uint32_t bar = sb + B_KVFULL + (s & 1) * 8, dst = sb + S_KV + (s & 1) * 16384;
                    if (DBGF(2)) { mbar_arrive(bar); continue; }
                    mbar_expect(bar, 16384);
#pragma unroll 1
                    for (int i = 0; i < 4; i++) tma2d(dst + i * 4096, &P.tm[M_KVO], (pair * 2 + rank) * 128 + (i & 1) * 64, (i >> 1) * 2048 + (DBGF(32 | 512) ? s & 7 : s) * 32, bar, POL(1));
                    if ((s & 7) == 7 && !DBGF(1)) { wait_count(&g_cnt(C_KV + 1 + (s >> 3)), e1 * 128); fence_async(); }
                }
            } else {
                uint32_t* flag = &g_cnt(C_FLAG + pair * 2 + rank - 32);
                const int x = pair * 2 + rank - 32;
#pragma unroll 1
                for (int s = 0; s < 64; s++) {
                    mbar_wait(sb + B_PERS, s & 1);
                    if (s < 63) wait_time(gtime() + P.dp, sb);
                    if (!DBGF(4)) bulk_s2g((role == 1 ? g_km : g_vmt) + (s * 32 + h) * 512, sb + S_QX, 2048);
                    if (s < 57) {
                        uint8_t* m = P.gm + ((s + 6) & 7) * M_SLOT + (x >> 1) * 1024 + (x & 1) * 256;
                        bulk_s2g(m, sb + S_SX, 256); bulk_s2g(m + 512, sb + S_SX, 128);
                        bulk_s2g(g_f + ((s + 6) & 7) * F_SLOT + x * 768, sb + S_SX + 256, 768);
                    }
                    bulk_commit();
                    bulk_wait_read();
                    mbar_arrive(sb + B_KVGO);
                    bulk_wait_all();
                    fence_async();
                    if ((s & 3) == 3) st_relaxed1(flag, epoch * 64 + s + 1);
                }
            }
            mbar_wait(sb + B_RESUME, 0);
            pair = lds32(sb + S_TAIL);
            it = ITEM_OFF(pair) + NPRE;
            continue;
        }
        if (it == ITEM_OFF(pair) && pair >= NCHAIN) it = -1; else sts32(sb + S_CUR, it);
        const int m0 = mb * 256 + rank * 128;
        if (type <= T_OP) {
            const CUtensorMap* ma = &P.tm[type == T_OP ? M_OA : M_BX];
            const CUtensorMap* mw = &P.tm[type == T_OP ? M_WO : type == T_QA ? M_WQ : nb < 16 ? M_WK : M_WV];
            const int nk = type == T_OP ? 64 : 16, nc = (nb & 15) * 4 + rank * 2, ma0 = type == T_OP ? 4096 + m0 : m0;
#pragma unroll 1
            for (int kt = 0; kt < nk; kt++) {
                if (type == T_OP && (kt & 15) == 0) dep_wait(sb, ++dep);
                if (DBGF(256) && pair >= NCHAIN) { acquire_stage(sb, p, 0); pipe_next(p); continue; }
                const uint32_t st = acquire_stage(sb, p, STAGE), bar = sb + B_FULL + st * 8;
                tma2d(sb + st * STAGE, ma, kt * 64, ma0, bar, type == T_OP ? POL(6) : type == T_QA ? POL(12) : POL(13));
                tma3d_mc(sb + st * STAGE + 16384 + rank * 16384, mw, 0, kt * 64, nc, bar, type == T_KV && mb == 7 ? POL(9) : EVICT_NORMAL);
                pipe_next(p);
            }
            if (type == T_QA) {
                dep += 2;
                dep_wait(sb, dep);
#pragma unroll 1
                for (int e = 0; e < 4; e++) {
                    const uint32_t st = acquire_stage(sb, p, 40960), bar = sb + B_FULL + st * 8, dst = sb + st * STAGE;
                    tma2d(dst, &P.tm[M_OA], nb * 256 + (e >> 1) * 128, (e & 1) * 2048 + m0, bar, POL(0));
                    tma2d(dst + 16384, &P.tm[M_OA], nb * 256 + (e >> 1) * 128 + 64, (e & 1) * 2048 + m0, bar, POL(0));
                    const uint32_t* src = ((e & 1) ? g_vmt : g_km) + ((mb * 8 + rank * 4) * 32 + nb * 2 + (e >> 1)) * 512;
#pragma unroll 1
                    for (int i = 0; i < 4; i++) bulk_g2s(dst + 32768 + i * 2048, src + i * 32 * 512, 2048, bar);
                    pipe_next(p);
                }
            }
        } else if (type == T_OPH) {
#pragma unroll 1
            for (int kt = 0; kt < 64; kt++) {
                if ((kt & 15) == 0) dep_wait(sb, ++dep);
                const uint32_t st = acquire_stage(sb, p, 32768), bar = sb + B_FULL + st * 8;
                tma2d(sb + st * STAGE, &P.tm[M_OA], kt * 64, 4096 + m0, bar, POL(6));
                tma2d_mc(sb + st * STAGE + 16384 + rank * 8192, &P.tm[M_WOH], nb * 128 + rank * 64, kt * 64, bar, EVICT_NORMAL);
                pipe_next(p);
            }
        } else if (type == T_A1) {
#pragma unroll 1
            for (int kt = 0; kt < 16; kt++) {
                if (kt == 15) dep_wait(sb, ++dep);
                const uint32_t st = acquire_stage(sb, p, kt == 15 ? STAGE + 1024 : STAGE), bar = sb + B_FULL + st * 8;
                if (kt == 15) bulk_g2s(sb + S_COEF, g_coef + nb * 128 + rank * 64, 1024, bar);
                tma4d(sb + st * STAGE, &P.tm[M_AB], kt * 64, nb * 16 + rank * 8, bar, POL(10));
                tma4d_mc(sb + st * STAGE + 16384 + rank * 16384, &P.tm[M_AX], kt * 64, mb * 128 + rank * 16, bar, POL(10));
                pipe_next(p);
            }
        } else {
            const int hw = type == T_A2H ? 64 : 128;
            const CUtensorMap* mc = &P.tm[type == T_A2H ? M_CREH : M_CRE];
#pragma unroll 1
            for (int kt = 0; kt < 32; kt++) {
                if ((kt & 15) == 0) dep_wait(sb, ++dep);
                const uint32_t st = acquire_stage(sb, p, 16384 + hw * 256), bar = sb + B_FULL + st * 8;
                tma3d(sb + st * STAGE, &P.tm[M_HT], 0, (kt & 1) * 1024 + (kt >> 1) * 64, mb * 4 + rank * 2, bar, POL(7));
                tma2d_mc(sb + st * STAGE + 16384 + rank * hw * 128, mc + (kt & 1), (kt >> 1) * 64, (nb * 2 + rank) * hw, bar, POL(11));
                pipe_next(p);
            }
#pragma unroll 1
            for (int col = nb * 2 * hw; col < (nb + 1) * 2 * hw; col += 128) {
                const uint32_t st = acquire_stage(sb, p, 32768 + 256), bar = sb + B_FULL + st * 8;
                tma4d(sb + st * STAGE, &P.tm[M_AX], col, mb * 128 + rank * 16, bar, POL(8));
                tma4d(sb + st * STAGE + 16384, &P.tm[M_AX], col + 64, mb * 128 + rank * 16, bar, POL(8));
                bulk_g2s(sb + st * STAGE + 32768, P.Dskip + col, 256, bar);
                pipe_next(p);
            }
        }
        if (it < 0) { dep_wait(sb, 1); pair = lds32(sb + S_TAIL); it = ITEM_OFF(pair); }
    }
}

__device__ __forceinline__ uint32_t fresh_tid() { uint32_t t; asm volatile("mov.u32 %0, %%tid.x;" : "=r"(t)); return t; }
__device__ __forceinline__ uint32_t fresh_ctaid() { uint32_t t; asm volatile("mov.u32 %0, %%ctaid.x;" : "=r"(t)); return logical_cta(t); }
__device__ __forceinline__ void reset_state(Cons& c, Pend& d, uint32_t sb, bool resumed) {
    const uint32_t t = fresh_tid(), b = fresh_ctaid();
    const int w = __shfl_sync(0xffffffffu, t >> 5, 0);
    c.sb = sb; c.wg = w >> 2; c.wq = w & 3; c.lane = t & 31;
    c.rank = __shfl_sync(0xffffffffu, b & 1, 0); c.pair = __shfl_sync(0xffffffffu, resumed && b < NCHAIN * 2 ? lds32(sb + S_TAIL) : b >> 1, 0);
    c.rel = mapa(sb + B_EMPTY, cluster_rank() ^ (c.lane & 1));
    c.p.stage = 0; c.p.phase = 0;
    c.nst = resumed && c.pair < NCHAIN ? 2 * NPRE : 0;
    d = Pend{};
}
#define PROF_ITEM(i)
#define PROF_MAIN(i)

__global__ void __launch_bounds__(384, 1) fused_kernel(const __grid_constant__ Params P) {
    extern __shared__ __align__(1024) uint8_t smem[];
    const uint32_t sb = smem_u32(smem);
    asm volatile("griddepcontrol.launch_dependents;");
    const int tid = threadIdx.x, lane = tid & 31;
    const int warp = __shfl_sync(0xffffffffu, tid >> 5, 0);
    const int pair = __shfl_sync(0xffffffffu, logical_cta(blockIdx.x) >> 1, 0), rank = __shfl_sync(0xffffffffu, blockIdx.x & 1, 0);
    if (tid == 0) {
        if (sb & 1023) spin_fault();
        sts32(sb + S_DEP, 0); sts32(sb + S_CUR, 0); sts32(sb + S_TAIL, pair); sts32(sb + S_CTA, pair * 2 + rank);
        for (int i = 0; i < NSTAGE; i++) { mbar_init(sb + B_FULL + i * 8, 1); mbar_init(sb + B_EMPTY + i * 8, 16); }
        mbar_init(sb + B_RESUME, 2);
        mbar_init(sb + B_KVFULL, 1); mbar_init(sb + B_KVFULL + 8, 1);
        mbar_init(sb + B_GO, 1); mbar_init(sb + B_KVGO, 1); mbar_init(sb + B_KVGO + 8, 1); mbar_init(sb + B_K, 1); mbar_init(sb + B_V, 1); mbar_init(sb + B_PERS, pair < 16 ? 1 : 8); mbar_init(sb + B_INIT, 3);
        mbar_init(sb + B_WO, 1);
        for (int i = 0; i < 2; i++) { mbar_init(sb + B_SFULL + i * 8, 4); mbar_init(sb + B_SFREE + i * 8, 1); }
        mbar_init(sb + B_RELA, 1); mbar_init(sb + B_RELB, 1);
        asm volatile("fence.mbarrier_init.release.cluster;" ::: "memory");
        if (pair < 16) { mbar_expect(sb + B_K, KE ? 1024 : 2048); mbar_expect(sb + B_PERS, 1024); }
        mbar_expect(sb + B_V, 2048);
    }
    __syncthreads();
    cluster_arrive();
    if (warp >= 8) {
        asm volatile("setmaxnreg.dec.sync.aligned.u32 24;");
        if (warp != 8) cluster_wait();
        if (warp == 10 && lane < M_COUNT) map_prefetch(&P.tm[lane]);
        if (warp == 11 && lane == 0 && pair < 16) {
            const uint32_t t0 = gtime();
#pragma unroll 1
            for (int i = 0; i < 32; i++) {
                wait_time(t0 + P.pf0 + i * P.pf1, sb);
                asm volatile("cp.async.bulk.prefetch.tensor.3d.L2.global [%0, {%1, %2, %3}];" ::"l"(&P.tm[M_CQ]), "r"((pair * 2 + rank) * 128 + (i & 1) * 64), "r"((i & 2) * 4), "r"((i >> 2) * 8) : "memory");
            }
        }
        if (warp == 9 && pair < NCHAIN) pacer(P, sb, lane);
        if (warp == 9) watcher(P, sb, rank, lane);
        if (warp >= 10 && lane == 0) store_warp(P, sb, warp - 10);
        if (warp == 8) {
            cluster_wait();
            if (lane == 0) producer(P, sb, lds32(sb + S_CTA) >> 1, rank);
            __syncwarp();
            cluster_arrive(); cluster_wait();
        }
    } else {
        asm volatile("setmaxnreg.inc.sync.aligned.u32 240;");
        Cons c;
        Pend d;
        if (pair < NCHAIN) {
            mem0_max(P, sb, tid);
            cluster_wait();
            reset_state(c, d, sb, false);
#pragma unroll 1
            for (int i = 0; i < NPRE; i++) {
                PROF_ITEM(i)
                const int item = ITEM(ITEM_OFF(pair) + i);
                float acc[128];
                mainloop<256, true>(acc, P, c, d, T_KV);
                epi_kv(acc, c, d, (item >> 5) & 7, item & 31);
            }
            ISTAMP(4)
            drain<0, true>(P, c, d);
            drain<1, true>(P, c, d);
            PROF_ITEM(NPRE)
            uint32_t wr[NR][4];
            load_weights(wr, sb, warp, lane, [&]() { staging_wait(c); });
            const int h = (pair & 15) * 2 + rank;
            if (pair < 16) chain_role<0>(P, wr, sb, h, warp, lane);
            else if (pair < 32) chain_role<1>(P, wr, sb, h, warp, lane);
            else chain_role<2>(P, wr, sb, h, warp, lane);
            fence_async_smem();
            bar_sync(1, 256);
            const uint32_t t2 = fresh_tid();
            if (t2 < 2) mbar_arrive_cluster(mapa(sb + B_RESUME, cluster_rank() ^ t2));
        } else if (pair >= NPAIR - 2) {
            const int ch = (pair - (NPAIR - 2)) * 512 + rank * 256 + tid;
            g_coef[ch] = ssm_coef(__bfloat162float(P.Lre[ch]), __bfloat162float(P.Lim[ch]), __bfloat162float(P.logdt[ch]));
            bar_sync(1, 256);
            if (tid == 0) red_release(&g_cnt(C_COEF));
        }
        reset_state(c, d, sb, true);
        if (c.pair >= NCHAIN) cluster_wait();
        for (int it = ITEM_OFF(c.pair) + (c.pair < NCHAIN ? NPRE + 1 : 0);; it++) {
            const bool last = it == ITEM_OFF(c.pair + 1);
            if (d.kind != PEND_NONE && (last || !bar_and(5 + c.wg, mbar_test(sb + B_FULL + c.p.stage * 8, c.p.phase)))) drain_all(P, c, d);
            if (last) break;
            const int item = ITEM(it), type = item >> 8, mb = (item >> 5) & 7, nb = item & 31;
            PROF_ITEM(it - ITEM_OFF(c.pair))
            if (type >= T_OPH) {
                float acc[64];
                mainloop<128>(acc, P, c, d, type);
                PROF_MAIN(it - ITEM_OFF(c.pair))
                if (type == T_OPH) epi_oph(acc, c, d, mb, nb);
                else epi_a2_half<0>(acc, P, c, mb, nb * 128);
            } else {
                float acc[128];
                mainloop<256>(acc, P, c, d, type);
                PROF_MAIN(it - ITEM_OFF(c.pair))
                if (type == T_KV) epi_kv(acc, c, d, mb, nb);
                else if (type == T_QA) epi_qa(acc, c, d, mb, nb);
                else if (type == T_OP) epi_op(acc, c, d, mb, nb);
                else if (type == T_A1) epi_a1(acc, P, c, d, mb, nb, (lds32(sb + S_EPOCH) + 1) & 1);
                else { epi_a2_half<0>(acc, P, c, mb, nb * 256); epi_a2_half<1>(acc, P, c, mb, nb * 256); }
            }
            if (it == ITEM_OFF(c.pair)) { dep_wait(sb, 1); c.pair = __shfl_sync(0xffffffffu, lds32(sb + S_TAIL), 0); it = ITEM_OFF(c.pair); }
        }
        staging_wait(c);
        staging_post(c, PEND_NONE, 0, 0, 0);
        cluster_arrive(); cluster_wait();
    }
}

typedef CUresult (*EncodeFn)(CUtensorMap*, CUtensorMapDataType, cuuint32_t, void*, const cuuint64_t*, const cuuint64_t*, const cuuint32_t*, const cuuint32_t*,
                             CUtensorMapInterleave, CUtensorMapSwizzle, CUtensorMapL2promotion, CUtensorMapFloatOOBfill);
void encode(EncodeFn fn, CUtensorMap* m, const void* base, int rank, const uint64_t* dims, const uint64_t* strides, const uint32_t* box, CUtensorMapSwizzle swz = CU_TENSOR_MAP_SWIZZLE_128B) {
    cuuint64_t d[5], s[5]; cuuint32_t b[5], e[5];
    for (int i = 0; i < rank; i++) { d[i] = dims[i]; b[i] = box[i]; e[i] = 1; if (i) s[i - 1] = strides[i - 1]; }
    fn(m, CU_TENSOR_MAP_DATA_TYPE_BFLOAT16, rank, (void*)base, d, s, b, e, CU_TENSOR_MAP_INTERLEAVE_NONE, swz,
       CU_TENSOR_MAP_L2_PROMOTION_L2_256B, CU_TENSOR_MAP_FLOAT_OOB_FILL_NONE);
}
void map_kmajor(EncodeFn fn, CUtensorMap* m, const void* base, uint64_t rows, uint64_t cols, uint32_t box_rows) {
    const uint64_t d[2] = {cols, rows}, s[1] = {cols * 2}; const uint32_t b[2] = {64, box_rows};
    encode(fn, m, base, 2, d, s, b);
}
void map_mnmajor(EncodeFn fn, CUtensorMap* m, const void* base, uint64_t krows, uint64_t cols) {
    const uint64_t d[3] = {64, krows, cols / 64}, s[2] = {cols * 2, 128}; const uint32_t b[3] = {64, 64, 2};
    encode(fn, m, base, 3, d, s, b);
}

}

extern "C" void kernel_launch(void* const* d_in, const int* in_sizes, int n_in, void* d_out, int out_size) {
    static Params P;
    static EncodeFn fn = nullptr;
    if (!fn) {
        cudaDriverEntryPointQueryResult q;
        cudaGetDriverEntryPoint("cuTensorMapEncodeTiled", (void**)&fn, cudaEnableDefault, &q);
        cudaFuncSetAttribute(fused_kernel, cudaFuncAttributeMaxDynamicSharedMemorySize, S_TOTAL);
    }
    const bf16* in[15];
    for (int i = 0; i < 15; i++) in[i] = (const bf16*)d_in[i];
    void *kvo, *ht, *gm;
    cudaGetSymbolAddress(&gm, g_m);
    P.gm = (uint8_t*)(((uintptr_t)gm + 32767) & ~(uintptr_t)32767);
    cudaGetSymbolAddress(&kvo, g_kvo);
    cudaGetSymbolAddress(&ht, g_ht);
    map_kmajor(fn, &P.tm[M_BX], in[9], 2048, 1024, 128);
    map_mnmajor(fn, &P.tm[M_WQ], in[11], 1024, 4096);
    map_mnmajor(fn, &P.tm[M_WK], in[12], 1024, 4096);
    map_mnmajor(fn, &P.tm[M_WV], in[13], 1024, 4096);
    map_mnmajor(fn, &P.tm[M_WO], in[14], 4096, 1024);
    map_kmajor(fn, &P.tm[M_OA], kvo, 3 * 2048, 4096, 128);
    P.swap_ri = in[4] < in[3];
    {
        const bf16* lo = P.swap_ri ? in[4] : in[3];
        const uint64_t diff = (uint64_t)((const char*)(P.swap_ri ? in[3] : in[4]) - (const char*)lo);
        const uint64_t d[4] = {1024, 8, 2, 128}, s[3] = {2048, diff, 16384}; const uint32_t b[4] = {64, 8, 2, 8};
        encode(fn, &P.tm[M_AB], lo, 4, d, s, b);
    }
    {
        const uint64_t d[4] = {1024, 2, 4, 1024}, s[3] = {2048, 64 * 2048, 4096}; const uint32_t b[4] = {64, 2, 4, 16};
        encode(fn, &P.tm[M_AX], in[0], 4, d, s, b);
    }
    map_mnmajor(fn, &P.tm[M_HT], ht, 2048, 2048);
    map_kmajor(fn, &P.tm[M_CRE], in[5], 1024, 1024, 128);
    map_kmajor(fn, &P.tm[M_CIM], in[6], 1024, 1024, 128);
    map_kmajor(fn, &P.tm[M_KVO], kvo, 3 * 2048, 4096, 32);
    map_kmajor(fn, &P.tm[M_HTS], ht, 2048, 2048, 32);
    map_kmajor(fn, &P.tm[M_WOH], in[14], 4096, 1024, 64);
    map_kmajor(fn, &P.tm[M_CREH], in[5], 1024, 1024, 64);
    map_kmajor(fn, &P.tm[M_CIMH], in[6], 1024, 1024, 64);
    for (int i = 0; i < 3; i++) {
        const uint64_t d[3] = {4096, 16, 64}, s[2] = {8192, 16 * 8192}; const uint32_t b[3] = {64, 8, 8};
        encode(fn, &P.tm[M_CQ + i], in[11 + i], 3, d, s, b);
    }
    {
        const uint64_t d[4] = {4096, 1, 1, 4096}, s[3] = {8192, 8192, 8192}; const uint32_t b[4] = {64, 1, 1, 32};
        encode(fn, &P.tm[M_KV4], kvo, 4, d, s, b);
    }
    for (int e = 0; e < 2; e++) {
        const uint64_t d[4] = {1024, 2, 4, 256}, s[3] = {8 * 2048, 2 * 2048, 16 * 2048}; const uint32_t b[4] = {64, 2, 4, 8};
        encode(fn, &P.tm[M_CO + e], in[14] + e * 1024, 4, d, s, b);
    }
    P.Wq = in[11]; P.Wk = in[12]; P.Wv = in[13]; P.Wo = in[14]; P.mem0 = in[10];
    P.Lre = in[1]; P.Lim = in[2]; P.logdt = in[7]; P.Dskip = in[8];
    P.out = (float*)d_out;
    P.two26 = 1u << 26;
    P.lag = 0x22023302;
    P.ds = 400; P.dc = 1600; P.alpha = 0.3f; P.extra = 200; P.da = 180; P.db = 420; P.dk = 750; P.dp = 1500; P.dv = 60; P.pf0 = 2000; P.pf1 = 250; P.back = 150; P.ds0 = 950;
    for (int i = 0; i < (DBGF(32) ? 1 : 2); i++) {
        cudaLaunchConfig_t cfg = {};
        cfg.gridDim = dim3(i ? 36 : 96); cfg.blockDim = dim3(384); cfg.dynamicSmemBytes = S_TOTAL; cfg.stream = cudaStreamPerThread;
        cudaLaunchAttribute at[2];
        at[0].id = cudaLaunchAttributeClusterDimension; at[0].val.clusterDim.x = i ? 2 : 6; at[0].val.clusterDim.y = at[0].val.clusterDim.z = 1;
        at[1].id = cudaLaunchAttributeProgrammaticStreamSerialization; at[1].val.programmaticStreamSerializationAllowed = 1;
        cfg.attrs = at; cfg.numAttrs = 1 + i;
        cudaLaunchKernelEx(&cfg, fused_kernel, P);
    }
}
```

```cpp
#include <cuda_runtime.h>
#include <cuda_bf16.h>
#include <cuda.h>
#include <stdint.h>
#include <string.h>

typedef __nv_bfloat16 bf16;

namespace {

#define POLL 200
constexpr int SPIN_LIMIT = 1 << 22;
constexpr int NPAIR = 66;
constexpr int NCHAIN = 48;
enum { T_KV = 0, T_QA = 1, T_OP = 2, T_A1 = 3, T_A2 = 4, T_CHAIN = 5, T_OPH = 6, T_A2H = 7 };
enum { M_BX = 0, M_WQ, M_WK, M_WV, M_WO, M_OA, M_AB, M_AX, M_HT, M_CRE, M_CIM, M_KVO, M_HTS, M_WOH, M_CREH, M_CIMH, M_CQ, M_CK, M_CV, M_CO, M_CO1, M_KV4, M_COUNT };
enum { C_KV = 0, C_HT = 8, C_DONE = 24, C_EPOCH = 25, C_COEF = 26, C_FLAG = 32, C_O = 96 };

struct Params {
    CUtensorMap tm[M_COUNT];
    const bf16 *Wq, *Wk, *Wv, *Wo, *mem0, *Lre, *Lim, *logdt, *Dskip;
    float* out;
    uint8_t* gm;
    int swap_ri, zero;
    uint32_t two26, lag;
    int ds, da, db, dk, dv, back, ds0, pf0, pf1, dc, extra, dp;
    float alpha;
#define DBGF(x) false
};

constexpr int NPRE = 1;
__constant__ uint16_t c_off[67] = {0, 5, 10, 15, 21, 25, 29, 35, 39, 43, 47, 51, 55, 59, 63, 67, 71, 76, 81, 86, 91, 95, 99, 103, 108, 112, 116, 120, 124, 128, 133, 137, 142, 147, 152, 157, 162, 166, 170, 175, 179, 183, 187, 191, 195, 200, 205, 209, 213, 232, 252, 272, 291, 311, 331, 349, 369, 389, 407, 427, 446, 466, 485, 505, 524, 543, 562};
__constant__ uint16_t c_items[640] = {
    32, 1280, 453, 492, 1056, 49, 1280, 485, 494, 1249, 34, 1280, 293, 301, 1120, 51, 1280, 458, 457, 428, 1959, 36, 1280, 896,
    642, 53, 1280, 898, 546, 38, 1280, 833, 961, 996, 1957, 55, 1280, 865, 578, 40, 1280, 495, 576, 57, 1280, 463, 579, 42,
    1280, 262, 675, 59, 1280, 264, 739, 44, 1280, 335, 608, 61, 1280, 897, 738, 46, 1280, 361, 707, 63, 1280, 265, 705, 0,
    1280, 388, 302, 1217, 1, 1280, 489, 493, 1248, 2, 1280, 391, 333, 1250, 3, 1280, 263, 459, 1088, 4, 1280, 866, 673, 5,
    1280, 931, 640, 6, 1280, 835, 737, 7, 1280, 899, 488, 1185, 8, 1280, 838, 643, 9, 1280, 839, 641, 10, 1280, 870, 672,
    11, 1280, 864, 515, 12, 1280, 871, 674, 13, 1280, 935, 933, 1219, 14, 1280, 772, 736, 15, 1280, 994, 964, 1091, 16, 1280,
    393, 332, 1216, 17, 1280, 484, 300, 1121, 18, 1280, 487, 364, 1058, 19, 1280, 423, 462, 1152, 20, 1280, 867, 544, 21, 1280,
    930, 545, 22, 1280, 900, 424, 1089, 23, 1280, 836, 577, 24, 1280, 903, 611, 25, 1280, 902, 609, 26, 1280, 928, 547, 27,
    1280, 869, 512, 28, 1280, 868, 901, 1251, 29, 1280, 932, 965, 1218, 30, 1280, 804, 704, 31, 1280, 962, 706, 33, 95, 94,
    127, 126, 159, 158, 255, 223, 191, 324, 352, 399, 422, 289, 425, 392, 490, 1024, 35, 93, 92, 125, 124, 157, 156, 189,
    221, 253, 252, 323, 254, 292, 418, 417, 386, 299, 365, 1956, 37, 91, 90, 123, 122, 155, 154, 187, 186, 251, 219, 250,
    334, 426, 366, 448, 449, 491, 430, 1123, 39, 89, 88, 121, 120, 153, 152, 185, 217, 184, 216, 218, 249, 248, 358, 288,
    321, 452, 514, 41, 87, 86, 119, 118, 151, 215, 247, 183, 214, 200, 199, 246, 325, 296, 420, 482, 268, 396, 1059, 43,
    85, 84, 117, 116, 149, 213, 181, 212, 180, 195, 193, 297, 363, 266, 326, 303, 455, 431, 1153, 45, 83, 82, 115, 114,
    147, 211, 179, 210, 178, 329, 243, 355, 356, 805, 837, 929, 610, 47, 81, 80, 113, 112, 145, 177, 176, 241, 190, 209,
    208, 240, 773, 832, 290, 480, 995, 966, 1057, 48, 79, 78, 111, 143, 142, 207, 175, 206, 174, 222, 192, 239, 256, 257,
    390, 389, 934, 997, 1090, 50, 77, 76, 109, 141, 140, 237, 173, 236, 234, 245, 205, 258, 771, 427, 421, 483, 513, 52,
    75, 74, 107, 139, 138, 171, 235, 170, 203, 202, 770, 774, 359, 775, 801, 963, 993, 397, 1958, 54, 73, 72, 105, 137,
    136, 169, 201, 233, 168, 362, 270, 394, 353, 807, 806, 960, 367, 1184, 56, 71, 103, 104, 135, 150, 167, 182, 231, 232,
    242, 238, 384, 224, 357, 387, 320, 486, 429, 1026, 58, 70, 102, 110, 134, 148, 166, 172, 230, 188, 267, 800, 244, 419,
    291, 295, 328, 269, 1027, 60, 69, 101, 108, 133, 146, 197, 165, 204, 198, 220, 322, 229, 398, 802, 803, 395, 454, 461,
    1155, 62, 68, 100, 106, 132, 144, 228, 164, 327, 196, 225, 768, 769, 260, 416, 481, 967, 999, 1122, 64, 67, 99, 97,
    131, 129, 163, 161, 271, 354, 259, 227, 261, 294, 450, 834, 992, 998, 1025, 65, 66, 98, 96, 130, 128, 162, 160, 298,
    226, 194, 385, 331, 330, 360, 451, 456, 460, 1154,
};
#define ITEM_OFF(p) c_off[p]
#define ITEM(i) c_items[i]

__device__ __align__(1024) bf16 g_kvo[3 * 2048 * 4096];
__device__ __align__(1024) bf16 g_ht[2048 * 2048];
__device__ __align__(1024) uint8_t g_m[9 * 32768];
__device__ __align__(1024) uint8_t g_f[8 * 49152];
__device__ __align__(1024) uint32_t g_km[64 * 32 * 512];
__device__ __align__(1024) uint32_t g_vmt[64 * 32 * 512];
__device__ __align__(1024) float2 g_agg[8 * 1024];
__device__ __align__(1024) float4 g_coef[1024];
__device__ __align__(1024) uint32_t g_cntl[128 * 32];
#define g_cnt(i) g_cntl[(i) * 32]
__device__ __align__(1024) uint32_t g_hint[6144 + 160];
#define SSTAMP(i, cond)
#define PROF(i)
#define GT_EDGE(o)
constexpr int M_SLOT = 32768, F_SLOT = 49152;

constexpr int STAGE = 49152, NSTAGE = 4;
constexpr int S_STG = NSTAGE * STAGE;
constexpr int S_BAR = S_STG + 32768;
constexpr int B_FULL = S_BAR, B_EMPTY = S_BAR + 32, B_RESUME = S_BAR + 64, B_KVFULL = S_BAR + 72, B_GO = S_BAR + 88, B_K = S_BAR + 96, B_PERS = S_BAR + 104, B_INIT = S_BAR + 112, B_RELA = S_BAR + 120, B_V = S_BAR + 128, B_WO = S_BAR + 136,
              B_SFULL = S_BAR + 144, B_SFREE = S_BAR + 160, S_DESC = S_BAR + 176, S_REDO = S_BAR + 256 + 512 + 64, S_EPOCH = S_BAR + 208, B_RELB = S_BAR + 216, B_KVGO = S_BAR + 224, S_DEP = S_BAR + 240, S_CUR = S_BAR + 244, S_TAIL = S_BAR + 248, S_CTA = S_BAR + 252;
constexpr int S_COEF = S_BAR + 256 + 512, S_TOTAL = S_COEF + 1024;
constexpr int S_W1 = 0;
constexpr int S_O = 24 * 4096, S_VL = S_O + 2048, S_MX = 25 * 4096, S_SC = S_MX + 64, S_SUM = S_MX + 128;
constexpr int S_KL = 26 * 4096;
constexpr int S_W2 = 27 * 4096;
constexpr int S_KV = S_W2 + 65536;
constexpr int S_P1 = S_W2 + 98304;
constexpr int S_QX = S_P1 + 16384;
constexpr int S_SX = S_QX + 2048;
static_assert(S_SX + 1280 <= S_BAR, "chain smem overlaps barriers");
constexpr int NR = 40, NS = 64 - NR;

__device__ __forceinline__ uint32_t logical_cta(uint32_t b) {
    const uint32_t c = b / 6, r = b - c * 6;
    return gridDim.x != 96 ? 96 + b : ((r >> 1) + (c >= 8) + (c >= 15)) % 3 * 32 + c * 2 + (r & 1);
}
__device__ __forceinline__ uint32_t cluster_rank() { uint32_t r; asm("mov.u32 %0, %%cluster_ctarank;" : "=r"(r)); return r; }
__device__ __forceinline__ uint16_t pair_mask() { return (uint16_t)(3u << (cluster_rank() & 6)); }
__device__ __forceinline__ void spin_fault() { asm volatile("st.global.u32 [%0], 0;" ::"l"(0ull) : "memory"); }
__device__ __forceinline__ uint32_t smem_u32(const void* p) { return (uint32_t)__cvta_generic_to_shared(p); }
__device__ __forceinline__ uint32_t opq(uint32_t x, int lane) { return __shfl_sync(0xffffffffu, x, lane); }
__device__ __forceinline__ uint32_t mapa(uint32_t a, uint32_t r) { uint32_t d; asm volatile("mapa.shared::cluster.u32 %0, %1, %2;" : "=r"(d) : "r"(a), "r"(r)); return d; }
__device__ __forceinline__ void mma16816(float* d, uint32_t a0, uint32_t a1, uint32_t a2, uint32_t a3, uint32_t b0, uint32_t b1) {
    asm("mma.sync.aligned.m16n8k16.row.col.f32.bf16.bf16.f32 {%0,%1,%2,%3}, {%4,%5,%6,%7}, {%8,%9}, {%0,%1,%2,%3};"
        : "+f"(d[0]), "+f"(d[1]), "+f"(d[2]), "+f"(d[3]) : "r"(a0), "r"(a1), "r"(a2), "r"(a3), "r"(b0), "r"(b1));
}
__device__ __forceinline__ void mma1688(float* d, uint32_t a0, uint32_t a1, uint32_t b0) {
    asm("mma.sync.aligned.m16n8k8.row.col.f32.bf16.bf16.f32 {%0,%1,%2,%3}, {%4,%5}, {%6}, {%0,%1,%2,%3};"
        : "+f"(d[0]), "+f"(d[1]), "+f"(d[2]), "+f"(d[3]) : "r"(a0), "r"(a1), "r"(b0));
}
__device__ __forceinline__ void ldsm4(uint32_t* r, uint32_t a) {
    asm volatile("ldmatrix.sync.aligned.m8n8.x4.shared.b16 {%0,%1,%2,%3}, [%4];" : "=r"(r[0]), "=r"(r[1]), "=r"(r[2]), "=r"(r[3]) : "r"(a));
}
__device__ __forceinline__ void ldsm4t(uint32_t* r, uint32_t a) {
    asm volatile("ldmatrix.sync.aligned.m8n8.x4.trans.shared.b16 {%0,%1,%2,%3}, [%4];" : "=r"(r[0]), "=r"(r[1]), "=r"(r[2]), "=r"(r[3]) : "r"(a));
}
__device__ __forceinline__ void stsm4(uint32_t a, uint32_t r0, uint32_t r1, uint32_t r2, uint32_t r3) {
    asm volatile("stmatrix.sync.aligned.m8n8.x4.shared.b16 [%0], {%1,%2,%3,%4};" ::"r"(a), "r"(r0), "r"(r1), "r"(r2), "r"(r3) : "memory");
}
__device__ __forceinline__ void stsm4t(uint32_t a, uint32_t r0, uint32_t r1, uint32_t r2, uint32_t r3) {
    asm volatile("stmatrix.sync.aligned.m8n8.x4.trans.shared.b16 [%0], {%1,%2,%3,%4};" ::"r"(a), "r"(r0), "r"(r1), "r"(r2), "r"(r3) : "memory");
}
__device__ __forceinline__ uint32_t pack2(float lo, float hi) { uint32_t d; asm("cvt.rn.bf16x2.f32 %0, %1, %2;" : "=r"(d) : "f"(hi), "f"(lo)); return d; }
__device__ __forceinline__ float bf_lo(uint32_t u) { return __uint_as_float(u << 16); }
__device__ __forceinline__ float bf_hi(uint32_t u) { return __uint_as_float(u & 0xffff0000u); }
__device__ __forceinline__ uint32_t hmul2(uint32_t a, uint32_t b) { uint32_t d; asm("mul.rn.bf16x2 %0, %1, %2;" : "=r"(d) : "r"(a), "r"(b)); return d; }
__device__ __forceinline__ float ex2(float x) { float y; asm("ex2.approx.ftz.f32 %0, %1;" : "=f"(y) : "f"(x)); return y; }
__device__ __forceinline__ float rcp(float x) { float y; asm("rcp.approx.ftz.f32 %0, %1;" : "=f"(y) : "f"(x)); return y; }
__device__ __forceinline__ void st_relaxed4(const void* p, uint32_t a, uint32_t b, uint32_t c, uint32_t d) {
    asm volatile("{\n.reg .b128 t;\nmov.b128 t, {%1,%2,%3,%4};\nst.relaxed.gpu.global.b128 [%0], t;\n}" ::"l"(p), "r"(a), "r"(b), "r"(c), "r"(d) : "memory");
}
__device__ __forceinline__ void st_relaxed2(const void* p, uint32_t a, uint32_t b) {
    asm volatile("{\n.reg .b64 t;\nmov.b64 t, {%1,%2};\nst.relaxed.gpu.global.b64 [%0], t;\n}" ::"l"(p), "r"(a), "r"(b) : "memory");
}
__device__ __forceinline__ void ld_relaxed2_if(uint32_t& a, uint32_t& b, const void* p, bool on) {
    asm volatile("{\n.reg .pred P;\n.reg .b64 t;\nsetp.ne.u32 P, %3, 0;\nmov.b64 t, {%0,%1};\n@P ld.relaxed.gpu.global.b64 t, [%2];\nmov.b64 {%0,%1}, t;\n}" : "+r"(a), "+r"(b) : "l"(p), "r"((uint32_t)on) : "memory");
}
__device__ __forceinline__ uint32_t ld_relaxed1(const void* p) { uint32_t v; asm volatile("ld.relaxed.gpu.global.u32 %0, [%1];" : "=r"(v) : "l"(p) : "memory"); return v; }
__device__ __forceinline__ void st_relaxed1(const void* p, uint32_t v) { asm volatile("st.relaxed.gpu.global.u32 [%0], %1;" ::"l"(p), "r"(v) : "memory"); }
__device__ __forceinline__ uint32_t ld_acquire(const void* p) { uint32_t v; asm volatile("ld.acquire.gpu.global.u32 %0, [%1];" : "=r"(v) : "l"(p) : "memory"); return v; }
__device__ __forceinline__ void red_release(void* p) { asm volatile("red.release.gpu.global.add.u32 [%0], 1;" ::"l"(p) : "memory"); }
__device__ __forceinline__ void st_stream2(float* p, float a, float b) { asm volatile("st.global.cs.v2.f32 [%0], {%1, %2};" ::"l"(p), "f"(a), "f"(b) : "memory"); }
__device__ __forceinline__ void fence_acquire() { asm volatile("fence.acquire.gpu;" ::: "memory"); }
__device__ __forceinline__ void fence_release() { asm volatile("fence.release.gpu;" ::: "memory"); }
__device__ __forceinline__ void fence_async() {  asm volatile("fence.proxy.async.global;" ::: "memory"); }
__device__ __forceinline__ void fence_async_smem() { asm volatile("fence.proxy.async.shared::cta;" ::: "memory"); }
__device__ __forceinline__ void wait_count(const uint32_t* p, uint32_t target) {
    int n = 0;
    while ((int32_t)(ld_acquire(p) - target) < 0) { __nanosleep(POLL); if (++n > SPIN_LIMIT) spin_fault(); }
}
__device__ __forceinline__ void bar_sync(int id, int n) { asm volatile("bar.sync %0, %1;" ::"r"(id), "r"(n) : "memory"); }
__device__ __forceinline__ void bar_arrive(int id, int n) { asm volatile("bar.arrive %0, %1;" ::"r"(id), "r"(n) : "memory"); }
__device__ __forceinline__ bool bar_and(int id, bool v) {
    uint32_t r;
    asm volatile("{\n.reg .pred P, Q;\nsetp.ne.u32 Q, %2, 0;\nbar.red.and.pred P, %1, 128, Q;\nselp.u32 %0, 1, 0, P;\n}" : "=r"(r) : "r"(id), "r"((uint32_t)v) : "memory");
    return r;
}
__device__ __forceinline__ void lds128(uint32_t* v, uint32_t a) { asm volatile("ld.shared.v4.b32 {%0,%1,%2,%3}, [%4];" : "=r"(v[0]), "=r"(v[1]), "=r"(v[2]), "=r"(v[3]) : "r"(a) : "memory"); }
__device__ __forceinline__ uint32_t lds32(uint32_t a) { uint32_t v; asm volatile("ld.shared.b32 %0, [%1];" : "=r"(v) : "r"(a) : "memory"); return v; }
__device__ __forceinline__ void lds64f(float* v, uint32_t a) { asm volatile("ld.shared.v2.f32 {%0,%1}, [%2];" : "=f"(v[0]), "=f"(v[1]) : "r"(a) : "memory"); }
__device__ __forceinline__ void sts128(uint32_t a, const uint32_t* v) { asm volatile("st.shared.v4.b32 [%0], {%1,%2,%3,%4};" ::"r"(a), "r"(v[0]), "r"(v[1]), "r"(v[2]), "r"(v[3]) : "memory"); }
__device__ __forceinline__ void sts64(uint32_t a, uint32_t x, uint32_t y) { asm volatile("st.shared.v2.b32 [%0], {%1,%2};" ::"r"(a), "r"(x), "r"(y) : "memory"); }
__device__ __forceinline__ void sts32(uint32_t a, uint32_t x) { asm volatile("st.shared.b32 [%0], %1;" ::"r"(a), "r"(x) : "memory"); }
__device__ __forceinline__ bool mbar_try(uint32_t b, uint32_t par) {
    uint32_t ok;
    asm volatile("{\n.reg .pred P;\nmbarrier.try_wait.parity.shared::cta.b64 P, [%1], %2;\nselp.u32 %0, 1, 0, P;\n}" : "=r"(ok) : "r"(b), "r"(par) : "memory");
    return ok;
}
__device__ __forceinline__ bool mbar_test(uint32_t b, uint32_t par) {
    uint32_t ok;
    asm volatile("{\n.reg .pred P;\nmbarrier.test_wait.parity.shared::cta.b64 P, [%1], %2;\nselp.u32 %0, 1, 0, P;\n}" : "=r"(ok) : "r"(b), "r"(par) : "memory");
    return ok;
}
__device__ __forceinline__ void mbar_wait(uint32_t b, uint32_t par) { int n = 0; while (!mbar_try(b, par)) { if (++n > SPIN_LIMIT) spin_fault(); } }
__device__ __forceinline__ void mbar_init(uint32_t b, uint32_t n) { asm volatile("mbarrier.init.shared::cta.b64 [%0], %1;" ::"r"(b), "r"(n) : "memory"); }
__device__ __forceinline__ void mbar_expect(uint32_t b, uint32_t bytes) { asm volatile("mbarrier.arrive.expect_tx.shared::cta.b64 _, [%0], %1;" ::"r"(b), "r"(bytes) : "memory"); }
__device__ __forceinline__ void mbar_arrive(uint32_t b) { asm volatile("mbarrier.arrive.shared::cta.b64 _, [%0];" ::"r"(b) : "memory"); }
__device__ __forceinline__ void mbar_arrive_cluster(uint32_t b) { asm volatile("mbarrier.arrive.shared::cluster.b64 _, [%0];" ::"r"(b) : "memory"); }
__device__ __forceinline__ void st_async1(uint32_t a, uint32_t x, uint32_t bar) {
    asm volatile("st.async.weak.shared::cluster.mbarrier::complete_tx::bytes.b32 [%0], %1, [%2];" ::"r"(a), "r"(x), "r"(bar) : "memory");
}
__device__ __forceinline__ void st_async2(uint32_t a, uint32_t x, uint32_t y, uint32_t bar) {
    asm volatile("st.async.weak.shared::cluster.mbarrier::complete_tx::bytes.v2.b32 [%0], {%1,%2}, [%3];" ::"r"(a), "r"(x), "r"(y), "r"(bar) : "memory");
}
__device__ __forceinline__ void cluster_arrive() { asm volatile("barrier.cluster.arrive.relaxed.aligned;" ::: "memory"); }
__device__ __forceinline__ void cluster_wait() { asm volatile("barrier.cluster.wait.aligned;" ::: "memory"); }
constexpr uint64_t EVICT_FIRST = 0x12F0000000000000ull, EVICT_NORMAL = 0x1000000000000000ull;
__device__ __forceinline__ void tma2d(uint32_t dst, const CUtensorMap* m, int c0, int c1, uint32_t bar, uint64_t pol) {
    asm volatile("cp.async.bulk.tensor.2d.shared::cluster.global.mbarrier::complete_tx::bytes.L2::cache_hint [%0], [%1, {%2, %3}], [%4], %5;" ::"r"(dst), "l"(m), "r"(c0), "r"(c1), "r"(bar), "l"(pol) : "memory");
}
__device__ __forceinline__ void tma4d(uint32_t dst, const CUtensorMap* m, int c0, int c3, uint32_t bar, uint64_t pol) {
    asm volatile("cp.async.bulk.tensor.4d.shared::cluster.global.mbarrier::complete_tx::bytes.L2::cache_hint [%0], [%1, {%2, 0, 0, %3}], [%4], %5;" ::"r"(dst), "l"(m), "r"(c0), "r"(c3), "r"(bar), "l"(pol) : "memory");
}
__device__ __forceinline__ void tma3d(uint32_t dst, const CUtensorMap* m, int c0, int c1, int c2, uint32_t bar, uint64_t pol) {
    asm volatile("cp.async.bulk.tensor.3d.shared::cluster.global.mbarrier::complete_tx::bytes.L2::cache_hint [%0], [%1, {%2, %3, %4}], [%5], %6;" ::"r"(dst), "l"(m), "r"(c0), "r"(c1), "r"(c2), "r"(bar), "l"(pol) : "memory");
}
__device__ __forceinline__ void tma_store2d(const CUtensorMap* m, int c0, int c1, uint32_t src, uint64_t pol) {
    asm volatile("cp.async.bulk.tensor.2d.global.shared::cta.bulk_group.L2::cache_hint [%0, {%1, %2}], [%3], %4;" ::"l"(m), "r"(c0), "r"(c1), "r"(src), "l"(pol) : "memory");
}
#define EF 63
#define POL(bit) ((EF >> (bit)) & 1 ? EVICT_FIRST : EVICT_NORMAL)
__device__ __forceinline__ void tma2d_mc(uint32_t dst, const CUtensorMap* m, int c0, int c1, uint32_t bar, uint64_t pol) {
    asm volatile("cp.async.bulk.tensor.2d.shared::cluster.global.mbarrier::complete_tx::bytes.multicast::cluster.L2::cache_hint [%0], [%1, {%2, %3}], [%4], %5, %6;" ::"r"(dst), "l"(m), "r"(c0), "r"(c1), "r"(bar), "h"(pair_mask()), "l"(pol) : "memory");
}
__device__ __forceinline__ void tma3d_mc(uint32_t dst, const CUtensorMap* m, int c0, int c1, int c2, uint32_t bar, uint64_t pol) {
    asm volatile("cp.async.bulk.tensor.3d.shared::cluster.global.mbarrier::complete_tx::bytes.multicast::cluster.L2::cache_hint [%0], [%1, {%2, %3, %4}], [%5], %6, %7;" ::"r"(dst), "l"(m), "r"(c0), "r"(c1), "r"(c2), "r"(bar), "h"(pair_mask()), "l"(pol) : "memory");
}
__device__ __forceinline__ void tma4d_mc(uint32_t dst, const CUtensorMap* m, int c0, int c3, uint32_t bar, uint64_t pol) {
    asm volatile("cp.async.bulk.tensor.4d.shared::cluster.global.mbarrier::complete_tx::bytes.multicast::cluster.L2::cache_hint [%0], [%1, {%2, 0, 0, %3}], [%4], %5, %6;" ::"r"(dst), "l"(m), "r"(c0), "r"(c3), "r"(bar), "h"(pair_mask()), "l"(pol) : "memory");
}
__device__ __forceinline__ void map_prefetch(const CUtensorMap* m) { asm volatile("prefetch.tensormap [%0];" ::"l"(m) : "memory"); }
__device__ __forceinline__ void bulk_g2s(uint32_t dst, const void* src, uint32_t bytes, uint32_t bar) {
    asm volatile("cp.async.bulk.shared::cluster.global.mbarrier::complete_tx::bytes [%0], [%1], %2, [%3];" ::"r"(dst), "l"(src), "r"(bytes), "r"(bar) : "memory");
}
__device__ __forceinline__ void bulk_s2g(void* dst, uint32_t src, uint32_t bytes) {
    asm volatile("cp.async.bulk.global.shared::cta.bulk_group [%0], [%1], %2;" ::"l"(dst), "r"(src), "r"(bytes) : "memory");
}
__device__ __forceinline__ void bulk_commit() { asm volatile("cp.async.bulk.commit_group;" ::: "memory"); }
__device__ __forceinline__ void bulk_wait_read() { asm volatile("cp.async.bulk.wait_group.read 0;" ::: "memory"); }
__device__ __forceinline__ void bulk_wait_all() { asm volatile("cp.async.bulk.wait_group 0;" ::: "memory"); }
__device__ __forceinline__ uint64_t mkdesc(uint32_t addr, uint32_t lbo, uint32_t sbo, uint32_t swz) {
    return (uint64_t)((addr & 0x3FFFF) >> 4) | ((uint64_t)(lbo >> 4) << 16) | ((uint64_t)(sbo >> 4) << 32) | ((uint64_t)swz << 62);
}
__device__ __forceinline__ void wg_fence() { asm volatile("wgmma.fence.sync.aligned;" ::: "memory"); }
__device__ __forceinline__ void wg_commit() { asm volatile("wgmma.commit_group.sync.aligned;" ::: "memory"); }
template <int N> __device__ __forceinline__ void wg_wait() { asm volatile("wgmma.wait_group.sync.aligned %0;" ::"n"(N) : "memory"); }
template <typename T> __device__ __forceinline__ void pin_ptr(T*& p) { asm volatile("" : "+l"(p)); }
template <int N> __device__ __forceinline__ void pin(uint32_t* d) {
#pragma unroll
    for (int i = 0; i < N; i++) asm volatile("" : "+r"(d[i])::"memory");
}
template <int N> __device__ __forceinline__ void pin(float* d) {
#pragma unroll
    for (int i = 0; i < N; i++) asm volatile("" : "+f"(d[i])::"memory");
}

template <int TA, int TB>
__device__ __forceinline__ void wgmma_ss256(float* d, uint64_t da, uint64_t db) {
    asm volatile("wgmma.mma_async.sync.aligned.m64n256k16.f32.bf16.bf16 "
        "{%0, %1, %2, %3, %4, %5, %6, %7, %8, %9, %10, %11, %12, %13, %14, %15, %16, %17, %18, %19, %20, %21, %22, %23, %24, %25, %26, %27, %28, %29, %30, %31, %32, %33, %34, %35, %36, %37, %38, %39, %40, %41, %42, %43, %44, %45, %46, %47, %48, %49, %50, %51, %52, %53, %54, %55, %56, %57, %58, %59, %60, %61, %62, %63, %64, %65, %66, %67, %68, %69, %70, %71, %72, %73, %74, %75, %76, %77, %78, %79, %80, %81, %82, %83, %84, %85, %86, %87, %88, %89, %90, %91, %92, %93, %94, %95, %96, %97, %98, %99, %100, %101, %102, %103, %104, %105, %106, %107, %108, %109, %110, %111, %112, %113, %114, %115, %116, %117, %118, %119, %120, %121, %122, %123, %124, %125, %126, %127}, %128, %129, 1, 1, 1, %130, %131;"
        : "+f"(d[0]), "+f"(d[1]), "+f"(d[2]), "+f"(d[3]), "+f"(d[4]), "+f"(d[5]), "+f"(d[6]), "+f"(d[7]), "+f"(d[8]), "+f"(d[9]), "+f"(d[10]), "+f"(d[11]), "+f"(d[12]), "+f"(d[13]), "+f"(d[14]), "+f"(d[15]), "+f"(d[16]), "+f"(d[17]), "+f"(d[18]), "+f"(d[19]), "+f"(d[20]), "+f"(d[21]), "+f"(d[22]), "+f"(d[23]), "+f"(d[24]), "+f"(d[25]), "+f"(d[26]), "+f"(d[27]), "+f"(d[28]), "+f"(d[29]), "+f"(d[30]), "+f"(d[31]), "+f"(d[32]), "+f"(d[33]), "+f"(d[34]), "+f"(d[35]), "+f"(d[36]), "+f"(d[37]), "+f"(d[38]), "+f"(d[39]), "+f"(d[40]), "+f"(d[41]), "+f"(d[42]), "+f"(d[43]), "+f"(d[44]), "+f"(d[45]), "+f"(d[46]), "+f"(d[47]), "+f"(d[48]), "+f"(d[49]), "+f"(d[50]), "+f"(d[51]), "+f"(d[52]), "+f"(d[53]), "+f"(d[54]), "+f"(d[55]), "+f"(d[56]), "+f"(d[57]), "+f"(d[58]), "+f"(d[59]), "+f"(d[60]), "+f"(d[61]), "+f"(d[62]), "+f"(d[63]), "+f"(d[64]), "+f"(d[65]), "+f"(d[66]), "+f"(d[67]), "+f"(d[68]), "+f"(d[69]), "+f"(d[70]), "+f"(d[71]), "+f"(d[72]), "+f"(d[73]), "+f"(d[74]), "+f"(d[75]), "+f"(d[76]), "+f"(d[77]), "+f"(d[78]), "+f"(d[79]), "+f"(d[80]), "+f"(d[81]), "+f"(d[82]), "+f"(d[83]), "+f"(d[84]), "+f"(d[85]), "+f"(d[86]), "+f"(d[87]), "+f"(d[88]), "+f"(d[89]), "+f"(d[90]), "+f"(d[91]), "+f"(d[92]), "+f"(d[93]), "+f"(d[94]), "+f"(d[95]), "+f"(d[96]), "+f"(d[97]), "+f"(d[98]), "+f"(d[99]), "+f"(d[100]), "+f"(d[101]), "+f"(d[102]), "+f"(d[103]), "+f"(d[104]), "+f"(d[105]), "+f"(d[106]), "+f"(d[107]), "+f"(d[108]), "+f"(d[109]), "+f"(d[110]), "+f"(d[111]), "+f"(d[112]), "+f"(d[113]), "+f"(d[114]), "+f"(d[115]), "+f"(d[116]), "+f"(d[117]), "+f"(d[118]), "+f"(d[119]), "+f"(d[120]), "+f"(d[121]), "+f"(d[122]), "+f"(d[123]), "+f"(d[124]), "+f"(d[125]), "+f"(d[126]), "+f"(d[127])
        : "l"(da), "l"(db), "n"(TA), "n"(TB));
}
template <int TA, int TB>
__device__ __forceinline__ void wgmma_ss256_first(float* d, uint64_t da, uint64_t db) {
    asm volatile("wgmma.mma_async.sync.aligned.m64n256k16.f32.bf16.bf16 "
        "{%0, %1, %2, %3, %4, %5, %6, %7, %8, %9, %10, %11, %12, %13, %14, %15, %16, %17, %18, %19, %20, %21, %22, %23, %24, %25, %26, %27, %28, %29, %30, %31, %32, %33, %34, %35, %36, %37, %38, %39, %40, %41, %42, %43, %44, %45, %46, %47, %48, %49, %50, %51, %52, %53, %54, %55, %56, %57, %58, %59, %60, %61, %62, %63, %64, %65, %66, %67, %68, %69, %70, %71, %72, %73, %74, %75, %76, %77, %78, %79, %80, %81, %82, %83, %84, %85, %86, %87, %88, %89, %90, %91, %92, %93, %94, %95, %96, %97, %98, %99, %100, %101, %102, %103, %104, %105, %106, %107, %108, %109, %110, %111, %112, %113, %114, %115, %116, %117, %118, %119, %120, %121, %122, %123, %124, %125, %126, %127}, %128, %129, 0, 1, 1, %130, %131;"
        : "=f"(d[0]), "=f"(d[1]), "=f"(d[2]), "=f"(d[3]), "=f"(d[4]), "=f"(d[5]), "=f"(d[6]), "=f"(d[7]), "=f"(d[8]), "=f"(d[9]), "=f"(d[10]), "=f"(d[11]), "=f"(d[12]), "=f"(d[13]), "=f"(d[14]), "=f"(d[15]), "=f"(d[16]), "=f"(d[17]), "=f"(d[18]), "=f"(d[19]), "=f"(d[20]), "=f"(d[21]), "=f"(d[22]), "=f"(d[23]), "=f"(d[24]), "=f"(d[25]), "=f"(d[26]), "=f"(d[27]), "=f"(d[28]), "=f"(d[29]), "=f"(d[30]), "=f"(d[31]), "=f"(d[32]), "=f"(d[33]), "=f"(d[34]), "=f"(d[35]), "=f"(d[36]), "=f"(d[37]), "=f"(d[38]), "=f"(d[39]), "=f"(d[40]), "=f"(d[41]), "=f"(d[42]), "=f"(d[43]), "=f"(d[44]), "=f"(d[45]), "=f"(d[46]), "=f"(d[47]), "=f"(d[48]), "=f"(d[49]), "=f"(d[50]), "=f"(d[51]), "=f"(d[52]), "=f"(d[53]), "=f"(d[54]), "=f"(d[55]), "=f"(d[56]), "=f"(d[57]), "=f"(d[58]), "=f"(d[59]), "=f"(d[60]), "=f"(d[61]), "=f"(d[62]), "=f"(d[63]), "=f"(d[64]), "=f"(d[65]), "=f"(d[66]), "=f"(d[67]), "=f"(d[68]), "=f"(d[69]), "=f"(d[70]), "=f"(d[71]), "=f"(d[72]), "=f"(d[73]), "=f"(d[74]), "=f"(d[75]), "=f"(d[76]), "=f"(d[77]), "=f"(d[78]), "=f"(d[79]), "=f"(d[80]), "=f"(d[81]), "=f"(d[82]), "=f"(d[83]), "=f"(d[84]), "=f"(d[85]), "=f"(d[86]), "=f"(d[87]), "=f"(d[88]), "=f"(d[89]), "=f"(d[90]), "=f"(d[91]), "=f"(d[92]), "=f"(d[93]), "=f"(d[94]), "=f"(d[95]), "=f"(d[96]), "=f"(d[97]), "=f"(d[98]), "=f"(d[99]), "=f"(d[100]), "=f"(d[101]), "=f"(d[102]), "=f"(d[103]), "=f"(d[104]), "=f"(d[105]), "=f"(d[106]), "=f"(d[107]), "=f"(d[108]), "=f"(d[109]), "=f"(d[110]), "=f"(d[111]), "=f"(d[112]), "=f"(d[113]), "=f"(d[114]), "=f"(d[115]), "=f"(d[116]), "=f"(d[117]), "=f"(d[118]), "=f"(d[119]), "=f"(d[120]), "=f"(d[121]), "=f"(d[122]), "=f"(d[123]), "=f"(d[124]), "=f"(d[125]), "=f"(d[126]), "=f"(d[127])
        : "l"(da), "l"(db), "n"(TA), "n"(TB));
}
template <int TA, int TB>
__device__ __forceinline__ void wgmma_ss128(float* d, uint64_t da, uint64_t db) {
    asm volatile("wgmma.mma_async.sync.aligned.m64n128k16.f32.bf16.bf16 "
        "{%0, %1, %2, %3, %4, %5, %6, %7, %8, %9, %10, %11, %12, %13, %14, %15, %16, %17, %18, %19, %20, %21, %22, %23, %24, %25, %26, %27, %28, %29, %30, %31, %32, %33, %34, %35, %36, %37, %38, %39, %40, %41, %42, %43, %44, %45, %46, %47, %48, %49, %50, %51, %52, %53, %54, %55, %56, %57, %58, %59, %60, %61, %62, %63}, %64, %65, 1, 1, 1, %66, %67;"
        : "+f"(d[0]), "+f"(d[1]), "+f"(d[2]), "+f"(d[3]), "+f"(d[4]), "+f"(d[5]), "+f"(d[6]), "+f"(d[7]), "+f"(d[8]), "+f"(d[9]), "+f"(d[10]), "+f"(d[11]), "+f"(d[12]), "+f"(d[13]), "+f"(d[14]), "+f"(d[15]), "+f"(d[16]), "+f"(d[17]), "+f"(d[18]), "+f"(d[19]), "+f"(d[20]), "+f"(d[21]), "+f"(d[22]), "+f"(d[23]), "+f"(d[24]), "+f"(d[25]), "+f"(d[26]), "+f"(d[27]), "+f"(d[28]), "+f"(d[29]), "+f"(d[30]), "+f"(d[31]), "+f"(d[32]), "+f"(d[33]), "+f"(d[34]), "+f"(d[35]), "+f"(d[36]), "+f"(d[37]), "+f"(d[38]), "+f"(d[39]), "+f"(d[40]), "+f"(d[41]), "+f"(d[42]), "+f"(d[43]), "+f"(d[44]), "+f"(d[45]), "+f"(d[46]), "+f"(d[47]), "+f"(d[48]), "+f"(d[49]), "+f"(d[50]), "+f"(d[51]), "+f"(d[52]), "+f"(d[53]), "+f"(d[54]), "+f"(d[55]), "+f"(d[56]), "+f"(d[57]), "+f"(d[58]), "+f"(d[59]), "+f"(d[60]), "+f"(d[61]), "+f"(d[62]), "+f"(d[63])
        : "l"(da), "l"(db), "n"(TA), "n"(TB));
}
template <int TA, int TB>
__device__ __forceinline__ void wgmma_ss128_first(float* d, uint64_t da, uint64_t db) {
    asm volatile("wgmma.mma_async.sync.aligned.m64n128k16.f32.bf16.bf16 "
        "{%0, %1, %2, %3, %4, %5, %6, %7, %8, %9, %10, %11, %12, %13, %14, %15, %16, %17, %18, %19, %20, %21, %22, %23, %24, %25, %26, %27, %28, %29, %30, %31, %32, %33, %34, %35, %36, %37, %38, %39, %40, %41, %42, %43, %44, %45, %46, %47, %48, %49, %50, %51, %52, %53, %54, %55, %56, %57, %58, %59, %60, %61, %62, %63}, %64, %65, 0, 1, 1, %66, %67;"
        : "=f"(d[0]), "=f"(d[1]), "=f"(d[2]), "=f"(d[3]), "=f"(d[4]), "=f"(d[5]), "=f"(d[6]), "=f"(d[7]), "=f"(d[8]), "=f"(d[9]), "=f"(d[10]), "=f"(d[11]), "=f"(d[12]), "=f"(d[13]), "=f"(d[14]), "=f"(d[15]), "=f"(d[16]), "=f"(d[17]), "=f"(d[18]), "=f"(d[19]), "=f"(d[20]), "=f"(d[21]), "=f"(d[22]), "=f"(d[23]), "=f"(d[24]), "=f"(d[25]), "=f"(d[26]), "=f"(d[27]), "=f"(d[28]), "=f"(d[29]), "=f"(d[30]), "=f"(d[31]), "=f"(d[32]), "=f"(d[33]), "=f"(d[34]), "=f"(d[35]), "=f"(d[36]), "=f"(d[37]), "=f"(d[38]), "=f"(d[39]), "=f"(d[40]), "=f"(d[41]), "=f"(d[42]), "=f"(d[43]), "=f"(d[44]), "=f"(d[45]), "=f"(d[46]), "=f"(d[47]), "=f"(d[48]), "=f"(d[49]), "=f"(d[50]), "=f"(d[51]), "=f"(d[52]), "=f"(d[53]), "=f"(d[54]), "=f"(d[55]), "=f"(d[56]), "=f"(d[57]), "=f"(d[58]), "=f"(d[59]), "=f"(d[60]), "=f"(d[61]), "=f"(d[62]), "=f"(d[63])
        : "l"(da), "l"(db), "n"(TA), "n"(TB));
}
template <int TB>
__device__ __forceinline__ void wgmma_rs128(float* d, const uint32_t* a, uint64_t db) {
    asm volatile("wgmma.mma_async.sync.aligned.m64n128k16.f32.bf16.bf16 "
        "{%0, %1, %2, %3, %4, %5, %6, %7, %8, %9, %10, %11, %12, %13, %14, %15, %16, %17, %18, %19, %20, %21, %22, %23, %24, %25, %26, %27, %28, %29, %30, %31, %32, %33, %34, %35, %36, %37, %38, %39, %40, %41, %42, %43, %44, %45, %46, %47, %48, %49, %50, %51, %52, %53, %54, %55, %56, %57, %58, %59, %60, %61, %62, %63}, {%64, %65, %66, %67}, %68, 1, 1, 1, %69;"
        : "+f"(d[0]), "+f"(d[1]), "+f"(d[2]), "+f"(d[3]), "+f"(d[4]), "+f"(d[5]), "+f"(d[6]), "+f"(d[7]), "+f"(d[8]), "+f"(d[9]), "+f"(d[10]), "+f"(d[11]), "+f"(d[12]), "+f"(d[13]), "+f"(d[14]), "+f"(d[15]), "+f"(d[16]), "+f"(d[17]), "+f"(d[18]), "+f"(d[19]), "+f"(d[20]), "+f"(d[21]), "+f"(d[22]), "+f"(d[23]), "+f"(d[24]), "+f"(d[25]), "+f"(d[26]), "+f"(d[27]), "+f"(d[28]), "+f"(d[29]), "+f"(d[30]), "+f"(d[31]), "+f"(d[32]), "+f"(d[33]), "+f"(d[34]), "+f"(d[35]), "+f"(d[36]), "+f"(d[37]), "+f"(d[38]), "+f"(d[39]), "+f"(d[40]), "+f"(d[41]), "+f"(d[42]), "+f"(d[43]), "+f"(d[44]), "+f"(d[45]), "+f"(d[46]), "+f"(d[47]), "+f"(d[48]), "+f"(d[49]), "+f"(d[50]), "+f"(d[51]), "+f"(d[52]), "+f"(d[53]), "+f"(d[54]), "+f"(d[55]), "+f"(d[56]), "+f"(d[57]), "+f"(d[58]), "+f"(d[59]), "+f"(d[60]), "+f"(d[61]), "+f"(d[62]), "+f"(d[63])
        : "r"(a[0]), "r"(a[1]), "r"(a[2]), "r"(a[3]), "l"(db), "n"(TB));
}
template <int TB>
__device__ __forceinline__ void wgmma_rs128_first(float* d, const uint32_t* a, uint64_t db) {
    asm volatile("wgmma.mma_async.sync.aligned.m64n128k16.f32.bf16.bf16 "
        "{%0, %1, %2, %3, %4, %5, %6, %7, %8, %9, %10, %11, %12, %13, %14, %15, %16, %17, %18, %19, %20, %21, %22, %23, %24, %25, %26, %27, %28, %29, %30, %31, %32, %33, %34, %35, %36, %37, %38, %39, %40, %41, %42, %43, %44, %45, %46, %47, %48, %49, %50, %51, %52, %53, %54, %55, %56, %57, %58, %59, %60, %61, %62, %63}, {%64, %65, %66, %67}, %68, 0, 1, 1, %69;"
        : "=f"(d[0]), "=f"(d[1]), "=f"(d[2]), "=f"(d[3]), "=f"(d[4]), "=f"(d[5]), "=f"(d[6]), "=f"(d[7]), "=f"(d[8]), "=f"(d[9]), "=f"(d[10]), "=f"(d[11]), "=f"(d[12]), "=f"(d[13]), "=f"(d[14]), "=f"(d[15]), "=f"(d[16]), "=f"(d[17]), "=f"(d[18]), "=f"(d[19]), "=f"(d[20]), "=f"(d[21]), "=f"(d[22]), "=f"(d[23]), "=f"(d[24]), "=f"(d[25]), "=f"(d[26]), "=f"(d[27]), "=f"(d[28]), "=f"(d[29]), "=f"(d[30]), "=f"(d[31]), "=f"(d[32]), "=f"(d[33]), "=f"(d[34]), "=f"(d[35]), "=f"(d[36]), "=f"(d[37]), "=f"(d[38]), "=f"(d[39]), "=f"(d[40]), "=f"(d[41]), "=f"(d[42]), "=f"(d[43]), "=f"(d[44]), "=f"(d[45]), "=f"(d[46]), "=f"(d[47]), "=f"(d[48]), "=f"(d[49]), "=f"(d[50]), "=f"(d[51]), "=f"(d[52]), "=f"(d[53]), "=f"(d[54]), "=f"(d[55]), "=f"(d[56]), "=f"(d[57]), "=f"(d[58]), "=f"(d[59]), "=f"(d[60]), "=f"(d[61]), "=f"(d[62]), "=f"(d[63])
        : "r"(a[0]), "r"(a[1]), "r"(a[2]), "r"(a[3]), "l"(db), "n"(TB));
}
template <int TB>
__device__ __forceinline__ void wgmma_rs64(float* d, const uint32_t* a, uint64_t db) {
    asm volatile("wgmma.mma_async.sync.aligned.m64n64k16.f32.bf16.bf16 "
        "{%0, %1, %2, %3, %4, %5, %6, %7, %8, %9, %10, %11, %12, %13, %14, %15, %16, %17, %18, %19, %20, %21, %22, %23, %24, %25, %26, %27, %28, %29, %30, %31}, {%32, %33, %34, %35}, %36, 1, 1, 1, %37;"
        : "+f"(d[0]), "+f"(d[1]), "+f"(d[2]), "+f"(d[3]), "+f"(d[4]), "+f"(d[5]), "+f"(d[6]), "+f"(d[7]), "+f"(d[8]), "+f"(d[9]), "+f"(d[10]), "+f"(d[11]), "+f"(d[12]), "+f"(d[13]), "+f"(d[14]), "+f"(d[15]), "+f"(d[16]), "+f"(d[17]), "+f"(d[18]), "+f"(d[19]), "+f"(d[20]), "+f"(d[21]), "+f"(d[22]), "+f"(d[23]), "+f"(d[24]), "+f"(d[25]), "+f"(d[26]), "+f"(d[27]), "+f"(d[28]), "+f"(d[29]), "+f"(d[30]), "+f"(d[31])
        : "r"(a[0]), "r"(a[1]), "r"(a[2]), "r"(a[3]), "l"(db), "n"(TB));
}
template <int TB>
__device__ __forceinline__ void wgmma_rs64_first(float* d, const uint32_t* a, uint64_t db) {
    asm volatile("wgmma.mma_async.sync.aligned.m64n64k16.f32.bf16.bf16 "
        "{%0, %1, %2, %3, %4, %5, %6, %7, %8, %9, %10, %11, %12, %13, %14, %15, %16, %17, %18, %19, %20, %21, %22, %23, %24, %25, %26, %27, %28, %29, %30, %31}, {%32, %33, %34, %35}, %36, 0, 1, 1, %37;"
        : "=f"(d[0]), "=f"(d[1]), "=f"(d[2]), "=f"(d[3]), "=f"(d[4]), "=f"(d[5]), "=f"(d[6]), "=f"(d[7]), "=f"(d[8]), "=f"(d[9]), "=f"(d[10]), "=f"(d[11]), "=f"(d[12]), "=f"(d[13]), "=f"(d[14]), "=f"(d[15]), "=f"(d[16]), "=f"(d[17]), "=f"(d[18]), "=f"(d[19]), "=f"(d[20]), "=f"(d[21]), "=f"(d[22]), "=f"(d[23]), "=f"(d[24]), "=f"(d[25]), "=f"(d[26]), "=f"(d[27]), "=f"(d[28]), "=f"(d[29]), "=f"(d[30]), "=f"(d[31])
        : "r"(a[0]), "r"(a[1]), "r"(a[2]), "r"(a[3]), "l"(db), "n"(TB));
}
template <int TB>
__device__ __forceinline__ void wgmma_rs16(float* d, const uint32_t* a, uint64_t db) {
    asm volatile("wgmma.mma_async.sync.aligned.m64n16k16.f32.bf16.bf16 "
        "{%0, %1, %2, %3, %4, %5, %6, %7}, {%8, %9, %10, %11}, %12, 1, 1, 1, %13;"
        : "+f"(d[0]), "+f"(d[1]), "+f"(d[2]), "+f"(d[3]), "+f"(d[4]), "+f"(d[5]), "+f"(d[6]), "+f"(d[7])
        : "r"(a[0]), "r"(a[1]), "r"(a[2]), "r"(a[3]), "l"(db), "n"(TB));
}
template <int TB>
__device__ __forceinline__ void wgmma_rs16_first(float* d, const uint32_t* a, uint64_t db) {
    asm volatile("wgmma.mma_async.sync.aligned.m64n16k16.f32.bf16.bf16 "
        "{%0, %1, %2, %3, %4, %5, %6, %7}, {%8, %9, %10, %11}, %12, 0, 1, 1, %13;"
        : "=f"(d[0]), "=f"(d[1]), "=f"(d[2]), "=f"(d[3]), "=f"(d[4]), "=f"(d[5]), "=f"(d[6]), "=f"(d[7])
        : "r"(a[0]), "r"(a[1]), "r"(a[2]), "r"(a[3]), "l"(db), "n"(TB));
}

__device__ __forceinline__ uint32_t delay_loop(int n, uint32_t x0) {
    uint32_t z;
    asm volatile("{\n.reg .pred P;\n.reg .u32 c, x;\nmov.u32 c, %1;\nmov.u32 x, %2;\nDL: mad.lo.u32 x, x, 1664525, 1013904223;\nadd.u32 c, c, -1;\nsetp.gt.s32 P, c, 0;\n@P bra DL;\n"
                 "setp.eq.u32 P, x, 0x7fffffff;\nselp.u32 %0, 16, 0, P;\n}" : "=r"(z) : "r"(n), "r"(x0) : "memory");
    return z;
}
__device__ __forceinline__ uint32_t gtime() { uint32_t t; asm volatile("mov.u32 %0, %%globaltimer_lo;" : "=r"(t)); return t; }
__device__ __forceinline__ void wait_time(uint32_t t, uint32_t sb) { while ((int32_t)(gtime() - t) < (int32_t)delay_loop(2, sb)) {} }
__device__ __forceinline__ uint32_t tpc_gpc(uint32_t t) { return t < 32 ? t & 7 : t < 60 ? (t - 32) % 7 + 1 : (t - 54) & 7; }
__device__ __forceinline__ uint32_t latest_stamp(const uint32_t* p, uint32_t seq, uint32_t ref, int backoff, uint32_t sb) {
    for (int n = 0;; n++) {
        uint32_t bad = 0; int32_t m = INT32_MIN;
#pragma unroll
        for (int i = 0; i < 3; i++) { const uint32_t v = ld_relaxed1(p + i * 256); bad |= (v ^ seq) & 31u; m = max(m, (int32_t)(v - (ref << 5)) >> 5); }
        if (__all_sync(0xffffffffu, bad == 0)) return ref + __reduce_max_sync(0xffffffffu, m);
        wait_time(gtime() + backoff, sb);
        if (n > SPIN_LIMIT) spin_fault();
    }
}
__device__ __forceinline__ void release_at(uint32_t t, uint32_t sb, uint32_t bar, int lane) {
    wait_time(t, sb);
    if (lane == 0) mbar_arrive(sb + bar);
}
__host__ __device__ constexpr int frag_word(int u, int f) { return (u == 0 ? 0 : u < 3 ? 3 * u - 1 : u == 3 ? 14 : 3 * u - 4) + f; }
__host__ __device__ constexpr int word_col(int e) { return ((0x32FED987CBA65410ull >> (4 * e)) & 14) * 64 + ((0x32FED987CBA65410ull >> (4 * e)) & 1) * 8; }

constexpr uint32_t CLEAR_LO = 0xFE000000u, CLEAR_HI = 0x5A7FEFEFu;
__device__ __forceinline__ void clear_slot(const Params& P, int slot, int cta, int lane) {
    const int i = cta * 2 + (lane >> 3), x = i & 63;
    if (lane < 16) st_relaxed4(P.gm + slot * M_SLOT + (x >> 1) * 1024 + (x & 1) * 256 + (i >> 7) * 512 + ((i >> 6) & 1) * 128 + (lane & 7) * 16, CLEAR_LO, CLEAR_HI, CLEAR_LO, CLEAR_HI);
    st_relaxed4(g_f + slot * F_SLOT + cta * 512 + lane * 16, 0, 0, 0, 0);
}
__device__ __forceinline__ void mem0_max(const Params& P, uint32_t sb, int tid) {
    uint32_t m = 0;
#pragma unroll
    for (int i = 0; i < 4; i++) {
        const uint4 x = __ldg((const uint4*)P.mem0 + i * 256 + tid);
        m = __vmaxu2(__vmaxu2(__vmaxu2(x.x & 0x7fff7fffu, x.y & 0x7fff7fffu), __vmaxu2(x.z & 0x7fff7fffu, x.w & 0x7fff7fffu)), m);
    }
    sts32(sb + S_COEF + (tid >> 5) * 4, __reduce_max_sync(0xffffffffu, max(m >> 16, m & 0xffffu)));
    bar_arrive(7, 288);
}
__device__ __forceinline__ uint32_t pack_mem0(const Params& P, uint32_t sb, int cta, int lane) {
    bar_sync(7, 288);
    const uint32_t e = __reduce_max_sync(0xffffffffu, lds32(sb + S_COEF + (lane & 7) * 4)) >> 7;
    if (e < 64 || e > 192) return 0x3F803F80u;
    const int i = cta * 2 + (lane >> 4), u = (i >> 5), x = i & 63, L = (i & 3) * 8 + ((lane & 15) >> 1);
    uint64_t w = 32;
#pragma unroll
    for (int f = 0; f < 3; f++) if (f < 2 || u % 3) {
        const float v = __bfloat162float(P.mem0[(L >> 2) * 1024 + word_col(frag_word(u, f)) + ((i >> 2) & 7) * 16 + (L & 3) * 2 + (lane & 1)]);
        w += (uint64_t)(int64_t)__float2int_rn(v * __uint_as_float((271 - e) << 23)) << (45 - 19 * f);
    }
    st_relaxed2(P.gm + 7 * M_SLOT + (x >> 1) * 1024 + (x & 1) * 256 + (i >> 7) * 512 + ((i >> 6) & 1) * 128 + (lane & 15) * 8, (uint32_t)w, (uint32_t)(w >> 32));
    return (e - 30) * 0x00800080u;
}
__device__ __forceinline__ void pacer(const Params& P, const uint32_t sb, const int lane) {
    constexpr uint32_t base = 2;
    int cta = lds32(sb + S_CTA);
#pragma unroll 1
    for (int i = 0; i < 8; i++) clear_slot(P, i, cta, lane);
    __syncwarp();
    if (lane == 0) { uint32_t smid; asm("mov.u32 %0, %%smid;" : "=r"(smid)); st_relaxed1(g_hint + 6144 + cta, smid >> 1); }
    sts32(sb + S_EPOCH + 4, pack_mem0(P, sb, cta, lane));
    fence_release();
    __syncwarp();
    float rate = 0.58f;
    uint32_t c0 = 0;
#pragma unroll 1
    for (int s = -1; s < 63; s++) {
        cta = lds32(sb + S_CTA);
        const int pair = cta >> 1;
        const uint32_t ahead = s > 0 ? (uint32_t)(rate * (float)(pair >= 32 ? P.dc - P.dv : P.dc)) : 0;
        mbar_wait(sb + B_GO, s & 1);
        SSTAMP(10, lane == 0 && s == 0)
        const uint32_t t0 = gtime();
        if (lane < 4) st_relaxed1(g_hint + ((s & 1) * 4 + lane) * 768 + (cta >> 5) * 256 + (cta & 31), (t0 + ahead + (lds32(sb + S_REDO) == s ? P.extra : 0)) << 5 | ((base + s) & 31u));
        wait_time(t0 + (s < 0 ? 2000 : s == 0 && pair >= 16 ? P.ds0 : P.ds), sb);
        const uint32_t t = latest_stamp(g_hint + ((s & 1) * 4 + (pair & 3)) * 768 + lane, base + s, t0, P.back, sb);
        if (s < 0) {
            fence_acquire();
            const uint32_t g = tpc_gpc(ld_relaxed1(g_hint + 6144 + (lane & 15) * 2));
            const uint32_t key = (__popc(__match_any_sync(0xffffffffu, g)) > 4 ? 0 : g + 1) * 16 + (lane & 15);
            const uint32_t tail = (pair & 48) + __popc(__ballot_sync(0xffffffffu, key < __shfl_sync(0xffffffffu, key, pair & 15))) / 2;
            mbar_wait(sb + B_INIT, 0);
            SSTAMP(4, lane == 0)
            sts32(sb + S_TAIL, tail);
            if (lane < 8) sts32(sb + S_SC + lane * 4, lds32(sb + S_EPOCH + 4));
            __syncwarp();
        }
        release_at(t + P.da, sb, B_RELA, lane);
        SSTAMP(11, lane == 0 && s == 0)
        release_at(t + P.db, sb, B_RELB, lane);
        {
            const uint32_t c1 = clock(), g1 = gtime();
            if (s > 1) rate += P.alpha * (__fdividef((float)(g1 - lds32(sb + S_EPOCH + 4)), (float)(c1 - c0)) - rate);
            __syncwarp();
            c0 = c1; sts32(sb + S_EPOCH + 4, g1);
        }
        if (s == 61) {
            sts32(sb + S_COEF, ITEM(ITEM_OFF(lds32(sb + S_TAIL)) + NPRE + 1) + (uint32_t)(uintptr_t)P.out);
            if (lane < M_CQ) map_prefetch(&P.tm[lane]);
        }
    }
}
__device__ __forceinline__ uint32_t xor_or(uint32_t a, uint32_t b, uint32_t t) { uint32_t d; asm("lop3.b32 %0, %1, %2, %3, 0x7E;" : "=r"(d) : "r"(a), "r"(b), "r"(t)); return d; }
__device__ __forceinline__ bool tags_ok(uint32_t bad) { return __all_sync(0xffffffffu, (bad & 1) == 0); }
#define RETRY(k)
#define RETRY_STAT(a, b)
#define UNIT_STAT(u0)
#define KE 0
#define ES 0
#define Q3 1
#define SFENCE() asm volatile("pmevent 1;" ::: "memory")
#define PF1 10
static_assert(NS == 24, "fragment residency");
__host__ __device__ constexpr bool in_smem(int n) { return n < 4 || n == 12 || n == 13; }
__host__ __device__ constexpr int unit_pos(int n) { return n < 4 ? n : n < 12 ? n - 4 : n < 14 ? n - 8 : n - 6; }

__host__ __device__ constexpr int fill_unit(int q) { return q < 4 ? q : q < 6 ? q + 8 : q < 14 ? q - 2 : q; }
__host__ __device__ constexpr int frag_off(int q) { return (q >> 2) * 16384 + ((q >> 1) & 1) * 8192 + (q & 1) * 512; }

constexpr uint32_t QBITS = 0x4B002000u;
constexpr uint64_t W_BIAS = ((uint64_t)QBITS << 45) + ((uint64_t)QBITS << 26) + (uint32_t)(QBITS << 7), W_CLEAR = 0 - 32 * W_BIAS;
static_assert(W_CLEAR == ((uint64_t)CLEAR_HI << 32 | CLEAR_LO), "clear value");
__host__ __device__ constexpr int unit_off(int u) { return (u & 1) * 16384 + (u >> 2) * 512 + ((u >> 1) & 1) * 128; }
__device__ __forceinline__ void red_add64(const uint8_t* p, uint64_t v) { asm volatile("red.relaxed.gpu.global.add.u64 [%0], %1;" ::"l"(p), "l"(v) : "memory"); }
template <int NF>
__device__ __forceinline__ uint64_t encode(const float* x, float S, uint32_t two26, uint32_t& bad) {
    uint32_t b[3];
#pragma unroll
    for (int i = 0; i < 3; i++) b[i] = i < NF ? __float_as_uint(fmaf(x[i], S, 8396800.f)) : QBITS;
    bad = xor_or(b[0], b[1], 0x4B000000u) | (NF == 3 ? b[2] ^ 0x4B000000u : 0);
    uint64_t w;
    asm("{\n.reg .b64 t;\nmov.b64 t, {%2, %3};\nmad.wide.u32 %0, %1, %4, t;\n}" : "=l"(w) : "r"(b[1]), "r"(b[2] << 7), "r"(b[0] << 13), "r"(two26));
    return w;
}
template <int NF>
__device__ __forceinline__ void emit(uint64_t* w, const float (*x)[3], const float* S, uint32_t two26, uint32_t lim, const uint8_t* p) {
    uint32_t bad[2];
    w[0] = encode<NF>(x[0], S[0], two26, bad[0]); w[1] = encode<NF>(x[1], S[1], two26, bad[1]);
    const bool ok = (bad[0] | bad[1]) < lim;
    w[0] |= ok; w[1] |= ok;
    red_add64(p, w[0]); red_add64(p + 1024, w[1]);
}
template <int NF>
__device__ __forceinline__ void repair(const uint64_t* w, const float (*x)[3], const float* S, const uint8_t* p, const uint8_t* pf) {
    if (!(w[0] & 1)) {
#pragma unroll
        for (int j = 0; j < 2; j++) {
            const float T = S[j] * 8192.f;
            asm volatile("red.relaxed.gpu.global.add.v4.f32 [%0], {%1,%2,%3,%4};" ::"l"(pf + j * 512), "f"(x[j][0] * T), "f"(x[j][1] * T), "f"(NF == 3 ? x[j][2] * T : 0.f), "f"(0.f) : "memory");
        }
        fence_release();
#pragma unroll
        for (int j = 0; j < 2; j++) {
            asm volatile("red.relaxed.gpu.global.or.b64 [%0], 64;" ::"l"(p + j * 1024) : "memory");
            red_add64(p + j * 1024, W_BIAS + 1 - w[j]);
        }
    }
    __syncwarp();
}
__device__ __forceinline__ void ld_words(uint32_t* v, const uint8_t* p) {
    asm volatile("{\n.reg .b64 a, b;\nld.relaxed.gpu.global.L1::no_allocate.v2.b64 {a, b}, [%4];\nmov.b64 {%0,%1}, a;\nmov.b64 {%2,%3}, b;\n}" : "=r"(v[0]), "=r"(v[1]), "=r"(v[2]), "=r"(v[3]) : "l"(p) : "memory");
}
__device__ __forceinline__ float field(const uint32_t* w, int f) { return __int2float_rn((int)(f == 0 ? w[1] : f == 1 ? __funnelshift_l(w[0], w[1], 19) : w[0] << 6)); }
template <int U>
__device__ __forceinline__ void decode(uint32_t* b, const uint32_t* v) {
#pragma unroll
    for (int f = 0; f < (U % 3 ? 3 : 2); f++) b[frag_word(U, f)] = pack2(field(v, f), field(v + 2, f));
}
__device__ __forceinline__ uint32_t status(const uint32_t (*v)[4], uint32_t c32) { return xor_or(v[0][0], v[0][2], c32) | xor_or(v[1][0], v[1][2], c32) | xor_or(v[2][0], v[2][2], c32); }
__device__ __forceinline__ void gather_slow(const Params& P, uint32_t* b, const uint8_t* pm, int s, int warp, uint32_t ln, uint32_t u2) {
    if (s == 0 && u2 == 0x3F803F80u) {
#pragma unroll
        for (int i = 0; i < 16; i++) b[i] = __ldg((const uint32_t*)(P.mem0 + (ln >> 2) * 1024 + word_col(i) + warp * 16 + (ln & 3) * 2));
        return;
    }
    uint32_t v[6][4], st;
    for (int n = 0;; n++) {
#pragma unroll
        for (int u = 0; u < 6; u++) ld_words(v[u], pm + unit_off(u));
        st = status(v, 32) | status(v + 3, 32);
        if (!__any_sync(0xffffffffu, st & 32)) break;
        __nanosleep(200);
        if (n > SPIN_LIMIT) spin_fault();
    }
    const bool side = __any_sync(0xffffffffu, st & 64);
    if (side) fence_acquire();
    const uint8_t* pf = g_f + ((s + 7) & 7) * F_SLOT + warp * 1024 + ln * 32;
#pragma unroll
    for (int u = 0; u < 6; u++) {
        float x[2][4] = {};
#pragma unroll
        for (int k = 0; k < 2; k++)
            asm volatile("{\n.reg .pred P;\nsetp.ne.u32 P, %5, 0;\n@P ld.relaxed.gpu.global.v4.f32 {%0,%1,%2,%3}, [%4];\n}"
                         : "+f"(x[k][0]), "+f"(x[k][1]), "+f"(x[k][2]), "+f"(x[k][3]) : "l"(pf + u * 8192 + k * 16), "r"((uint32_t)side) : "memory");
#pragma unroll
        for (int f = 0; f < (u % 3 ? 3 : 2); f++) b[frag_word(u, f)] = pack2(field(v[u], f) + x[0][f], field(v[u] + 2, f) + x[1][f]);
    }
}
__device__ __forceinline__ uint32_t max_abs2(uint32_t a, uint32_t b) { uint32_t d; asm("max.NaN.xorsign.abs.bf16x2 %0, %1, %2;" : "=r"(d) : "r"(a), "r"(b)); return d; }
__device__ __forceinline__ uint32_t max6(const uint32_t* b) {
    const uint32_t m = max_abs2(max_abs2(max_abs2(b[0], b[1]), max_abs2(b[2], b[3])), max_abs2(b[4], b[5]));
    return max(m & 0x7fff0000u, (m << 16) & 0x7fff0000u);
}

template <bool TR>
__device__ __forceinline__ void put_partials(uint32_t a, const float* x, const float* y) {
    if (TR) stsm4t(a, pack2(x[0], x[1]), pack2(x[2], x[3]), pack2(y[0], y[1]), pack2(y[2], y[3]));
    else stsm4(a, pack2(x[0], x[1]), pack2(x[2], x[3]), pack2(y[0], y[1]), pack2(y[2], y[3]));
}
__device__ __forceinline__ void reduce_load(uint32_t (*x)[4], uint32_t a) { ldsm4t(x[0], a); ldsm4t(x[1], a + 512); }
__device__ __forceinline__ uint32_t reduce8(const uint32_t (*x)[4], uint32_t l8, uint32_t u2) {
    uint32_t p[2];
#pragma unroll
    for (int i = 0; i < 2; i++) {
        float d[4] = {};
        mma16816(d, x[i][0], x[i][1], x[i][2], x[i][3], (l8 & 32) ? 0u : u2, (l8 & 32) ? u2 : 0u);
        p[i] = pack2((l8 & 8) ? d[2] : d[0], (l8 & 8) ? d[3] : d[1]);
    }
    return (l8 & 16) ? p[1] : p[0];
}
__device__ __forceinline__ void score_half(float (*a)[4], const uint32_t (*qa)[4], const uint32_t (*kf)[4]) {
#pragma unroll
    for (int w = 0; w < 2; w++) {
        mma16816(a[w], qa[w][0], qa[w][1], qa[w][2], qa[w][3], kf[w][0], kf[w][1]);
        mma16816(a[2 + w], qa[w][0], qa[w][1], qa[w][2], qa[w][3], kf[w][2], kf[w][3]);
    }
}
__device__ __forceinline__ void score_sum(float* S, const float (*a)[4]) {
    S[0] = (a[0][0] + a[1][0]) + (a[2][2] + a[3][2]);
    S[1] = (a[0][1] + a[1][1]) + (a[2][3] + a[3][3]);
}
__device__ __forceinline__ float quad_max(float m) {
    return fmaxf(fmaxf(m, __shfl_xor_sync(0xffffffffu, m, 1)), fmaxf(__shfl_xor_sync(0xffffffffu, m, 2), __shfl_xor_sync(0xffffffffu, m, 3)));
}

#define ISTAMP(i)
__device__ __forceinline__ float next_scale(uint32_t sb, int slot, int warp, uint32_t u2) {
    uint32_t x[2][4];
    lds128(x[0], sb + S_MX + slot * 32); lds128(x[1], sb + S_MX + slot * 32 + 16);
    const uint32_t mx = max(max(max(x[0][0], x[0][1]), max(x[0][2], x[0][3])), max(max(x[1][0], x[1][1]), max(x[1][2], x[1][3])));
    const float top = fminf(fmaxf(__uint_as_float(mx) * bf_hi(u2), 0x1p-40f), 0x1p40f) * (1.f / (12288.f * 8192.f));
    const uint32_t un = pack2(top, top);
    sts32(sb + S_SC + warp * 4, un);
    return rcp(bf_hi(un) * 8192.f);
}
#define NEARLY 1
#define U3POS 1
#define VPOS 1
#define ROT 0
#define BPOS 1
#define ONLINE 0
#define NBAR 1
#define ORD3 0
#define F2 1
#define EARLY 0
#define TK 0
#define OBN 4
#define CH4 1
#define RPOS 1
#define AF 0
#define AFENCE(i) if ((AF >> (i)) & 1) SFENCE();
#define FPOS 99
#define PACE 1
#define PF2 12
__host__ __device__ constexpr int w2_t(int i) { return i < 16 ? i & 1 : 2; }
__host__ __device__ constexpr int w2_k(int i) { return i < 16 ? i >> 1 : i - 16; }
template <typename G>
__device__ __forceinline__ void load_weights(uint32_t (*wr)[4], const uint32_t sb, const int warp, const int lane, G stores_read) {
    const uint32_t frag = sb + warp * 1024 + (lane >> 4) * 8192 + (lane & 7) * 128 + ((((lane >> 3) & 1) ^ (lane & 7)) << 4);
    const uint32_t rel = mapa(sb + B_EMPTY, cluster_rank() ^ (lane & 1));
#define RELEASE(st) { if ((st) >= 2) fence_async_smem(); __syncwarp(); if (lane < 2) mbar_arrive_cluster(rel + (st) * 8); }
    mbar_wait(sb + B_FULL, 0); mbar_wait(sb + B_FULL + 8, 0);
    RELEASE(0) RELEASE(1)
#pragma unroll
    for (int st = 2; st < 4; st++) {
        mbar_wait(sb + B_FULL + st * 8, 0);
        ISTAMP(st - 2)
#pragma unroll
        for (int f = 0; f < 12; f++) ldsm4t(wr[st * 12 - 24 + f], (frag ^ ((f & 3) << 5)) + st * STAGE + (f >> 2) * 16384);
        RELEASE(st)
    }
#pragma unroll 2
    for (int u = 0; u < 6; u++) {
        uint32_t x[4][4];
#pragma unroll
        for (int i = 0; i < 4; i++) lds128(x[i], (frag ^ (i << 5)) + u * 16384);
        __syncwarp();
#pragma unroll
        for (int i = 0; i < 4; i++) sts128(sb + warp * 1024 + lane * 16 + u * 16384 + frag_off(i), x[i]);
    }
    SSTAMP(0, threadIdx.x == 0)
    stores_read();
    SSTAMP(2, threadIdx.x == 0)
    mbar_wait(sb + B_FULL, 1); mbar_wait(sb + B_FULL + 8, 1);
    RELEASE(0) RELEASE(1)
#pragma unroll
    for (int st = 2; st < 4; st++) {
        mbar_wait(sb + B_FULL + st * 8, 1);
#pragma unroll
        for (int f = 0; f < (st == 2 ? 12 : 4); f++) ldsm4t(wr[st * 12 + f], (frag ^ ((f & 3) << 5)) + st * STAGE + (f >> 2) * 16384);
        RELEASE(st)
    }
    ISTAMP(2)
    bar_sync(1, 256);
    if (warp == 7 && lane < 3) mbar_arrive_cluster(mapa(sb + B_INIT, (cluster_rank() & 1) + lane * 2));
}
template <int ROLE>
__device__ __forceinline__ void chain_role(const Params& P, const uint32_t (*wr)[4], const uint32_t sb, const int h, const int warp, const int lane) {
    constexpr int NU = ROLE == 0 ? 2 : 3;
    const bool att = ROLE == 0 && warp < 4;
    uint32_t l8 = opq(sb + lane * 8, lane);
#define PERSIST() { mbar_wait(sb + B_KVGO, slot ^ 1); const uint32_t pa_ = ((l8 - sb) >> 1) + (sb + S_QX + warp * 128); sts32(pa_, r0); sts32(pa_ + 1024, r1); \
                    fence_async_smem(); __syncwarp(); if (l8 == sb) mbar_arrive(sb + B_PERS); }
    if (ROLE) sts32(sb + S_SX + warp * 128 + lane * 4, warp >= 2 ? 0 : (lane & 1) ? CLEAR_HI : CLEAR_LO);
    const uint32_t rdelta = __shfl_sync(0xffffffffu, mapa(sb, (cluster_rank() + (ROLE == 1 ? 4 : 2)) % 6) - sb, 0);
    const uint32_t vdelta = ROLE ? 0 : __shfl_sync(0xffffffffu, mapa(sb, (cluster_rank() + 4) % 6) - sb, 0);
    ISTAMP(3)
    __syncwarp();
#define GATHER_OFF(s) ((((s) + 7) & 7) * M_SLOT + warp * 2048 + (l8 & 56) * 2 + (l8 & 64) * 4 + (l8 & 128) * 8)
    uint32_t mo = GATHER_OFF(0);
    if (ROT) mbar_wait(sb + B_RELA, 0);
    for (int s = 0; s < (ROLE == 0 ? 63 : 64);) {
        const int slot = s & 1;
        l8 += s & P.zero;
        const uint32_t w1a = l8 * 2 + (S_W1 + warp * 1024 - sb);
        PROF(9)
        uint32_t u2, r0, r1, pld, pub, pbar, x[2][4];
        {
#define pm (P.gm + mo)
            uint32_t as[24][4], b[16], v[6][4];
            float acc[8][4];
#define W1LD(n) _Pragma("unroll") for (int i_ = 0; i_ < 4; i_++) ldsm4t(as[unit_pos(n) * 4 + i_], w1a + frag_off(unit_pos(n) * 4 + i_));
#define W1LD2(n, p) { const uint32_t wa_ = w1a + (as[unit_pos(p) * 4][0] & as[unit_pos(p) * 4 + 1][0] & as[unit_pos(p) * 4 + 2][0] & as[unit_pos(p) * 4 + 3][0] & P.zero); \
                      _Pragma("unroll") for (int i_ = 0; i_ < 4; i_++) ldsm4t(as[unit_pos(n) * 4 + i_], wa_ + frag_off(unit_pos(n) * 4 + i_)); }
#define W1MMA(n) _Pragma("unroll") for (int i_ = 0; i_ < 4; i_++) { const uint32_t* a_ = in_smem(n) ? as[unit_pos(n) * 4 + i_] : wr[unit_pos(n) * 4 + i_]; \
                                                                   mma16816(acc[((n) & 1) * 4 + i_], a_[0], a_[1], a_[2], a_[3], b[(n) & 14], b[(n) | 1]); }
#pragma unroll
            for (int T = 0; T < 8; T++) { acc[T][0] = acc[T][1] = acc[T][2] = acc[T][3] = 0.f; }
            if (!ROT) mbar_wait(sb + B_RELA, slot);
            PROF(12)
#pragma unroll
            for (int u = 0; u < 3; u++) ld_words(v[u], pm + unit_off(u));
            __syncwarp();
#pragma unroll
            for (int i = 0; i < PF1; i++) ldsm4t(as[i], w1a + frag_off(i));
            __syncwarp();
            mo += mbar_try(sb + B_RELB, slot) & P.zero;
            PROF(13)
#pragma unroll
            for (int u = 3; u < 6; u++) ld_words(v[u], pm + unit_off(u));
            uint32_t st = status(v, ((uint32_t)((uintptr_t)pm >> 32) & P.zero) + 32);
            pin<1>(&st);
            SFENCE();
            UNIT_STAT(0)
            PROF(0)
            decode<0>(b, v[0]); decode<1>(b, v[1]); decode<2>(b, v[2]);
#pragma unroll
            for (int i = PF1; i < 12; i++) ldsm4t(as[i], w1a + frag_off(i));
            W1MMA(0) W1MMA(1) W1MMA(2)
            if (TK & 1) W1LD2(3, 2) else { W1LD(3) }
            SFENCE();
            if (TK & 8) { W1MMA(5) W1MMA(4) W1MMA(3) W1MMA(6) } else { W1MMA(5) W1MMA(4) W1MMA(6) W1MMA(3) }
            if (U3POS == 0) W1MMA(7)
            if (TK & 2) W1LD2(12, 3) else { W1LD(12) }
            uint32_t mx = max6(b);
            pin<1>(&mx);
            SFENCE();
            PROF(10)
            if (U3POS == 1) W1MMA(7)
            const uint32_t mxa = sb + S_MX + slot * 32 + warp * 4;
            sts32(mxa, __reduce_max_sync(0xffffffffu, mx));
            UNIT_STAT(3)
            st |= status(v + 3, 32);
            const bool redo = __any_sync(0xffffffffu, st & 96);
            const bool kvok = ROLE || mbar_test(sb + B_KVFULL + slot * 8, (s >> 1) & 1);
            decode<4>(b, v[4]); decode<5>(b, v[5]); decode<3>(b, v[3]);
            u2 = lds32(sb + S_SC + warp * 4);
            W1MMA(8) W1MMA(10) if (ORD3) { W1MMA(14) W1MMA(12) } else { W1MMA(12) W1MMA(14) }
            if (TK & 4) W1LD2(13, 12) else { W1LD(13) }
            if (__builtin_expect(redo || !kvok, 0)) {
                if (redo) {
                    RETRY(3)
                    sts32(sb + S_REDO, s);
                    gather_slow(P, b, P.gm + GATHER_OFF(s), s, warp, (l8 - sb) >> 3, u2);
                    sts32(mxa, __reduce_max_sync(0xffffffffu, max6(b)));
#pragma unroll
                    for (int T = 0; T < 8; T++) { acc[T][0] = acc[T][1] = acc[T][2] = acc[T][3] = 0.f; }
#pragma unroll
                    for (int n = 0; n < 15; n += n < 8 ? 1 : 2) {
                        if (in_smem(n)) { W1LD(n) }
                        W1MMA(n)
                    }
                    W1LD(13)
                }
                if (ROLE == 0) mbar_wait(sb + B_KVFULL + slot * 8, (s >> 1) & 1);
            }
#undef pm
            SSTAMP(7, threadIdx.x == 0 && s == 0)
            PROF(14)
            const uint32_t pst = (l8 - sb) * 16 + ((warp * 16) ^ ((l8 * 2) & 112)) + (sb + S_P1);
            put_partials<ROLE == 2>(pst, acc[0], acc[1]); put_partials<ROLE == 2>(pst + 4096, acc[2], acc[3]);
            W1MMA(9)
            SFENCE();
            pld = (l8 & 64) * 4 + (l8 & 128) + (l8 & 56) * 2 + (sb + S_P1 + warp * 1024);
            const uint32_t rd = s == 63 ? 0 : rdelta;
            pub = ((l8 - sb) >> 1) + (ROLE ? sb + rd + (ROLE == 1 ? S_KL : S_VL) + warp * 128 : sb + S_QX + (warp & 4) * 128 + (warp & 1) * 256 + (warp & 2) * 64);
            pbar = sb + rd + (ROLE == 1 && s != 63 ? B_K : B_V);
#define PUBLISH0() { r0 = reduce8(x, l8, u2); if (ROLE) st_async1(pub, r0, KE && ROLE == 1 && s != 63 ? pbar + (B_PERS - B_K) : pbar); else sts32(pub, r0); }
            if (RPOS == 0) { bar_sync(1, 256); reduce_load(x, pld); SFENCE(); }
            W1MMA(11)
            if (RPOS == 1) { bar_sync(1, 256); reduce_load(x, pld); }
            if (RPOS != 2 || F2) SFENCE();
#define W1MMH(n, o) _Pragma("unroll") for (int i_ = o; i_ < o + 2; i_++) { const uint32_t* a_ = in_smem(n) ? as[unit_pos(n) * 4 + i_] : wr[unit_pos(n) * 4 + i_]; \
                                                                   mma16816(acc[((n) & 1) * 4 + i_], a_[0], a_[1], a_[2], a_[3], b[(n) & 14], b[(n) | 1]); }
            if (ES) { W1MMH(15, 0) W1MMH(15, 2) W1MMH(13, 0) } else W1MMA(15)
            if (RPOS == 0) PUBLISH0()
            if (RPOS == 2) { bar_sync(1, 256); reduce_load(x, pld); }
            if (RPOS != 1 || F2) SFENCE();
            if (ES) { W1MMH(13, 2) put_partials<ROLE == 2>(pst + 8192, acc[4], acc[5]); } else W1MMA(13)
            if (RPOS == 1) PUBLISH0()
            if (!ES) put_partials<ROLE == 2>(pst + 8192, acc[4], acc[5]);
            put_partials<ROLE == 2>(pst + 12288, acc[6], acc[7]);
            if (RPOS == 2) PUBLISH0()
        }
        SSTAMP(8, threadIdx.x == 0 && s == 0)
        PROF(1)
        if (ROLE) {
            bar_sync(1, 256);
            reduce_load(x, pld + 8192);
            r1 = reduce8(x, l8, u2);
            st_async1(pub + 1024, r1, pbar);
            if (s == 63) {
                PERSIST()
                mbar_wait(sb + B_V, 0);
                break;
            }
            PROF(2)
        }
        uint32_t ln, w2a, ro;
#define W2ADDR(late) { l8 += pub & P.zero; ln = (l8 - sb) >> 3; \
        w2a = sb + S_W2 + (ROLE ? (warp >> 2) * 16384 : late * 32768) + ((((ln & 7) + (ln >> 4) * 8) * 128 + ((((ln >> 3) & 1) ^ (ln & 7)) << 4)) ^ ((warp & 3) << 5)); \
        ro = (s & 7) * M_SLOT + (ROLE ? warp * 2048 + unit_off(ROLE) : (warp & 3) * 2048 + late * unit_off(3)) + (ln & 2) * 128 + (ln & 1) * 64 + (ln >> 2) * 8; }
        constexpr int RO2 = ROLE ? unit_off(ROLE + 3) - unit_off(ROLE) : 8192;
        float Sj[2];
        uint32_t w[24][4], ob[4][4];
        float S;
#define W2LD(i) ldsm4t(w[i], w2a + w2_t(i) * (ROLE ? 32768 : 16384) + (w2_k(i) & 1) * 8192 + (w2_k(i) >> 1) * 2048)
#define W2MMA(d, i) mma16816(d, w[i][0], w[i][1], w[i][2], w[i][3], ob[w2_k(i) >> 1][(w2_k(i) & 1) * 2], ob[w2_k(i) >> 1][(w2_k(i) & 1) * 2 + 1])
#define LEADER(wp) (l8 == sb + ((wp) - warp) * 256)
        if (att) {
            const float cs = 0.08838834764831845f * 1.4426950408889634f;
            uint32_t qa[4][4], kf[4][4], vf[4][4], vv[4];
            float T[5][2], sa[4][4] = {};
            const uint32_t l16 = l8 * 2 - sb;
            const uint32_t kaddr = (l8 & 56) * 16 + (((l8 >> 2) ^ (l8 * 2)) & 48) + ((l8 * 2) & 64) + (sb + S_KV + warp * 1024 + slot * 16384);
            bar_sync(1, 256);
            reduce_load(x, pld + 8192);
            __syncwarp();
#pragma unroll
            for (int i = 0; i < 2; i++) { ldsm4(qa[i], l16 + S_QX + i * 512); ldsm4(kf[i], kaddr ^ (i * 64)); }
            AFENCE(0)
            sts32(pub + 1024, reduce8(x, l8, u2));
            __syncwarp();
#pragma unroll
            for (int i = 2; i < 4; i++) ldsm4(kf[i], (kaddr ^ ((i & 1) * 64)) + 4096);
            score_half(sa, qa, kf);
            bar_sync(2, 256);
            PROF(2)
#pragma unroll
            for (int i = 2; i < 4; i++) ldsm4(qa[i], l16 + S_QX + i * 512);
            float sm[4][4] = {};
            const bool kearly = KE && mbar_try(sb + B_PERS, slot);
            score_half(sa, qa + 2, kf + 2);
            score_sum(T[0], sa);
            sts64(l8 + S_SX + warp * 256, __float_as_uint(T[0][0]), __float_as_uint(T[0][1]));
            PROF(4)
            if (KE) {
                if (!kearly) mbar_wait(sb + B_PERS, slot);
                ldsm4(kf[0], l16 + S_KL); ldsm4(kf[1], l16 + S_KL + 512);
                score_half(sm, qa, kf);
            }
            if (BPOS == 0) bar_sync(4, 128);
            mbar_wait(sb + B_K, slot);
            PROF(11)
#pragma unroll
            for (int i = KE ? 2 : 0; i < 4; i++) ldsm4(kf[i], l16 + S_KL + i * 512);
            if (BPOS == 1) bar_sync(4, 128); else __syncwarp();
#pragma unroll
            for (int n = 0; n < 4; n++) lds64f(T[n], l8 + S_SX + n * 256);
            if (!KE) score_half(sm, qa, kf);
            score_half(sm, qa + 2, kf + 2);
            const uint32_t vaddr = (l8 & 56) * 16 + (l8 & 128) * 8 + (((warp & 1) * 64 + ((l8 >> 2) & 16)) ^ ((l8 * 2) & 112)) + (sb + S_KV + 8192 + (warp >> 1) * 4096 + slot * 16384);
            float mx = fmaxf(fmaxf(fmaxf(T[0][0], T[0][1]), fmaxf(T[1][0], T[1][1])), fmaxf(fmaxf(T[2][0], T[2][1]), fmaxf(T[3][0], T[3][1])));
            score_sum(T[4], sm);
            float m = quad_max(fmaxf(mx, fmaxf(T[4][0], T[4][1])));
            if (VPOS == 0) {
#pragma unroll
                for (int i = 0; i < 4; i++) ldsm4t(vf[i], (vaddr ^ ((i & 1) << 5)) + (i >> 1) * 2048);
            }
            mbar_wait(sb + B_V, slot);
            if (VPOS == 1) {
#pragma unroll
                for (int i = 0; i < 4; i++) ldsm4t(vf[i], (vaddr ^ ((i & 1) << 5)) + (i >> 1) * 2048);
            }
            ldsm4(vv, l16 + S_VL + warp * 512);
            uint32_t pa[5];
#pragma unroll
            for (int n = 0; n < 5; n++) { T[n][0] = ex2((T[n][0] - m) * cs); T[n][1] = ex2((T[n][1] - m) * cs); pa[n] = pack2(T[n][0], T[n][1]); }
            float sum = (((T[0][0] + T[0][1]) + (T[1][0] + T[1][1])) + ((T[2][0] + T[2][1]) + (T[3][0] + T[3][1]))) + (T[4][0] + T[4][1]);
            PROF(3)
            W2ADDR(1)
            const uint32_t lo = sb + S_O + warp * 512 + (ln & 3) * 64 + (ln >> 2) * 8, ls = sb + S_SUM + (ln & 3) * 32 + (ln & 4) * 4 + (ln >> 3) * 4;
            const uint32_t sdelta = warp < 2 ? rdelta : vdelta;
            if (Q3 & 2) sum = (sum + __shfl_xor_sync(0xffffffffu, sum, 1)) + (__shfl_xor_sync(0xffffffffu, sum, 2) + __shfl_xor_sync(0xffffffffu, sum, 3));
            else { sum += __shfl_xor_sync(0xffffffffu, sum, 1); sum += __shfl_xor_sync(0xffffffffu, sum, 2); }
            float O[2][4];
#pragma unroll
            for (int i = 0; i < 2; i++) { O[i][0] = O[i][1] = O[i][2] = O[i][3] = 0.f; }
#pragma unroll
            for (int i = 0; i < 2; i++) {
                mma16816(O[0], vf[2 * i][0], vf[2 * i][1], vf[2 * i][2], vf[2 * i][3], pa[2 * i], pa[2 * i + 1]);
                mma16816(O[1], vf[2 * i + 1][0], vf[2 * i + 1][1], vf[2 * i + 1][2], vf[2 * i + 1][3], pa[2 * i], pa[2 * i + 1]);
            }
            mma1688(O[0], vv[0], vv[1], pa[4]);
            mma1688(O[1], vv[2], vv[3], pa[4]);
            uint32_t o[2][2];
#pragma unroll
            for (int j = 0; j < 2; j++) { o[j][0] = pack2(O[0][j], O[0][2 + j]); o[j][1] = pack2(O[1][j], O[1][2 + j]); }
#pragma unroll
            for (int j = 0; j < 2; j++) st_async2(lo + rdelta + j * 256, o[j][0], o[j][1], sb + rdelta + B_K);
            st_async1(ls + sdelta + (warp & 1) * 128, __float_as_uint(sum), sb + sdelta + B_K);
#pragma unroll
            for (int j = 0; j < 2; j++) st_async2(lo + vdelta + j * 256, o[j][0], o[j][1], sb + vdelta + B_K);
#pragma unroll
            for (int j = 0; j < 2; j++) sts64(lo + j * 256, o[j][0], o[j][1]);
            sts32(ls + warp * 128, __float_as_uint(sum));
            PROF(5)
            bar_sync(3, 256);
            if (LEADER(0)) { mbar_expect(sb + B_K, KE ? 1024 : 2048); if (KE) mbar_expect(sb + B_PERS, 1024); mbar_expect(sb + B_V, 2048); mbar_arrive(sb + B_KVGO + slot * 8); }
            S = next_scale(sb, slot, warp, u2);
            if (s == 0) mbar_wait(sb + B_WO, 0);
            pin<1>(&S);
            SFENCE();
#pragma unroll
            for (int j = 0; j < 4; j++) lds128(ob[j], l8 * 2 - sb + S_O + j * 512);
            lds64f(Sj, sb + S_SUM + (l8 & 24));
#pragma unroll
            for (int i = 0; i < PF2; i++) W2LD(i);
        } else {
            if (ROLE == 0) { bar_sync(1, 256); reduce_load(x, pld + 8192); sts32(pub + 1024, reduce8(x, l8, u2)); bar_arrive(2, 256); }
            if (LEADER(7)) { if (s) mbar_arrive(sb + B_GO); if (ROLE) mbar_expect(sb + B_K, 2304); }
            S = next_scale(sb, slot, warp, u2);
            if (s == 0) mbar_wait(sb + B_WO, 0);
            if (ROLE != 0) PERSIST()
            W2ADDR(0)
#pragma unroll
            for (int i = 0; i < PF2; i++) {
                W2LD(i);
                if (ROLE == 0 && (i & PACE) == PACE) w2a += w[i][0] & P.zero;
            }
            ro = opq(ro, ln);
            const uint32_t sa = opq(sb + S_SUM + (l8 & 24), ln), oa = opq(l8 * 2 - sb + S_O, ln);
            if (ROLE == 0) bar_sync(3, 256); else mbar_wait(sb + B_K, slot);
            if (OBN == 4 || !ROLE) lds64f(Sj, sa);
#pragma unroll
            for (int j = 0; j < 4; j++) { if (ROLE && j == OBN) SFENCE(); lds128(ob[j], oa + j * 512); }
            if (OBN < 4 && ROLE) lds64f(Sj, sa);
        }
        SSTAMP(9, threadIdx.x == 224 && s == 0)
        if (OBN == 4 || !ROLE) SFENCE();
        PROF(6)
        {
            const uint8_t* pr = P.gm + ro;
            float c[4][4];
            uint32_t lim = 0;
#pragma unroll
            for (int i = 0; i < 4; i++) { c[i][0] = c[i][1] = c[i][2] = c[i][3] = 0.f; }
#pragma unroll
            for (int i = 0; i < 16; i++) {
                W2MMA(c[i & (ROLE && !CH4 ? 1 : 3)], i);
                if (i + PF2 < (ROLE ? 16 + NEARLY : 16)) W2LD(i + PF2);
                if (i == 5) {
                    const uint32_t z = __float_as_uint(c[1][0]) & P.zero;
                    Sj[0] = S * rcp(__uint_as_float(__float_as_uint(Sj[0]) | z)); Sj[1] = S * rcp(__uint_as_float(__float_as_uint(Sj[1]) | z));
                }
                if (i == 5) lim = __any_sync(0xffffffffu, fmaxf(fmaxf(fabsf(c[0][0]), fabsf(c[0][2])), fmaxf(fabsf(c[1][0]), fabsf(c[1][2]))) * Sj[0] >= (ROLE && !CH4 ? 24.f : 20.f)) ? 16384 : 0;
                if (i == FPOS) { pin<1>(&lim); pin<2>(Sj); pin_ptr(pr); SFENCE(); }
            }
            if (ROLE == 0 || CH4) {
#pragma unroll
                for (int i = 0; i < 8; i++) { c[i >> 2][i & 3] += c[2 + (i >> 2)][i & 3]; c[2 + (i >> 2)][i & 3] = 0.f; }
            }
            const float xa[2][3] = {{c[0][0], c[0][2], c[1][0]}, {c[0][1], c[0][3], c[1][1]}};
            uint64_t wa[2], wb[2];
            emit<NU>(wa, xa, Sj, P.two26, lim, pr);
            PROF(7)
            mo = GATHER_OFF(s + 1);
            pin<1>(&mo);
            if (ROLE) {
                SFENCE();
#pragma unroll
                for (int i = 16 + NEARLY; i < 24; i++) { if (i == 16 + NBAR) bar_sync(2, 256); W2LD(i); __syncwarp(); }
                SFENCE();
#pragma unroll
                for (int i = 16; i < 24; i++) W2MMA(c[2 + (i & 1)], i);
#pragma unroll
                for (int i = 0; i < 4; i++) c[2][i] += c[3][i];
            }
            const float y[2][3] = {{ROLE ? c[1][2] : c[1][0], ROLE ? c[2][0] : c[1][2], c[2][2]}, {ROLE ? c[1][3] : c[1][1], ROLE ? c[2][1] : c[1][3], c[2][3]}};
            const bool released = !ROT || mbar_test(sb + B_RELA, slot ^ 1);
            emit<NU>(wb, y, Sj, P.two26, lim, pr + RO2);
            PROF(8)
            if (!__all_sync(0xffffffffu, (wa[0] & wb[0] & 1) && released && s)) {
                if (__builtin_expect(!__all_sync(0xffffffffu, wa[0] & wb[0] & 1), 0)) {
                    RETRY(5)
                    const uint8_t* pf = g_f + (s & 7) * F_SLOT + (ROLE ? ROLE * 8192 + warp * 1024 : (warp & 3) * 1024 + (att ? 24576 : 0)) + (ln & 3) * 128 + (ln >> 2) * 16;
                    repair<NU>(wa, xa, Sj, pr, pf);
                    repair<NU>(wb, y, Sj, pr + RO2, pf + (ROLE ? 24576 : 4096));
                }
                if (s == 0) { bar_sync(1, 256); if (LEADER(7)) mbar_arrive(sb + B_GO); }
                if (ROT) mbar_wait(sb + B_RELA, slot ^ 1);
            }
        }
        s++;
    }
}
struct Pipe { uint32_t stage, phase; };
struct Cons {
    uint32_t sb, rel;
    int wg, wq, lane, rank, pair;
    uint32_t nst;
    Pipe p;
};
__device__ __forceinline__ void pipe_next(Pipe& p) { p.stage = (p.stage + 1) & (NSTAGE - 1); p.phase ^= (p.stage == 0); }
__device__ __forceinline__ void release(const Cons& c, uint32_t stage) { if (c.lane < 2) mbar_arrive_cluster(c.rel + stage * 8); }

enum { PEND_NONE = 0, PEND_KVO = 1, PEND_HT = 2, PEND_OUT = 3, PEND_OUTH = 4 };
struct Pend { uint32_t pk[64]; int kind, row, col, cnt; };

__device__ __forceinline__ void staging_wait(const Cons& c) { if (c.nst) mbar_wait(c.sb + B_SFREE + c.wg * 8, (c.nst - 1) & 1); }
__device__ __forceinline__ void staging_post(Cons& c, int kind, int row, int col, int cnt) {
    __syncwarp();
    if (c.lane == 0) {
        if (c.wq == 0) { const uint32_t x[4] = {(uint32_t)kind, (uint32_t)row, (uint32_t)col, (uint32_t)cnt}; sts128(c.sb + S_DESC + c.wg * 16, x); }
        mbar_arrive(c.sb + B_SFULL + c.wg * 8);
    }
    c.nst++;
}
template <int HF, bool KVONLY = false>
__device__ __forceinline__ void drain(const Params& P, Cons& c, const Pend& d) {
    const uint32_t* pk = d.pk + HF * 32;
    if (!KVONLY && d.kind >= PEND_OUT) {
        if (HF == 1 && d.kind == PEND_OUTH) return;
        float* o = P.out + (size_t)(d.row + c.wq * 16 + (c.lane >> 2)) * 2048 + d.col + HF * 128 + (c.lane & 3) * 2;
#pragma unroll
        for (int j = 0; j < 16; j++) {
            st_stream2(o + j * 8, bf_lo(pk[j * 2]), bf_hi(pk[j * 2]));
            st_stream2(o + 8 * 2048 + j * 8, bf_lo(pk[j * 2 + 1]), bf_hi(pk[j * 2 + 1]));
        }
    } else if (d.kind != PEND_NONE) {
        const bool ht = !KVONLY && d.kind == PEND_HT;
        const int hi = (c.lane >> 3) & 1;
        const uint32_t base = c.sb + S_STG + c.wg * 16384 + ((ht ? hi * 32 + c.wq * 8 : c.wq * 16 + hi * 8) + (c.lane & 7)) * 128;
        staging_wait(c);
#pragma unroll
        for (int j = 0; j < 8; j++) {
            const int ch = (j & 3) * 2 + (c.lane >> 4);
            stsm4(base + (j >> 2) * 8192 + ((ch ^ (c.lane & 7)) << 4), pk[j * 4], pk[j * 4 + 1], pk[j * 4 + 2], pk[j * 4 + 3]);
        }
        fence_async_smem();
        staging_post(c, d.kind, d.row, d.col + HF * 128, HF ? d.cnt : -1);
    }
}
__device__ __forceinline__ void drain_all(const Params& P, Cons& c, Pend& d) { drain<0>(P, c, d); drain<1>(P, c, d); d.kind = PEND_NONE; }

__device__ __forceinline__ void store_warp(const Params& P, uint32_t sb, int wg) {
    const uint32_t stg = sb + S_STG + wg * 16384;
#pragma unroll 1
    for (uint32_t n = 0;; n++) {
        mbar_wait(sb + B_SFULL + wg * 8, n & 1);
        uint32_t x[4];
        lds128(x, sb + S_DESC + wg * 16);
        if (x[0] == PEND_NONE) break;
        const bool ht = x[0] == PEND_HT;
        const CUtensorMap* m = &P.tm[ht ? M_HTS : M_KVO];
#pragma unroll 1
        for (int i = 0; i < 4; i++) if (!(DBGF(128) && gridDim.x != 96)) tma_store2d(m, x[2] + (i >> 1) * 64, x[1] + (i & 1) * (ht ? 1024 : 32), stg + i * 4096, ht ? EVICT_NORMAL : x[1] < 4096 ? POL(4) : POL(5));
        bulk_commit();
        bulk_wait_read();
        mbar_arrive(sb + B_SFREE + wg * 8);
        if ((int)x[3] >= 0) {
            bulk_wait_all(); fence_async();
            asm volatile("red.relaxed.gpu.global.add.u32 [%0], 1;" ::"l"(&g_cnt(x[3])) : "memory");
        }
    }
}

template <int N, int TA, int TB, bool FIRST>
__device__ __forceinline__ void issue_ktile(float* acc, const Cons& c) {
    mbar_wait(c.sb + B_FULL + c.p.stage * 8, c.p.phase);
    const uint32_t a = c.sb + c.p.stage * STAGE + c.wg * 8192, b = c.sb + c.p.stage * STAGE + 16384;
    const uint64_t da = mkdesc(a, TA ? 8192 : 16, 1024, 1), db = mkdesc(b, TB ? 8192 : 16, 1024, 1);
    wg_fence();
#pragma unroll
    for (int k = 0; k < 4; k++) {
        const uint64_t x = da + (TA ? 128 : 2) * k, y = db + (TB ? 128 : 2) * k;
        if (N == 256) { if (FIRST && k == 0) wgmma_ss256_first<TA, TB>(acc, x, y); else wgmma_ss256<TA, TB>(acc, x, y); }
        else { if (FIRST && k == 0) wgmma_ss128_first<TA, TB>(acc, x, y); else wgmma_ss128<TA, TB>(acc, x, y); }
    }
    wg_commit();
}
template <int N, bool FIRST>
__device__ __forceinline__ void issue_any(float* acc, const Cons& c, int type) {
    if (N == 256 && type == T_A1) issue_ktile<N, 0, 0, FIRST>(acc, c);
    else if (type == (N == 256 ? T_A2 : T_A2H)) issue_ktile<N, 1, 0, FIRST>(acc, c);
    else issue_ktile<N, 0, 1, FIRST>(acc, c);
}
template <int N, bool KVONLY = false>
__device__ __forceinline__ void mainloop(float* acc, const Params& P, Cons& c, Pend& d, int type) {
    const int nk = (type == T_OP || type == T_OPH) ? 64 : (type == T_A2 || type == T_A2H) ? 32 : 16;
    issue_any<N, true>(acc, c, type);
    drain<0, KVONLY>(P, c, d);
    uint32_t prev = c.p.stage;
    pipe_next(c.p);
    const int hold = c.wg ? nk - (int)((P.lag >> (4 * type)) & 7) : -1;
    for (int kt = 1; kt < nk; kt++) {
        if (kt == hold) bar_sync(8, 256);
        issue_any<N, false>(acc, c, type);
        wg_wait<1>();
        release(c, prev);
        if (kt == 2) drain<1, KVONLY>(P, c, d);
        prev = c.p.stage;
        pipe_next(c.p);
    }
    if (c.wg == 0 && ((P.lag >> (4 * type)) & 7)) bar_arrive(8, 256);
    d.kind = PEND_NONE;
    wg_wait<0>();
    pin<N / 2>(acc);
    release(c, prev);
}
__device__ __forceinline__ void pack_half(uint32_t* pk, const float* a) {
#pragma unroll
    for (int i = 0; i < 32; i++) pk[i] = pack2(a[2 * i], a[2 * i + 1]);
}

__device__ __forceinline__ void epi_kv(const float* acc, const Cons& c, Pend& d, int mb, int nb) {
    pack_half(d.pk, acc); pack_half(d.pk + 32, acc + 64);
    d.kind = PEND_KVO; d.row = (nb >> 4) * 2048 + mb * 256 + c.rank * 128 + c.wg * 64; d.col = (nb & 15) * 256; d.cnt = C_KV + mb;
}

__device__ __forceinline__ void qa_scores(float* S, float* Sm, uint32_t* q, const Cons& c, const Pipe& p) {
    mbar_wait(c.sb + B_FULL + p.stage * 8, p.phase);
    const uint32_t st = c.sb + p.stage * STAGE;
    const uint64_t dk = mkdesc(st + c.wg * 8192, 16, 1024, 1), dm = mkdesc(st + 32768 + c.wg * 4096, 128, 2048, 0);
    pin<32>(q);
    wg_fence();
    wgmma_rs64_first<0>(S, q, dk);
#pragma unroll
    for (int i = 1; i < 8; i++) wgmma_rs64<0>(S, q + i * 4, dk + (i >> 2) * 1024 + (i & 3) * 2);
    wgmma_rs16_first<0>(Sm, q, dm);
#pragma unroll
    for (int i = 1; i < 8; i++) wgmma_rs16<0>(Sm, q + i * 4, dm + i * 16);
    wg_commit();
}
__device__ __forceinline__ void qa_softmax(uint32_t (*pa)[4], const float* S, const float* Sm, const Cons& c) {
    const int t = c.lane & 3, i0 = (c.wq & 1) * 16 + (c.lane >> 2);
    const bool sg = c.wq >= 2;
    const float cs = 0.08838834764831845f * 1.4426950408889634f, masked = -1e9f / 0.08838834764831845f;
    float x[2][10];
#pragma unroll
    for (int r = 0; r < 2; r++) {
#pragma unroll
        for (int j = 0; j < 4; j++)
#pragma unroll
            for (int e = 0; e < 2; e++) {
                const float v = sg ? S[16 + j * 4 + r * 2 + e] : S[j * 4 + r * 2 + e];
                x[r][j * 2 + e] = (j * 8 + 2 * t + e > i0 + r * 8) ? masked : v;
            }
        x[r][8] = sg ? Sm[4 + r * 2] : Sm[r * 2];
        x[r][9] = sg ? Sm[5 + r * 2] : Sm[1 + r * 2];
        float m = x[r][0];
#pragma unroll
        for (int i = 1; i < 10; i++) m = fmaxf(m, x[r][i]);
        m = fmaxf(m, __shfl_xor_sync(0xffffffffu, m, 1));
        m = fmaxf(m, __shfl_xor_sync(0xffffffffu, m, 2));
        float sum = 0.f;
#pragma unroll
        for (int i = 0; i < 10; i++) { x[r][i] = ex2((x[r][i] - m) * cs); sum += x[r][i]; }
        sum += __shfl_xor_sync(0xffffffffu, sum, 1);
        sum += __shfl_xor_sync(0xffffffffu, sum, 2);
        const float inv = rcp(sum);
#pragma unroll
        for (int i = 0; i < 10; i++) x[r][i] *= inv;
    }
#pragma unroll
    for (int ks = 0; ks < 2; ks++)
#pragma unroll
        for (int i = 0; i < 4; i++) {
            const uint32_t p = pack2(x[i & 1][ks * 4 + (i >> 1) * 2], x[i & 1][ks * 4 + (i >> 1) * 2 + 1]);
            pa[ks][i] = sg ? 0u : p;
            pa[2 + ks][i] = sg ? p : 0u;
        }
#pragma unroll
    for (int r = 0; r < 2; r++) {
        const uint32_t p = pack2(x[r][8], x[r][9]);
        pa[4][r] = sg ? 0u : p;
        pa[4][2 + r] = sg ? p : 0u;
    }
}
__device__ __forceinline__ void qa_values(float* O, uint32_t (*pa)[4], const Cons& c, const Pipe& p) {
    mbar_wait(c.sb + B_FULL + p.stage * 8, p.phase);
    const uint32_t st = c.sb + p.stage * STAGE;
    const uint64_t dv = mkdesc(st + c.wg * 8192, 16384, 1024, 1), dm = mkdesc(st + 32768 + c.wg * 4096, 2048, 128, 0);
    pin<20>(&pa[0][0]);
    wg_fence();
    wgmma_rs128_first<1>(O, pa[0], dv);
#pragma unroll
    for (int ks = 1; ks < 4; ks++) wgmma_rs128<1>(O, pa[ks], dv + ks * 128);
    wgmma_rs128<0>(O, pa[4], dm);
    wg_commit();
}
__device__ __forceinline__ void epi_qa(const float* acc, Cons& c, Pend& d, int mb, int nb) {
    uint32_t* q = d.pk;
    pack_half(q, acc);
    pack_half(q + 32, acc + 64);
#pragma unroll 1
    for (int hh = 0; hh < 2; hh++) {
        uint32_t pa[5][4];
        float S[32], Sm[8], O[64];
        qa_scores(S, Sm, q, c, c.p);
        wg_wait<0>();
        pin<32>(S); pin<8>(Sm);
        release(c, c.p.stage);
        pipe_next(c.p);
        qa_softmax(pa, S, Sm, c);
        qa_values(O, pa, c, c.p);
#pragma unroll
        for (int i = 0; i < 32; i++) q[i] = q[32 + i];
        pin<32>(q);
        wg_wait<0>();
        pin<64>(O);
        release(c, c.p.stage);
        pipe_next(c.p);
        pack_half(q + 32, O);
    }
    d.kind = PEND_KVO; d.row = 4096 + mb * 256 + c.rank * 128 + c.wg * 64; d.col = nb * 256; d.cnt = C_O + mb * 4 + (nb >> 2);
}

__device__ __forceinline__ void epi_op(const float* acc, const Cons& c, Pend& d, int mb, int nb) {
    pack_half(d.pk, acc); pack_half(d.pk + 32, acc + 64);
    d.kind = PEND_OUT; d.row = mb * 256 + c.rank * 128 + c.wg * 64; d.col = 1024 + nb * 256;
}

__device__ __forceinline__ void epi_oph(const float* acc, const Cons& c, Pend& d, int mb, int nb) {
    pack_half(d.pk, acc);
    d.kind = PEND_OUTH; d.row = mb * 256 + c.rank * 128 + c.wg * 64; d.col = 1024 + nb * 128;
}

template <int HF>
__device__ __forceinline__ void epi_a2_half(const float* acc, const Params& P, Cons& c, int mb, int col0) {
    const int g = c.lane >> 2, t = c.lane & 3;
    const int row = mb * 256 + (g >> 1) * 64 + (c.rank * 16 + c.wg * 8 + c.wq * 2) * 2 + (g & 1);
    float* o = P.out + (size_t)row * 2048 + col0 + HF * 128 + t * 2;
    mbar_wait(c.sb + B_FULL + c.p.stage * 8, c.p.phase);
    const uint32_t st = c.sb + c.p.stage * STAGE, da = st + 32768 + (c.lane >> 3) * 16;
    const uint32_t xa = st + (c.wg * 64 + c.wq * 16 + (c.lane & 15)) * 128 + (((c.lane >> 4) ^ (c.lane & 7)) << 4);
#pragma unroll
    for (int j4 = 0; j4 < 4; j4++) {
        uint32_t x[8], dv[4];
        ldsm4(dv, da + j4 * 64);
        ldsm4(x, (xa ^ ((j4 & 1) << 6)) + (j4 >> 1) * 16384);
        ldsm4(x + 4, (xa ^ ((j4 & 1) << 6) ^ 32) + (j4 >> 1) * 16384);
#pragma unroll
        for (int i = 0; i < 4; i++) {
            const int j = j4 * 4 + i;
            const float* a = acc + HF * 64 + j * 4;
            const uint32_t u0 = hmul2(x[2 * i], dv[i]), u1 = hmul2(x[2 * i + 1], dv[i]);
            st_stream2(o + j * 8, a[0] + bf_lo(u0), a[1] + bf_hi(u0));
            st_stream2(o + 2 * 2048 + j * 8, a[2] + bf_lo(u1), a[3] + bf_hi(u1));
        }
    }
    __syncwarp();
    release(c, c.p.stage);
    pipe_next(c.p);
}

#define TSTAMP(i)
__device__ __forceinline__ float2 cmul(float2 a, float2 b) { return make_float2(fmaf(a.x, b.x, -a.y * b.y), fmaf(a.x, b.y, a.y * b.x)); }
__device__ __forceinline__ float2 cfma(float2 a, float2 b, float2 u) { return make_float2(fmaf(a.x, b.x, fmaf(-a.y, b.y, u.x)), fmaf(a.x, b.y, fmaf(a.y, b.x, u.y))); }
__device__ __forceinline__ float4 ssm_coef(float lre, float lim, float logdt) {
    const float dt = __bfloat162float(__float2bfloat16(expf(logdt)));
    const float ea = expf(dt * lre);
    float sn, cn;
    sincosf(dt * lim, &sn, &cn);
    const float br = ea * cn, bi = ea * sn, nr = br - 1.f;
    float cr, ci;
    if (fabsf(lre) >= fabsf(lim)) { const float r = lim / lre, dn = lre + lim * r; cr = (nr + bi * r) / dn; ci = (bi - nr * r) / dn; }
    else { const float r = lre / lim, dn = lre * r + lim; cr = (nr * r + bi) / dn; ci = (bi * r - nr) / dn; }
    return make_float4(br, bi, cr, ci);
}
__device__ __forceinline__ void epi_a1(const float* acc, const Params& P, const Cons& c, Pend& d, int mb, int nb, uint32_t atag) {
    const int t = c.lane & 3;
    const int p = nb * 128 + c.rank * 64 + c.wg * 32 + c.wq * 8 + (c.lane >> 2);
    uint32_t cw[4];
    lds128(cw, c.sb + S_COEF + (p & 63) * 16);
    const float4 cf = make_float4(__uint_as_float(cw[0]), __uint_as_float(cw[1]), __uint_as_float(cw[2]), __uint_as_float(cw[3]));
    TSTAMP(1)
    const float2 lam = make_float2(cf.x, P.swap_ri ? -cf.y : cf.y);
    const float a0 = P.swap_ri ? -2.f * cf.w : 2.f * cf.z, a1 = P.swap_ri ? 2.f * cf.z : -2.f * cf.w;
    const float b0 = P.swap_ri ? -2.f * cf.z : -2.f * cf.w, b1 = P.swap_ri ? -2.f * cf.w : -2.f * cf.z;
    float2 h = make_float2(0.f, 0.f);
#pragma unroll
    for (int round = 0; round < 2; round++) {
#pragma unroll
        for (int j = 0; j < 32; j++) {
            h = cfma(lam, h, make_float2(acc[j * 4], acc[j * 4 + 2]));
            const float r0 = fmaf(a0, h.x, a1 * h.y), m0 = fmaf(b0, h.x, b1 * h.y);
            h = cfma(lam, h, make_float2(acc[j * 4 + 1], acc[j * 4 + 3]));
            d.pk[j * 2] = pack2(r0, fmaf(a0, h.x, a1 * h.y));
            d.pk[j * 2 + 1] = pack2(m0, fmaf(b0, h.x, b1 * h.y));
        }
        if (round) break;
        float2 l64 = lam;
#pragma unroll
        for (int i = 0; i < 6; i++) l64 = cmul(l64, l64);
        const float2 l128 = cmul(l64, l64), l256 = cmul(l128, l128);
        float2 o = make_float2(__shfl_up_sync(0xffffffffu, h.x, 1), __shfl_up_sync(0xffffffffu, h.y, 1));
        if (t >= 1) h = cfma(l64, o, h);
        o = make_float2(__shfl_up_sync(0xffffffffu, h.x, 2), __shfl_up_sync(0xffffffffu, h.y, 2));
        if (t >= 2) h = cfma(l128, o, h);
        TSTAMP(2)
        if (t == 3) st_relaxed2(&g_agg[mb * 1024 + p], (__float_as_uint(h.x) & ~1u) | atag, __float_as_uint(h.y));
        h = make_float2(__shfl_up_sync(0xffffffffu, h.x, 1), __shfl_up_sync(0xffffffffu, h.y, 1));
        if (t == 0) h = make_float2(0.f, 0.f);
        uint32_t ax[7], ay[7];
        int n = 0;
        while (true) {
            uint32_t bad = 0;
#pragma unroll
            for (int j = 0; j < 7; j++) { ax[j] = atag; ay[j] = 0; ld_relaxed2_if(ax[j], ay[j], &g_agg[j * 1024 + p], j < mb); }
#pragma unroll
            for (int j = 0; j < 7; j++) bad |= ax[j] ^ atag;
            if (tags_ok(bad)) break;
            __nanosleep(400);
            if (++n > SPIN_LIMIT) spin_fault();
        }
        float2 carry = make_float2(0.f, 0.f);
#pragma unroll
        for (int j = 0; j < 7; j++) if (j < mb) carry = cfma(l256, carry, make_float2(__uint_as_float(ax[j]), __uint_as_float(ay[j])));
        float2 w = (t & 1) ? l64 : make_float2(1.f, 0.f);
        if (t & 2) w = cmul(w, l128);
        h = cfma(w, carry, h);
        TSTAMP(3)
    }
    TSTAMP(4)
    d.kind = PEND_HT; d.row = nb * 128 + c.rank * 64 + c.wg * 32; d.col = mb * 256; d.cnt = C_HT + mb * 2 + (nb >> 2);
}

__device__ __forceinline__ uint32_t acquire_stage(uint32_t sb, Pipe& p, uint32_t bytes) {
    mbar_wait(sb + B_EMPTY + p.stage * 8, p.phase ^ 1);
    mbar_expect(sb + B_FULL + p.stage * 8, bytes);
    return p.stage;
}
#define AHEAD 1
__device__ __forceinline__ void watcher(const Params& P, const uint32_t sb, const int rank, const int lane) {
    const uint32_t epoch = ld_relaxed1(&g_cnt(C_EPOCH)), e1 = epoch + 1;
    sts32(sb + S_EPOCH, epoch);
    __syncwarp();
    if (lane == 0 && atomicInc(&g_cnt(C_DONE), (DBGF(32) ? 95 : NPAIR * 2 - 1) + (epoch & P.zero)) == (DBGF(32) ? 95 : NPAIR * 2 - 1)) atomicAdd(&g_cnt(C_EPOCH), 1);
    if (gridDim.x != 96) {
        uint32_t v;
        asm("mov.u32 %0, %%smid;" : "=r"(v));
        if (lane == 0 && rank == 0) st_relaxed1(g_hint + 6272 + (blockIdx.x >> 1), e1 << 8 | v >> 1);
        for (int k = 0;; k++) {
            __nanosleep(1000);
            v = ld_relaxed1(g_hint + 6272 + min(lane, 17));
            if (__all_sync(0xffffffffu, (v ^ e1 << 8) < 256)) break;
            if (k > SPIN_LIMIT) spin_fault();
        }
        const uint32_t key = ((v & 255) >= 62 ? 0 : tpc_gpc(v & 255)) * 32 + lane;
        sts32(sb + S_TAIL, 48 + __popc(__ballot_sync(0xffffffffu, key < __shfl_sync(0xffffffffu, key, blockIdx.x >> 1)) & 0x3ffff));
        __syncwarp();
    }
    uint32_t met = 1;
    if (lane == 0) asm volatile("st.release.cta.shared.u32 [%0], 1;" ::"r"(sb + S_DEP) : "memory");
    const int pair = lds32(sb + S_TAIL), first = ITEM_OFF(pair) + (pair < NCHAIN ? NPRE + 1 : 1);
#pragma unroll 1
    for (int it = first; it < ITEM_OFF(pair + 1); it++) {
        const int item = ITEM(it), type = item >> 8, mb = (item >> 5) & 7, nb = item & 31;
        const int n = (0x24021420 >> (type * 4)) & 7;
        for (int k = 0; it > first && (int)lds32(sb + S_CUR) < it - AHEAD; k++) { __nanosleep(200); if (k > SPIN_LIMIT) spin_fault(); }
#pragma unroll 1
        for (int i = 0; i < n; i++) {
            int idx = n == 4 ? C_O + mb * 4 + i : C_HT + mb * 2 + i;
            uint32_t target = e1 * 16;
            if (type == T_A1) { idx = C_COEF; target = e1 * 4; }
            if (type == T_QA) {
                idx = i ? C_FLAG + (lane & 1) * 32 + nb * 2 + ((lane >> 1) & 1) : C_KV + mb;
                target = i ? epoch * 64 + mb * 8 + rank * 4 + 4 : e1 * 128;
            }
            if (lane < 4) { wait_count(&g_cnt(idx), target); fence_async(); }
            __syncwarp();
            if (lane == 0) asm volatile("st.release.cta.shared.u32 [%0], %1;" ::"r"(sb + S_DEP), "r"(++met) : "memory");
        }
    }
}
__device__ __forceinline__ bool dep_met(uint32_t sb, uint32_t n) { uint32_t v; asm volatile("ld.acquire.cta.shared.u32 %0, [%1];" : "=r"(v) : "r"(sb + S_DEP) : "memory"); return v >= n; }
__device__ __forceinline__ void dep_wait(uint32_t sb, uint32_t n) { for (int k = 0; !dep_met(sb, n); k++) { __nanosleep(32); if (k > SPIN_LIMIT * 8) spin_fault(); } }
__device__ __forceinline__ void producer(const Params& P, const uint32_t sb, int pair, const int rank) {
    Pipe p = {0, 0};
    uint32_t dep = 1;
    for (int it = ITEM_OFF(pair); it < ITEM_OFF(pair + 1); it++) {
        const int item = ITEM(it), type = item >> 8, mb = (item >> 5) & 7, nb = item & 31;
        if (type == T_CHAIN) {
            sts32(sb + S_CUR, 0);
            const uint32_t epoch = ld_relaxed1(&g_cnt(C_EPOCH)), e1 = epoch + 1;
            const int role = pair >> 4, h = (pair & 15) * 2 + rank;
#pragma unroll 1
            for (int i = 0, q = 0; i < 8; i++) {
                const int n = (0x13003333 >> (i * 4)) & 3;
                const uint32_t st = acquire_stage(sb, p, n * 16384);
                SSTAMP(1, i == 6) SSTAMP(3, i == 7)
#pragma unroll 1
                for (int k = 0; k < 2 * n; k++, q++)
                    tma3d(sb + st * STAGE + k * 8192, &P.tm[M_CQ + role], h * 128 + (fill_unit(q >> 1) & 1) * 64, word_col((fill_unit(q >> 1) & 14) + (q & 1)) & 8, word_col((fill_unit(q >> 1) & 14) + (q & 1)) >> 4, sb + B_FULL + st * 8, role ? EVICT_NORMAL : POL(3));
                pipe_next(p);
            }
            if (role == 0 && !DBGF(1)) { wait_count(&g_cnt(C_KV), e1 * 128); fence_async(); }
            mbar_wait(sb + B_EMPTY + 16, 1); mbar_wait(sb + B_EMPTY + 24, 1);
            mbar_expect(sb + B_WO, role ? 98304 : 65536);
            if (role == 0) { mbar_expect(sb + B_KVFULL, 16384); mbar_expect(sb + B_KVFULL + 8, 16384); }
#pragma unroll 1
            for (int k = role ? 0 : -4; k < 12; k++) {
                const bool kv = role == 0 && (k & 8);
                const int sg = k > 0;
                tma4d(kv ? sb + S_KV + sg * 16384 + (k & 3) * 4096 : sb + S_W2 + k * 8192, &P.tm[kv ? M_KV4 : M_CO + (k & 1)],
                      kv ? h * 128 + (k & 1) * 64 : (role == 0 ? 0 : role == 1 ? 256 : 640) + (k >> 1) * 64, kv ? (k & 2) * 1024 + sg * 32 : h * 8, sb + (kv ? B_KVFULL + sg * 8 : B_WO), POL(2));
            }
            SSTAMP(5, true)
            if (pair < 16) {
#pragma unroll 1
                for (int s = 2; s < 63; s++) {
                    mbar_wait(sb + B_KVGO + (s & 1) * 8, ((s >> 1) + 1) & 1);
                    wait_time(gtime() + P.dk, sb);
                    SSTAMP(6, s == 2)
                    const uint32_t bar = sb + B_KVFULL + (s & 1) * 8, dst = sb + S_KV + (s & 1) * 16384;
                    if (DBGF(2)) { mbar_arrive(bar); continue; }
                    mbar_expect(bar, 16384);
#pragma unroll 1
                    for (int i = 0; i < 4; i++) tma2d(dst + i * 4096, &P.tm[M_KVO], (pair * 2 + rank) * 128 + (i & 1) * 64, (i >> 1) * 2048 + (DBGF(32 | 512) ? s & 7 : s) * 32, bar, POL(1));
                    if ((s & 7) == 7 && !DBGF(1)) { wait_count(&g_cnt(C_KV + 1 + (s >> 3)), e1 * 128); fence_async(); }
                }
            } else {
                uint32_t* flag = &g_cnt(C_FLAG + pair * 2 + rank - 32);
                const int x = pair * 2 + rank - 32;
#pragma unroll 1
                for (int s = 0; s < 64; s++) {
                    mbar_wait(sb + B_PERS, s & 1);
                    if (s < 63) wait_time(gtime() + P.dp, sb);
                    if (!DBGF(4)) bulk_s2g((role == 1 ? g_km : g_vmt) + (s * 32 + h) * 512, sb + S_QX, 2048);
                    if (s < 57) {
                        uint8_t* m = P.gm + ((s + 6) & 7) * M_SLOT + (x >> 1) * 1024 + (x & 1) * 256;
                        bulk_s2g(m, sb + S_SX, 256); bulk_s2g(m + 512, sb + S_SX, 128);
                        bulk_s2g(g_f + ((s + 6) & 7) * F_SLOT + x * 768, sb + S_SX + 256, 768);
                    }
                    bulk_commit();
                    bulk_wait_read();
                    mbar_arrive(sb + B_KVGO);
                    bulk_wait_all();
                    fence_async();
                    if ((s & 3) == 3) st_relaxed1(flag, epoch * 64 + s + 1);
                }
            }
            mbar_wait(sb + B_RESUME, 0);
            pair = lds32(sb + S_TAIL);
            it = ITEM_OFF(pair) + NPRE;
            continue;
        }
        if (it == ITEM_OFF(pair) && pair >= NCHAIN) it = -1; else sts32(sb + S_CUR, it);
        const int m0 = mb * 256 + rank * 128;
        if (type <= T_OP) {
            const CUtensorMap* ma = &P.tm[type == T_OP ? M_OA : M_BX];
            const CUtensorMap* mw = &P.tm[type == T_OP ? M_WO : type == T_QA ? M_WQ : nb < 16 ? M_WK : M_WV];
            const int nk = type == T_OP ? 64 : 16, nc = (nb & 15) * 4 + rank * 2, ma0 = type == T_OP ? 4096 + m0 : m0;
#pragma unroll 1
            for (int kt = 0; kt < nk; kt++) {
                if (type == T_OP && (kt & 15) == 0) dep_wait(sb, ++dep);
                if (DBGF(256) && pair >= NCHAIN) { acquire_stage(sb, p, 0); pipe_next(p); continue; }
                const uint32_t st = acquire_stage(sb, p, STAGE), bar = sb + B_FULL + st * 8;
                tma2d(sb + st * STAGE, ma, kt * 64, ma0, bar, type == T_OP ? POL(6) : type == T_QA ? POL(12) : POL(13));
                tma3d_mc(sb + st * STAGE + 16384 + rank * 16384, mw, 0, kt * 64, nc, bar, type == T_KV && mb == 7 ? POL(9) : EVICT_NORMAL);
                pipe_next(p);
            }
            if (type == T_QA) {
                dep += 2;
                dep_wait(sb, dep);
#pragma unroll 1
                for (int e = 0; e < 4; e++) {
                    const uint32_t st = acquire_stage(sb, p, 40960), bar = sb + B_FULL + st * 8, dst = sb + st * STAGE;
                    tma2d(dst, &P.tm[M_OA], nb * 256 + (e >> 1) * 128, (e & 1) * 2048 + m0, bar, POL(0));
                    tma2d(dst + 16384, &P.tm[M_OA], nb * 256 + (e >> 1) * 128 + 64, (e & 1) * 2048 + m0, bar, POL(0));
                    const uint32_t* src = ((e & 1) ? g_vmt : g_km) + ((mb * 8 + rank * 4) * 32 + nb * 2 + (e >> 1)) * 512;
#pragma unroll 1
                    for (int i = 0; i < 4; i++) bulk_g2s(dst + 32768 + i * 2048, src + i * 32 * 512, 2048, bar);
                    pipe_next(p);
                }
            }
        } else if (type == T_OPH) {
#pragma unroll 1
            for (int kt = 0; kt < 64; kt++) {
                if ((kt & 15) == 0) dep_wait(sb, ++dep);
                const uint32_t st = acquire_stage(sb, p, 32768), bar = sb + B_FULL + st * 8;
                tma2d(sb + st * STAGE, &P.tm[M_OA], kt * 64, 4096 + m0, bar, POL(6));
                tma2d_mc(sb + st * STAGE + 16384 + rank * 8192, &P.tm[M_WOH], nb * 128 + rank * 64, kt * 64, bar, EVICT_NORMAL);
                pipe_next(p);
            }
        } else if (type == T_A1) {
#pragma unroll 1
            for (int kt = 0; kt < 16; kt++) {
                if (kt == 15) dep_wait(sb, ++dep);
                const uint32_t st = acquire_stage(sb, p, kt == 15 ? STAGE + 1024 : STAGE), bar = sb + B_FULL + st * 8;
                if (kt == 15) bulk_g2s(sb + S_COEF, g_coef + nb * 128 + rank * 64, 1024, bar);
                tma4d(sb + st * STAGE, &P.tm[M_AB], kt * 64, nb * 16 + rank * 8, bar, POL(10));
                tma4d_mc(sb + st * STAGE + 16384 + rank * 16384, &P.tm[M_AX], kt * 64, mb * 128 + rank * 16, bar, POL(10));
                pipe_next(p);
            }
        } else {
            const int hw = type == T_A2H ? 64 : 128;
            const CUtensorMap* mc = &P.tm[type == T_A2H ? M_CREH : M_CRE];
#pragma unroll 1
            for (int kt = 0; kt < 32; kt++) {
                if ((kt & 15) == 0) dep_wait(sb, ++dep);
                const uint32_t st = acquire_stage(sb, p, 16384 + hw * 256), bar = sb + B_FULL + st * 8;
                tma3d(sb + st * STAGE, &P.tm[M_HT], 0, (kt & 1) * 1024 + (kt >> 1) * 64, mb * 4 + rank * 2, bar, POL(7));
                tma2d_mc(sb + st * STAGE + 16384 + rank * hw * 128, mc + (kt & 1), (kt >> 1) * 64, (nb * 2 + rank) * hw, bar, POL(11));
                pipe_next(p);
            }
#pragma unroll 1
            for (int col = nb * 2 * hw; col < (nb + 1) * 2 * hw; col += 128) {
                const uint32_t st = acquire_stage(sb, p, 32768 + 256), bar = sb + B_FULL + st * 8;
                tma4d(sb + st * STAGE, &P.tm[M_AX], col, mb * 128 + rank * 16, bar, POL(8));
                tma4d(sb + st * STAGE + 16384, &P.tm[M_AX], col + 64, mb * 128 + rank * 16, bar, POL(8));
                bulk_g2s(sb + st * STAGE + 32768, P.Dskip + col, 256, bar);
                pipe_next(p);
            }
        }
        if (it < 0) { dep_wait(sb, 1); pair = lds32(sb + S_TAIL); it = ITEM_OFF(pair); }
    }
}

__device__ __forceinline__ uint32_t fresh_tid() { uint32_t t; asm volatile("mov.u32 %0, %%tid.x;" : "=r"(t)); return t; }
__device__ __forceinline__ uint32_t fresh_ctaid() { uint32_t t; asm volatile("mov.u32 %0, %%ctaid.x;" : "=r"(t)); return logical_cta(t); }
__device__ __forceinline__ void reset_state(Cons& c, Pend& d, uint32_t sb, bool resumed) {
    const uint32_t t = fresh_tid(), b = fresh_ctaid();
    const int w = __shfl_sync(0xffffffffu, t >> 5, 0);
    c.sb = sb; c.wg = w >> 2; c.wq = w & 3; c.lane = t & 31;
    c.rank = __shfl_sync(0xffffffffu, b & 1, 0); c.pair = __shfl_sync(0xffffffffu, resumed && b < NCHAIN * 2 ? lds32(sb + S_TAIL) : b >> 1, 0);
    c.rel = mapa(sb + B_EMPTY, cluster_rank() ^ (c.lane & 1));
    c.p.stage = 0; c.p.phase = 0;
    c.nst = resumed && c.pair < NCHAIN ? 2 * NPRE : 0;
    d = Pend{};
}
#define PROF_ITEM(i)
#define PROF_MAIN(i)

__global__ void __launch_bounds__(384, 1) fused_kernel(const __grid_constant__ Params P) {
    extern __shared__ __align__(1024) uint8_t smem[];
    const uint32_t sb = smem_u32(smem);
    asm volatile("griddepcontrol.launch_dependents;");
    const int tid = threadIdx.x, lane = tid & 31;
    const int warp = __shfl_sync(0xffffffffu, tid >> 5, 0);
    const int pair = __shfl_sync(0xffffffffu, logical_cta(blockIdx.x) >> 1, 0), rank = __shfl_sync(0xffffffffu, blockIdx.x & 1, 0);
    if (tid == 0) {
        if (sb & 1023) spin_fault();
        sts32(sb + S_DEP, 0); sts32(sb + S_CUR, 0); sts32(sb + S_TAIL, pair); sts32(sb + S_CTA, pair * 2 + rank);
        for (int i = 0; i < NSTAGE; i++) { mbar_init(sb + B_FULL + i * 8, 1); mbar_init(sb + B_EMPTY + i * 8, 16); }
        mbar_init(sb + B_RESUME, 2);
        mbar_init(sb + B_KVFULL, 1); mbar_init(sb + B_KVFULL + 8, 1);
        mbar_init(sb + B_GO, 1); mbar_init(sb + B_KVGO, 1); mbar_init(sb + B_KVGO + 8, 1); mbar_init(sb + B_K, 1); mbar_init(sb + B_V, 1); mbar_init(sb + B_PERS, pair < 16 ? 1 : 8); mbar_init(sb + B_INIT, 3);
        mbar_init(sb + B_WO, 1);
        for (int i = 0; i < 2; i++) { mbar_init(sb + B_SFULL + i * 8, 4); mbar_init(sb + B_SFREE + i * 8, 1); }
        mbar_init(sb + B_RELA, 1); mbar_init(sb + B_RELB, 1);
        asm volatile("fence.mbarrier_init.release.cluster;" ::: "memory");
        if (pair < 16) { mbar_expect(sb + B_K, KE ? 1024 : 2048); mbar_expect(sb + B_PERS, 1024); }
        mbar_expect(sb + B_V, 2048);
    }
    __syncthreads();
    cluster_arrive();
    if (warp >= 8) {
        asm volatile("setmaxnreg.dec.sync.aligned.u32 24;");
        if (warp != 8) cluster_wait();
        if (warp == 10 && lane < M_COUNT) map_prefetch(&P.tm[lane]);
        if (warp == 11 && lane == 0 && pair < 16) {
            const uint32_t t0 = gtime();
#pragma unroll 1
            for (int i = 0; i < 32; i++) {
                wait_time(t0 + P.pf0 + i * P.pf1, sb);
                asm volatile("cp.async.bulk.prefetch.tensor.3d.L2.global [%0, {%1, %2, %3}];" ::"l"(&P.tm[M_CQ]), "r"((pair * 2 + rank) * 128 + (i & 1) * 64), "r"((i & 2) * 4), "r"((i >> 2) * 8) : "memory");
            }
        }
        if (warp == 9 && pair < NCHAIN) pacer(P, sb, lane);
        if (warp == 9) watcher(P, sb, rank, lane);
        if (warp >= 10 && lane == 0) store_warp(P, sb, warp - 10);
        if (warp == 8) {
            cluster_wait();
            if (lane == 0) producer(P, sb, lds32(sb + S_CTA) >> 1, rank);
            __syncwarp();
            cluster_arrive(); cluster_wait();
        }
    } else {
        asm volatile("setmaxnreg.inc.sync.aligned.u32 240;");
        Cons c;
        Pend d;
        if (pair < NCHAIN) {
            mem0_max(P, sb, tid);
            cluster_wait();
            reset_state(c, d, sb, false);
#pragma unroll 1
            for (int i = 0; i < NPRE; i++) {
                PROF_ITEM(i)
                const int item = ITEM(ITEM_OFF(pair) + i);
                float acc[128];
                mainloop<256, true>(acc, P, c, d, T_KV);
                epi_kv(acc, c, d, (item >> 5) & 7, item & 31);
            }
            ISTAMP(4)
            drain<0, true>(P, c, d);
            drain<1, true>(P, c, d);
            PROF_ITEM(NPRE)
            uint32_t wr[NR][4];
            load_weights(wr, sb, warp, lane, [&]() { staging_wait(c); });
            const int h = (pair & 15) * 2 + rank;
            if (pair < 16) chain_role<0>(P, wr, sb, h, warp, lane);
            else if (pair < 32) chain_role<1>(P, wr, sb, h, warp, lane);
            else chain_role<2>(P, wr, sb, h, warp, lane);
            fence_async_smem();
            bar_sync(1, 256);
            const uint32_t t2 = fresh_tid();
            if (t2 < 2) mbar_arrive_cluster(mapa(sb + B_RESUME, cluster_rank() ^ t2));
        } else if (pair >= NPAIR - 2) {
            const int ch = (pair - (NPAIR - 2)) * 512 + rank * 256 + tid;
            g_coef[ch] = ssm_coef(__bfloat162float(P.Lre[ch]), __bfloat162float(P.Lim[ch]), __bfloat162float(P.logdt[ch]));
            bar_sync(1, 256);
            if (tid == 0) red_release(&g_cnt(C_COEF));
        }
        reset_state(c, d, sb, true);
        if (c.pair >= NCHAIN) cluster_wait();
        for (int it = ITEM_OFF(c.pair) + (c.pair < NCHAIN ? NPRE + 1 : 0);; it++) {
            const bool last = it == ITEM_OFF(c.pair + 1);
            if (d.kind != PEND_NONE && (last || !bar_and(5 + c.wg, mbar_test(sb + B_FULL + c.p.stage * 8, c.p.phase)))) drain_all(P, c, d);
            if (last) break;
            const int item = ITEM(it), type = item >> 8, mb = (item >> 5) & 7, nb = item & 31;
            PROF_ITEM(it - ITEM_OFF(c.pair))
            if (type >= T_OPH) {
                float acc[64];
                mainloop<128>(acc, P, c, d, type);
                PROF_MAIN(it - ITEM_OFF(c.pair))
                if (type == T_OPH) epi_oph(acc, c, d, mb, nb);
                else epi_a2_half<0>(acc, P, c, mb, nb * 128);
            } else {
                float acc[128];
                mainloop<256>(acc, P, c, d, type);
                PROF_MAIN(it - ITEM_OFF(c.pair))
                if (type == T_KV) epi_kv(acc, c, d, mb, nb);
                else if (type == T_QA) epi_qa(acc, c, d, mb, nb);
                else if (type == T_OP) epi_op(acc, c, d, mb, nb);
                else if (type == T_A1) epi_a1(acc, P, c, d, mb, nb, (lds32(sb + S_EPOCH) + 1) & 1);
                else { epi_a2_half<0>(acc, P, c, mb, nb * 256); epi_a2_half<1>(acc, P, c, mb, nb * 256); }
            }
            if (it == ITEM_OFF(c.pair)) { dep_wait(sb, 1); c.pair = __shfl_sync(0xffffffffu, lds32(sb + S_TAIL), 0); it = ITEM_OFF(c.pair); }
        }
        staging_wait(c);
        staging_post(c, PEND_NONE, 0, 0, 0);
        cluster_arrive(); cluster_wait();
    }
}

typedef CUresult (*EncodeFn)(CUtensorMap*, CUtensorMapDataType, cuuint32_t, void*, const cuuint64_t*, const cuuint64_t*, const cuuint32_t*, const cuuint32_t*,
                             CUtensorMapInterleave, CUtensorMapSwizzle, CUtensorMapL2promotion, CUtensorMapFloatOOBfill);
void encode(EncodeFn fn, CUtensorMap* m, const void* base, int rank, const uint64_t* dims, const uint64_t* strides, const uint32_t* box, CUtensorMapSwizzle swz = CU_TENSOR_MAP_SWIZZLE_128B) {
    cuuint64_t d[5], s[5]; cuuint32_t b[5], e[5];
    for (int i = 0; i < rank; i++) { d[i] = dims[i]; b[i] = box[i]; e[i] = 1; if (i) s[i - 1] = strides[i - 1]; }
    fn(m, CU_TENSOR_MAP_DATA_TYPE_BFLOAT16, rank, (void*)base, d, s, b, e, CU_TENSOR_MAP_INTERLEAVE_NONE, swz,
       CU_TENSOR_MAP_L2_PROMOTION_L2_256B, CU_TENSOR_MAP_FLOAT_OOB_FILL_NONE);
}
void map_kmajor(EncodeFn fn, CUtensorMap* m, const void* base, uint64_t rows, uint64_t cols, uint32_t box_rows) {
    const uint64_t d[2] = {cols, rows}, s[1] = {cols * 2}; const uint32_t b[2] = {64, box_rows};
    encode(fn, m, base, 2, d, s, b);
}
void map_mnmajor(EncodeFn fn, CUtensorMap* m, const void* base, uint64_t krows, uint64_t cols) {
    const uint64_t d[3] = {64, krows, cols / 64}, s[2] = {cols * 2, 128}; const uint32_t b[3] = {64, 64, 2};
    encode(fn, m, base, 3, d, s, b);
}

}

extern "C" void kernel_launch(void* const* d_in, const int* in_sizes, int n_in, void* d_out, int out_size) {
    static Params P;
    static EncodeFn fn = nullptr;
    if (!fn) {
        cudaDriverEntryPointQueryResult q;
        cudaGetDriverEntryPoint("cuTensorMapEncodeTiled", (void**)&fn, cudaEnableDefault, &q);
        cudaFuncSetAttribute(fused_kernel, cudaFuncAttributeMaxDynamicSharedMemorySize, S_TOTAL);
    }
    const bf16* in[15];
    for (int i = 0; i < 15; i++) in[i] = (const bf16*)d_in[i];
    void *kvo, *ht, *gm;
    cudaGetSymbolAddress(&gm, g_m);
    P.gm = (uint8_t*)(((uintptr_t)gm + 32767) & ~(uintptr_t)32767);
    cudaGetSymbolAddress(&kvo, g_kvo);
    cudaGetSymbolAddress(&ht, g_ht);
    map_kmajor(fn, &P.tm[M_BX], in[9], 2048, 1024, 128);
    map_mnmajor(fn, &P.tm[M_WQ], in[11], 1024, 4096);
    map_mnmajor(fn, &P.tm[M_WK], in[12], 1024, 4096);
    map_mnmajor(fn, &P.tm[M_WV], in[13], 1024, 4096);
    map_mnmajor(fn, &P.tm[M_WO], in[14], 4096, 1024);
    map_kmajor(fn, &P.tm[M_OA], kvo, 3 * 2048, 4096, 128);
    P.swap_ri = in[4] < in[3];
    {
        const bf16* lo = P.swap_ri ? in[4] : in[3];
        const uint64_t diff = (uint64_t)((const char*)(P.swap_ri ? in[3] : in[4]) - (const char*)lo);
        const uint64_t d[4] = {1024, 8, 2, 128}, s[3] = {2048, diff, 16384}; const uint32_t b[4] = {64, 8, 2, 8};
        encode(fn, &P.tm[M_AB], lo, 4, d, s, b);
    }
    {
        const uint64_t d[4] = {1024, 2, 4, 1024}, s[3] = {2048, 64 * 2048, 4096}; const uint32_t b[4] = {64, 2, 4, 16};
        encode(fn, &P.tm[M_AX], in[0], 4, d, s, b);
    }
    map_mnmajor(fn, &P.tm[M_HT], ht, 2048, 2048);
    map_kmajor(fn, &P.tm[M_CRE], in[5], 1024, 1024, 128);
    map_kmajor(fn, &P.tm[M_CIM], in[6], 1024, 1024, 128);
    map_kmajor(fn, &P.tm[M_KVO], kvo, 3 * 2048, 4096, 32);
    map_kmajor(fn, &P.tm[M_HTS], ht, 2048, 2048, 32);
    map_kmajor(fn, &P.tm[M_WOH], in[14], 4096, 1024, 64);
    map_kmajor(fn, &P.tm[M_CREH], in[5], 1024, 1024, 64);
    map_kmajor(fn, &P.tm[M_CIMH], in[6], 1024, 1024, 64);
    for (int i = 0; i < 3; i++) {
        const uint64_t d[3] = {4096, 16, 64}, s[2] = {8192, 16 * 8192}; const uint32_t b[3] = {64, 8, 8};
        encode(fn, &P.tm[M_CQ + i], in[11 + i], 3, d, s, b);
    }
    {
        const uint64_t d[4] = {4096, 1, 1, 4096}, s[3] = {8192, 8192, 8192}; const uint32_t b[4] = {64, 1, 1, 32};
        encode(fn, &P.tm[M_KV4], kvo, 4, d, s, b);
    }
    for (int e = 0; e < 2; e++) {
        const uint64_t d[4] = {1024, 2, 4, 256}, s[3] = {8 * 2048, 2 * 2048, 16 * 2048}; const uint32_t b[4] = {64, 2, 4, 8};
        encode(fn, &P.tm[M_CO + e], in[14] + e * 1024, 4, d, s, b);
    }
    P.Wq = in[11]; P.Wk = in[12]; P.Wv = in[13]; P.Wo = in[14]; P.mem0 = in[10];
    P.Lre = in[1]; P.Lim = in[2]; P.logdt = in[7]; P.Dskip = in[8];
    P.out = (float*)d_out;
    P.two26 = 1u << 26;
    P.lag = 0x22023302;
    P.ds = 400; P.dc = 1600; P.alpha = 0.3f; P.extra = 200; P.da = 180; P.db = 420; P.dk = 750; P.dp = 1500; P.dv = 60; P.pf0 = 2000; P.pf1 = 250; P.back = 150; P.ds0 = 950;
    for (int i = 0; i < (DBGF(32) ? 1 : 2); i++) {
        cudaLaunchConfig_t cfg = {};
        cfg.gridDim = dim3(i ? 36 : 96); cfg.blockDim = dim3(384); cfg.dynamicSmemBytes = S_TOTAL; cfg.stream = cudaStreamPerThread;
        cudaLaunchAttribute at[2];
        at[0].id = cudaLaunchAttributeClusterDimension; at[0].val.clusterDim.x = i ? 2 : 6; at[0].val.clusterDim.y = at[0].val.clusterDim.z = 1;
        at[1].id = cudaLaunchAttributeProgrammaticStreamSerialization; at[1].val.programmaticStreamSerializationAllowed = 1;
        cfg.attrs = at; cfg.numAttrs = 1 + i;
        cudaLaunchKernelEx(&cfg, fused_kernel, P);
    }
}
```

```cpp
#include <cuda_runtime.h>
#include <cuda_bf16.h>
#include <cuda.h>
#include <stdint.h>
#include <string.h>

typedef __nv_bfloat16 bf16;

namespace {

#define POLL 200
constexpr int SPIN_LIMIT = 1 << 22;
constexpr int NPAIR = 66;
constexpr int NCHAIN = 48;
enum { T_KV = 0, T_QA = 1, T_OP = 2, T_A1 = 3, T_A2 = 4, T_CHAIN = 5, T_OPH = 6, T_A2H = 7 };
enum { M_BX = 0, M_WQ, M_WK, M_WV, M_WO, M_OA, M_AB, M_AX, M_HT, M_CRE, M_CIM, M_KVO, M_HTS, M_WOH, M_CREH, M_CIMH, M_CQ, M_CK, M_CV, M_CO, M_CO1, M_KV4, M_COUNT };
enum { C_KV = 0, C_HT = 8, C_DONE = 24, C_EPOCH = 25, C_COEF = 26, C_FLAG = 32, C_O = 96 };

struct Params {
    CUtensorMap tm[M_COUNT];
    const bf16 *Wq, *Wk, *Wv, *Wo, *mem0, *Lre, *Lim, *logdt, *Dskip;
    float* out;
    uint8_t* gm;
    int swap_ri, zero;
    uint32_t two26, lag;
    int ds, da, db, dk, dv, back, ds0, pf0, pf1, dc, extra, dp;
    float alpha;
#define DBGF(x) false
};

constexpr int NPRE = 1;
__constant__ uint16_t c_off[67] = {0, 5, 10, 15, 21, 25, 29, 35, 39, 43, 47, 51, 55, 59, 63, 67, 71, 76, 81, 86, 91, 95, 99, 103, 108, 112, 116, 120, 124, 128, 133, 137, 142, 147, 152, 157, 162, 166, 170, 175, 179, 183, 187, 191, 195, 200, 205, 209, 213, 232, 252, 272, 291, 311, 331, 349, 369, 389, 407, 427, 446, 466, 485, 505, 524, 543, 562};
__constant__ uint16_t c_items[640] = {
    32, 1280, 453, 492, 1056, 49, 1280, 485, 494, 1249, 34, 1280, 293, 301, 1120, 51, 1280, 458, 457, 428, 1959, 36, 1280, 896,
    642, 53, 1280, 898, 546, 38, 1280, 833, 961, 996, 1957, 55, 1280, 865, 578, 40, 1280, 495, 576, 57, 1280, 463, 579, 42,
    1280, 262, 675, 59, 1280, 264, 739, 44, 1280, 335, 608, 61, 1280, 897, 738, 46, 1280, 361, 707, 63, 1280, 265, 705, 0,
    1280, 388, 302, 1217, 1, 1280, 489, 493, 1248, 2, 1280, 391, 333, 1250, 3, 1280, 263, 459, 1088, 4, 1280, 866, 673, 5,
    1280, 931, 640, 6, 1280, 835, 737, 7, 1280, 899, 488, 1185, 8, 1280, 838, 643, 9, 1280, 839, 641, 10, 1280, 870, 672,
    11, 1280, 864, 515, 12, 1280, 871, 674, 13, 1280, 935, 933, 1219, 14, 1280, 772, 736, 15, 1280, 994, 964, 1091, 16, 1280,
    393, 332, 1216, 17, 1280, 484, 300, 1121, 18, 1280, 487, 364, 1058, 19, 1280, 423, 462, 1152, 20, 1280, 867, 544, 21, 1280,
    930, 545, 22, 1280, 900, 424, 1089, 23, 1280, 836, 577, 24, 1280, 903, 611, 25, 1280, 902, 609, 26, 1280, 928, 547, 27,
    1280, 869, 512, 28, 1280, 868, 901, 1251, 29, 1280, 932, 965, 1218, 30, 1280, 804, 704, 31, 1280, 962, 706, 33, 95, 94,
    127, 126, 159, 158, 255, 223, 191, 324, 352, 399, 422, 289, 425, 392, 490, 1024, 35, 93, 92, 125, 124, 157, 156, 189,
    221, 253, 252, 323, 254, 292, 418, 417, 386, 299, 365, 1956, 37, 91, 90, 123, 122, 155, 154, 187, 186, 251, 219, 250,
    334, 426, 366, 448, 449, 491, 430, 1123, 39, 89, 88, 121, 120, 153, 152, 185, 217, 184, 216, 218, 249, 248, 358, 288,
    321, 452, 514, 41, 87, 86, 119, 118, 151, 215, 247, 183, 214, 200, 199, 246, 325, 296, 420, 482, 268, 396, 1059, 43,
    85, 84, 117, 116, 149, 213, 181, 212, 180, 195, 193, 297, 363, 266, 326, 303, 455, 431, 1153, 45, 83, 82, 115, 114,
    147, 211, 179, 210, 178, 329, 243, 355, 356, 805, 837, 929, 610, 47, 81, 80, 113, 112, 145, 177, 176, 241, 190, 209,
    208, 240, 773, 832, 290, 480, 995, 966, 1057, 48, 79, 78, 111, 143, 142, 207, 175, 206, 174, 222, 192, 239, 256, 257,
    390, 389, 934, 997, 1090, 50, 77, 76, 109, 141, 140, 237, 173, 236, 234, 245, 205, 258, 771, 427, 421, 483, 513, 52,
    75, 74, 107, 139, 138, 171, 235, 170, 203, 202, 770, 774, 359, 775, 801, 963, 993, 397, 1958, 54, 73, 72, 105, 137,
    136, 169, 201, 233, 168, 362, 270, 394, 353, 807, 806, 960, 367, 1184, 56, 71, 103, 104, 135, 150, 167, 182, 231, 232,
    242, 238, 384, 224, 357, 387, 320, 486, 429, 1026, 58, 70, 102, 110, 134, 148, 166, 172, 230, 188, 267, 800, 244, 419,
    291, 295, 328, 269, 1027, 60, 69, 101, 108, 133, 146, 197, 165, 204, 198, 220, 322, 229, 398, 802, 803, 395, 454, 461,
    1155, 62, 68, 100, 106, 132, 144, 228, 164, 327, 196, 225, 768, 769, 260, 416, 481, 967, 999, 1122, 64, 67, 99, 97,
    131, 129, 163, 161, 271, 354, 259, 227, 261, 294, 450, 834, 992, 998, 1025, 65, 66, 98, 96, 130, 128, 162, 160, 298,
    226, 194, 385, 331, 330, 360, 451, 456, 460, 1154,
};
#define ITEM_OFF(p) c_off[p]
#define ITEM(i) c_items[i]

__device__ __align__(1024) bf16 g_kvo[3 * 2048 * 4096];
__device__ __align__(1024) bf16 g_ht[2048 * 2048];
__device__ __align__(1024) uint8_t g_m[9 * 32768];
__device__ __align__(1024) uint8_t g_f[8 * 49152];
__device__ __align__(1024) uint32_t g_km[64 * 32 * 512];
__device__ __align__(1024) uint32_t g_vmt[64 * 32 * 512];
__device__ __align__(1024) float2 g_agg[8 * 1024];
__device__ __align__(1024) float4 g_coef[1024];
__device__ __align__(1024) uint32_t g_cntl[128 * 32];
#define g_cnt(i) g_cntl[(i) * 32]
__device__ __align__(1024) uint32_t g_hint[6144 + 160];
#define SSTAMP(i, cond)
#define PROF(i)
#define GT_EDGE(o)
constexpr int M_SLOT = 32768, F_SLOT = 49152;

constexpr int STAGE = 49152, NSTAGE = 4;
constexpr int S_STG = NSTAGE * STAGE;
constexpr int S_BAR = S_STG + 32768;
constexpr int B_FULL = S_BAR, B_EMPTY = S_BAR + 32, B_RESUME = S_BAR + 64, B_KVFULL = S_BAR + 72, B_GO = S_BAR + 88, B_K = S_BAR + 96, B_PERS = S_BAR + 104, B_INIT = S_BAR + 112, B_RELA = S_BAR + 120, B_V = S_BAR + 128, B_WO = S_BAR + 136,
              B_SFULL = S_BAR + 144, B_SFREE = S_BAR + 160, S_DESC = S_BAR + 176, S_REDO = S_BAR + 256 + 512 + 64, S_EPOCH = S_BAR + 208, B_RELB = S_BAR + 216, B_KVGO = S_BAR + 224, S_DEP = S_BAR + 240, S_CUR = S_BAR + 244, S_TAIL = S_BAR + 248, S_CTA = S_BAR + 252;
constexpr int S_COEF = S_BAR + 256 + 512, S_TOTAL = S_COEF + 1024;
constexpr int S_W1 = 0;
constexpr int S_O = 24 * 4096, S_VL = S_O + 2048, S_MX = 25 * 4096, S_SC = S_MX + 64, S_SUM = S_MX + 128;
constexpr int S_KL = 26 * 4096;
constexpr int S_W2 = 27 * 4096;
constexpr int S_KV = S_W2 + 65536;
constexpr int S_P1 = S_W2 + 98304;
constexpr int S_QX = S_P1 + 16384;
constexpr int S_SX = S_QX + 2048;
static_assert(S_SX + 1280 <= S_BAR, "chain smem overlaps barriers");
constexpr int NR = 40, NS = 64 - NR;

__device__ __forceinline__ uint32_t logical_cta(uint32_t b) {
    const uint32_t c = b / 6, r = b - c * 6;
    return gridDim.x != 96 ? 96 + b : ((r >> 1) + (c >= 8) + (c >= 15)) % 3 * 32 + c * 2 + (r & 1);
}
__device__ __forceinline__ uint32_t cluster_rank() { uint32_t r; asm("mov.u32 %0, %%cluster_ctarank;" : "=r"(r)); return r; }
__device__ __forceinline__ uint16_t pair_mask() { return (uint16_t)(3u << (cluster_rank() & 6)); }
__device__ __forceinline__ void spin_fault() { asm volatile("st.global.u32 [%0], 0;" ::"l"(0ull) : "memory"); }
__device__ __forceinline__ uint32_t smem_u32(const void* p) { return (uint32_t)__cvta_generic_to_shared(p); }
__device__ __forceinline__ uint32_t opq(uint32_t x, int lane) { return __shfl_sync(0xffffffffu, x, lane); }
__device__ __forceinline__ uint32_t mapa(uint32_t a, uint32_t r) { uint32_t d; asm volatile("mapa.shared::cluster.u32 %0, %1, %2;" : "=r"(d) : "r"(a), "r"(r)); return d; }
__device__ __forceinline__ void mma16816(float* d, uint32_t a0, uint32_t a1, uint32_t a2, uint32_t a3, uint32_t b0, uint32_t b1) {
    asm("mma.sync.aligned.m16n8k16.row.col.f32.bf16.bf16.f32 {%0,%1,%2,%3}, {%4,%5,%6,%7}, {%8,%9}, {%0,%1,%2,%3};"
        : "+f"(d[0]), "+f"(d[1]), "+f"(d[2]), "+f"(d[3]) : "r"(a0), "r"(a1), "r"(a2), "r"(a3), "r"(b0), "r"(b1));
}
__device__ __forceinline__ void mma1688(float* d, uint32_t a0, uint32_t a1, uint32_t b0) {
    asm("mma.sync.aligned.m16n8k8.row.col.f32.bf16.bf16.f32 {%0,%1,%2,%3}, {%4,%5}, {%6}, {%0,%1,%2,%3};"
        : "+f"(d[0]), "+f"(d[1]), "+f"(d[2]), "+f"(d[3]) : "r"(a0), "r"(a1), "r"(b0));
}
__device__ __forceinline__ void ldsm4(uint32_t* r, uint32_t a) {
    asm volatile("ldmatrix.sync.aligned.m8n8.x4.shared.b16 {%0,%1,%2,%3}, [%4];" : "=r"(r[0]), "=r"(r[1]), "=r"(r[2]), "=r"(r[3]) : "r"(a));
}
__device__ __forceinline__ void ldsm4t(uint32_t* r, uint32_t a) {
    asm volatile("ldmatrix.sync.aligned.m8n8.x4.trans.shared.b16 {%0,%1,%2,%3}, [%4];" : "=r"(r[0]), "=r"(r[1]), "=r"(r[2]), "=r"(r[3]) : "r"(a));
}
__device__ __forceinline__ void stsm4(uint32_t a, uint32_t r0, uint32_t r1, uint32_t r2, uint32_t r3) {
    asm volatile("stmatrix.sync.aligned.m8n8.x4.shared.b16 [%0], {%1,%2,%3,%4};" ::"r"(a), "r"(r0), "r"(r1), "r"(r2), "r"(r3) : "memory");
}
__device__ __forceinline__ void stsm4t(uint32_t a, uint32_t r0, uint32_t r1, uint32_t r2, uint32_t r3) {
    asm volatile("stmatrix.sync.aligned.m8n8.x4.trans.shared.b16 [%0], {%1,%2,%3,%4};" ::"r"(a), "r"(r0), "r"(r1), "r"(r2), "r"(r3) : "memory");
}
__device__ __forceinline__ uint32_t pack2(float lo, float hi) { uint32_t d; asm("cvt.rn.bf16x2.f32 %0, %1, %2;" : "=r"(d) : "f"(hi), "f"(lo)); return d; }
__device__ __forceinline__ float bf_lo(uint32_t u) { return __uint_as_float(u << 16); }
__device__ __forceinline__ float bf_hi(uint32_t u) { return __uint_as_float(u & 0xffff0000u); }
__device__ __forceinline__ uint32_t hmul2(uint32_t a, uint32_t b) { uint32_t d; asm("mul.rn.bf16x2 %0, %1, %2;" : "=r"(d) : "r"(a), "r"(b)); return d; }
__device__ __forceinline__ float ex2(float x) { float y; asm("ex2.approx.ftz.f32 %0, %1;" : "=f"(y) : "f"(x)); return y; }
__device__ __forceinline__ float rcp(float x) { float y; asm("rcp.approx.ftz.f32 %0, %1;" : "=f"(y) : "f"(x)); return y; }
__device__ __forceinline__ void st_relaxed4(const void* p, uint32_t a, uint32_t b, uint32_t c, uint32_t d) {
    asm volatile("{\n.reg .b128 t;\nmov.b128 t, {%1,%2,%3,%4};\nst.relaxed.gpu.global.b128 [%0], t;\n}" ::"l"(p), "r"(a), "r"(b), "r"(c), "r"(d) : "memory");
}
__device__ __forceinline__ void st_relaxed2(const void* p, uint32_t a, uint32_t b) {
    asm volatile("{\n.reg .b64 t;\nmov.b64 t, {%1,%2};\nst.relaxed.gpu.global.b64 [%0], t;\n}" ::"l"(p), "r"(a), "r"(b) : "memory");
}
__device__ __forceinline__ void ld_relaxed2_if(uint32_t& a, uint32_t& b, const void* p, bool on) {
    asm volatile("{\n.reg .pred P;\n.reg .b64 t;\nsetp.ne.u32 P, %3, 0;\nmov.b64 t, {%0,%1};\n@P ld.relaxed.gpu.global.b64 t, [%2];\nmov.b64 {%0,%1}, t;\n}" : "+r"(a), "+r"(b) : "l"(p), "r"((uint32_t)on) : "memory");
}
__device__ __forceinline__ uint32_t ld_relaxed1(const void* p) { uint32_t v; asm volatile("ld.relaxed.gpu.global.u32 %0, [%1];" : "=r"(v) : "l"(p) : "memory"); return v; }
__device__ __forceinline__ void st_relaxed1(const void* p, uint32_t v) { asm volatile("st.relaxed.gpu.global.u32 [%0], %1;" ::"l"(p), "r"(v) : "memory"); }
__device__ __forceinline__ uint32_t ld_acquire(const void* p) { uint32_t v; asm volatile("ld.acquire.gpu.global.u32 %0, [%1];" : "=r"(v) : "l"(p) : "memory"); return v; }
__device__ __forceinline__ void red_release(void* p) { asm volatile("red.release.gpu.global.add.u32 [%0], 1;" ::"l"(p) : "memory"); }
__device__ __forceinline__ void st_stream2(float* p, float a, float b) { asm volatile("st.global.cs.v2.f32 [%0], {%1, %2};" ::"l"(p), "f"(a), "f"(b) : "memory"); }
__device__ __forceinline__ void fence_acquire() { asm volatile("fence.acquire.gpu;" ::: "memory"); }
__device__ __forceinline__ void fence_release() { asm volatile("fence.release.gpu;" ::: "memory"); }
__device__ __forceinline__ void fence_async() {  asm volatile("fence.proxy.async.global;" ::: "memory"); }
__device__ __forceinline__ void fence_async_smem() { asm volatile("fence.proxy.async.shared::cta;" ::: "memory"); }
__device__ __forceinline__ void wait_count(const uint32_t* p, uint32_t target) {
    int n = 0;
    while ((int32_t)(ld_acquire(p) - target) < 0) { __nanosleep(POLL); if (++n > SPIN_LIMIT) spin_fault(); }
}
__device__ __forceinline__ void bar_sync(int id, int n) { asm volatile("bar.sync %0, %1;" ::"r"(id), "r"(n) : "memory"); }
__device__ __forceinline__ void bar_arrive(int id, int n) { asm volatile("bar.arrive %0, %1;" ::"r"(id), "r"(n) : "memory"); }
__device__ __forceinline__ bool bar_and(int id, bool v) {
    uint32_t r;
    asm volatile("{\n.reg .pred P, Q;\nsetp.ne.u32 Q, %2, 0;\nbar.red.and.pred P, %1, 128, Q;\nselp.u32 %0, 1, 0, P;\n}" : "=r"(r) : "r"(id), "r"((uint32_t)v) : "memory");
    return r;
}
__device__ __forceinline__ void lds128(uint32_t* v, uint32_t a) { asm volatile("ld.shared.v4.b32 {%0,%1,%2,%3}, [%4];" : "=r"(v[0]), "=r"(v[1]), "=r"(v[2]), "=r"(v[3]) : "r"(a) : "memory"); }
__device__ __forceinline__ uint32_t lds32(uint32_t a) { uint32_t v; asm volatile("ld.shared.b32 %0, [%1];" : "=r"(v) : "r"(a) : "memory"); return v; }
__device__ __forceinline__ void lds64f(float* v, uint32_t a) { asm volatile("ld.shared.v2.f32 {%0,%1}, [%2];" : "=f"(v[0]), "=f"(v[1]) : "r"(a) : "memory"); }
__device__ __forceinline__ void sts128(uint32_t a, const uint32_t* v) { asm volatile("st.shared.v4.b32 [%0], {%1,%2,%3,%4};" ::"r"(a), "r"(v[0]), "r"(v[1]), "r"(v[2]), "r"(v[3]) : "memory"); }
__device__ __forceinline__ void sts64(uint32_t a, uint32_t x, uint32_t y) { asm volatile("st.shared.v2.b32 [%0], {%1,%2};" ::"r"(a), "r"(x), "r"(y) : "memory"); }
__device__ __forceinline__ void sts32(uint32_t a, uint32_t x) { asm volatile("st.shared.b32 [%0], %1;" ::"r"(a), "r"(x) : "memory"); }
__device__ __forceinline__ bool mbar_try(uint32_t b, uint32_t par) {
    uint32_t ok;
    asm volatile("{\n.reg .pred P;\nmbarrier.try_wait.parity.shared::cta.b64 P, [%1], %2;\nselp.u32 %0, 1, 0, P;\n}" : "=r"(ok) : "r"(b), "r"(par) : "memory");
    return ok;
}
__device__ __forceinline__ bool mbar_test(uint32_t b, uint32_t par) {
    uint32_t ok;
    asm volatile("{\n.reg .pred P;\nmbarrier.test_wait.parity.shared::cta.b64 P, [%1], %2;\nselp.u32 %0, 1, 0, P;\n}" : "=r"(ok) : "r"(b), "r"(par) : "memory");
    return ok;
}
__device__ __forceinline__ void mbar_wait(uint32_t b, uint32_t par) { int n = 0; while (!mbar_try(b, par)) { if (++n > SPIN_LIMIT) spin_fault(); } }
__device__ __forceinline__ void mbar_init(uint32_t b, uint32_t n) { asm volatile("mbarrier.init.shared::cta.b64 [%0], %1;" ::"r"(b), "r"(n) : "memory"); }
__device__ __forceinline__ void mbar_expect(uint32_t b, uint32_t bytes) { asm volatile("mbarrier.arrive.expect_tx.shared::cta.b64 _, [%0], %1;" ::"r"(b), "r"(bytes) : "memory"); }
__device__ __forceinline__ void mbar_arrive(uint32_t b) { asm volatile("mbarrier.arrive.shared::cta.b64 _, [%0];" ::"r"(b) : "memory"); }
__device__ __forceinline__ void mbar_arrive_cluster(uint32_t b) { asm volatile("mbarrier.arrive.shared::cluster.b64 _, [%0];" ::"r"(b) : "memory"); }
__device__ __forceinline__ void st_async1(uint32_t a, uint32_t x, uint32_t bar) {
    asm volatile("st.async.weak.shared::cluster.mbarrier::complete_tx::bytes.b32 [%0], %1, [%2];" ::"r"(a), "r"(x), "r"(bar) : "memory");
}
__device__ __forceinline__ void st_async2(uint32_t a, uint32_t x, uint32_t y, uint32_t bar) {
    asm volatile("st.async.weak.shared::cluster.mbarrier::complete_tx::bytes.v2.b32 [%0], {%1,%2}, [%3];" ::"r"(a), "r"(x), "r"(y), "r"(bar) : "memory");
}
__device__ __forceinline__ void cluster_arrive() { asm volatile("barrier.cluster.arrive.relaxed.aligned;" ::: "memory"); }
__device__ __forceinline__ void cluster_wait() { asm volatile("barrier.cluster.wait.aligned;" ::: "memory"); }
constexpr uint64_t EVICT_FIRST = 0x12F0000000000000ull, EVICT_NORMAL = 0x1000000000000000ull;
__device__ __forceinline__ void tma2d(uint32_t dst, const CUtensorMap* m, int c0, int c1, uint32_t bar, uint64_t pol) {
    asm volatile("cp.async.bulk.tensor.2d.shared::cluster.global.mbarrier::complete_tx::bytes.L2::cache_hint [%0], [%1, {%2, %3}], [%4], %5;" ::"r"(dst), "l"(m), "r"(c0), "r"(c1), "r"(bar), "l"(pol) : "memory");
}
__device__ __forceinline__ void tma4d(uint32_t dst, const CUtensorMap* m, int c0, int c3, uint32_t bar, uint64_t pol) {
    asm volatile("cp.async.bulk.tensor.4d.shared::cluster.global.mbarrier::complete_tx::bytes.L2::cache_hint [%0], [%1, {%2, 0, 0, %3}], [%4], %5;" ::"r"(dst), "l"(m), "r"(c0), "r"(c3), "r"(bar), "l"(pol) : "memory");
}
__device__ __forceinline__ void tma3d(uint32_t dst, const CUtensorMap* m, int c0, int c1, int c2, uint32_t bar, uint64_t pol) {
    asm volatile("cp.async.bulk.tensor.3d.shared::cluster.global.mbarrier::complete_tx::bytes.L2::cache_hint [%0], [%1, {%2, %3, %4}], [%5], %6;" ::"r"(dst), "l"(m), "r"(c0), "r"(c1), "r"(c2), "r"(bar), "l"(pol) : "memory");
}
__device__ __forceinline__ void tma_store2d(const CUtensorMap* m, int c0, int c1, uint32_t src, uint64_t pol) {
    asm volatile("cp.async.bulk.tensor.2d.global.shared::cta.bulk_group.L2::cache_hint [%0, {%1, %2}], [%3], %4;" ::"l"(m), "r"(c0), "r"(c1), "r"(src), "l"(pol) : "memory");
}
#define EF 63
#define POL(bit) ((EF >> (bit)) & 1 ? EVICT_FIRST : EVICT_NORMAL)
__device__ __forceinline__ void tma2d_mc(uint32_t dst, const CUtensorMap* m, int c0, int c1, uint32_t bar, uint64_t pol) {
    asm volatile("cp.async.bulk.tensor.2d.shared::cluster.global.mbarrier::complete_tx::bytes.multicast::cluster.L2::cache_hint [%0], [%1, {%2, %3}], [%4], %5, %6;" ::"r"(dst), "l"(m), "r"(c0), "r"(c1), "r"(bar), "h"(pair_mask()), "l"(pol) : "memory");
}
__device__ __forceinline__ void tma3d_mc(uint32_t dst, const CUtensorMap* m, int c0, int c1, int c2, uint32_t bar, uint64_t pol) {
    asm volatile("cp.async.bulk.tensor.3d.shared::cluster.global.mbarrier::complete_tx::bytes.multicast::cluster.L2::cache_hint [%0], [%1, {%2, %3, %4}], [%5], %6, %7;" ::"r"(dst), "l"(m), "r"(c0), "r"(c1), "r"(c2), "r"(bar), "h"(pair_mask()), "l"(pol) : "memory");
}
__device__ __forceinline__ void tma4d_mc(uint32_t dst, const CUtensorMap* m, int c0, int c3, uint32_t bar, uint64_t pol) {
    asm volatile("cp.async.bulk.tensor.4d.shared::cluster.global.mbarrier::complete_tx::bytes.multicast::cluster.L2::cache_hint [%0], [%1, {%2, 0, 0, %3}], [%4], %5, %6;" ::"r"(dst), "l"(m), "r"(c0), "r"(c3), "r"(bar), "h"(pair_mask()), "l"(pol) : "memory");
}
__device__ __forceinline__ void map_prefetch(const CUtensorMap* m) { asm volatile("prefetch.tensormap [%0];" ::"l"(m) : "memory"); }
__device__ __forceinline__ void bulk_g2s(uint32_t dst, const void* src, uint32_t bytes, uint32_t bar) {
    asm volatile("cp.async.bulk.shared::cluster.global.mbarrier::complete_tx::bytes [%0], [%1], %2, [%3];" ::"r"(dst), "l"(src), "r"(bytes), "r"(bar) : "memory");
}
__device__ __forceinline__ void bulk_s2g(void* dst, uint32_t src, uint32_t bytes) {
    asm volatile("cp.async.bulk.global.shared::cta.bulk_group [%0], [%1], %2;" ::"l"(dst), "r"(src), "r"(bytes) : "memory");
}
__device__ __forceinline__ void bulk_commit() { asm volatile("cp.async.bulk.commit_group;" ::: "memory"); }
__device__ __forceinline__ void bulk_wait_read() { asm volatile("cp.async.bulk.wait_group.read 0;" ::: "memory"); }
__device__ __forceinline__ void bulk_wait_all() { asm volatile("cp.async.bulk.wait_group 0;" ::: "memory"); }
__device__ __forceinline__ uint64_t mkdesc(uint32_t addr, uint32_t lbo, uint32_t sbo, uint32_t swz) {
    return (uint64_t)((addr & 0x3FFFF) >> 4) | ((uint64_t)(lbo >> 4) << 16) | ((uint64_t)(sbo >> 4) << 32) | ((uint64_t)swz << 62);
}
__device__ __forceinline__ void wg_fence() { asm volatile("wgmma.fence.sync.aligned;" ::: "memory"); }
__device__ __forceinline__ void wg_commit() { asm volatile("wgmma.commit_group.sync.aligned;" ::: "memory"); }
template <int N> __device__ __forceinline__ void wg_wait() { asm volatile("wgmma.wait_group.sync.aligned %0;" ::"n"(N) : "memory"); }
template <typename T> __device__ __forceinline__ void pin_ptr(T*& p) { asm volatile("" : "+l"(p)); }
template <int N> __device__ __forceinline__ void pin(uint32_t* d) {
#pragma unroll
    for (int i = 0; i < N; i++) asm volatile("" : "+r"(d[i])::"memory");
}
template <int N> __device__ __forceinline__ void pin(float* d) {
#pragma unroll
    for (int i = 0; i < N; i++) asm volatile("" : "+f"(d[i])::"memory");
}

template <int TA, int TB>
__device__ __forceinline__ void wgmma_ss256(float* d, uint64_t da, uint64_t db) {
    asm volatile("wgmma.mma_async.sync.aligned.m64n256k16.f32.bf16.bf16 "
        "{%0, %1, %2, %3, %4, %5, %6, %7, %8, %9, %10, %11, %12, %13, %14, %15, %16, %17, %18, %19, %20, %21, %22, %23, %24, %25, %26, %27, %28, %29, %30, %31, %32, %33, %34, %35, %36, %37, %38, %39, %40, %41, %42, %43, %44, %45, %46, %47, %48, %49, %50, %51, %52, %53, %54, %55, %56, %57, %58, %59, %60, %61, %62, %63, %64, %65, %66, %67, %68, %69, %70, %71, %72, %73, %74, %75, %76, %77, %78, %79, %80, %81, %82, %83, %84, %85, %86, %87, %88, %89, %90, %91, %92, %93, %94, %95, %96, %97, %98, %99, %100, %101, %102, %103, %104, %105, %106, %107, %108, %109, %110, %111, %112, %113, %114, %115, %116, %117, %118, %119, %120, %121, %122, %123, %124, %125, %126, %127}, %128, %129, 1, 1, 1, %130, %131;"
        : "+f"(d[0]), "+f"(d[1]), "+f"(d[2]), "+f"(d[3]), "+f"(d[4]), "+f"(d[5]), "+f"(d[6]), "+f"(d[7]), "+f"(d[8]), "+f"(d[9]), "+f"(d[10]), "+f"(d[11]), "+f"(d[12]), "+f"(d[13]), "+f"(d[14]), "+f"(d[15]), "+f"(d[16]), "+f"(d[17]), "+f"(d[18]), "+f"(d[19]), "+f"(d[20]), "+f"(d[21]), "+f"(d[22]), "+f"(d[23]), "+f"(d[24]), "+f"(d[25]), "+f"(d[26]), "+f"(d[27]), "+f"(d[28]), "+f"(d[29]), "+f"(d[30]), "+f"(d[31]), "+f"(d[32]), "+f"(d[33]), "+f"(d[34]), "+f"(d[35]), "+f"(d[36]), "+f"(d[37]), "+f"(d[38]), "+f"(d[39]), "+f"(d[40]), "+f"(d[41]), "+f"(d[42]), "+f"(d[43]), "+f"(d[44]), "+f"(d[45]), "+f"(d[46]), "+f"(d[47]), "+f"(d[48]), "+f"(d[49]), "+f"(d[50]), "+f"(d[51]), "+f"(d[52]), "+f"(d[53]), "+f"(d[54]), "+f"(d[55]), "+f"(d[56]), "+f"(d[57]), "+f"(d[58]), "+f"(d[59]), "+f"(d[60]), "+f"(d[61]), "+f"(d[62]), "+f"(d[63]), "+f"(d[64]), "+f"(d[65]), "+f"(d[66]), "+f"(d[67]), "+f"(d[68]), "+f"(d[69]), "+f"(d[70]), "+f"(d[71]), "+f"(d[72]), "+f"(d[73]), "+f"(d[74]), "+f"(d[75]), "+f"(d[76]), "+f"(d[77]), "+f"(d[78]), "+f"(d[79]), "+f"(d[80]), "+f"(d[81]), "+f"(d[82]), "+f"(d[83]), "+f"(d[84]), "+f"(d[85]), "+f"(d[86]), "+f"(d[87]), "+f"(d[88]), "+f"(d[89]), "+f"(d[90]), "+f"(d[91]), "+f"(d[92]), "+f"(d[93]), "+f"(d[94]), "+f"(d[95]), "+f"(d[96]), "+f"(d[97]), "+f"(d[98]), "+f"(d[99]), "+f"(d[100]), "+f"(d[101]), "+f"(d[102]), "+f"(d[103]), "+f"(d[104]), "+f"(d[105]), "+f"(d[106]), "+f"(d[107]), "+f"(d[108]), "+f"(d[109]), "+f"(d[110]), "+f"(d[111]), "+f"(d[112]), "+f"(d[113]), "+f"(d[114]), "+f"(d[115]), "+f"(d[116]), "+f"(d[117]), "+f"(d[118]), "+f"(d[119]), "+f"(d[120]), "+f"(d[121]), "+f"(d[122]), "+f"(d[123]), "+f"(d[124]), "+f"(d[125]), "+f"(d[126]), "+f"(d[127])
        : "l"(da), "l"(db), "n"(TA), "n"(TB));
}
template <int TA, int TB>
__device__ __forceinline__ void wgmma_ss256_first(float* d, uint64_t da, uint64_t db) {
    asm volatile("wgmma.mma_async.sync.aligned.m64n256k16.f32.bf16.bf16 "
        "{%0, %1, %2, %3, %4, %5, %6, %7, %8, %9, %10, %11, %12, %13, %14, %15, %16, %17, %18, %19, %20, %21, %22, %23, %24, %25, %26, %27, %28, %29, %30, %31, %32, %33, %34, %35, %36, %37, %38, %39, %40, %41, %42, %43, %44, %45, %46, %47, %48, %49, %50, %51, %52, %53, %54, %55, %56, %57, %58, %59, %60, %61, %62, %63, %64, %65, %66, %67, %68, %69, %70, %71, %72, %73, %74, %75, %76, %77, %78, %79, %80, %81, %82, %83, %84, %85, %86, %87, %88, %89, %90, %91, %92, %93, %94, %95, %96, %97, %98, %99, %100, %101, %102, %103, %104, %105, %106, %107, %108, %109, %110, %111, %112, %113, %114, %115, %116, %117, %118, %119, %120, %121, %122, %123, %124, %125, %126, %127}, %128, %129, 0, 1, 1, %130, %131;"
        : "=f"(d[0]), "=f"(d[1]), "=f"(d[2]), "=f"(d[3]), "=f"(d[4]), "=f"(d[5]), "=f"(d[6]), "=f"(d[7]), "=f"(d[8]), "=f"(d[9]), "=f"(d[10]), "=f"(d[11]), "=f"(d[12]), "=f"(d[13]), "=f"(d[14]), "=f"(d[15]), "=f"(d[16]), "=f"(d[17]), "=f"(d[18]), "=f"(d[19]), "=f"(d[20]), "=f"(d[21]), "=f"(d[22]), "=f"(d[23]), "=f"(d[24]), "=f"(d[25]), "=f"(d[26]), "=f"(d[27]), "=f"(d[28]), "=f"(d[29]), "=f"(d[30]), "=f"(d[31]), "=f"(d[32]), "=f"(d[33]), "=f"(d[34]), "=f"(d[35]), "=f"(d[36]), "=f"(d[37]), "=f"(d[38]), "=f"(d[39]), "=f"(d[40]), "=f"(d[41]), "=f"(d[42]), "=f"(d[43]), "=f"(d[44]), "=f"(d[45]), "=f"(d[46]), "=f"(d[47]), "=f"(d[48]), "=f"(d[49]), "=f"(d[50]), "=f"(d[51]), "=f"(d[52]), "=f"(d[53]), "=f"(d[54]), "=f"(d[55]), "=f"(d[56]), "=f"(d[57]), "=f"(d[58]), "=f"(d[59]), "=f"(d[60]), "=f"(d[61]), "=f"(d[62]), "=f"(d[63]), "=f"(d[64]), "=f"(d[65]), "=f"(d[66]), "=f"(d[67]), "=f"(d[68]), "=f"(d[69]), "=f"(d[70]), "=f"(d[71]), "=f"(d[72]), "=f"(d[73]), "=f"(d[74]), "=f"(d[75]), "=f"(d[76]), "=f"(d[77]), "=f"(d[78]), "=f"(d[79]), "=f"(d[80]), "=f"(d[81]), "=f"(d[82]), "=f"(d[83]), "=f"(d[84]), "=f"(d[85]), "=f"(d[86]), "=f"(d[87]), "=f"(d[88]), "=f"(d[89]), "=f"(d[90]), "=f"(d[91]), "=f"(d[92]), "=f"(d[93]), "=f"(d[94]), "=f"(d[95]), "=f"(d[96]), "=f"(d[97]), "=f"(d[98]), "=f"(d[99]), "=f"(d[100]), "=f"(d[101]), "=f"(d[102]), "=f"(d[103]), "=f"(d[104]), "=f"(d[105]), "=f"(d[106]), "=f"(d[107]), "=f"(d[108]), "=f"(d[109]), "=f"(d[110]), "=f"(d[111]), "=f"(d[112]), "=f"(d[113]), "=f"(d[114]), "=f"(d[115]), "=f"(d[116]), "=f"(d[117]), "=f"(d[118]), "=f"(d[119]), "=f"(d[120]), "=f"(d[121]), "=f"(d[122]), "=f"(d[123]), "=f"(d[124]), "=f"(d[125]), "=f"(d[126]), "=f"(d[127])
        : "l"(da), "l"(db), "n"(TA), "n"(TB));
}
template <int TA, int TB>
__device__ __forceinline__ void wgmma_ss128(float* d, uint64_t da, uint64_t db) {
    asm volatile("wgmma.mma_async.sync.aligned.m64n128k16.f32.bf16.bf16 "
        "{%0, %1, %2, %3, %4, %5, %6, %7, %8, %9, %10, %11, %12, %13, %14, %15, %16, %17, %18, %19, %20, %21, %22, %23, %24, %25, %26, %27, %28, %29, %30, %31, %32, %33, %34, %35, %36, %37, %38, %39, %40, %41, %42, %43, %44, %45, %46, %47, %48, %49, %50, %51, %52, %53, %54, %55, %56, %57, %58, %59, %60, %61, %62, %63}, %64, %65, 1, 1, 1, %66, %67;"
        : "+f"(d[0]), "+f"(d[1]), "+f"(d[2]), "+f"(d[3]), "+f"(d[4]), "+f"(d[5]), "+f"(d[6]), "+f"(d[7]), "+f"(d[8]), "+f"(d[9]), "+f"(d[10]), "+f"(d[11]), "+f"(d[12]), "+f"(d[13]), "+f"(d[14]), "+f"(d[15]), "+f"(d[16]), "+f"(d[17]), "+f"(d[18]), "+f"(d[19]), "+f"(d[20]), "+f"(d[21]), "+f"(d[22]), "+f"(d[23]), "+f"(d[24]), "+f"(d[25]), "+f"(d[26]), "+f"(d[27]), "+f"(d[28]), "+f"(d[29]), "+f"(d[30]), "+f"(d[31]), "+f"(d[32]), "+f"(d[33]), "+f"(d[34]), "+f"(d[35]), "+f"(d[36]), "+f"(d[37]), "+f"(d[38]), "+f"(d[39]), "+f"(d[40]), "+f"(d[41]), "+f"(d[42]), "+f"(d[43]), "+f"(d[44]), "+f"(d[45]), "+f"(d[46]), "+f"(d[47]), "+f"(d[48]), "+f"(d[49]), "+f"(d[50]), "+f"(d[51]), "+f"(d[52]), "+f"(d[53]), "+f"(d[54]), "+f"(d[55]), "+f"(d[56]), "+f"(d[57]), "+f"(d[58]), "+f"(d[59]), "+f"(d[60]), "+f"(d[61]), "+f"(d[62]), "+f"(d[63])
        : "l"(da), "l"(db), "n"(TA), "n"(TB));
}
template <int TA, int TB>
__device__ __forceinline__ void wgmma_ss128_first(float* d, uint64_t da, uint64_t db) {
    asm volatile("wgmma.mma_async.sync.aligned.m64n128k16.f32.bf16.bf16 "
        "{%0, %1, %2, %3, %4, %5, %6, %7, %8, %9, %10, %11, %12, %13, %14, %15, %16, %17, %18, %19, %20, %21, %22, %23, %24, %25, %26, %27, %28, %29, %30, %31, %32, %33, %34, %35, %36, %37, %38, %39, %40, %41, %42, %43, %44, %45, %46, %47, %48, %49, %50, %51, %52, %53, %54, %55, %56, %57, %58, %59, %60, %61, %62, %63}, %64, %65, 0, 1, 1, %66, %67;"
        : "=f"(d[0]), "=f"(d[1]), "=f"(d[2]), "=f"(d[3]), "=f"(d[4]), "=f"(d[5]), "=f"(d[6]), "=f"(d[7]), "=f"(d[8]), "=f"(d[9]), "=f"(d[10]), "=f"(d[11]), "=f"(d[12]), "=f"(d[13]), "=f"(d[14]), "=f"(d[15]), "=f"(d[16]), "=f"(d[17]), "=f"(d[18]), "=f"(d[19]), "=f"(d[20]), "=f"(d[21]), "=f"(d[22]), "=f"(d[23]), "=f"(d[24]), "=f"(d[25]), "=f"(d[26]), "=f"(d[27]), "=f"(d[28]), "=f"(d[29]), "=f"(d[30]), "=f"(d[31]), "=f"(d[32]), "=f"(d[33]), "=f"(d[34]), "=f"(d[35]), "=f"(d[36]), "=f"(d[37]), "=f"(d[38]), "=f"(d[39]), "=f"(d[40]), "=f"(d[41]), "=f"(d[42]), "=f"(d[43]), "=f"(d[44]), "=f"(d[45]), "=f"(d[46]), "=f"(d[47]), "=f"(d[48]), "=f"(d[49]), "=f"(d[50]), "=f"(d[51]), "=f"(d[52]), "=f"(d[53]), "=f"(d[54]), "=f"(d[55]), "=f"(d[56]), "=f"(d[57]), "=f"(d[58]), "=f"(d[59]), "=f"(d[60]), "=f"(d[61]), "=f"(d[62]), "=f"(d[63])
        : "l"(da), "l"(db), "n"(TA), "n"(TB));
}
template <int TB>
__device__ __forceinline__ void wgmma_rs128(float* d, const uint32_t* a, uint64_t db) {
    asm volatile("wgmma.mma_async.sync.aligned.m64n128k16.f32.bf16.bf16 "
        "{%0, %1, %2, %3, %4, %5, %6, %7, %8, %9, %10, %11, %12, %13, %14, %15, %16, %17, %18, %19, %20, %21, %22, %23, %24, %25, %26, %27, %28, %29, %30, %31, %32, %33, %34, %35, %36, %37, %38, %39, %40, %41, %42, %43, %44, %45, %46, %47, %48, %49, %50, %51, %52, %53, %54, %55, %56, %57, %58, %59, %60, %61, %62, %63}, {%64, %65, %66, %67}, %68, 1, 1, 1, %69;"
        : "+f"(d[0]), "+f"(d[1]), "+f"(d[2]), "+f"(d[3]), "+f"(d[4]), "+f"(d[5]), "+f"(d[6]), "+f"(d[7]), "+f"(d[8]), "+f"(d[9]), "+f"(d[10]), "+f"(d[11]), "+f"(d[12]), "+f"(d[13]), "+f"(d[14]), "+f"(d[15]), "+f"(d[16]), "+f"(d[17]), "+f"(d[18]), "+f"(d[19]), "+f"(d[20]), "+f"(d[21]), "+f"(d[22]), "+f"(d[23]), "+f"(d[24]), "+f"(d[25]), "+f"(d[26]), "+f"(d[27]), "+f"(d[28]), "+f"(d[29]), "+f"(d[30]), "+f"(d[31]), "+f"(d[32]), "+f"(d[33]), "+f"(d[34]), "+f"(d[35]), "+f"(d[36]), "+f"(d[37]), "+f"(d[38]), "+f"(d[39]), "+f"(d[40]), "+f"(d[41]), "+f"(d[42]), "+f"(d[43]), "+f"(d[44]), "+f"(d[45]), "+f"(d[46]), "+f"(d[47]), "+f"(d[48]), "+f"(d[49]), "+f"(d[50]), "+f"(d[51]), "+f"(d[52]), "+f"(d[53]), "+f"(d[54]), "+f"(d[55]), "+f"(d[56]), "+f"(d[57]), "+f"(d[58]), "+f"(d[59]), "+f"(d[60]), "+f"(d[61]), "+f"(d[62]), "+f"(d[63])
        : "r"(a[0]), "r"(a[1]), "r"(a[2]), "r"(a[3]), "l"(db), "n"(TB));
}
template <int TB>
__device__ __forceinline__ void wgmma_rs128_first(float* d, const uint32_t* a, uint64_t db) {
    asm volatile("wgmma.mma_async.sync.aligned.m64n128k16.f32.bf16.bf16 "
        "{%0, %1, %2, %3, %4, %5, %6, %7, %8, %9, %10, %11, %12, %13, %14, %15, %16, %17, %18, %19, %20, %21, %22, %23, %24, %25, %26, %27, %28, %29, %30, %31, %32, %33, %34, %35, %36, %37, %38, %39, %40, %41, %42, %43, %44, %45, %46, %47, %48, %49, %50, %51, %52, %53, %54, %55, %56, %57, %58, %59, %60, %61, %62, %63}, {%64, %65, %66, %67}, %68, 0, 1, 1, %69;"
        : "=f"(d[0]), "=f"(d[1]), "=f"(d[2]), "=f"(d[3]), "=f"(d[4]), "=f"(d[5]), "=f"(d[6]), "=f"(d[7]), "=f"(d[8]), "=f"(d[9]), "=f"(d[10]), "=f"(d[11]), "=f"(d[12]), "=f"(d[13]), "=f"(d[14]), "=f"(d[15]), "=f"(d[16]), "=f"(d[17]), "=f"(d[18]), "=f"(d[19]), "=f"(d[20]), "=f"(d[21]), "=f"(d[22]), "=f"(d[23]), "=f"(d[24]), "=f"(d[25]), "=f"(d[26]), "=f"(d[27]), "=f"(d[28]), "=f"(d[29]), "=f"(d[30]), "=f"(d[31]), "=f"(d[32]), "=f"(d[33]), "=f"(d[34]), "=f"(d[35]), "=f"(d[36]), "=f"(d[37]), "=f"(d[38]), "=f"(d[39]), "=f"(d[40]), "=f"(d[41]), "=f"(d[42]), "=f"(d[43]), "=f"(d[44]), "=f"(d[45]), "=f"(d[46]), "=f"(d[47]), "=f"(d[48]), "=f"(d[49]), "=f"(d[50]), "=f"(d[51]), "=f"(d[52]), "=f"(d[53]), "=f"(d[54]), "=f"(d[55]), "=f"(d[56]), "=f"(d[57]), "=f"(d[58]), "=f"(d[59]), "=f"(d[60]), "=f"(d[61]), "=f"(d[62]), "=f"(d[63])
        : "r"(a[0]), "r"(a[1]), "r"(a[2]), "r"(a[3]), "l"(db), "n"(TB));
}
template <int TB>
__device__ __forceinline__ void wgmma_rs64(float* d, const uint32_t* a, uint64_t db) {
    asm volatile("wgmma.mma_async.sync.aligned.m64n64k16.f32.bf16.bf16 "
        "{%0, %1, %2, %3, %4, %5, %6, %7, %8, %9, %10, %11, %12, %13, %14, %15, %16, %17, %18, %19, %20, %21, %22, %23, %24, %25, %26, %27, %28, %29, %30, %31}, {%32, %33, %34, %35}, %36, 1, 1, 1, %37;"
        : "+f"(d[0]), "+f"(d[1]), "+f"(d[2]), "+f"(d[3]), "+f"(d[4]), "+f"(d[5]), "+f"(d[6]), "+f"(d[7]), "+f"(d[8]), "+f"(d[9]), "+f"(d[10]), "+f"(d[11]), "+f"(d[12]), "+f"(d[13]), "+f"(d[14]), "+f"(d[15]), "+f"(d[16]), "+f"(d[17]), "+f"(d[18]), "+f"(d[19]), "+f"(d[20]), "+f"(d[21]), "+f"(d[22]), "+f"(d[23]), "+f"(d[24]), "+f"(d[25]), "+f"(d[26]), "+f"(d[27]), "+f"(d[28]), "+f"(d[29]), "+f"(d[30]), "+f"(d[31])
        : "r"(a[0]), "r"(a[1]), "r"(a[2]), "r"(a[3]), "l"(db), "n"(TB));
}
template <int TB>
__device__ __forceinline__ void wgmma_rs64_first(float* d, const uint32_t* a, uint64_t db) {
    asm volatile("wgmma.mma_async.sync.aligned.m64n64k16.f32.bf16.bf16 "
        "{%0, %1, %2, %3, %4, %5, %6, %7, %8, %9, %10, %11, %12, %13, %14, %15, %16, %17, %18, %19, %20, %21, %22, %23, %24, %25, %26, %27, %28, %29, %30, %31}, {%32, %33, %34, %35}, %36, 0, 1, 1, %37;"
        : "=f"(d[0]), "=f"(d[1]), "=f"(d[2]), "=f"(d[3]), "=f"(d[4]), "=f"(d[5]), "=f"(d[6]), "=f"(d[7]), "=f"(d[8]), "=f"(d[9]), "=f"(d[10]), "=f"(d[11]), "=f"(d[12]), "=f"(d[13]), "=f"(d[14]), "=f"(d[15]), "=f"(d[16]), "=f"(d[17]), "=f"(d[18]), "=f"(d[19]), "=f"(d[20]), "=f"(d[21]), "=f"(d[22]), "=f"(d[23]), "=f"(d[24]), "=f"(d[25]), "=f"(d[26]), "=f"(d[27]), "=f"(d[28]), "=f"(d[29]), "=f"(d[30]), "=f"(d[31])
        : "r"(a[0]), "r"(a[1]), "r"(a[2]), "r"(a[3]), "l"(db), "n"(TB));
}
template <int TB>
__device__ __forceinline__ void wgmma_rs16(float* d, const uint32_t* a, uint64_t db) {
    asm volatile("wgmma.mma_async.sync.aligned.m64n16k16.f32.bf16.bf16 "
        "{%0, %1, %2, %3, %4, %5, %6, %7}, {%8, %9, %10, %11}, %12, 1, 1, 1, %13;"
        : "+f"(d[0]), "+f"(d[1]), "+f"(d[2]), "+f"(d[3]), "+f"(d[4]), "+f"(d[5]), "+f"(d[6]), "+f"(d[7])
        : "r"(a[0]), "r"(a[1]), "r"(a[2]), "r"(a[3]), "l"(db), "n"(TB));
}
template <int TB>
__device__ __forceinline__ void wgmma_rs16_first(float* d, const uint32_t* a, uint64_t db) {
    asm volatile("wgmma.mma_async.sync.aligned.m64n16k16.f32.bf16.bf16 "
        "{%0, %1, %2, %3, %4, %5, %6, %7}, {%8, %9, %10, %11}, %12, 0, 1, 1, %13;"
        : "=f"(d[0]), "=f"(d[1]), "=f"(d[2]), "=f"(d[3]), "=f"(d[4]), "=f"(d[5]), "=f"(d[6]), "=f"(d[7])
        : "r"(a[0]), "r"(a[1]), "r"(a[2]), "r"(a[3]), "l"(db), "n"(TB));
}

__device__ __forceinline__ uint32_t delay_loop(int n, uint32_t x0) {
    uint32_t z;
    asm volatile("{\n.reg .pred P;\n.reg .u32 c, x;\nmov.u32 c, %1;\nmov.u32 x, %2;\nDL: mad.lo.u32 x, x, 1664525, 1013904223;\nadd.u32 c, c, -1;\nsetp.gt.s32 P, c, 0;\n@P bra DL;\n"
                 "setp.eq.u32 P, x, 0x7fffffff;\nselp.u32 %0, 16, 0, P;\n}" : "=r"(z) : "r"(n), "r"(x0) : "memory");
    return z;
}
__device__ __forceinline__ uint32_t gtime() { uint32_t t; asm volatile("mov.u32 %0, %%globaltimer_lo;" : "=r"(t)); return t; }
__device__ __forceinline__ void wait_time(uint32_t t, uint32_t sb) { while ((int32_t)(gtime() - t) < (int32_t)delay_loop(2, sb)) {} }
__device__ __forceinline__ uint32_t tpc_gpc(uint32_t t) { return t < 32 ? t & 7 : t < 60 ? (t - 32) % 7 + 1 : (t - 54) & 7; }
__device__ __forceinline__ uint32_t latest_stamp(const uint32_t* p, uint32_t seq, uint32_t ref, int backoff, uint32_t sb) {
    for (int n = 0;; n++) {
        uint32_t bad = 0; int32_t m = INT32_MIN;
#pragma unroll
        for (int i = 0; i < 3; i++) { const uint32_t v = ld_relaxed1(p + i * 256); bad |= (v ^ seq) & 31u; m = max(m, (int32_t)(v - (ref << 5)) >> 5); }
        if (__all_sync(0xffffffffu, bad == 0)) return ref + __reduce_max_sync(0xffffffffu, m);
        wait_time(gtime() + backoff, sb);
        if (n > SPIN_LIMIT) spin_fault();
    }
}
__device__ __forceinline__ void release_at(uint32_t t, uint32_t sb, uint32_t bar, int lane) {
    wait_time(t, sb);
    if (lane == 0) mbar_arrive(sb + bar);
}
__host__ __device__ constexpr int frag_word(int u, int f) { return (u == 0 ? 0 : u < 3 ? 3 * u - 1 : u == 3 ? 14 : 3 * u - 4) + f; }
__host__ __device__ constexpr int word_col(int e) { return ((0x32FED987CBA65410ull >> (4 * e)) & 14) * 64 + ((0x32FED987CBA65410ull >> (4 * e)) & 1) * 8; }

constexpr uint32_t CLEAR_LO = 0xFE000000u, CLEAR_HI = 0x5A7FEFEFu;
__device__ __forceinline__ void clear_slot(const Params& P, int slot, int cta, int lane) {
    const int i = cta * 2 + (lane >> 3), x = i & 63;
    if (lane < 16) st_relaxed4(P.gm + slot * M_SLOT + (x >> 1) * 1024 + (x & 1) * 256 + (i >> 7) * 512 + ((i >> 6) & 1) * 128 + (lane & 7) * 16, CLEAR_LO, CLEAR_HI, CLEAR_LO, CLEAR_HI);
    st_relaxed4(g_f + slot * F_SLOT + cta * 512 + lane * 16, 0, 0, 0, 0);
}
__device__ __forceinline__ void mem0_max(const Params& P, uint32_t sb, int tid) {
    uint32_t m = 0;
#pragma unroll
    for (int i = 0; i < 4; i++) {
        const uint4 x = __ldg((const uint4*)P.mem0 + i * 256 + tid);
        m = __vmaxu2(__vmaxu2(__vmaxu2(x.x & 0x7fff7fffu, x.y & 0x7fff7fffu), __vmaxu2(x.z & 0x7fff7fffu, x.w & 0x7fff7fffu)), m);
    }
    sts32(sb + S_COEF + (tid >> 5) * 4, __reduce_max_sync(0xffffffffu, max(m >> 16, m & 0xffffu)));
    bar_arrive(7, 288);
}
__device__ __forceinline__ uint32_t pack_mem0(const Params& P, uint32_t sb, int cta, int lane) {
    bar_sync(7, 288);
    const uint32_t e = __reduce_max_sync(0xffffffffu, lds32(sb + S_COEF + (lane & 7) * 4)) >> 7;
    if (e < 64 || e > 192) return 0x3F803F80u;
    const int i = cta * 2 + (lane >> 4), u = (i >> 5), x = i & 63, L = (i & 3) * 8 + ((lane & 15) >> 1);
    uint64_t w = 32;
#pragma unroll
    for (int f = 0; f < 3; f++) if (f < 2 || u % 3) {
        const float v = __bfloat162float(P.mem0[(L >> 2) * 1024 + word_col(frag_word(u, f)) + ((i >> 2) & 7) * 16 + (L & 3) * 2 + (lane & 1)]);
        w += (uint64_t)(int64_t)__float2int_rn(v * __uint_as_float((271 - e) << 23)) << (45 - 19 * f);
    }
    st_relaxed2(P.gm + 7 * M_SLOT + (x >> 1) * 1024 + (x & 1) * 256 + (i >> 7) * 512 + ((i >> 6) & 1) * 128 + (lane & 15) * 8, (uint32_t)w, (uint32_t)(w >> 32));
    return (e - 30) * 0x00800080u;
}
__device__ __forceinline__ void pacer(const Params& P, const uint32_t sb, const int lane) {
    constexpr uint32_t base = 2;
    int cta = lds32(sb + S_CTA);
#pragma unroll 1
    for (int i = 0; i < 8; i++) clear_slot(P, i, cta, lane);
    __syncwarp();
    if (lane == 0) { uint32_t smid; asm("mov.u32 %0, %%smid;" : "=r"(smid)); st_relaxed1(g_hint + 6144 + cta, smid >> 1); }
    sts32(sb + S_EPOCH + 4, pack_mem0(P, sb, cta, lane));
    fence_release();
    __syncwarp();
    float rate = 0.58f;
    uint32_t c0 = 0;
#pragma unroll 1
    for (int s = -1; s < 63; s++) {
        cta = lds32(sb + S_CTA);
        const int pair = cta >> 1;
        const uint32_t ahead = s > 0 ? (uint32_t)(rate * (float)(pair >= 32 ? P.dc - P.dv : P.dc)) : 0;
        mbar_wait(sb + B_GO, s & 1);
        SSTAMP(10, lane == 0 && s == 0)
        const uint32_t t0 = gtime();
        if (lane < 4) st_relaxed1(g_hint + ((s & 1) * 4 + lane) * 768 + (cta >> 5) * 256 + (cta & 31), (t0 + ahead + (lds32(sb + S_REDO) == s ? P.extra : 0)) << 5 | ((base + s) & 31u));
        wait_time(t0 + (s < 0 ? 2000 : s == 0 && pair >= 16 ? P.ds0 : P.ds), sb);
        const uint32_t t = latest_stamp(g_hint + ((s & 1) * 4 + (pair & 3)) * 768 + lane, base + s, t0, P.back, sb);
        if (s < 0) {
            fence_acquire();
            const uint32_t g = tpc_gpc(ld_relaxed1(g_hint + 6144 + (lane & 15) * 2));
            const uint32_t key = (__popc(__match_any_sync(0xffffffffu, g)) > 4 ? 0 : g + 1) * 16 + (lane & 15);
            const uint32_t tail = (pair & 48) + __popc(__ballot_sync(0xffffffffu, key < __shfl_sync(0xffffffffu, key, pair & 15))) / 2;
            mbar_wait(sb + B_INIT, 0);
            SSTAMP(4, lane == 0)
            sts32(sb + S_TAIL, tail);
            if (lane < 8) sts32(sb + S_SC + lane * 4, lds32(sb + S_EPOCH + 4));
            __syncwarp();
        }
        release_at(t + P.da, sb, B_RELA, lane);
        SSTAMP(11, lane == 0 && s == 0)
        release_at(t + P.db, sb, B_RELB, lane);
        {
            const uint32_t c1 = clock(), g1 = gtime();
            if (s > 1) rate += P.alpha * (__fdividef((float)(g1 - lds32(sb + S_EPOCH + 4)), (float)(c1 - c0)) - rate);
            __syncwarp();
            c0 = c1; sts32(sb + S_EPOCH + 4, g1);
        }
        if (s == 61) {
            sts32(sb + S_COEF, ITEM(ITEM_OFF(lds32(sb + S_TAIL)) + NPRE + 1) + (uint32_t)(uintptr_t)P.out);
            if (lane < M_CQ) map_prefetch(&P.tm[lane]);
        }
    }
}
__device__ __forceinline__ uint32_t xor_or(uint32_t a, uint32_t b, uint32_t t) { uint32_t d; asm("lop3.b32 %0, %1, %2, %3, 0x7E;" : "=r"(d) : "r"(a), "r"(b), "r"(t)); return d; }
__device__ __forceinline__ bool tags_ok(uint32_t bad) { return __all_sync(0xffffffffu, (bad & 1) == 0); }
#define RETRY(k)
#define RETRY_STAT(a, b)
#define UNIT_STAT(u0)
#define KE 0
#define ES 0
#define Q3 1
#define SFENCE() asm volatile("pmevent 1;" ::: "memory")
#define PF1 10
static_assert(NS == 24, "fragment residency");
__host__ __device__ constexpr bool in_smem(int n) { return n < 4 || n == 12 || n == 13; }
__host__ __device__ constexpr int unit_pos(int n) { return n < 4 ? n : n < 12 ? n - 4 : n < 14 ? n - 8 : n - 6; }

__host__ __device__ constexpr int fill_unit(int q) { return q < 4 ? q : q < 6 ? q + 8 : q < 14 ? q - 2 : q; }
__host__ __device__ constexpr int frag_off(int q) { return (q >> 2) * 16384 + ((q >> 1) & 1) * 8192 + (q & 1) * 512; }

constexpr uint32_t QBITS = 0x4B002000u;
constexpr uint64_t W_BIAS = ((uint64_t)QBITS << 45) + ((uint64_t)QBITS << 26) + (uint32_t)(QBITS << 7), W_CLEAR = 0 - 32 * W_BIAS;
static_assert(W_CLEAR == ((uint64_t)CLEAR_HI << 32 | CLEAR_LO), "clear value");
__host__ __device__ constexpr int unit_off(int u) { return (u & 1) * 16384 + (u >> 2) * 512 + ((u >> 1) & 1) * 128; }
__device__ __forceinline__ void red_add64(const uint8_t* p, uint64_t v) { asm volatile("red.relaxed.gpu.global.add.u64 [%0], %1;" ::"l"(p), "l"(v) : "memory"); }
template <int NF>
__device__ __forceinline__ uint64_t encode(const float* x, float S, uint32_t two26, uint32_t& bad) {
    uint32_t b[3];
#pragma unroll
    for (int i = 0; i < 3; i++) b[i] = i < NF ? __float_as_uint(fmaf(x[i], S, 8396800.f)) : QBITS;
    bad = xor_or(b[0], b[1], 0x4B000000u) | (NF == 3 ? b[2] ^ 0x4B000000u : 0);
    uint64_t w;
    asm("{\n.reg .b64 t;\nmov.b64 t, {%2, %3};\nmad.wide.u32 %0, %1, %4, t;\n}" : "=l"(w) : "r"(b[1]), "r"(b[2] << 7), "r"(b[0] << 13), "r"(two26));
    return w;
}
template <int NF>
__device__ __forceinline__ void emit(uint64_t* w, const float (*x)[3], const float* S, uint32_t two26, uint32_t lim, const uint8_t* p) {
    uint32_t bad[2];
    w[0] = encode<NF>(x[0], S[0], two26, bad[0]); w[1] = encode<NF>(x[1], S[1], two26, bad[1]);
    const bool ok = (bad[0] | bad[1]) < lim;
    w[0] |= ok; w[1] |= ok;
    red_add64(p, w[0]); red_add64(p + 1024, w[1]);
}
template <int NF>
__device__ __forceinline__ void repair(const uint64_t* w, const float (*x)[3], const float* S, const uint8_t* p, const uint8_t* pf) {
    if (!(w[0] & 1)) {
#pragma unroll
        for (int j = 0; j < 2; j++) {
            const float T = S[j] * 8192.f;
            asm volatile("red.relaxed.gpu.global.add.v4.f32 [%0], {%1,%2,%3,%4};" ::"l"(pf + j * 512), "f"(x[j][0] * T), "f"(x[j][1] * T), "f"(NF == 3 ? x[j][2] * T : 0.f), "f"(0.f) : "memory");
        }
        fence_release();
#pragma unroll
        for (int j = 0; j < 2; j++) {
            asm volatile("red.relaxed.gpu.global.or.b64 [%0], 64;" ::"l"(p + j * 1024) : "memory");
            red_add64(p + j * 1024, W_BIAS + 1 - w[j]);
        }
    }
    __syncwarp();
}
__device__ __forceinline__ void ld_words(uint32_t* v, const uint8_t* p) {
    asm volatile("{\n.reg .b64 a, b;\nld.relaxed.gpu.global.L1::no_allocate.v2.b64 {a, b}, [%4];\nmov.b64 {%0,%1}, a;\nmov.b64 {%2,%3}, b;\n}" : "=r"(v[0]), "=r"(v[1]), "=r"(v[2]), "=r"(v[3]) : "l"(p) : "memory");
}
__device__ __forceinline__ float field(const uint32_t* w, int f) { return __int2float_rn((int)(f == 0 ? w[1] : f == 1 ? __funnelshift_l(w[0], w[1], 19) : w[0] << 6)); }
template <int U>
__device__ __forceinline__ void decode(uint32_t* b, const uint32_t* v) {
#pragma unroll
    for (int f = 0; f < (U % 3 ? 3 : 2); f++) b[frag_word(U, f)] = pack2(field(v, f), field(v + 2, f));
}
__device__ __forceinline__ uint32_t status(const uint32_t (*v)[4], uint32_t c32) { return xor_or(v[0][0], v[0][2], c32) | xor_or(v[1][0], v[1][2], c32) | xor_or(v[2][0], v[2][2], c32); }
__device__ __forceinline__ void gather_slow(const Params& P, uint32_t* b, const uint8_t* pm, int s, int warp, uint32_t ln, uint32_t u2) {
    if (s == 0 && u2 == 0x3F803F80u) {
#pragma unroll
        for (int i = 0; i < 16; i++) b[i] = __ldg((const uint32_t*)(P.mem0 + (ln >> 2) * 1024 + word_col(i) + warp * 16 + (ln & 3) * 2));
        return;
    }
    uint32_t v[6][4], st;
    for (int n = 0;; n++) {
#pragma unroll
        for (int u = 0; u < 6; u++) ld_words(v[u], pm + unit_off(u));
        st = status(v, 32) | status(v + 3, 32);
        if (!__any_sync(0xffffffffu, st & 32)) break;
        __nanosleep(200);
        if (n > SPIN_LIMIT) spin_fault();
    }
    const bool side = __any_sync(0xffffffffu, st & 64);
    if (side) fence_acquire();
    const uint8_t* pf = g_f + ((s + 7) & 7) * F_SLOT + warp * 1024 + ln * 32;
#pragma unroll
    for (int u = 0; u < 6; u++) {
        float x[2][4] = {};
#pragma unroll
        for (int k = 0; k < 2; k++)
            asm volatile("{\n.reg .pred P;\nsetp.ne.u32 P, %5, 0;\n@P ld.relaxed.gpu.global.v4.f32 {%0,%1,%2,%3}, [%4];\n}"
                         : "+f"(x[k][0]), "+f"(x[k][1]), "+f"(x[k][2]), "+f"(x[k][3]) : "l"(pf + u * 8192 + k * 16), "r"((uint32_t)side) : "memory");
#pragma unroll
        for (int f = 0; f < (u % 3 ? 3 : 2); f++) b[frag_word(u, f)] = pack2(field(v[u], f) + x[0][f], field(v[u] + 2, f) + x[1][f]);
    }
}
__device__ __forceinline__ uint32_t max_abs2(uint32_t a, uint32_t b) { uint32_t d; asm("max.NaN.xorsign.abs.bf16x2 %0, %1, %2;" : "=r"(d) : "r"(a), "r"(b)); return d; }
__device__ __forceinline__ uint32_t max6(const uint32_t* b) {
    const uint32_t m = max_abs2(max_abs2(max_abs2(b[0], b[1]), max_abs2(b[2], b[3])), max_abs2(b[4], b[5]));
    return max(m & 0x7fff0000u, (m << 16) & 0x7fff0000u);
}

template <bool TR>
__device__ __forceinline__ void put_partials(uint32_t a, const float* x, const float* y) {
    if (TR) stsm4t(a, pack2(x[0], x[1]), pack2(x[2], x[3]), pack2(y[0], y[1]), pack2(y[2], y[3]));
    else stsm4(a, pack2(x[0], x[1]), pack2(x[2], x[3]), pack2(y[0], y[1]), pack2(y[2], y[3]));
}
__device__ __forceinline__ void reduce_load(uint32_t (*x)[4], uint32_t a) { ldsm4t(x[0], a); ldsm4t(x[1], a + 512); }
__device__ __forceinline__ uint32_t reduce8(const uint32_t (*x)[4], uint32_t l8, uint32_t u2) {
    uint32_t p[2];
#pragma unroll
    for (int i = 0; i < 2; i++) {
        float d[4] = {};
        mma16816(d, x[i][0], x[i][1], x[i][2], x[i][3], (l8 & 32) ? 0u : u2, (l8 & 32) ? u2 : 0u);
        p[i] = pack2((l8 & 8) ? d[2] : d[0], (l8 & 8) ? d[3] : d[1]);
    }
    return (l8 & 16) ? p[1] : p[0];
}
__device__ __forceinline__ void score_half(float (*a)[4], const uint32_t (*qa)[4], const uint32_t (*kf)[4]) {
#pragma unroll
    for (int w = 0; w < 2; w++) {
        mma16816(a[w], qa[w][0], qa[w][1], qa[w][2], qa[w][3], kf[w][0], kf[w][1]);
        mma16816(a[2 + w], qa[w][0], qa[w][1], qa[w][2], qa[w][3], kf[w][2], kf[w][3]);
    }
}
__device__ __forceinline__ void score_sum(float* S, const float (*a)[4]) {
    S[0] = (a[0][0] + a[1][0]) + (a[2][2] + a[3][2]);
    S[1] = (a[0][1] + a[1][1]) + (a[2][3] + a[3][3]);
}
__device__ __forceinline__ float quad_max(float m) {
    return fmaxf(fmaxf(m, __shfl_xor_sync(0xffffffffu, m, 1)), fmaxf(__shfl_xor_sync(0xffffffffu, m, 2), __shfl_xor_sync(0xffffffffu, m, 3)));
}

#define ISTAMP(i)
__device__ __forceinline__ float next_scale(uint32_t sb, int slot, int warp, uint32_t u2) {
    uint32_t x[2][4];
    lds128(x[0], sb + S_MX + slot * 32); lds128(x[1], sb + S_MX + slot * 32 + 16);
    const uint32_t mx = max(max(max(x[0][0], x[0][1]), max(x[0][2], x[0][3])), max(max(x[1][0], x[1][1]), max(x[1][2], x[1][3])));
    const float top = fminf(fmaxf(__uint_as_float(mx) * bf_hi(u2), 0x1p-40f), 0x1p40f) * (1.f / (12288.f * 8192.f));
    const uint32_t un = pack2(top, top);
    sts32(sb + S_SC + warp * 4, un);
    return rcp(bf_hi(un) * 8192.f);
}
#define NEARLY 1
#define U3POS 1
#define VPOS 1
#define ROT 0
#define BPOS 1
#define ONLINE 0
#define NBAR 1
#define ORD3 0
#define F2 0
#define LOOPB 1
#define TK 4
#define OBN 4
#define CH4 1
#define RPOS 1
#define AF 0
#define AFENCE(i) if ((AF >> (i)) & 1) SFENCE();
#define FPOS 99
#define PACE 1
#define PF2 12
__host__ __device__ constexpr int w2_t(int i) { return i < 16 ? i & 1 : 2; }
__host__ __device__ constexpr int w2_k(int i) { return i < 16 ? i >> 1 : i - 16; }
template <typename G>
__device__ __forceinline__ void load_weights(uint32_t (*wr)[4], const uint32_t sb, const int warp, const int lane, G stores_read) {
    const uint32_t frag = sb + warp * 1024 + (lane >> 4) * 8192 + (lane & 7) * 128 + ((((lane >> 3) & 1) ^ (lane & 7)) << 4);
    const uint32_t rel = mapa(sb + B_EMPTY, cluster_rank() ^ (lane & 1));
#define RELEASE(st) { if ((st) >= 2) fence_async_smem(); __syncwarp(); if (lane < 2) mbar_arrive_cluster(rel + (st) * 8); }
    mbar_wait(sb + B_FULL, 0); mbar_wait(sb + B_FULL + 8, 0);
    RELEASE(0) RELEASE(1)
#pragma unroll
    for (int st = 2; st < 4; st++) {
        mbar_wait(sb + B_FULL + st * 8, 0);
        ISTAMP(st - 2)
#pragma unroll
        for (int f = 0; f < 12; f++) ldsm4t(wr[st * 12 - 24 + f], (frag ^ ((f & 3) << 5)) + st * STAGE + (f >> 2) * 16384);
        RELEASE(st)
    }
#pragma unroll 2
    for (int u = 0; u < 6; u++) {
        uint32_t x[4][4];
#pragma unroll
        for (int i = 0; i < 4; i++) lds128(x[i], (frag ^ (i << 5)) + u * 16384);
        __syncwarp();
#pragma unroll
        for (int i = 0; i < 4; i++) sts128(sb + warp * 1024 + lane * 16 + u * 16384 + frag_off(i), x[i]);
    }
    SSTAMP(0, threadIdx.x == 0)
    stores_read();
    SSTAMP(2, threadIdx.x == 0)
    mbar_wait(sb + B_FULL, 1); mbar_wait(sb + B_FULL + 8, 1);
    RELEASE(0) RELEASE(1)
#pragma unroll
    for (int st = 2; st < 4; st++) {
        mbar_wait(sb + B_FULL + st * 8, 1);
#pragma unroll
        for (int f = 0; f < (st == 2 ? 12 : 4); f++) ldsm4t(wr[st * 12 + f], (frag ^ ((f & 3) << 5)) + st * STAGE + (f >> 2) * 16384);
        RELEASE(st)
    }
    ISTAMP(2)
    bar_sync(1, 256);
    if (warp == 7 && lane < 3) mbar_arrive_cluster(mapa(sb + B_INIT, (cluster_rank() & 1) + lane * 2));
}
template <int ROLE>
__device__ __forceinline__ void chain_role(const Params& P, const uint32_t (*wr)[4], const uint32_t sb, const int h, const int warp, const int lane) {
    constexpr int NU = ROLE == 0 ? 2 : 3;
    const bool att = ROLE == 0 && warp < 4;
    uint32_t l8 = opq(sb + lane * 8, lane);
#define PERSIST() { mbar_wait(sb + B_KVGO, slot ^ 1); const uint32_t pa_ = ((l8 - sb) >> 1) + (sb + S_QX + warp * 128); sts32(pa_, r0); sts32(pa_ + 1024, r1); \
                    fence_async_smem(); __syncwarp(); if (l8 == sb) mbar_arrive(sb + B_PERS); }
    if (ROLE) sts32(sb + S_SX + warp * 128 + lane * 4, warp >= 2 ? 0 : (lane & 1) ? CLEAR_HI : CLEAR_LO);
    const uint32_t rdelta = __shfl_sync(0xffffffffu, mapa(sb, (cluster_rank() + (ROLE == 1 ? 4 : 2)) % 6) - sb, 0);
    const uint32_t vdelta = ROLE ? 0 : __shfl_sync(0xffffffffu, mapa(sb, (cluster_rank() + 4) % 6) - sb, 0);
    ISTAMP(3)
    __syncwarp();
#define GATHER_OFF(s) ((((s) + 7) & 7) * M_SLOT + warp * 2048 + (l8 & 56) * 2 + (l8 & 64) * 4 + (l8 & 128) * 8)
    uint32_t mo = GATHER_OFF(0);
    sts32(sb + S_SC + 32 + warp * 4, 0);
    if (ROT) mbar_wait(sb + B_RELA, 0);
    for (int s = 0; s < (ROLE == 0 ? 63 : 64);) {
        const int slot = s & 1;
        l8 += s & P.zero;
        const uint32_t w1a = l8 * 2 + (S_W1 + warp * 1024 - sb);
        PROF(9)
        uint32_t u2, r0, r1, pld, pub, pbar, x[2][4];
        {
#define pm (P.gm + mo)
            uint32_t as[24][4], b[16], v[6][4];
            float acc[8][4];
#define W1LD(n) _Pragma("unroll") for (int i_ = 0; i_ < 4; i_++) ldsm4t(as[unit_pos(n) * 4 + i_], w1a + frag_off(unit_pos(n) * 4 + i_));
#define W1LD2(n, p) { const uint32_t wa_ = w1a + (as[unit_pos(p) * 4][0] & as[unit_pos(p) * 4 + 1][0] & as[unit_pos(p) * 4 + 2][0] & as[unit_pos(p) * 4 + 3][0] & P.zero); \
                      _Pragma("unroll") for (int i_ = 0; i_ < 4; i_++) ldsm4t(as[unit_pos(n) * 4 + i_], wa_ + frag_off(unit_pos(n) * 4 + i_)); }
#define W1MMA(n) _Pragma("unroll") for (int i_ = 0; i_ < 4; i_++) { const uint32_t* a_ = in_smem(n) ? as[unit_pos(n) * 4 + i_] : wr[unit_pos(n) * 4 + i_]; \
                                                                   mma16816(acc[((n) & 1) * 4 + i_], a_[0], a_[1], a_[2], a_[3], b[(n) & 14], b[(n) | 1]); }
#pragma unroll
            for (int T = 0; T < 8; T++) { acc[T][0] = acc[T][1] = acc[T][2] = acc[T][3] = 0.f; }
            if (!ROT) mbar_wait(sb + B_RELA, slot);
            PROF(12)
#pragma unroll
            for (int u = 0; u < 3; u++) ld_words(v[u], pm + unit_off(u));
            __syncwarp();
#pragma unroll
            for (int i = 0; i < PF1; i++) ldsm4t(as[i], w1a + frag_off(i));
            __syncwarp();
            mo += mbar_try(sb + B_RELB, slot) & P.zero;
            PROF(13)
#pragma unroll
            for (int u = 3; u < 6; u++) ld_words(v[u], pm + unit_off(u));
            uint32_t st = status(v, ((uint32_t)((uintptr_t)pm >> 32) & P.zero) + 32);
            pin<1>(&st);
            SFENCE();
            UNIT_STAT(0)
            PROF(0)
            decode<0>(b, v[0]); decode<1>(b, v[1]); decode<2>(b, v[2]);
#pragma unroll
            for (int i = PF1; i < 12; i++) ldsm4t(as[i], w1a + frag_off(i));
            W1MMA(0) W1MMA(1) W1MMA(2)
            if (TK & 1) W1LD2(3, 2) else { W1LD(3) }
            SFENCE();
            if (TK & 8) { W1MMA(5) W1MMA(4) W1MMA(3) W1MMA(6) } else { W1MMA(5) W1MMA(4) W1MMA(6) W1MMA(3) }
            if (U3POS == 0) W1MMA(7)
            if (TK & 2) W1LD2(12, 3) else { W1LD(12) }
            uint32_t mx = max6(b);
            pin<1>(&mx);
            SFENCE();
            PROF(10)
            if (U3POS == 1) W1MMA(7)
            const uint32_t mxa = sb + S_MX + slot * 32 + warp * 4;
            sts32(mxa, __reduce_max_sync(0xffffffffu, mx));
            UNIT_STAT(3)
            st |= status(v + 3, 32);
            const bool redo = __any_sync(0xffffffffu, st & 96);
            const bool kvok = ROLE || mbar_test(sb + B_KVFULL + slot * 8, (s >> 1) & 1);
            decode<4>(b, v[4]); decode<5>(b, v[5]); decode<3>(b, v[3]);
            u2 = lds32(sb + S_SC + warp * 4);
            W1MMA(8) W1MMA(10) if (ORD3) { W1MMA(14) W1MMA(12) } else { W1MMA(12) W1MMA(14) }
            if (TK & 4) W1LD2(13, 12) else { W1LD(13) }
            if (__builtin_expect(redo || !kvok, 0)) {
                if (redo) {
                    if (LOOPB && lds32(sb + S_SC + 32 + warp * 4) != s) {
                        RETRY(4)
                        __syncwarp();
                        sts32(sb + S_SC + 32 + warp * 4, s);
                        if (LOOPB == 2) sts32(sb + S_REDO, s);
                        mo = GATHER_OFF(s);
                        continue;
                    }
                    RETRY(3)
                    sts32(sb + S_REDO, s);
                    gather_slow(P, b, P.gm + GATHER_OFF(s), s, warp, (l8 - sb) >> 3, u2);
                    sts32(mxa, __reduce_max_sync(0xffffffffu, max6(b)));
#pragma unroll
                    for (int T = 0; T < 8; T++) { acc[T][0] = acc[T][1] = acc[T][2] = acc[T][3] = 0.f; }
#pragma unroll
                    for (int n = 0; n < 15; n += n < 8 ? 1 : 2) {
                        if (in_smem(n)) { W1LD(n) }
                        W1MMA(n)
                    }
                    W1LD(13)
                }
                if (ROLE == 0) mbar_wait(sb + B_KVFULL + slot * 8, (s >> 1) & 1);
            }
#undef pm
            SSTAMP(7, threadIdx.x == 0 && s == 0)
            PROF(14)
            const uint32_t pst = (l8 - sb) * 16 + ((warp * 16) ^ ((l8 * 2) & 112)) + (sb + S_P1);
            put_partials<ROLE == 2>(pst, acc[0], acc[1]); put_partials<ROLE == 2>(pst + 4096, acc[2], acc[3]);
            W1MMA(9)
            SFENCE();
            pld = (l8 & 64) * 4 + (l8 & 128) + (l8 & 56) * 2 + (sb + S_P1 + warp * 1024);
            const uint32_t rd = s == 63 ? 0 : rdelta;
            pub = ((l8 - sb) >> 1) + (ROLE ? sb + rd + (ROLE == 1 ? S_KL : S_VL) + warp * 128 : sb + S_QX + (warp & 4) * 128 + (warp & 1) * 256 + (warp & 2) * 64);
            pbar = sb + rd + (ROLE == 1 && s != 63 ? B_K : B_V);
#define PUBLISH0() { r0 = reduce8(x, l8, u2); if (ROLE) st_async1(pub, r0, KE && ROLE == 1 && s != 63 ? pbar + (B_PERS - B_K) : pbar); else sts32(pub, r0); }
            if (RPOS == 0) { bar_sync(1, 256); reduce_load(x, pld); SFENCE(); }
            W1MMA(11)
            if (RPOS == 1) { bar_sync(1, 256); reduce_load(x, pld); }
            if (RPOS != 2 || F2) SFENCE();
#define W1MMH(n, o) _Pragma("unroll") for (int i_ = o; i_ < o + 2; i_++) { const uint32_t* a_ = in_smem(n) ? as[unit_pos(n) * 4 + i_] : wr[unit_pos(n) * 4 + i_]; \
                                                                   mma16816(acc[((n) & 1) * 4 + i_], a_[0], a_[1], a_[2], a_[3], b[(n) & 14], b[(n) | 1]); }
            if (ES) { W1MMH(15, 0) W1MMH(15, 2) W1MMH(13, 0) } else W1MMA(15)
            if (RPOS == 0) PUBLISH0()
            if (RPOS == 2) { bar_sync(1, 256); reduce_load(x, pld); }
            if (RPOS != 1 || F2) SFENCE();
            if (ES) { W1MMH(13, 2) put_partials<ROLE == 2>(pst + 8192, acc[4], acc[5]); } else W1MMA(13)
            if (RPOS == 1) PUBLISH0()
            if (!ES) put_partials<ROLE == 2>(pst + 8192, acc[4], acc[5]);
            put_partials<ROLE == 2>(pst + 12288, acc[6], acc[7]);
            if (RPOS == 2) PUBLISH0()
        }
        SSTAMP(8, threadIdx.x == 0 && s == 0)
        PROF(1)
        if (ROLE) {
            bar_sync(1, 256);
            reduce_load(x, pld + 8192);
            r1 = reduce8(x, l8, u2);
            st_async1(pub + 1024, r1, pbar);
            if (s == 63) {
                PERSIST()
                mbar_wait(sb + B_V, 0);
                break;
            }
            PROF(2)
        }
        uint32_t ln, w2a, ro;
#define W2ADDR(late) { l8 += pub & P.zero; ln = (l8 - sb) >> 3; \
        w2a = sb + S_W2 + (ROLE ? (warp >> 2) * 16384 : late * 32768) + ((((ln & 7) + (ln >> 4) * 8) * 128 + ((((ln >> 3) & 1) ^ (ln & 7)) << 4)) ^ ((warp & 3) << 5)); \
        ro = (s & 7) * M_SLOT + (ROLE ? warp * 2048 + unit_off(ROLE) : (warp & 3) * 2048 + late * unit_off(3)) + (ln & 2) * 128 + (ln & 1) * 64 + (ln >> 2) * 8; }
        constexpr int RO2 = ROLE ? unit_off(ROLE + 3) - unit_off(ROLE) : 8192;
        float Sj[2];
        uint32_t w[24][4], ob[4][4];
        float S;
#define W2LD(i) ldsm4t(w[i], w2a + w2_t(i) * (ROLE ? 32768 : 16384) + (w2_k(i) & 1) * 8192 + (w2_k(i) >> 1) * 2048)
#define W2MMA(d, i) mma16816(d, w[i][0], w[i][1], w[i][2], w[i][3], ob[w2_k(i) >> 1][(w2_k(i) & 1) * 2], ob[w2_k(i) >> 1][(w2_k(i) & 1) * 2 + 1])
#define LEADER(wp) (l8 == sb + ((wp) - warp) * 256)
        if (att) {
            const float cs = 0.08838834764831845f * 1.4426950408889634f;
            uint32_t qa[4][4], kf[4][4], vf[4][4], vv[4];
            float T[5][2], sa[4][4] = {};
            const uint32_t l16 = l8 * 2 - sb;
            const uint32_t kaddr = (l8 & 56) * 16 + (((l8 >> 2) ^ (l8 * 2)) & 48) + ((l8 * 2) & 64) + (sb + S_KV + warp * 1024 + slot * 16384);
            bar_sync(1, 256);
            reduce_load(x, pld + 8192);
            __syncwarp();
#pragma unroll
            for (int i = 0; i < 2; i++) { ldsm4(qa[i], l16 + S_QX + i * 512); ldsm4(kf[i], kaddr ^ (i * 64)); }
            AFENCE(0)
            sts32(pub + 1024, reduce8(x, l8, u2));
            __syncwarp();
#pragma unroll
            for (int i = 2; i < 4; i++) ldsm4(kf[i], (kaddr ^ ((i & 1) * 64)) + 4096);
            score_half(sa, qa, kf);
            bar_sync(2, 256);
            PROF(2)
#pragma unroll
            for (int i = 2; i < 4; i++) ldsm4(qa[i], l16 + S_QX + i * 512);
            float sm[4][4] = {};
            const bool kearly = KE && mbar_try(sb + B_PERS, slot);
            score_half(sa, qa + 2, kf + 2);
            score_sum(T[0], sa);
            sts64(l8 + S_SX + warp * 256, __float_as_uint(T[0][0]), __float_as_uint(T[0][1]));
            PROF(4)
            if (KE) {
                if (!kearly) mbar_wait(sb + B_PERS, slot);
                ldsm4(kf[0], l16 + S_KL); ldsm4(kf[1], l16 + S_KL + 512);
                score_half(sm, qa, kf);
            }
            if (BPOS == 0) bar_sync(4, 128);
            mbar_wait(sb + B_K, slot);
            PROF(11)
#pragma unroll
            for (int i = KE ? 2 : 0; i < 4; i++) ldsm4(kf[i], l16 + S_KL + i * 512);
            if (BPOS == 1) bar_sync(4, 128); else __syncwarp();
#pragma unroll
            for (int n = 0; n < 4; n++) lds64f(T[n], l8 + S_SX + n * 256);
            if (!KE) score_half(sm, qa, kf);
            score_half(sm, qa + 2, kf + 2);
            const uint32_t vaddr = (l8 & 56) * 16 + (l8 & 128) * 8 + (((warp & 1) * 64 + ((l8 >> 2) & 16)) ^ ((l8 * 2) & 112)) + (sb + S_KV + 8192 + (warp >> 1) * 4096 + slot * 16384);
            float mx = fmaxf(fmaxf(fmaxf(T[0][0], T[0][1]), fmaxf(T[1][0], T[1][1])), fmaxf(fmaxf(T[2][0], T[2][1]), fmaxf(T[3][0], T[3][1])));
            score_sum(T[4], sm);
            float m = quad_max(fmaxf(mx, fmaxf(T[4][0], T[4][1])));
            if (VPOS == 0) {
#pragma unroll
                for (int i = 0; i < 4; i++) ldsm4t(vf[i], (vaddr ^ ((i & 1) << 5)) + (i >> 1) * 2048);
            }
            mbar_wait(sb + B_V, slot);
            if (VPOS == 1) {
#pragma unroll
                for (int i = 0; i < 4; i++) ldsm4t(vf[i], (vaddr ^ ((i & 1) << 5)) + (i >> 1) * 2048);
            }
            ldsm4(vv, l16 + S_VL + warp * 512);
            uint32_t pa[5];
#pragma unroll
            for (int n = 0; n < 5; n++) { T[n][0] = ex2((T[n][0] - m) * cs); T[n][1] = ex2((T[n][1] - m) * cs); pa[n] = pack2(T[n][0], T[n][1]); }
            float sum = (((T[0][0] + T[0][1]) + (T[1][0] + T[1][1])) + ((T[2][0] + T[2][1]) + (T[3][0] + T[3][1]))) + (T[4][0] + T[4][1]);
            PROF(3)
            W2ADDR(1)
            const uint32_t lo = sb + S_O + warp * 512 + (ln & 3) * 64 + (ln >> 2) * 8, ls = sb + S_SUM + (ln & 3) * 32 + (ln & 4) * 4 + (ln >> 3) * 4;
            const uint32_t sdelta = warp < 2 ? rdelta : vdelta;
            if (Q3 & 2) sum = (sum + __shfl_xor_sync(0xffffffffu, sum, 1)) + (__shfl_xor_sync(0xffffffffu, sum, 2) + __shfl_xor_sync(0xffffffffu, sum, 3));
            else { sum += __shfl_xor_sync(0xffffffffu, sum, 1); sum += __shfl_xor_sync(0xffffffffu, sum, 2); }
            float O[2][4];
#pragma unroll
            for (int i = 0; i < 2; i++) { O[i][0] = O[i][1] = O[i][2] = O[i][3] = 0.f; }
#pragma unroll
            for (int i = 0; i < 2; i++) {
                mma16816(O[0], vf[2 * i][0], vf[2 * i][1], vf[2 * i][2], vf[2 * i][3], pa[2 * i], pa[2 * i + 1]);
                mma16816(O[1], vf[2 * i + 1][0], vf[2 * i + 1][1], vf[2 * i + 1][2], vf[2 * i + 1][3], pa[2 * i], pa[2 * i + 1]);
            }
            mma1688(O[0], vv[0], vv[1], pa[4]);
            mma1688(O[1], vv[2], vv[3], pa[4]);
            uint32_t o[2][2];
#pragma unroll
            for (int j = 0; j < 2; j++) { o[j][0] = pack2(O[0][j], O[0][2 + j]); o[j][1] = pack2(O[1][j], O[1][2 + j]); }
#pragma unroll
            for (int j = 0; j < 2; j++) st_async2(lo + rdelta + j * 256, o[j][0], o[j][1], sb + rdelta + B_K);
            st_async1(ls + sdelta + (warp & 1) * 128, __float_as_uint(sum), sb + sdelta + B_K);
#pragma unroll
            for (int j = 0; j < 2; j++) st_async2(lo + vdelta + j * 256, o[j][0], o[j][1], sb + vdelta + B_K);
#pragma unroll
            for (int j = 0; j < 2; j++) sts64(lo + j * 256, o[j][0], o[j][1]);
            sts32(ls + warp * 128, __float_as_uint(sum));
            PROF(5)
            bar_sync(3, 256);
            if (LEADER(0)) { mbar_expect(sb + B_K, KE ? 1024 : 2048); if (KE) mbar_expect(sb + B_PERS, 1024); mbar_expect(sb + B_V, 2048); mbar_arrive(sb + B_KVGO + slot * 8); }
            S = next_scale(sb, slot, warp, u2);
            if (s == 0) mbar_wait(sb + B_WO, 0);
            pin<1>(&S);
            SFENCE();
#pragma unroll
            for (int j = 0; j < 4; j++) lds128(ob[j], l8 * 2 - sb + S_O + j * 512);
            lds64f(Sj, sb + S_SUM + (l8 & 24));
#pragma unroll
            for (int i = 0; i < PF2; i++) W2LD(i);
        } else {
            if (ROLE == 0) { bar_sync(1, 256); reduce_load(x, pld + 8192); sts32(pub + 1024, reduce8(x, l8, u2)); bar_arrive(2, 256); }
            if (LEADER(7)) { if (s) mbar_arrive(sb + B_GO); if (ROLE) mbar_expect(sb + B_K, 2304); }
            S = next_scale(sb, slot, warp, u2);
            if (s == 0) mbar_wait(sb + B_WO, 0);
            if (ROLE != 0) PERSIST()
            W2ADDR(0)
#pragma unroll
            for (int i = 0; i < PF2; i++) {
                W2LD(i);
                if (ROLE == 0 && (i & PACE) == PACE) w2a += w[i][0] & P.zero;
            }
            ro = opq(ro, ln);
            const uint32_t sa = opq(sb + S_SUM + (l8 & 24), ln), oa = opq(l8 * 2 - sb + S_O, ln);
            if (ROLE == 0) bar_sync(3, 256); else mbar_wait(sb + B_K, slot);
            if (OBN == 4 || !ROLE) lds64f(Sj, sa);
#pragma unroll
            for (int j = 0; j < 4; j++) { if (ROLE && j == OBN) SFENCE(); lds128(ob[j], oa + j * 512); }
            if (OBN < 4 && ROLE) lds64f(Sj, sa);
        }
        SSTAMP(9, threadIdx.x == 224 && s == 0)
        if (OBN == 4 || !ROLE) SFENCE();
        PROF(6)
        {
            const uint8_t* pr = P.gm + ro;
            float c[4][4];
            uint32_t lim = 0;
#pragma unroll
            for (int i = 0; i < 4; i++) { c[i][0] = c[i][1] = c[i][2] = c[i][3] = 0.f; }
#pragma unroll
            for (int i = 0; i < 16; i++) {
                W2MMA(c[i & (ROLE && !CH4 ? 1 : 3)], i);
                if (i + PF2 < (ROLE ? 16 + NEARLY : 16)) W2LD(i + PF2);
                if (i == 5) {
                    const uint32_t z = __float_as_uint(c[1][0]) & P.zero;
                    Sj[0] = S * rcp(__uint_as_float(__float_as_uint(Sj[0]) | z)); Sj[1] = S * rcp(__uint_as_float(__float_as_uint(Sj[1]) | z));
                }
                if (i == 5) lim = __any_sync(0xffffffffu, fmaxf(fmaxf(fabsf(c[0][0]), fabsf(c[0][2])), fmaxf(fabsf(c[1][0]), fabsf(c[1][2]))) * Sj[0] >= (ROLE && !CH4 ? 24.f : 20.f)) ? 16384 : 0;
                if (i == FPOS) { pin<1>(&lim); pin<2>(Sj); pin_ptr(pr); SFENCE(); }
            }
            if (ROLE == 0 || CH4) {
#pragma unroll
                for (int i = 0; i < 8; i++) { c[i >> 2][i & 3] += c[2 + (i >> 2)][i & 3]; c[2 + (i >> 2)][i & 3] = 0.f; }
            }
            const float xa[2][3] = {{c[0][0], c[0][2], c[1][0]}, {c[0][1], c[0][3], c[1][1]}};
            uint64_t wa[2], wb[2];
            emit<NU>(wa, xa, Sj, P.two26, lim, pr);
            PROF(7)
            mo = GATHER_OFF(s + 1);
            pin<1>(&mo);
            if (ROLE) {
                SFENCE();
#pragma unroll
                for (int i = 16 + NEARLY; i < 24; i++) { if (i == 16 + NBAR) bar_sync(2, 256); W2LD(i); __syncwarp(); }
                SFENCE();
#pragma unroll
                for (int i = 16; i < 24; i++) W2MMA(c[2 + (i & 1)], i);
#pragma unroll
                for (int i = 0; i < 4; i++) c[2][i] += c[3][i];
            }
            const float y[2][3] = {{ROLE ? c[1][2] : c[1][0], ROLE ? c[2][0] : c[1][2], c[2][2]}, {ROLE ? c[1][3] : c[1][1], ROLE ? c[2][1] : c[1][3], c[2][3]}};
            const bool released = !ROT || mbar_test(sb + B_RELA, slot ^ 1);
            emit<NU>(wb, y, Sj, P.two26, lim, pr + RO2);
            PROF(8)
            if (!__all_sync(0xffffffffu, (wa[0] & wb[0] & 1) && released && s)) {
                if (__builtin_expect(!__all_sync(0xffffffffu, wa[0] & wb[0] & 1), 0)) {
                    RETRY(5)
                    const uint8_t* pf = g_f + (s & 7) * F_SLOT + (ROLE ? ROLE * 8192 + warp * 1024 : (warp & 3) * 1024 + (att ? 24576 : 0)) + (ln & 3) * 128 + (ln >> 2) * 16;
                    repair<NU>(wa, xa, Sj, pr, pf);
                    repair<NU>(wb, y, Sj, pr + RO2, pf + (ROLE ? 24576 : 4096));
                }
                if (s == 0) { bar_sync(1, 256); if (LEADER(7)) mbar_arrive(sb + B_GO); }
                if (ROT) mbar_wait(sb + B_RELA, slot ^ 1);
            }
        }
        s++;
    }
}
struct Pipe { uint32_t stage, phase; };
struct Cons {
    uint32_t sb, rel;
    int wg, wq, lane, rank, pair;
    uint32_t nst;
    Pipe p;
};
__device__ __forceinline__ void pipe_next(Pipe& p) { p.stage = (p.stage + 1) & (NSTAGE - 1); p.phase ^= (p.stage == 0); }
__device__ __forceinline__ void release(const Cons& c, uint32_t stage) { if (c.lane < 2) mbar_arrive_cluster(c.rel + stage * 8); }

enum { PEND_NONE = 0, PEND_KVO = 1, PEND_HT = 2, PEND_OUT = 3, PEND_OUTH = 4 };
struct Pend { uint32_t pk[64]; int kind, row, col, cnt; };

__device__ __forceinline__ void staging_wait(const Cons& c) { if (c.nst) mbar_wait(c.sb + B_SFREE + c.wg * 8, (c.nst - 1) & 1); }
__device__ __forceinline__ void staging_post(Cons& c, int kind, int row, int col, int cnt) {
    __syncwarp();
    if (c.lane == 0) {
        if (c.wq == 0) { const uint32_t x[4] = {(uint32_t)kind, (uint32_t)row, (uint32_t)col, (uint32_t)cnt}; sts128(c.sb + S_DESC + c.wg * 16, x); }
        mbar_arrive(c.sb + B_SFULL + c.wg * 8);
    }
    c.nst++;
}
template <int HF, bool KVONLY = false>
__device__ __forceinline__ void drain(const Params& P, Cons& c, const Pend& d) {
    const uint32_t* pk = d.pk + HF * 32;
    if (!KVONLY && d.kind >= PEND_OUT) {
        if (HF == 1 && d.kind == PEND_OUTH) return;
        float* o = P.out + (size_t)(d.row + c.wq * 16 + (c.lane >> 2)) * 2048 + d.col + HF * 128 + (c.lane & 3) * 2;
#pragma unroll
        for (int j = 0; j < 16; j++) {
            st_stream2(o + j * 8, bf_lo(pk[j * 2]), bf_hi(pk[j * 2]));
            st_stream2(o + 8 * 2048 + j * 8, bf_lo(pk[j * 2 + 1]), bf_hi(pk[j * 2 + 1]));
        }
    } else if (d.kind != PEND_NONE) {
        const bool ht = !KVONLY && d.kind == PEND_HT;
        const int hi = (c.lane >> 3) & 1;
        const uint32_t base = c.sb + S_STG + c.wg * 16384 + ((ht ? hi * 32 + c.wq * 8 : c.wq * 16 + hi * 8) + (c.lane & 7)) * 128;
        staging_wait(c);
#pragma unroll
        for (int j = 0; j < 8; j++) {
            const int ch = (j & 3) * 2 + (c.lane >> 4);
            stsm4(base + (j >> 2) * 8192 + ((ch ^ (c.lane & 7)) << 4), pk[j * 4], pk[j * 4 + 1], pk[j * 4 + 2], pk[j * 4 + 3]);
        }
        fence_async_smem();
        staging_post(c, d.kind, d.row, d.col + HF * 128, HF ? d.cnt : -1);
    }
}
__device__ __forceinline__ void drain_all(const Params& P, Cons& c, Pend& d) { drain<0>(P, c, d); drain<1>(P, c, d); d.kind = PEND_NONE; }

__device__ __forceinline__ void store_warp(const Params& P, uint32_t sb, int wg) {
    const uint32_t stg = sb + S_STG + wg * 16384;
#pragma unroll 1
    for (uint32_t n = 0;; n++) {
        mbar_wait(sb + B_SFULL + wg * 8, n & 1);
        uint32_t x[4];
        lds128(x, sb + S_DESC + wg * 16);
        if (x[0] == PEND_NONE) break;
        const bool ht = x[0] == PEND_HT;
        const CUtensorMap* m = &P.tm[ht ? M_HTS : M_KVO];
#pragma unroll 1
        for (int i = 0; i < 4; i++) if (!(DBGF(128) && gridDim.x != 96)) tma_store2d(m, x[2] + (i >> 1) * 64, x[1] + (i & 1) * (ht ? 1024 : 32), stg + i * 4096, ht ? EVICT_NORMAL : x[1] < 4096 ? POL(4) : POL(5));
        bulk_commit();
        bulk_wait_read();
        mbar_arrive(sb + B_SFREE + wg * 8);
        if ((int)x[3] >= 0) {
            bulk_wait_all(); fence_async();
            asm volatile("red.relaxed.gpu.global.add.u32 [%0], 1;" ::"l"(&g_cnt(x[3])) : "memory");
        }
    }
}

template <int N, int TA, int TB, bool FIRST>
__device__ __forceinline__ void issue_ktile(float* acc, const Cons& c) {
    mbar_wait(c.sb + B_FULL + c.p.stage * 8, c.p.phase);
    const uint32_t a = c.sb + c.p.stage * STAGE + c.wg * 8192, b = c.sb + c.p.stage * STAGE + 16384;
    const uint64_t da = mkdesc(a, TA ? 8192 : 16, 1024, 1), db = mkdesc(b, TB ? 8192 : 16, 1024, 1);
    wg_fence();
#pragma unroll
    for (int k = 0; k < 4; k++) {
        const uint64_t x = da + (TA ? 128 : 2) * k, y = db + (TB ? 128 : 2) * k;
        if (N == 256) { if (FIRST && k == 0) wgmma_ss256_first<TA, TB>(acc, x, y); else wgmma_ss256<TA, TB>(acc, x, y); }
        else { if (FIRST && k == 0) wgmma_ss128_first<TA, TB>(acc, x, y); else wgmma_ss128<TA, TB>(acc, x, y); }
    }
    wg_commit();
}
template <int N, bool FIRST>
__device__ __forceinline__ void issue_any(float* acc, const Cons& c, int type) {
    if (N == 256 && type == T_A1) issue_ktile<N, 0, 0, FIRST>(acc, c);
    else if (type == (N == 256 ? T_A2 : T_A2H)) issue_ktile<N, 1, 0, FIRST>(acc, c);
    else issue_ktile<N, 0, 1, FIRST>(acc, c);
}
template <int N, bool KVONLY = false>
__device__ __forceinline__ void mainloop(float* acc, const Params& P, Cons& c, Pend& d, int type) {
    const int nk = (type == T_OP || type == T_OPH) ? 64 : (type == T_A2 || type == T_A2H) ? 32 : 16;
    issue_any<N, true>(acc, c, type);
    drain<0, KVONLY>(P, c, d);
    uint32_t prev = c.p.stage;
    pipe_next(c.p);
    const int hold = c.wg ? nk - (int)((P.lag >> (4 * type)) & 7) : -1;
    for (int kt = 1; kt < nk; kt++) {
        if (kt == hold) bar_sync(8, 256);
        issue_any<N, false>(acc, c, type);
        wg_wait<1>();
        release(c, prev);
        if (kt == 2) drain<1, KVONLY>(P, c, d);
        prev = c.p.stage;
        pipe_next(c.p);
    }
    if (c.wg == 0 && ((P.lag >> (4 * type)) & 7)) bar_arrive(8, 256);
    d.kind = PEND_NONE;
    wg_wait<0>();
    pin<N / 2>(acc);
    release(c, prev);
}
__device__ __forceinline__ void pack_half(uint32_t* pk, const float* a) {
#pragma unroll
    for (int i = 0; i < 32; i++) pk[i] = pack2(a[2 * i], a[2 * i + 1]);
}

__device__ __forceinline__ void epi_kv(const float* acc, const Cons& c, Pend& d, int mb, int nb) {
    pack_half(d.pk, acc); pack_half(d.pk + 32, acc + 64);
    d.kind = PEND_KVO; d.row = (nb >> 4) * 2048 + mb * 256 + c.rank * 128 + c.wg * 64; d.col = (nb & 15) * 256; d.cnt = C_KV + mb;
}

__device__ __forceinline__ void qa_scores(float* S, float* Sm, uint32_t* q, const Cons& c, const Pipe& p) {
    mbar_wait(c.sb + B_FULL + p.stage * 8, p.phase);
    const uint32_t st = c.sb + p.stage * STAGE;
    const uint64_t dk = mkdesc(st + c.wg * 8192, 16, 1024, 1), dm = mkdesc(st + 32768 + c.wg * 4096, 128, 2048, 0);
    pin<32>(q);
    wg_fence();
    wgmma_rs64_first<0>(S, q, dk);
#pragma unroll
    for (int i = 1; i < 8; i++) wgmma_rs64<0>(S, q + i * 4, dk + (i >> 2) * 1024 + (i & 3) * 2);
    wgmma_rs16_first<0>(Sm, q, dm);
#pragma unroll
    for (int i = 1; i < 8; i++) wgmma_rs16<0>(Sm, q + i * 4, dm + i * 16);
    wg_commit();
}
__device__ __forceinline__ void qa_softmax(uint32_t (*pa)[4], const float* S, const float* Sm, const Cons& c) {
    const int t = c.lane & 3, i0 = (c.wq & 1) * 16 + (c.lane >> 2);
    const bool sg = c.wq >= 2;
    const float cs = 0.08838834764831845f * 1.4426950408889634f, masked = -1e9f / 0.08838834764831845f;
    float x[2][10];
#pragma unroll
    for (int r = 0; r < 2; r++) {
#pragma unroll
        for (int j = 0; j < 4; j++)
#pragma unroll
            for (int e = 0; e < 2; e++) {
                const float v = sg ? S[16 + j * 4 + r * 2 + e] : S[j * 4 + r * 2 + e];
                x[r][j * 2 + e] = (j * 8 + 2 * t + e > i0 + r * 8) ? masked : v;
            }
        x[r][8] = sg ? Sm[4 + r * 2] : Sm[r * 2];
        x[r][9] = sg ? Sm[5 + r * 2] : Sm[1 + r * 2];
        float m = x[r][0];
#pragma unroll
        for (int i = 1; i < 10; i++) m = fmaxf(m, x[r][i]);
        m = fmaxf(m, __shfl_xor_sync(0xffffffffu, m, 1));
        m = fmaxf(m, __shfl_xor_sync(0xffffffffu, m, 2));
        float sum = 0.f;
#pragma unroll
        for (int i = 0; i < 10; i++) { x[r][i] = ex2((x[r][i] - m) * cs); sum += x[r][i]; }
        sum += __shfl_xor_sync(0xffffffffu, sum, 1);
        sum += __shfl_xor_sync(0xffffffffu, sum, 2);
        const float inv = rcp(sum);
#pragma unroll
        for (int i = 0; i < 10; i++) x[r][i] *= inv;
    }
#pragma unroll
    for (int ks = 0; ks < 2; ks++)
#pragma unroll
        for (int i = 0; i < 4; i++) {
            const uint32_t p = pack2(x[i & 1][ks * 4 + (i >> 1) * 2], x[i & 1][ks * 4 + (i >> 1) * 2 + 1]);
            pa[ks][i] = sg ? 0u : p;
            pa[2 + ks][i] = sg ? p : 0u;
        }
#pragma unroll
    for (int r = 0; r < 2; r++) {
        const uint32_t p = pack2(x[r][8], x[r][9]);
        pa[4][r] = sg ? 0u : p;
        pa[4][2 + r] = sg ? p : 0u;
    }
}
__device__ __forceinline__ void qa_values(float* O, uint32_t (*pa)[4], const Cons& c, const Pipe& p) {
    mbar_wait(c.sb + B_FULL + p.stage * 8, p.phase);
    const uint32_t st = c.sb + p.stage * STAGE;
    const uint64_t dv = mkdesc(st + c.wg * 8192, 16384, 1024, 1), dm = mkdesc(st + 32768 + c.wg * 4096, 2048, 128, 0);
    pin<20>(&pa[0][0]);
    wg_fence();
    wgmma_rs128_first<1>(O, pa[0], dv);
#pragma unroll
    for (int ks = 1; ks < 4; ks++) wgmma_rs128<1>(O, pa[ks], dv + ks * 128);
    wgmma_rs128<0>(O, pa[4], dm);
    wg_commit();
}
__device__ __forceinline__ void epi_qa(const float* acc, Cons& c, Pend& d, int mb, int nb) {
    uint32_t* q = d.pk;
    pack_half(q, acc);
    pack_half(q + 32, acc + 64);
#pragma unroll 1
    for (int hh = 0; hh < 2; hh++) {
        uint32_t pa[5][4];
        float S[32], Sm[8], O[64];
        qa_scores(S, Sm, q, c, c.p);
        wg_wait<0>();
        pin<32>(S); pin<8>(Sm);
        release(c, c.p.stage);
        pipe_next(c.p);
        qa_softmax(pa, S, Sm, c);
        qa_values(O, pa, c, c.p);
#pragma unroll
        for (int i = 0; i < 32; i++) q[i] = q[32 + i];
        pin<32>(q);
        wg_wait<0>();
        pin<64>(O);
        release(c, c.p.stage);
        pipe_next(c.p);
        pack_half(q + 32, O);
    }
    d.kind = PEND_KVO; d.row = 4096 + mb * 256 + c.rank * 128 + c.wg * 64; d.col = nb * 256; d.cnt = C_O + mb * 4 + (nb >> 2);
}

__device__ __forceinline__ void epi_op(const float* acc, const Cons& c, Pend& d, int mb, int nb) {
    pack_half(d.pk, acc); pack_half(d.pk + 32, acc + 64);
    d.kind = PEND_OUT; d.row = mb * 256 + c.rank * 128 + c.wg * 64; d.col = 1024 + nb * 256;
}

__device__ __forceinline__ void epi_oph(const float* acc, const Cons& c, Pend& d, int mb, int nb) {
    pack_half(d.pk, acc);
    d.kind = PEND_OUTH; d.row = mb * 256 + c.rank * 128 + c.wg * 64; d.col = 1024 + nb * 128;
}

template <int HF>
__device__ __forceinline__ void epi_a2_half(const float* acc, const Params& P, Cons& c, int mb, int col0) {
    const int g = c.lane >> 2, t = c.lane & 3;
    const int row = mb * 256 + (g >> 1) * 64 + (c.rank * 16 + c.wg * 8 + c.wq * 2) * 2 + (g & 1);
    float* o = P.out + (size_t)row * 2048 + col0 + HF * 128 + t * 2;
    mbar_wait(c.sb + B_FULL + c.p.stage * 8, c.p.phase);
    const uint32_t st = c.sb + c.p.stage * STAGE, da = st + 32768 + (c.lane >> 3) * 16;
    const uint32_t xa = st + (c.wg * 64 + c.wq * 16 + (c.lane & 15)) * 128 + (((c.lane >> 4) ^ (c.lane & 7)) << 4);
#pragma unroll
    for (int j4 = 0; j4 < 4; j4++) {
        uint32_t x[8], dv[4];
        ldsm4(dv, da + j4 * 64);
        ldsm4(x, (xa ^ ((j4 & 1) << 6)) + (j4 >> 1) * 16384);
        ldsm4(x + 4, (xa ^ ((j4 & 1) << 6) ^ 32) + (j4 >> 1) * 16384);
#pragma unroll
        for (int i = 0; i < 4; i++) {
            const int j = j4 * 4 + i;
            const float* a = acc + HF * 64 + j * 4;
            const uint32_t u0 = hmul2(x[2 * i], dv[i]), u1 = hmul2(x[2 * i + 1], dv[i]);
            st_stream2(o + j * 8, a[0] + bf_lo(u0), a[1] + bf_hi(u0));
            st_stream2(o + 2 * 2048 + j * 8, a[2] + bf_lo(u1), a[3] + bf_hi(u1));
        }
    }
    __syncwarp();
    release(c, c.p.stage);
    pipe_next(c.p);
}

#define TSTAMP(i)
__device__ __forceinline__ float2 cmul(float2 a, float2 b) { return make_float2(fmaf(a.x, b.x, -a.y * b.y), fmaf(a.x, b.y, a.y * b.x)); }
__device__ __forceinline__ float2 cfma(float2 a, float2 b, float2 u) { return make_float2(fmaf(a.x, b.x, fmaf(-a.y, b.y, u.x)), fmaf(a.x, b.y, fmaf(a.y, b.x, u.y))); }
__device__ __forceinline__ float4 ssm_coef(float lre, float lim, float logdt) {
    const float dt = __bfloat162float(__float2bfloat16(expf(logdt)));
    const float ea = expf(dt * lre);
    float sn, cn;
    sincosf(dt * lim, &sn, &cn);
    const float br = ea * cn, bi = ea * sn, nr = br - 1.f;
    float cr, ci;
    if (fabsf(lre) >= fabsf(lim)) { const float r = lim / lre, dn = lre + lim * r; cr = (nr + bi * r) / dn; ci = (bi - nr * r) / dn; }
    else { const float r = lre / lim, dn = lre * r + lim; cr = (nr * r + bi) / dn; ci = (bi * r - nr) / dn; }
    return make_float4(br, bi, cr, ci);
}
__device__ __forceinline__ void epi_a1(const float* acc, const Params& P, const Cons& c, Pend& d, int mb, int nb, uint32_t atag) {
    const int t = c.lane & 3;
    const int p = nb * 128 + c.rank * 64 + c.wg * 32 + c.wq * 8 + (c.lane >> 2);
    uint32_t cw[4];
    lds128(cw, c.sb + S_COEF + (p & 63) * 16);
    const float4 cf = make_float4(__uint_as_float(cw[0]), __uint_as_float(cw[1]), __uint_as_float(cw[2]), __uint_as_float(cw[3]));
    TSTAMP(1)
    const float2 lam = make_float2(cf.x, P.swap_ri ? -cf.y : cf.y);
    const float a0 = P.swap_ri ? -2.f * cf.w : 2.f * cf.z, a1 = P.swap_ri ? 2.f * cf.z : -2.f * cf.w;
    const float b0 = P.swap_ri ? -2.f * cf.z : -2.f * cf.w, b1 = P.swap_ri ? -2.f * cf.w : -2.f * cf.z;
    float2 h = make_float2(0.f, 0.f);
#pragma unroll
    for (int round = 0; round < 2; round++) {
#pragma unroll
        for (int j = 0; j < 32; j++) {
            h = cfma(lam, h, make_float2(acc[j * 4], acc[j * 4 + 2]));
            const float r0 = fmaf(a0, h.x, a1 * h.y), m0 = fmaf(b0, h.x, b1 * h.y);
            h = cfma(lam, h, make_float2(acc[j * 4 + 1], acc[j * 4 + 3]));
            d.pk[j * 2] = pack2(r0, fmaf(a0, h.x, a1 * h.y));
            d.pk[j * 2 + 1] = pack2(m0, fmaf(b0, h.x, b1 * h.y));
        }
        if (round) break;
        float2 l64 = lam;
#pragma unroll
        for (int i = 0; i < 6; i++) l64 = cmul(l64, l64);
        const float2 l128 = cmul(l64, l64), l256 = cmul(l128, l128);
        float2 o = make_float2(__shfl_up_sync(0xffffffffu, h.x, 1), __shfl_up_sync(0xffffffffu, h.y, 1));
        if (t >= 1) h = cfma(l64, o, h);
        o = make_float2(__shfl_up_sync(0xffffffffu, h.x, 2), __shfl_up_sync(0xffffffffu, h.y, 2));
        if (t >= 2) h = cfma(l128, o, h);
        TSTAMP(2)
        if (t == 3) st_relaxed2(&g_agg[mb * 1024 + p], (__float_as_uint(h.x) & ~1u) | atag, __float_as_uint(h.y));
        h = make_float2(__shfl_up_sync(0xffffffffu, h.x, 1), __shfl_up_sync(0xffffffffu, h.y, 1));
        if (t == 0) h = make_float2(0.f, 0.f);
        uint32_t ax[7], ay[7];
        int n = 0;
        while (true) {
            uint32_t bad = 0;
#pragma unroll
            for (int j = 0; j < 7; j++) { ax[j] = atag; ay[j] = 0; ld_relaxed2_if(ax[j], ay[j], &g_agg[j * 1024 + p], j < mb); }
#pragma unroll
            for (int j = 0; j < 7; j++) bad |= ax[j] ^ atag;
            if (tags_ok(bad)) break;
            __nanosleep(400);
            if (++n > SPIN_LIMIT) spin_fault();
        }
        float2 carry = make_float2(0.f, 0.f);
#pragma unroll
        for (int j = 0; j < 7; j++) if (j < mb) carry = cfma(l256, carry, make_float2(__uint_as_float(ax[j]), __uint_as_float(ay[j])));
        float2 w = (t & 1) ? l64 : make_float2(1.f, 0.f);
        if (t & 2) w = cmul(w, l128);
        h = cfma(w, carry, h);
        TSTAMP(3)
    }
    TSTAMP(4)
    d.kind = PEND_HT; d.row = nb * 128 + c.rank * 64 + c.wg * 32; d.col = mb * 256; d.cnt = C_HT + mb * 2 + (nb >> 2);
}

__device__ __forceinline__ uint32_t acquire_stage(uint32_t sb, Pipe& p, uint32_t bytes) {
    mbar_wait(sb + B_EMPTY + p.stage * 8, p.phase ^ 1);
    mbar_expect(sb + B_FULL + p.stage * 8, bytes);
    return p.stage;
}
#define AHEAD 1
__device__ __forceinline__ void watcher(const Params& P, const uint32_t sb, const int rank, const int lane) {
    const uint32_t epoch = ld_relaxed1(&g_cnt(C_EPOCH)), e1 = epoch + 1;
    sts32(sb + S_EPOCH, epoch);
    __syncwarp();
    if (lane == 0 && atomicInc(&g_cnt(C_DONE), (DBGF(32) ? 95 : NPAIR * 2 - 1) + (epoch & P.zero)) == (DBGF(32) ? 95 : NPAIR * 2 - 1)) atomicAdd(&g_cnt(C_EPOCH), 1);
    if (gridDim.x != 96) {
        uint32_t v;
        asm("mov.u32 %0, %%smid;" : "=r"(v));
        if (lane == 0 && rank == 0) st_relaxed1(g_hint + 6272 + (blockIdx.x >> 1), e1 << 8 | v >> 1);
        for (int k = 0;; k++) {
            __nanosleep(1000);
            v = ld_relaxed1(g_hint + 6272 + min(lane, 17));
            if (__all_sync(0xffffffffu, (v ^ e1 << 8) < 256)) break;
            if (k > SPIN_LIMIT) spin_fault();
        }
        const uint32_t key = ((v & 255) >= 62 ? 0 : tpc_gpc(v & 255)) * 32 + lane;
        sts32(sb + S_TAIL, 48 + __popc(__ballot_sync(0xffffffffu, key < __shfl_sync(0xffffffffu, key, blockIdx.x >> 1)) & 0x3ffff));
        __syncwarp();
    }
    uint32_t met = 1;
    if (lane == 0) asm volatile("st.release.cta.shared.u32 [%0], 1;" ::"r"(sb + S_DEP) : "memory");
    const int pair = lds32(sb + S_TAIL), first = ITEM_OFF(pair) + (pair < NCHAIN ? NPRE + 1 : 1);
#pragma unroll 1
    for (int it = first; it < ITEM_OFF(pair + 1); it++) {
        const int item = ITEM(it), type = item >> 8, mb = (item >> 5) & 7, nb = item & 31;
        const int n = (0x24021420 >> (type * 4)) & 7;
        for (int k = 0; it > first && (int)lds32(sb + S_CUR) < it - AHEAD; k++) { __nanosleep(200); if (k > SPIN_LIMIT) spin_fault(); }
#pragma unroll 1
        for (int i = 0; i < n; i++) {
            int idx = n == 4 ? C_O + mb * 4 + i : C_HT + mb * 2 + i;
            uint32_t target = e1 * 16;
            if (type == T_A1) { idx = C_COEF; target = e1 * 4; }
            if (type == T_QA) {
                idx = i ? C_FLAG + (lane & 1) * 32 + nb * 2 + ((lane >> 1) & 1) : C_KV + mb;
                target = i ? epoch * 64 + mb * 8 + rank * 4 + 4 : e1 * 128;
            }
            if (lane < 4) { wait_count(&g_cnt(idx), target); fence_async(); }
            __syncwarp();
            if (lane == 0) asm volatile("st.release.cta.shared.u32 [%0], %1;" ::"r"(sb + S_DEP), "r"(++met) : "memory");
        }
    }
}
__device__ __forceinline__ bool dep_met(uint32_t sb, uint32_t n) { uint32_t v; asm volatile("ld.acquire.cta.shared.u32 %0, [%1];" : "=r"(v) : "r"(sb + S_DEP) : "memory"); return v >= n; }
__device__ __forceinline__ void dep_wait(uint32_t sb, uint32_t n) { for (int k = 0; !dep_met(sb, n); k++) { __nanosleep(32); if (k > SPIN_LIMIT * 8) spin_fault(); } }
__device__ __forceinline__ void producer(const Params& P, const uint32_t sb, int pair, const int rank) {
    Pipe p = {0, 0};
    uint32_t dep = 1;
    for (int it = ITEM_OFF(pair); it < ITEM_OFF(pair + 1); it++) {
        const int item = ITEM(it), type = item >> 8, mb = (item >> 5) & 7, nb = item & 31;
        if (type == T_CHAIN) {
            sts32(sb + S_CUR, 0);
            const uint32_t epoch = ld_relaxed1(&g_cnt(C_EPOCH)), e1 = epoch + 1;
            const int role = pair >> 4, h = (pair & 15) * 2 + rank;
#pragma unroll 1
            for (int i = 0, q = 0; i < 8; i++) {
                const int n = (0x13003333 >> (i * 4)) & 3;
                const uint32_t st = acquire_stage(sb, p, n * 16384);
                SSTAMP(1, i == 6) SSTAMP(3, i == 7)
#pragma unroll 1
                for (int k = 0; k < 2 * n; k++, q++)
                    tma3d(sb + st * STAGE + k * 8192, &P.tm[M_CQ + role], h * 128 + (fill_unit(q >> 1) & 1) * 64, word_col((fill_unit(q >> 1) & 14) + (q & 1)) & 8, word_col((fill_unit(q >> 1) & 14) + (q & 1)) >> 4, sb + B_FULL + st * 8, role ? EVICT_NORMAL : POL(3));
                pipe_next(p);
            }
            if (role == 0 && !DBGF(1)) { wait_count(&g_cnt(C_KV), e1 * 128); fence_async(); }
            mbar_wait(sb + B_EMPTY + 16, 1); mbar_wait(sb + B_EMPTY + 24, 1);
            mbar_expect(sb + B_WO, role ? 98304 : 65536);
            if (role == 0) { mbar_expect(sb + B_KVFULL, 16384); mbar_expect(sb + B_KVFULL + 8, 16384); }
#pragma unroll 1
            for (int k = role ? 0 : -4; k < 12; k++) {
                const bool kv = role == 0 && (k & 8);
                const int sg = k > 0;
                tma4d(kv ? sb + S_KV + sg * 16384 + (k & 3) * 4096 : sb + S_W2 + k * 8192, &P.tm[kv ? M_KV4 : M_CO + (k & 1)],
                      kv ? h * 128 + (k & 1) * 64 : (role == 0 ? 0 : role == 1 ? 256 : 640) + (k >> 1) * 64, kv ? (k & 2) * 1024 + sg * 32 : h * 8, sb + (kv ? B_KVFULL + sg * 8 : B_WO), POL(2));
            }
            SSTAMP(5, true)
            if (pair < 16) {
#pragma unroll 1
                for (int s = 2; s < 63; s++) {
                    mbar_wait(sb + B_KVGO + (s & 1) * 8, ((s >> 1) + 1) & 1);
                    wait_time(gtime() + P.dk, sb);
                    SSTAMP(6, s == 2)
                    const uint32_t bar = sb + B_KVFULL + (s & 1) * 8, dst = sb + S_KV + (s & 1) * 16384;
                    if (DBGF(2)) { mbar_arrive(bar); continue; }
                    mbar_expect(bar, 16384);
#pragma unroll 1
                    for (int i = 0; i < 4; i++) tma2d(dst + i * 4096, &P.tm[M_KVO], (pair * 2 + rank) * 128 + (i & 1) * 64, (i >> 1) * 2048 + (DBGF(32 | 512) ? s & 7 : s) * 32, bar, POL(1));
                    if ((s & 7) == 7 && !DBGF(1)) { wait_count(&g_cnt(C_KV + 1 + (s >> 3)), e1 * 128); fence_async(); }
                }
            } else {
                uint32_t* flag = &g_cnt(C_FLAG + pair * 2 + rank - 32);
                const int x = pair * 2 + rank - 32;
#pragma unroll 1
                for (int s = 0; s < 64; s++) {
                    mbar_wait(sb + B_PERS, s & 1);
                    if (s < 63) wait_time(gtime() + P.dp, sb);
                    if (!DBGF(4)) bulk_s2g((role == 1 ? g_km : g_vmt) + (s * 32 + h) * 512, sb + S_QX, 2048);
                    if (s < 57) {
                        uint8_t* m = P.gm + ((s + 6) & 7) * M_SLOT + (x >> 1) * 1024 + (x & 1) * 256;
                        bulk_s2g(m, sb + S_SX, 256); bulk_s2g(m + 512, sb + S_SX, 128);
                        bulk_s2g(g_f + ((s + 6) & 7) * F_SLOT + x * 768, sb + S_SX + 256, 768);
                    }
                    bulk_commit();
                    bulk_wait_read();
                    mbar_arrive(sb + B_KVGO);
                    bulk_wait_all();
                    fence_async();
                    if ((s & 3) == 3) st_relaxed1(flag, epoch * 64 + s + 1);
                }
            }
            mbar_wait(sb + B_RESUME, 0);
            pair = lds32(sb + S_TAIL);
            it = ITEM_OFF(pair) + NPRE;
            continue;
        }
        if (it == ITEM_OFF(pair) && pair >= NCHAIN) it = -1; else sts32(sb + S_CUR, it);
        const int m0 = mb * 256 + rank * 128;
        if (type <= T_OP) {
            const CUtensorMap* ma = &P.tm[type == T_OP ? M_OA : M_BX];
            const CUtensorMap* mw = &P.tm[type == T_OP ? M_WO : type == T_QA ? M_WQ : nb < 16 ? M_WK : M_WV];
            const int nk = type == T_OP ? 64 : 16, nc = (nb & 15) * 4 + rank * 2, ma0 = type == T_OP ? 4096 + m0 : m0;
#pragma unroll 1
            for (int kt = 0; kt < nk; kt++) {
                if (type == T_OP && (kt & 15) == 0) dep_wait(sb, ++dep);
                if (DBGF(256) && pair >= NCHAIN) { acquire_stage(sb, p, 0); pipe_next(p); continue; }
                const uint32_t st = acquire_stage(sb, p, STAGE), bar = sb + B_FULL + st * 8;
                tma2d(sb + st * STAGE, ma, kt * 64, ma0, bar, type == T_OP ? POL(6) : type == T_QA ? POL(12) : POL(13));
                tma3d_mc(sb + st * STAGE + 16384 + rank * 16384, mw, 0, kt * 64, nc, bar, type == T_KV && mb == 7 ? POL(9) : EVICT_NORMAL);
                pipe_next(p);
            }
            if (type == T_QA) {
                dep += 2;
                dep_wait(sb, dep);
#pragma unroll 1
                for (int e = 0; e < 4; e++) {
                    const uint32_t st = acquire_stage(sb, p, 40960), bar = sb + B_FULL + st * 8, dst = sb + st * STAGE;
                    tma2d(dst, &P.tm[M_OA], nb * 256 + (e >> 1) * 128, (e & 1) * 2048 + m0, bar, POL(0));
                    tma2d(dst + 16384, &P.tm[M_OA], nb * 256 + (e >> 1) * 128 + 64, (e & 1) * 2048 + m0, bar, POL(0));
                    const uint32_t* src = ((e & 1) ? g_vmt : g_km) + ((mb * 8 + rank * 4) * 32 + nb * 2 + (e >> 1)) * 512;
#pragma unroll 1
                    for (int i = 0; i < 4; i++) bulk_g2s(dst + 32768 + i * 2048, src + i * 32 * 512, 2048, bar);
                    pipe_next(p);
                }
            }
        } else if (type == T_OPH) {
#pragma unroll 1
            for (int kt = 0; kt < 64; kt++) {
                if ((kt & 15) == 0) dep_wait(sb, ++dep);
                const uint32_t st = acquire_stage(sb, p, 32768), bar = sb + B_FULL + st * 8;
                tma2d(sb + st * STAGE, &P.tm[M_OA], kt * 64, 4096 + m0, bar, POL(6));
                tma2d_mc(sb + st * STAGE + 16384 + rank * 8192, &P.tm[M_WOH], nb * 128 + rank * 64, kt * 64, bar, EVICT_NORMAL);
                pipe_next(p);
            }
        } else if (type == T_A1) {
#pragma unroll 1
            for (int kt = 0; kt < 16; kt++) {
                if (kt == 15) dep_wait(sb, ++dep);
                const uint32_t st = acquire_stage(sb, p, kt == 15 ? STAGE + 1024 : STAGE), bar = sb + B_FULL + st * 8;
                if (kt == 15) bulk_g2s(sb + S_COEF, g_coef + nb * 128 + rank * 64, 1024, bar);
                tma4d(sb + st * STAGE, &P.tm[M_AB], kt * 64, nb * 16 + rank * 8, bar, POL(10));
                tma4d_mc(sb + st * STAGE + 16384 + rank * 16384, &P.tm[M_AX], kt * 64, mb * 128 + rank * 16, bar, POL(10));
                pipe_next(p);
            }
        } else {
            const int hw = type == T_A2H ? 64 : 128;
            const CUtensorMap* mc = &P.tm[type == T_A2H ? M_CREH : M_CRE];
#pragma unroll 1
            for (int kt = 0; kt < 32; kt++) {
                if ((kt & 15) == 0) dep_wait(sb, ++dep);
                const uint32_t st = acquire_stage(sb, p, 16384 + hw * 256), bar = sb + B_FULL + st * 8;
                tma3d(sb + st * STAGE, &P.tm[M_HT], 0, (kt & 1) * 1024 + (kt >> 1) * 64, mb * 4 + rank * 2, bar, POL(7));
                tma2d_mc(sb + st * STAGE + 16384 + rank * hw * 128, mc + (kt & 1), (kt >> 1) * 64, (nb * 2 + rank) * hw, bar, POL(11));
                pipe_next(p);
            }
#pragma unroll 1
            for (int col = nb * 2 * hw; col < (nb + 1) * 2 * hw; col += 128) {
                const uint32_t st = acquire_stage(sb, p, 32768 + 256), bar = sb + B_FULL + st * 8;
                tma4d(sb + st * STAGE, &P.tm[M_AX], col, mb * 128 + rank * 16, bar, POL(8));
                tma4d(sb + st * STAGE + 16384, &P.tm[M_AX], col + 64, mb * 128 + rank * 16, bar, POL(8));
                bulk_g2s(sb + st * STAGE + 32768, P.Dskip + col, 256, bar);
                pipe_next(p);
            }
        }
        if (it < 0) { dep_wait(sb, 1); pair = lds32(sb + S_TAIL); it = ITEM_OFF(pair); }
    }
}

__device__ __forceinline__ uint32_t fresh_tid() { uint32_t t; asm volatile("mov.u32 %0, %%tid.x;" : "=r"(t)); return t; }
__device__ __forceinline__ uint32_t fresh_ctaid() { uint32_t t; asm volatile("mov.u32 %0, %%ctaid.x;" : "=r"(t)); return logical_cta(t); }
__device__ __forceinline__ void reset_state(Cons& c, Pend& d, uint32_t sb, bool resumed) {
    const uint32_t t = fresh_tid(), b = fresh_ctaid();
    const int w = __shfl_sync(0xffffffffu, t >> 5, 0);
    c.sb = sb; c.wg = w >> 2; c.wq = w & 3; c.lane = t & 31;
    c.rank = __shfl_sync(0xffffffffu, b & 1, 0); c.pair = __shfl_sync(0xffffffffu, resumed && b < NCHAIN * 2 ? lds32(sb + S_TAIL) : b >> 1, 0);
    c.rel = mapa(sb + B_EMPTY, cluster_rank() ^ (c.lane & 1));
    c.p.stage = 0; c.p.phase = 0;
    c.nst = resumed && c.pair < NCHAIN ? 2 * NPRE : 0;
    d = Pend{};
}
#define PROF_ITEM(i)
#define PROF_MAIN(i)

__global__ void __launch_bounds__(384, 1) fused_kernel(const __grid_constant__ Params P) {
    extern __shared__ __align__(1024) uint8_t smem[];
    const uint32_t sb = smem_u32(smem);
    asm volatile("griddepcontrol.launch_dependents;");
    const int tid = threadIdx.x, lane = tid & 31;
    const int warp = __shfl_sync(0xffffffffu, tid >> 5, 0);
    const int pair = __shfl_sync(0xffffffffu, logical_cta(blockIdx.x) >> 1, 0), rank = __shfl_sync(0xffffffffu, blockIdx.x & 1, 0);
    if (tid == 0) {
        if (sb & 1023) spin_fault();
        sts32(sb + S_DEP, 0); sts32(sb + S_CUR, 0); sts32(sb + S_TAIL, pair); sts32(sb + S_CTA, pair * 2 + rank);
        for (int i = 0; i < NSTAGE; i++) { mbar_init(sb + B_FULL + i * 8, 1); mbar_init(sb + B_EMPTY + i * 8, 16); }
        mbar_init(sb + B_RESUME, 2);
        mbar_init(sb + B_KVFULL, 1); mbar_init(sb + B_KVFULL + 8, 1);
        mbar_init(sb + B_GO, 1); mbar_init(sb + B_KVGO, 1); mbar_init(sb + B_KVGO + 8, 1); mbar_init(sb + B_K, 1); mbar_init(sb + B_V, 1); mbar_init(sb + B_PERS, pair < 16 ? 1 : 8); mbar_init(sb + B_INIT, 3);
        mbar_init(sb + B_WO, 1);
        for (int i = 0; i < 2; i++) { mbar_init(sb + B_SFULL + i * 8, 4); mbar_init(sb + B_SFREE + i * 8, 1); }
        mbar_init(sb + B_RELA, 1); mbar_init(sb + B_RELB, 1);
        asm volatile("fence.mbarrier_init.release.cluster;" ::: "memory");
        if (pair < 16) { mbar_expect(sb + B_K, KE ? 1024 : 2048); mbar_expect(sb + B_PERS, 1024); }
        mbar_expect(sb + B_V, 2048);
    }
    __syncthreads();
    cluster_arrive();
    if (warp >= 8) {
        asm volatile("setmaxnreg.dec.sync.aligned.u32 24;");
        if (warp != 8) cluster_wait();
        if (warp == 10 && lane < M_COUNT) map_prefetch(&P.tm[lane]);
        if (warp == 11 && lane == 0 && pair < 16) {
            const uint32_t t0 = gtime();
#pragma unroll 1
            for (int i = 0; i < 32; i++) {
                wait_time(t0 + P.pf0 + i * P.pf1, sb);
                asm volatile("cp.async.bulk.prefetch.tensor.3d.L2.global [%0, {%1, %2, %3}];" ::"l"(&P.tm[M_CQ]), "r"((pair * 2 + rank) * 128 + (i & 1) * 64), "r"((i & 2) * 4), "r"((i >> 2) * 8) : "memory");
            }
        }
        if (warp == 9 && pair < NCHAIN) pacer(P, sb, lane);
        if (warp == 9) watcher(P, sb, rank, lane);
        if (warp >= 10 && lane == 0) store_warp(P, sb, warp - 10);
        if (warp == 8) {
            cluster_wait();
            if (lane == 0) producer(P, sb, lds32(sb + S_CTA) >> 1, rank);
            __syncwarp();
            cluster_arrive(); cluster_wait();
        }
    } else {
        asm volatile("setmaxnreg.inc.sync.aligned.u32 240;");
        Cons c;
        Pend d;
        if (pair < NCHAIN) {
            mem0_max(P, sb, tid);
            cluster_wait();
            reset_state(c, d, sb, false);
#pragma unroll 1
            for (int i = 0; i < NPRE; i++) {
                PROF_ITEM(i)
                const int item = ITEM(ITEM_OFF(pair) + i);
                float acc[128];
                mainloop<256, true>(acc, P, c, d, T_KV);
                epi_kv(acc, c, d, (item >> 5) & 7, item & 31);
            }
            ISTAMP(4)
            drain<0, true>(P, c, d);
            drain<1, true>(P, c, d);
            PROF_ITEM(NPRE)
            uint32_t wr[NR][4];
            load_weights(wr, sb, warp, lane, [&]() { staging_wait(c); });
            const int h = (pair & 15) * 2 + rank;
            if (pair < 16) chain_role<0>(P, wr, sb, h, warp, lane);
            else if (pair < 32) chain_role<1>(P, wr, sb, h, warp, lane);
            else chain_role<2>(P, wr, sb, h, warp, lane);
            fence_async_smem();
            bar_sync(1, 256);
            const uint32_t t2 = fresh_tid();
            if (t2 < 2) mbar_arrive_cluster(mapa(sb + B_RESUME, cluster_rank() ^ t2));
        } else if (pair >= NPAIR - 2) {
            const int ch = (pair - (NPAIR - 2)) * 512 + rank * 256 + tid;
            g_coef[ch] = ssm_coef(__bfloat162float(P.Lre[ch]), __bfloat162float(P.Lim[ch]), __bfloat162float(P.logdt[ch]));
            bar_sync(1, 256);
            if (tid == 0) red_release(&g_cnt(C_COEF));
        }
        reset_state(c, d, sb, true);
        if (c.pair >= NCHAIN) cluster_wait();
        for (int it = ITEM_OFF(c.pair) + (c.pair < NCHAIN ? NPRE + 1 : 0);; it++) {
            const bool last = it == ITEM_OFF(c.pair + 1);
            if (d.kind != PEND_NONE && (last || !bar_and(5 + c.wg, mbar_test(sb + B_FULL + c.p.stage * 8, c.p.phase)))) drain_all(P, c, d);
            if (last) break;
            const int item = ITEM(it), type = item >> 8, mb = (item >> 5) & 7, nb = item & 31;
            PROF_ITEM(it - ITEM_OFF(c.pair))
            if (type >= T_OPH) {
                float acc[64];
                mainloop<128>(acc, P, c, d, type);
                PROF_MAIN(it - ITEM_OFF(c.pair))
                if (type == T_OPH) epi_oph(acc, c, d, mb, nb);
                else epi_a2_half<0>(acc, P, c, mb, nb * 128);
            } else {
                float acc[128];
                mainloop<256>(acc, P, c, d, type);
                PROF_MAIN(it - ITEM_OFF(c.pair))
                if (type == T_KV) epi_kv(acc, c, d, mb, nb);
                else if (type == T_QA) epi_qa(acc, c, d, mb, nb);
                else if (type == T_OP) epi_op(acc, c, d, mb, nb);
                else if (type == T_A1) epi_a1(acc, P, c, d, mb, nb, (lds32(sb + S_EPOCH) + 1) & 1);
                else { epi_a2_half<0>(acc, P, c, mb, nb * 256); epi_a2_half<1>(acc, P, c, mb, nb * 256); }
            }
            if (it == ITEM_OFF(c.pair)) { dep_wait(sb, 1); c.pair = __shfl_sync(0xffffffffu, lds32(sb + S_TAIL), 0); it = ITEM_OFF(c.pair); }
        }
        staging_wait(c);
        staging_post(c, PEND_NONE, 0, 0, 0);
        cluster_arrive(); cluster_wait();
    }
}

typedef CUresult (*EncodeFn)(CUtensorMap*, CUtensorMapDataType, cuuint32_t, void*, const cuuint64_t*, const cuuint64_t*, const cuuint32_t*, const cuuint32_t*,
                             CUtensorMapInterleave, CUtensorMapSwizzle, CUtensorMapL2promotion, CUtensorMapFloatOOBfill);
void encode(EncodeFn fn, CUtensorMap* m, const void* base, int rank, const uint64_t* dims, const uint64_t* strides, const uint32_t* box, CUtensorMapSwizzle swz = CU_TENSOR_MAP_SWIZZLE_128B) {
    cuuint64_t d[5], s[5]; cuuint32_t b[5], e[5];
    for (int i = 0; i < rank; i++) { d[i] = dims[i]; b[i] = box[i]; e[i] = 1; if (i) s[i - 1] = strides[i - 1]; }
    fn(m, CU_TENSOR_MAP_DATA_TYPE_BFLOAT16, rank, (void*)base, d, s, b, e, CU_TENSOR_MAP_INTERLEAVE_NONE, swz,
       CU_TENSOR_MAP_L2_PROMOTION_L2_256B, CU_TENSOR_MAP_FLOAT_OOB_FILL_NONE);
}
void map_kmajor(EncodeFn fn, CUtensorMap* m, const void* base, uint64_t rows, uint64_t cols, uint32_t box_rows) {
    const uint64_t d[2] = {cols, rows}, s[1] = {cols * 2}; const uint32_t b[2] = {64, box_rows};
    encode(fn, m, base, 2, d, s, b);
}
void map_mnmajor(EncodeFn fn, CUtensorMap* m, const void* base, uint64_t krows, uint64_t cols) {
    const uint64_t d[3] = {64, krows, cols / 64}, s[2] = {cols * 2, 128}; const uint32_t b[3] = {64, 64, 2};
    encode(fn, m, base, 3, d, s, b);
}

}

extern "C" void kernel_launch(void* const* d_in, const int* in_sizes, int n_in, void* d_out, int out_size) {
    static Params P;
    static EncodeFn fn = nullptr;
    if (!fn) {
        cudaDriverEntryPointQueryResult q;
        cudaGetDriverEntryPoint("cuTensorMapEncodeTiled", (void**)&fn, cudaEnableDefault, &q);
        cudaFuncSetAttribute(fused_kernel, cudaFuncAttributeMaxDynamicSharedMemorySize, S_TOTAL);
    }
    const bf16* in[15];
    for (int i = 0; i < 15; i++) in[i] = (const bf16*)d_in[i];
    void *kvo, *ht, *gm;
    cudaGetSymbolAddress(&gm, g_m);
    P.gm = (uint8_t*)(((uintptr_t)gm + 32767) & ~(uintptr_t)32767);
    cudaGetSymbolAddress(&kvo, g_kvo);
    cudaGetSymbolAddress(&ht, g_ht);
    map_kmajor(fn, &P.tm[M_BX], in[9], 2048, 1024, 128);
    map_mnmajor(fn, &P.tm[M_WQ], in[11], 1024, 4096);
    map_mnmajor(fn, &P.tm[M_WK], in[12], 1024, 4096);
    map_mnmajor(fn, &P.tm[M_WV], in[13], 1024, 4096);
    map_mnmajor(fn, &P.tm[M_WO], in[14], 4096, 1024);
    map_kmajor(fn, &P.tm[M_OA], kvo, 3 * 2048, 4096, 128);
    P.swap_ri = in[4] < in[3];
    {
        const bf16* lo = P.swap_ri ? in[4] : in[3];
        const uint64_t diff = (uint64_t)((const char*)(P.swap_ri ? in[3] : in[4]) - (const char*)lo);
        const uint64_t d[4] = {1024, 8, 2, 128}, s[3] = {2048, diff, 16384}; const uint32_t b[4] = {64, 8, 2, 8};
        encode(fn, &P.tm[M_AB], lo, 4, d, s, b);
    }
    {
        const uint64_t d[4] = {1024, 2, 4, 1024}, s[3] = {2048, 64 * 2048, 4096}; const uint32_t b[4] = {64, 2, 4, 16};
        encode(fn, &P.tm[M_AX], in[0], 4, d, s, b);
    }
    map_mnmajor(fn, &P.tm[M_HT], ht, 2048, 2048);
    map_kmajor(fn, &P.tm[M_CRE], in[5], 1024, 1024, 128);
    map_kmajor(fn, &P.tm[M_CIM], in[6], 1024, 1024, 128);
    map_kmajor(fn, &P.tm[M_KVO], kvo, 3 * 2048, 4096, 32);
    map_kmajor(fn, &P.tm[M_HTS], ht, 2048, 2048, 32);
    map_kmajor(fn, &P.tm[M_WOH], in[14], 4096, 1024, 64);
    map_kmajor(fn, &P.tm[M_CREH], in[5], 1024, 1024, 64);
    map_kmajor(fn, &P.tm[M_CIMH], in[6], 1024, 1024, 64);
    for (int i = 0; i < 3; i++) {
        const uint64_t d[3] = {4096, 16, 64}, s[2] = {8192, 16 * 8192}; const uint32_t b[3] = {64, 8, 8};
        encode(fn, &P.tm[M_CQ + i], in[11 + i], 3, d, s, b);
    }
    {
        const uint64_t d[4] = {4096, 1, 1, 4096}, s[3] = {8192, 8192, 8192}; const uint32_t b[4] = {64, 1, 1, 32};
        encode(fn, &P.tm[M_KV4], kvo, 4, d, s, b);
    }
    for (int e = 0; e < 2; e++) {
        const uint64_t d[4] = {1024, 2, 4, 256}, s[3] = {8 * 2048, 2 * 2048, 16 * 2048}; const uint32_t b[4] = {64, 2, 4, 8};
        encode(fn, &P.tm[M_CO + e], in[14] + e * 1024, 4, d, s, b);
    }
    P.Wq = in[11]; P.Wk = in[12]; P.Wv = in[13]; P.Wo = in[14]; P.mem0 = in[10];
    P.Lre = in[1]; P.Lim = in[2]; P.logdt = in[7]; P.Dskip = in[8];
    P.out = (float*)d_out;
    P.two26 = 1u << 26;
    P.lag = 0x22023302;
    P.ds = 400; P.dc = 1600; P.alpha = 0.3f; P.extra = 200; P.da = 140; P.db = 375; P.dk = 750; P.dp = 1500; P.dv = 60; P.pf0 = 2000; P.pf1 = 250; P.back = 150; P.ds0 = 800;
    for (int i = 0; i < (DBGF(32) ? 1 : 2); i++) {
        cudaLaunchConfig_t cfg = {};
        cfg.gridDim = dim3(i ? 36 : 96); cfg.blockDim = dim3(384); cfg.dynamicSmemBytes = S_TOTAL; cfg.stream = cudaStreamPerThread;
        cudaLaunchAttribute at[2];
        at[0].id = cudaLaunchAttributeClusterDimension; at[0].val.clusterDim.x = i ? 2 : 6; at[0].val.clusterDim.y = at[0].val.clusterDim.z = 1;
        at[1].id = cudaLaunchAttributeProgrammaticStreamSerialization; at[1].val.programmaticStreamSerializationAllowed = 1;
        cfg.attrs = at; cfg.numAttrs = 1 + i;
        cudaLaunchKernelEx(&cfg, fused_kernel, P);
    }
}
```

```cpp
#include <cuda_runtime.h>
#include <cuda_bf16.h>
#include <cuda.h>
#include <stdint.h>
#include <string.h>

typedef __nv_bfloat16 bf16;

namespace {

#define POLL 200
constexpr int SPIN_LIMIT = 1 << 22;
constexpr int NPAIR = 66;
constexpr int NCHAIN = 48;
enum { T_KV = 0, T_QA = 1, T_OP = 2, T_A1 = 3, T_A2 = 4, T_CHAIN = 5, T_OPH = 6, T_A2H = 7 };
enum { M_BX = 0, M_WQ, M_WK, M_WV, M_WO, M_OA, M_AB, M_AX, M_HT, M_CRE, M_CIM, M_KVO, M_HTS, M_WOH, M_CREH, M_CIMH, M_CQ, M_CK, M_CV, M_CO, M_CO1, M_KV4, M_COUNT };
enum { C_KV = 0, C_HT = 8, C_DONE = 24, C_EPOCH = 25, C_COEF = 26, C_FLAG = 32, C_O = 96 };

struct Params {
    CUtensorMap tm[M_COUNT];
    const bf16 *Wq, *Wk, *Wv, *Wo, *mem0, *Lre, *Lim, *logdt, *Dskip;
    float* out;
    uint8_t* gm;
    int swap_ri, zero;
    uint32_t two26, lag;
    int ds, da, db, dk, dv, back, ds0, pf0, pf1, dc, extra, dp;
    float alpha;
#define DBGF(x) false
};

constexpr int NPRE = 1;
__constant__ uint16_t c_off[67] = {0, 5, 10, 15, 21, 25, 29, 35, 39, 43, 47, 51, 55, 59, 63, 67, 71, 76, 81, 86, 91, 95, 99, 103, 108, 112, 116, 120, 124, 128, 133, 137, 142, 147, 152, 157, 162, 166, 170, 175, 179, 183, 187, 191, 195, 200, 205, 209, 213, 232, 252, 272, 291, 311, 331, 349, 369, 389, 407, 427, 446, 466, 485, 505, 524, 543, 562};
__constant__ uint16_t c_items[640] = {
    32, 1280, 453, 492, 1056, 49, 1280, 485, 494, 1249, 34, 1280, 293, 301, 1120, 51, 1280, 458, 457, 428, 1959, 36, 1280, 896,
    642, 53, 1280, 898, 546, 38, 1280, 833, 961, 996, 1957, 55, 1280, 865, 578, 40, 1280, 495, 576, 57, 1280, 463, 579, 42,
    1280, 262, 675, 59, 1280, 264, 739, 44, 1280, 335, 608, 61, 1280, 897, 738, 46, 1280, 361, 707, 63, 1280, 265, 705, 0,
    1280, 388, 302, 1217, 1, 1280, 489, 493, 1248, 2, 1280, 391, 333, 1250, 3, 1280, 263, 459, 1088, 4, 1280, 866, 673, 5,
    1280, 931, 640, 6, 1280, 835, 737, 7, 1280, 899, 488, 1185, 8, 1280, 838, 643, 9, 1280, 839, 641, 10, 1280, 870, 672,
    11, 1280, 864, 515, 12, 1280, 871, 674, 13, 1280, 935, 933, 1219, 14, 1280, 772, 736, 15, 1280, 994, 964, 1091, 16, 1280,
    393, 332, 1216, 17, 1280, 484, 300, 1121, 18, 1280, 487, 364, 1058, 19, 1280, 423, 462, 1152, 20, 1280, 867, 544, 21, 1280,
    930, 545, 22, 1280, 900, 424, 1089, 23, 1280, 836, 577, 24, 1280, 903, 611, 25, 1280, 902, 609, 26, 1280, 928, 547, 27,
    1280, 869, 512, 28, 1280, 868, 901, 1251, 29, 1280, 932, 965, 1218, 30, 1280, 804, 704, 31, 1280, 962, 706, 33, 95, 94,
    127, 126, 159, 158, 255, 223, 191, 324, 352, 399, 422, 289, 425, 392, 490, 1024, 35, 93, 92, 125, 124, 157, 156, 189,
    221, 253, 252, 323, 254, 292, 418, 417, 386, 299, 365, 1956, 37, 91, 90, 123, 122, 155, 154, 187, 186, 251, 219, 250,
    334, 426, 366, 448, 449, 491, 430, 1123, 39, 89, 88, 121, 120, 153, 152, 185, 217, 184, 216, 218, 249, 248, 358, 288,
    321, 452, 514, 41, 87, 86, 119, 118, 151, 215, 247, 183, 214, 200, 199, 246, 325, 296, 420, 482, 268, 396, 1059, 43,
    85, 84, 117, 116, 149, 213, 181, 212, 180, 195, 193, 297, 363, 266, 326, 303, 455, 431, 1153, 45, 83, 82, 115, 114,
    147, 211, 179, 210, 178, 329, 243, 355, 356, 805, 837, 929, 610, 47, 81, 80, 113, 112, 145, 177, 176, 241, 190, 209,
    208, 240, 773, 832, 290, 480, 995, 966, 1057, 48, 79, 78, 111, 143, 142, 207, 175, 206, 174, 222, 192, 239, 256, 257,
    390, 389, 934, 997, 1090, 50, 77, 76, 109, 141, 140, 237, 173, 236, 234, 245, 205, 258, 771, 427, 421, 483, 513, 52,
    75, 74, 107, 139, 138, 171, 235, 170, 203, 202, 770, 774, 359, 775, 801, 963, 993, 397, 1958, 54, 73, 72, 105, 137,
    136, 169, 201, 233, 168, 362, 270, 394, 353, 807, 806, 960, 367, 1184, 56, 71, 103, 104, 135, 150, 167, 182, 231, 232,
    242, 238, 384, 224, 357, 387, 320, 486, 429, 1026, 58, 70, 102, 110, 134, 148, 166, 172, 230, 188, 267, 800, 244, 419,
    291, 295, 328, 269, 1027, 60, 69, 101, 108, 133, 146, 197, 165, 204, 198, 220, 322, 229, 398, 802, 803, 395, 454, 461,
    1155, 62, 68, 100, 106, 132, 144, 228, 164, 327, 196, 225, 768, 769, 260, 416, 481, 967, 999, 1122, 64, 67, 99, 97,
    131, 129, 163, 161, 271, 354, 259, 227, 261, 294, 450, 834, 992, 998, 1025, 65, 66, 98, 96, 130, 128, 162, 160, 298,
    226, 194, 385, 331, 330, 360, 451, 456, 460, 1154,
};
#define ITEM_OFF(p) c_off[p]
#define ITEM(i) c_items[i]

__device__ __align__(1024) bf16 g_kvo[3 * 2048 * 4096];
__device__ __align__(1024) bf16 g_ht[2048 * 2048];
__device__ __align__(1024) uint8_t g_m[9 * 32768];
__device__ __align__(1024) uint8_t g_f[8 * 49152];
__device__ __align__(1024) uint32_t g_km[64 * 32 * 512];
__device__ __align__(1024) uint32_t g_vmt[64 * 32 * 512];
__device__ __align__(1024) float2 g_agg[8 * 1024];
__device__ __align__(1024) float4 g_coef[1024];
__device__ __align__(1024) uint32_t g_cntl[128 * 32];
#define g_cnt(i) g_cntl[(i) * 32]
__device__ __align__(1024) uint32_t g_hint[6144 + 160];
#define SSTAMP(i, cond)
#define PROF(i)
#define GT_EDGE(o)
constexpr int M_SLOT = 32768, F_SLOT = 49152;

constexpr int STAGE = 49152, NSTAGE = 4;
constexpr int S_STG = NSTAGE * STAGE;
constexpr int S_BAR = S_STG + 32768;
constexpr int B_FULL = S_BAR, B_EMPTY = S_BAR + 32, B_RESUME = S_BAR + 64, B_KVFULL = S_BAR + 72, B_GO = S_BAR + 88, B_K = S_BAR + 96, B_PERS = S_BAR + 104, B_INIT = S_BAR + 112, B_RELA = S_BAR + 120, B_V = S_BAR + 128, B_WO = S_BAR + 136,
              B_SFULL = S_BAR + 144, B_SFREE = S_BAR + 160, S_DESC = S_BAR + 176, S_REDO = S_BAR + 256 + 512 + 64, S_EPOCH = S_BAR + 208, B_RELB = S_BAR + 216, B_KVGO = S_BAR + 224, S_DEP = S_BAR + 240, S_CUR = S_BAR + 244, S_TAIL = S_BAR + 248, S_CTA = S_BAR + 252;
constexpr int S_COEF = S_BAR + 256 + 512, S_TOTAL = S_COEF + 1024;
constexpr int S_W1 = 0;
constexpr int S_O = 24 * 4096, S_VL = S_O + 2048, S_MX = 25 * 4096, S_SC = S_MX + 64, S_SUM = S_MX + 128;
constexpr int S_KL = 26 * 4096;
constexpr int S_W2 = 27 * 4096;
constexpr int S_KV = S_W2 + 65536;
constexpr int S_P1 = S_W2 + 98304;
constexpr int S_QX = S_P1 + 16384;
constexpr int S_SX = S_QX + 2048;
static_assert(S_SX + 1280 <= S_BAR, "chain smem overlaps barriers");
constexpr int NR = 40, NS = 64 - NR;

__device__ __forceinline__ uint32_t logical_cta(uint32_t b) {
    const uint32_t c = b / 6, r = b - c * 6;
    return gridDim.x != 96 ? 96 + b : ((r >> 1) + (c >= 8) + (c >= 15)) % 3 * 32 + c * 2 + (r & 1);
}
__device__ __forceinline__ uint32_t cluster_rank() { uint32_t r; asm("mov.u32 %0, %%cluster_ctarank;" : "=r"(r)); return r; }
__device__ __forceinline__ uint16_t pair_mask() { return (uint16_t)(3u << (cluster_rank() & 6)); }
__device__ __forceinline__ void spin_fault() { asm volatile("st.global.u32 [%0], 0;" ::"l"(0ull) : "memory"); }
__device__ __forceinline__ uint32_t smem_u32(const void* p) { return (uint32_t)__cvta_generic_to_shared(p); }
__device__ __forceinline__ uint32_t opq(uint32_t x, int lane) { return __shfl_sync(0xffffffffu, x, lane); }
__device__ __forceinline__ uint32_t mapa(uint32_t a, uint32_t r) { uint32_t d; asm volatile("mapa.shared::cluster.u32 %0, %1, %2;" : "=r"(d) : "r"(a), "r"(r)); return d; }
__device__ __forceinline__ void mma16816(float* d, uint32_t a0, uint32_t a1, uint32_t a2, uint32_t a3, uint32_t b0, uint32_t b1) {
    asm("mma.sync.aligned.m16n8k16.row.col.f32.bf16.bf16.f32 {%0,%1,%2,%3}, {%4,%5,%6,%7}, {%8,%9}, {%0,%1,%2,%3};"
        : "+f"(d[0]), "+f"(d[1]), "+f"(d[2]), "+f"(d[3]) : "r"(a0), "r"(a1), "r"(a2), "r"(a3), "r"(b0), "r"(b1));
}
__device__ __forceinline__ void mma1688(float* d, uint32_t a0, uint32_t a1, uint32_t b0) {
    asm("mma.sync.aligned.m16n8k8.row.col.f32.bf16.bf16.f32 {%0,%1,%2,%3}, {%4,%5}, {%6}, {%0,%1,%2,%3};"
        : "+f"(d[0]), "+f"(d[1]), "+f"(d[2]), "+f"(d[3]) : "r"(a0), "r"(a1), "r"(b0));
}
__device__ __forceinline__ void ldsm4(uint32_t* r, uint32_t a) {
    asm volatile("ldmatrix.sync.aligned.m8n8.x4.shared.b16 {%0,%1,%2,%3}, [%4];" : "=r"(r[0]), "=r"(r[1]), "=r"(r[2]), "=r"(r[3]) : "r"(a));
}
__device__ __forceinline__ void ldsm4t(uint32_t* r, uint32_t a) {
    asm volatile("ldmatrix.sync.aligned.m8n8.x4.trans.shared.b16 {%0,%1,%2,%3}, [%4];" : "=r"(r[0]), "=r"(r[1]), "=r"(r[2]), "=r"(r[3]) : "r"(a));
}
__device__ __forceinline__ void stsm4(uint32_t a, uint32_t r0, uint32_t r1, uint32_t r2, uint32_t r3) {
    asm volatile("stmatrix.sync.aligned.m8n8.x4.shared.b16 [%0], {%1,%2,%3,%4};" ::"r"(a), "r"(r0), "r"(r1), "r"(r2), "r"(r3) : "memory");
}
__device__ __forceinline__ void stsm4t(uint32_t a, uint32_t r0, uint32_t r1, uint32_t r2, uint32_t r3) {
    asm volatile("stmatrix.sync.aligned.m8n8.x4.trans.shared.b16 [%0], {%1,%2,%3,%4};" ::"r"(a), "r"(r0), "r"(r1), "r"(r2), "r"(r3) : "memory");
}
__device__ __forceinline__ uint32_t pack2(float lo, float hi) { uint32_t d; asm("cvt.rn.bf16x2.f32 %0, %1, %2;" : "=r"(d) : "f"(hi), "f"(lo)); return d; }
__device__ __forceinline__ float bf_lo(uint32_t u) { return __uint_as_float(u << 16); }
__device__ __forceinline__ float bf_hi(uint32_t u) { return __uint_as_float(u & 0xffff0000u); }
__device__ __forceinline__ uint32_t hmul2(uint32_t a, uint32_t b) { uint32_t d; asm("mul.rn.bf16x2 %0, %1, %2;" : "=r"(d) : "r"(a), "r"(b)); return d; }
__device__ __forceinline__ float ex2(float x) { float y; asm("ex2.approx.ftz.f32 %0, %1;" : "=f"(y) : "f"(x)); return y; }
__device__ __forceinline__ float rcp(float x) { float y; asm("rcp.approx.ftz.f32 %0, %1;" : "=f"(y) : "f"(x)); return y; }
__device__ __forceinline__ void st_relaxed4(const void* p, uint32_t a, uint32_t b, uint32_t c, uint32_t d) {
    asm volatile("{\n.reg .b128 t;\nmov.b128 t, {%1,%2,%3,%4};\nst.relaxed.gpu.global.b128 [%0], t;\n}" ::"l"(p), "r"(a), "r"(b), "r"(c), "r"(d) : "memory");
}
__device__ __forceinline__ void st_relaxed2(const void* p, uint32_t a, uint32_t b) {
    asm volatile("{\n.reg .b64 t;\nmov.b64 t, {%1,%2};\nst.relaxed.gpu.global.b64 [%0], t;\n}" ::"l"(p), "r"(a), "r"(b) : "memory");
}
__device__ __forceinline__ void ld_relaxed2_if(uint32_t& a, uint32_t& b, const void* p, bool on) {
    asm volatile("{\n.reg .pred P;\n.reg .b64 t;\nsetp.ne.u32 P, %3, 0;\nmov.b64 t, {%0,%1};\n@P ld.relaxed.gpu.global.b64 t, [%2];\nmov.b64 {%0,%1}, t;\n}" : "+r"(a), "+r"(b) : "l"(p), "r"((uint32_t)on) : "memory");
}
__device__ __forceinline__ uint32_t ld_relaxed1(const void* p) { uint32_t v; asm volatile("ld.relaxed.gpu.global.u32 %0, [%1];" : "=r"(v) : "l"(p) : "memory"); return v; }
__device__ __forceinline__ void st_relaxed1(const void* p, uint32_t v) { asm volatile("st.relaxed.gpu.global.u32 [%0], %1;" ::"l"(p), "r"(v) : "memory"); }
__device__ __forceinline__ uint32_t ld_acquire(const void* p) { uint32_t v; asm volatile("ld.acquire.gpu.global.u32 %0, [%1];" : "=r"(v) : "l"(p) : "memory"); return v; }
__device__ __forceinline__ void red_release(void* p) { asm volatile("red.release.gpu.global.add.u32 [%0], 1;" ::"l"(p) : "memory"); }
__device__ __forceinline__ void st_stream2(float* p, float a, float b) { asm volatile("st.global.cs.v2.f32 [%0], {%1, %2};" ::"l"(p), "f"(a), "f"(b) : "memory"); }
__device__ __forceinline__ void fence_acquire() { asm volatile("fence.acquire.gpu;" ::: "memory"); }
__device__ __forceinline__ void fence_release() { asm volatile("fence.release.gpu;" ::: "memory"); }
__device__ __forceinline__ void fence_async() {  asm volatile("fence.proxy.async.global;" ::: "memory"); }
__device__ __forceinline__ void fence_async_smem() { asm volatile("fence.proxy.async.shared::cta;" ::: "memory"); }
__device__ __forceinline__ void wait_count(const uint32_t* p, uint32_t target) {
    int n = 0;
    while ((int32_t)(ld_acquire(p) - target) < 0) { __nanosleep(POLL); if (++n > SPIN_LIMIT) spin_fault(); }
}
__device__ __forceinline__ void bar_sync(int id, int n) { asm volatile("bar.sync %0, %1;" ::"r"(id), "r"(n) : "memory"); }
__device__ __forceinline__ void bar_arrive(int id, int n) { asm volatile("bar.arrive %0, %1;" ::"r"(id), "r"(n) : "memory"); }
__device__ __forceinline__ bool bar_and(int id, bool v) {
    uint32_t r;
    asm volatile("{\n.reg .pred P, Q;\nsetp.ne.u32 Q, %2, 0;\nbar.red.and.pred P, %1, 128, Q;\nselp.u32 %0, 1, 0, P;\n}" : "=r"(r) : "r"(id), "r"((uint32_t)v) : "memory");
    return r;
}
__device__ __forceinline__ void lds128(uint32_t* v, uint32_t a) { asm volatile("ld.shared.v4.b32 {%0,%1,%2,%3}, [%4];" : "=r"(v[0]), "=r"(v[1]), "=r"(v[2]), "=r"(v[3]) : "r"(a) : "memory"); }
__device__ __forceinline__ uint32_t lds32(uint32_t a) { uint32_t v; asm volatile("ld.shared.b32 %0, [%1];" : "=r"(v) : "r"(a) : "memory"); return v; }
__device__ __forceinline__ void lds64f(float* v, uint32_t a) { asm volatile("ld.shared.v2.f32 {%0,%1}, [%2];" : "=f"(v[0]), "=f"(v[1]) : "r"(a) : "memory"); }
__device__ __forceinline__ void sts128(uint32_t a, const uint32_t* v) { asm volatile("st.shared.v4.b32 [%0], {%1,%2,%3,%4};" ::"r"(a), "r"(v[0]), "r"(v[1]), "r"(v[2]), "r"(v[3]) : "memory"); }
__device__ __forceinline__ void sts64(uint32_t a, uint32_t x, uint32_t y) { asm volatile("st.shared.v2.b32 [%0], {%1,%2};" ::"r"(a), "r"(x), "r"(y) : "memory"); }
__device__ __forceinline__ void sts32(uint32_t a, uint32_t x) { asm volatile("st.shared.b32 [%0], %1;" ::"r"(a), "r"(x) : "memory"); }
__device__ __forceinline__ bool mbar_try(uint32_t b, uint32_t par) {
    uint32_t ok;
    asm volatile("{\n.reg .pred P;\nmbarrier.try_wait.parity.shared::cta.b64 P, [%1], %2;\nselp.u32 %0, 1, 0, P;\n}" : "=r"(ok) : "r"(b), "r"(par) : "memory");
    return ok;
}
__device__ __forceinline__ bool mbar_test(uint32_t b, uint32_t par) {
    uint32_t ok;
    asm volatile("{\n.reg .pred P;\nmbarrier.test_wait.parity.shared::cta.b64 P, [%1], %2;\nselp.u32 %0, 1, 0, P;\n}" : "=r"(ok) : "r"(b), "r"(par) : "memory");
    return ok;
}
__device__ __forceinline__ void mbar_wait(uint32_t b, uint32_t par) { int n = 0; while (!mbar_try(b, par)) { if (++n > SPIN_LIMIT) spin_fault(); } }
__device__ __forceinline__ void mbar_init(uint32_t b, uint32_t n) { asm volatile("mbarrier.init.shared::cta.b64 [%0], %1;" ::"r"(b), "r"(n) : "memory"); }
__device__ __forceinline__ void mbar_expect(uint32_t b, uint32_t bytes) { asm volatile("mbarrier.arrive.expect_tx.shared::cta.b64 _, [%0], %1;" ::"r"(b), "r"(bytes) : "memory"); }
__device__ __forceinline__ void mbar_arrive(uint32_t b) { asm volatile("mbarrier.arrive.shared::cta.b64 _, [%0];" ::"r"(b) : "memory"); }
__device__ __forceinline__ void mbar_arrive_cluster(uint32_t b) { asm volatile("mbarrier.arrive.shared::cluster.b64 _, [%0];" ::"r"(b) : "memory"); }
__device__ __forceinline__ void st_async1(uint32_t a, uint32_t x, uint32_t bar) {
    asm volatile("st.async.weak.shared::cluster.mbarrier::complete_tx::bytes.b32 [%0], %1, [%2];" ::"r"(a), "r"(x), "r"(bar) : "memory");
}
__device__ __forceinline__ void st_async2(uint32_t a, uint32_t x, uint32_t y, uint32_t bar) {
    asm volatile("st.async.weak.shared::cluster.mbarrier::complete_tx::bytes.v2.b32 [%0], {%1,%2}, [%3];" ::"r"(a), "r"(x), "r"(y), "r"(bar) : "memory");
}
__device__ __forceinline__ void cluster_arrive() { asm volatile("barrier.cluster.arrive.relaxed.aligned;" ::: "memory"); }
__device__ __forceinline__ void cluster_wait() { asm volatile("barrier.cluster.wait.aligned;" ::: "memory"); }
constexpr uint64_t EVICT_FIRST = 0x12F0000000000000ull, EVICT_NORMAL = 0x1000000000000000ull;
__device__ __forceinline__ void tma2d(uint32_t dst, const CUtensorMap* m, int c0, int c1, uint32_t bar, uint64_t pol) {
    asm volatile("cp.async.bulk.tensor.2d.shared::cluster.global.mbarrier::complete_tx::bytes.L2::cache_hint [%0], [%1, {%2, %3}], [%4], %5;" ::"r"(dst), "l"(m), "r"(c0), "r"(c1), "r"(bar), "l"(pol) : "memory");
}
__device__ __forceinline__ void tma4d(uint32_t dst, const CUtensorMap* m, int c0, int c3, uint32_t bar, uint64_t pol) {
    asm volatile("cp.async.bulk.tensor.4d.shared::cluster.global.mbarrier::complete_tx::bytes.L2::cache_hint [%0], [%1, {%2, 0, 0, %3}], [%4], %5;" ::"r"(dst), "l"(m), "r"(c0), "r"(c3), "r"(bar), "l"(pol) : "memory");
}
__device__ __forceinline__ void tma3d(uint32_t dst, const CUtensorMap* m, int c0, int c1, int c2, uint32_t bar, uint64_t pol) {
    asm volatile("cp.async.bulk.tensor.3d.shared::cluster.global.mbarrier::complete_tx::bytes.L2::cache_hint [%0], [%1, {%2, %3, %4}], [%5], %6;" ::"r"(dst), "l"(m), "r"(c0), "r"(c1), "r"(c2), "r"(bar), "l"(pol) : "memory");
}
__device__ __forceinline__ void tma_store2d(const CUtensorMap* m, int c0, int c1, uint32_t src, uint64_t pol) {
    asm volatile("cp.async.bulk.tensor.2d.global.shared::cta.bulk_group.L2::cache_hint [%0, {%1, %2}], [%3], %4;" ::"l"(m), "r"(c0), "r"(c1), "r"(src), "l"(pol) : "memory");
}
#define EF 63
#define POL(bit) ((EF >> (bit)) & 1 ? EVICT_FIRST : EVICT_NORMAL)
__device__ __forceinline__ void tma2d_mc(uint32_t dst, const CUtensorMap* m, int c0, int c1, uint32_t bar, uint64_t pol) {
    asm volatile("cp.async.bulk.tensor.2d.shared::cluster.global.mbarrier::complete_tx::bytes.multicast::cluster.L2::cache_hint [%0], [%1, {%2, %3}], [%4], %5, %6;" ::"r"(dst), "l"(m), "r"(c0), "r"(c1), "r"(bar), "h"(pair_mask()), "l"(pol) : "memory");
}
__device__ __forceinline__ void tma3d_mc(uint32_t dst, const CUtensorMap* m, int c0, int c1, int c2, uint32_t bar, uint64_t pol) {
    asm volatile("cp.async.bulk.tensor.3d.shared::cluster.global.mbarrier::complete_tx::bytes.multicast::cluster.L2::cache_hint [%0], [%1, {%2, %3, %4}], [%5], %6, %7;" ::"r"(dst), "l"(m), "r"(c0), "r"(c1), "r"(c2), "r"(bar), "h"(pair_mask()), "l"(pol) : "memory");
}
__device__ __forceinline__ void tma4d_mc(uint32_t dst, const CUtensorMap* m, int c0, int c3, uint32_t bar, uint64_t pol) {
    asm volatile("cp.async.bulk.tensor.4d.shared::cluster.global.mbarrier::complete_tx::bytes.multicast::cluster.L2::cache_hint [%0], [%1, {%2, 0, 0, %3}], [%4], %5, %6;" ::"r"(dst), "l"(m), "r"(c0), "r"(c3), "r"(bar), "h"(pair_mask()), "l"(pol) : "memory");
}
__device__ __forceinline__ void map_prefetch(const CUtensorMap* m) { asm volatile("prefetch.tensormap [%0];" ::"l"(m) : "memory"); }
__device__ __forceinline__ void bulk_g2s(uint32_t dst, const void* src, uint32_t bytes, uint32_t bar) {
    asm volatile("cp.async.bulk.shared::cluster.global.mbarrier::complete_tx::bytes [%0], [%1], %2, [%3];" ::"r"(dst), "l"(src), "r"(bytes), "r"(bar) : "memory");
}
__device__ __forceinline__ void bulk_s2g(void* dst, uint32_t src, uint32_t bytes) {
    asm volatile("cp.async.bulk.global.shared::cta.bulk_group [%0], [%1], %2;" ::"l"(dst), "r"(src), "r"(bytes) : "memory");
}
__device__ __forceinline__ void bulk_commit() { asm volatile("cp.async.bulk.commit_group;" ::: "memory"); }
__device__ __forceinline__ void bulk_wait_read() { asm volatile("cp.async.bulk.wait_group.read 0;" ::: "memory"); }
__device__ __forceinline__ void bulk_wait_all() { asm volatile("cp.async.bulk.wait_group 0;" ::: "memory"); }
__device__ __forceinline__ uint64_t mkdesc(uint32_t addr, uint32_t lbo, uint32_t sbo, uint32_t swz) {
    return (uint64_t)((addr & 0x3FFFF) >> 4) | ((uint64_t)(lbo >> 4) << 16) | ((uint64_t)(sbo >> 4) << 32) | ((uint64_t)swz << 62);
}
__device__ __forceinline__ void wg_fence() { asm volatile("wgmma.fence.sync.aligned;" ::: "memory"); }
__device__ __forceinline__ void wg_commit() { asm volatile("wgmma.commit_group.sync.aligned;" ::: "memory"); }
template <int N> __device__ __forceinline__ void wg_wait() { asm volatile("wgmma.wait_group.sync.aligned %0;" ::"n"(N) : "memory"); }
template <typename T> __device__ __forceinline__ void pin_ptr(T*& p) { asm volatile("" : "+l"(p)); }
template <int N> __device__ __forceinline__ void pin(uint32_t* d) {
#pragma unroll
    for (int i = 0; i < N; i++) asm volatile("" : "+r"(d[i])::"memory");
}
template <int N> __device__ __forceinline__ void pin(float* d) {
#pragma unroll
    for (int i = 0; i < N; i++) asm volatile("" : "+f"(d[i])::"memory");
}

template <int TA, int TB>
__device__ __forceinline__ void wgmma_ss256(float* d, uint64_t da, uint64_t db) {
    asm volatile("wgmma.mma_async.sync.aligned.m64n256k16.f32.bf16.bf16 "
        "{%0, %1, %2, %3, %4, %5, %6, %7, %8, %9, %10, %11, %12, %13, %14, %15, %16, %17, %18, %19, %20, %21, %22, %23, %24, %25, %26, %27, %28, %29, %30, %31, %32, %33, %34, %35, %36, %37, %38, %39, %40, %41, %42, %43, %44, %45, %46, %47, %48, %49, %50, %51, %52, %53, %54, %55, %56, %57, %58, %59, %60, %61, %62, %63, %64, %65, %66, %67, %68, %69, %70, %71, %72, %73, %74, %75, %76, %77, %78, %79, %80, %81, %82, %83, %84, %85, %86, %87, %88, %89, %90, %91, %92, %93, %94, %95, %96, %97, %98, %99, %100, %101, %102, %103, %104, %105, %106, %107, %108, %109, %110, %111, %112, %113, %114, %115, %116, %117, %118, %119, %120, %121, %122, %123, %124, %125, %126, %127}, %128, %129, 1, 1, 1, %130, %131;"
        : "+f"(d[0]), "+f"(d[1]), "+f"(d[2]), "+f"(d[3]), "+f"(d[4]), "+f"(d[5]), "+f"(d[6]), "+f"(d[7]), "+f"(d[8]), "+f"(d[9]), "+f"(d[10]), "+f"(d[11]), "+f"(d[12]), "+f"(d[13]), "+f"(d[14]), "+f"(d[15]), "+f"(d[16]), "+f"(d[17]), "+f"(d[18]), "+f"(d[19]), "+f"(d[20]), "+f"(d[21]), "+f"(d[22]), "+f"(d[23]), "+f"(d[24]), "+f"(d[25]), "+f"(d[26]), "+f"(d[27]), "+f"(d[28]), "+f"(d[29]), "+f"(d[30]), "+f"(d[31]), "+f"(d[32]), "+f"(d[33]), "+f"(d[34]), "+f"(d[35]), "+f"(d[36]), "+f"(d[37]), "+f"(d[38]), "+f"(d[39]), "+f"(d[40]), "+f"(d[41]), "+f"(d[42]), "+f"(d[43]), "+f"(d[44]), "+f"(d[45]), "+f"(d[46]), "+f"(d[47]), "+f"(d[48]), "+f"(d[49]), "+f"(d[50]), "+f"(d[51]), "+f"(d[52]), "+f"(d[53]), "+f"(d[54]), "+f"(d[55]), "+f"(d[56]), "+f"(d[57]), "+f"(d[58]), "+f"(d[59]), "+f"(d[60]), "+f"(d[61]), "+f"(d[62]), "+f"(d[63]), "+f"(d[64]), "+f"(d[65]), "+f"(d[66]), "+f"(d[67]), "+f"(d[68]), "+f"(d[69]), "+f"(d[70]), "+f"(d[71]), "+f"(d[72]), "+f"(d[73]), "+f"(d[74]), "+f"(d[75]), "+f"(d[76]), "+f"(d[77]), "+f"(d[78]), "+f"(d[79]), "+f"(d[80]), "+f"(d[81]), "+f"(d[82]), "+f"(d[83]), "+f"(d[84]), "+f"(d[85]), "+f"(d[86]), "+f"(d[87]), "+f"(d[88]), "+f"(d[89]), "+f"(d[90]), "+f"(d[91]), "+f"(d[92]), "+f"(d[93]), "+f"(d[94]), "+f"(d[95]), "+f"(d[96]), "+f"(d[97]), "+f"(d[98]), "+f"(d[99]), "+f"(d[100]), "+f"(d[101]), "+f"(d[102]), "+f"(d[103]), "+f"(d[104]), "+f"(d[105]), "+f"(d[106]), "+f"(d[107]), "+f"(d[108]), "+f"(d[109]), "+f"(d[110]), "+f"(d[111]), "+f"(d[112]), "+f"(d[113]), "+f"(d[114]), "+f"(d[115]), "+f"(d[116]), "+f"(d[117]), "+f"(d[118]), "+f"(d[119]), "+f"(d[120]), "+f"(d[121]), "+f"(d[122]), "+f"(d[123]), "+f"(d[124]), "+f"(d[125]), "+f"(d[126]), "+f"(d[127])
        : "l"(da), "l"(db), "n"(TA), "n"(TB));
}
template <int TA, int TB>
__device__ __forceinline__ void wgmma_ss256_first(float* d, uint64_t da, uint64_t db) {
    asm volatile("wgmma.mma_async.sync.aligned.m64n256k16.f32.bf16.bf16 "
        "{%0, %1, %2, %3, %4, %5, %6, %7, %8, %9, %10, %11, %12, %13, %14, %15, %16, %17, %18, %19, %20, %21, %22, %23, %24, %25, %26, %27, %28, %29, %30, %31, %32, %33, %34, %35, %36, %37, %38, %39, %40, %41, %42, %43, %44, %45, %46, %47, %48, %49, %50, %51, %52, %53, %54, %55, %56, %57, %58, %59, %60, %61, %62, %63, %64, %65, %66, %67, %68, %69, %70, %71, %72, %73, %74, %75, %76, %77, %78, %79, %80, %81, %82, %83, %84, %85, %86, %87, %88, %89, %90, %91, %92, %93, %94, %95, %96, %97, %98, %99, %100, %101, %102, %103, %104, %105, %106, %107, %108, %109, %110, %111, %112, %113, %114, %115, %116, %117, %118, %119, %120, %121, %122, %123, %124, %125, %126, %127}, %128, %129, 0, 1, 1, %130, %131;"
        : "=f"(d[0]), "=f"(d[1]), "=f"(d[2]), "=f"(d[3]), "=f"(d[4]), "=f"(d[5]), "=f"(d[6]), "=f"(d[7]), "=f"(d[8]), "=f"(d[9]), "=f"(d[10]), "=f"(d[11]), "=f"(d[12]), "=f"(d[13]), "=f"(d[14]), "=f"(d[15]), "=f"(d[16]), "=f"(d[17]), "=f"(d[18]), "=f"(d[19]), "=f"(d[20]), "=f"(d[21]), "=f"(d[22]), "=f"(d[23]), "=f"(d[24]), "=f"(d[25]), "=f"(d[26]), "=f"(d[27]), "=f"(d[28]), "=f"(d[29]), "=f"(d[30]), "=f"(d[31]), "=f"(d[32]), "=f"(d[33]), "=f"(d[34]), "=f"(d[35]), "=f"(d[36]), "=f"(d[37]), "=f"(d[38]), "=f"(d[39]), "=f"(d[40]), "=f"(d[41]), "=f"(d[42]), "=f"(d[43]), "=f"(d[44]), "=f"(d[45]), "=f"(d[46]), "=f"(d[47]), "=f"(d[48]), "=f"(d[49]), "=f"(d[50]), "=f"(d[51]), "=f"(d[52]), "=f"(d[53]), "=f"(d[54]), "=f"(d[55]), "=f"(d[56]), "=f"(d[57]), "=f"(d[58]), "=f"(d[59]), "=f"(d[60]), "=f"(d[61]), "=f"(d[62]), "=f"(d[63]), "=f"(d[64]), "=f"(d[65]), "=f"(d[66]), "=f"(d[67]), "=f"(d[68]), "=f"(d[69]), "=f"(d[70]), "=f"(d[71]), "=f"(d[72]), "=f"(d[73]), "=f"(d[74]), "=f"(d[75]), "=f"(d[76]), "=f"(d[77]), "=f"(d[78]), "=f"(d[79]), "=f"(d[80]), "=f"(d[81]), "=f"(d[82]), "=f"(d[83]), "=f"(d[84]), "=f"(d[85]), "=f"(d[86]), "=f"(d[87]), "=f"(d[88]), "=f"(d[89]), "=f"(d[90]), "=f"(d[91]), "=f"(d[92]), "=f"(d[93]), "=f"(d[94]), "=f"(d[95]), "=f"(d[96]), "=f"(d[97]), "=f"(d[98]), "=f"(d[99]), "=f"(d[100]), "=f"(d[101]), "=f"(d[102]), "=f"(d[103]), "=f"(d[104]), "=f"(d[105]), "=f"(d[106]), "=f"(d[107]), "=f"(d[108]), "=f"(d[109]), "=f"(d[110]), "=f"(d[111]), "=f"(d[112]), "=f"(d[113]), "=f"(d[114]), "=f"(d[115]), "=f"(d[116]), "=f"(d[117]), "=f"(d[118]), "=f"(d[119]), "=f"(d[120]), "=f"(d[121]), "=f"(d[122]), "=f"(d[123]), "=f"(d[124]), "=f"(d[125]), "=f"(d[126]), "=f"(d[127])
        : "l"(da), "l"(db), "n"(TA), "n"(TB));
}
template <int TA, int TB>
__device__ __forceinline__ void wgmma_ss128(float* d, uint64_t da, uint64_t db) {
    asm volatile("wgmma.mma_async.sync.aligned.m64n128k16.f32.bf16.bf16 "
        "{%0, %1, %2, %3, %4, %5, %6, %7, %8, %9, %10, %11, %12, %13, %14, %15, %16, %17, %18, %19, %20, %21, %22, %23, %24, %25, %26, %27, %28, %29, %30, %31, %32, %33, %34, %35, %36, %37, %38, %39, %40, %41, %42, %43, %44, %45, %46, %47, %48, %49, %50, %51, %52, %53, %54, %55, %56, %57, %58, %59, %60, %61, %62, %63}, %64, %65, 1, 1, 1, %66, %67;"
        : "+f"(d[0]), "+f"(d[1]), "+f"(d[2]), "+f"(d[3]), "+f"(d[4]), "+f"(d[5]), "+f"(d[6]), "+f"(d[7]), "+f"(d[8]), "+f"(d[9]), "+f"(d[10]), "+f"(d[11]), "+f"(d[12]), "+f"(d[13]), "+f"(d[14]), "+f"(d[15]), "+f"(d[16]), "+f"(d[17]), "+f"(d[18]), "+f"(d[19]), "+f"(d[20]), "+f"(d[21]), "+f"(d[22]), "+f"(d[23]), "+f"(d[24]), "+f"(d[25]), "+f"(d[26]), "+f"(d[27]), "+f"(d[28]), "+f"(d[29]), "+f"(d[30]), "+f"(d[31]), "+f"(d[32]), "+f"(d[33]), "+f"(d[34]), "+f"(d[35]), "+f"(d[36]), "+f"(d[37]), "+f"(d[38]), "+f"(d[39]), "+f"(d[40]), "+f"(d[41]), "+f"(d[42]), "+f"(d[43]), "+f"(d[44]), "+f"(d[45]), "+f"(d[46]), "+f"(d[47]), "+f"(d[48]), "+f"(d[49]), "+f"(d[50]), "+f"(d[51]), "+f"(d[52]), "+f"(d[53]), "+f"(d[54]), "+f"(d[55]), "+f"(d[56]), "+f"(d[57]), "+f"(d[58]), "+f"(d[59]), "+f"(d[60]), "+f"(d[61]), "+f"(d[62]), "+f"(d[63])
        : "l"(da), "l"(db), "n"(TA), "n"(TB));
}
template <int TA, int TB>
__device__ __forceinline__ void wgmma_ss128_first(float* d, uint64_t da, uint64_t db) {
    asm volatile("wgmma.mma_async.sync.aligned.m64n128k16.f32.bf16.bf16 "
        "{%0, %1, %2, %3, %4, %5, %6, %7, %8, %9, %10, %11, %12, %13, %14, %15, %16, %17, %18, %19, %20, %21, %22, %23, %24, %25, %26, %27, %28, %29, %30, %31, %32, %33, %34, %35, %36, %37, %38, %39, %40, %41, %42, %43, %44, %45, %46, %47, %48, %49, %50, %51, %52, %53, %54, %55, %56, %57, %58, %59, %60, %61, %62, %63}, %64, %65, 0, 1, 1, %66, %67;"
        : "=f"(d[0]), "=f"(d[1]), "=f"(d[2]), "=f"(d[3]), "=f"(d[4]), "=f"(d[5]), "=f"(d[6]), "=f"(d[7]), "=f"(d[8]), "=f"(d[9]), "=f"(d[10]), "=f"(d[11]), "=f"(d[12]), "=f"(d[13]), "=f"(d[14]), "=f"(d[15]), "=f"(d[16]), "=f"(d[17]), "=f"(d[18]), "=f"(d[19]), "=f"(d[20]), "=f"(d[21]), "=f"(d[22]), "=f"(d[23]), "=f"(d[24]), "=f"(d[25]), "=f"(d[26]), "=f"(d[27]), "=f"(d[28]), "=f"(d[29]), "=f"(d[30]), "=f"(d[31]), "=f"(d[32]), "=f"(d[33]), "=f"(d[34]), "=f"(d[35]), "=f"(d[36]), "=f"(d[37]), "=f"(d[38]), "=f"(d[39]), "=f"(d[40]), "=f"(d[41]), "=f"(d[42]), "=f"(d[43]), "=f"(d[44]), "=f"(d[45]), "=f"(d[46]), "=f"(d[47]), "=f"(d[48]), "=f"(d[49]), "=f"(d[50]), "=f"(d[51]), "=f"(d[52]), "=f"(d[53]), "=f"(d[54]), "=f"(d[55]), "=f"(d[56]), "=f"(d[57]), "=f"(d[58]), "=f"(d[59]), "=f"(d[60]), "=f"(d[61]), "=f"(d[62]), "=f"(d[63])
        : "l"(da), "l"(db), "n"(TA), "n"(TB));
}
template <int TB>
__device__ __forceinline__ void wgmma_rs128(float* d, const uint32_t* a, uint64_t db) {
    asm volatile("wgmma.mma_async.sync.aligned.m64n128k16.f32.bf16.bf16 "
        "{%0, %1, %2, %3, %4, %5, %6, %7, %8, %9, %10, %11, %12, %13, %14, %15, %16, %17, %18, %19, %20, %21, %22, %23, %24, %25, %26, %27, %28, %29, %30, %31, %32, %33, %34, %35, %36, %37, %38, %39, %40, %41, %42, %43, %44, %45, %46, %47, %48, %49, %50, %51, %52, %53, %54, %55, %56, %57, %58, %59, %60, %61, %62, %63}, {%64, %65, %66, %67}, %68, 1, 1, 1, %69;"
        : "+f"(d[0]), "+f"(d[1]), "+f"(d[2]), "+f"(d[3]), "+f"(d[4]), "+f"(d[5]), "+f"(d[6]), "+f"(d[7]), "+f"(d[8]), "+f"(d[9]), "+f"(d[10]), "+f"(d[11]), "+f"(d[12]), "+f"(d[13]), "+f"(d[14]), "+f"(d[15]), "+f"(d[16]), "+f"(d[17]), "+f"(d[18]), "+f"(d[19]), "+f"(d[20]), "+f"(d[21]), "+f"(d[22]), "+f"(d[23]), "+f"(d[24]), "+f"(d[25]), "+f"(d[26]), "+f"(d[27]), "+f"(d[28]), "+f"(d[29]), "+f"(d[30]), "+f"(d[31]), "+f"(d[32]), "+f"(d[33]), "+f"(d[34]), "+f"(d[35]), "+f"(d[36]), "+f"(d[37]), "+f"(d[38]), "+f"(d[39]), "+f"(d[40]), "+f"(d[41]), "+f"(d[42]), "+f"(d[43]), "+f"(d[44]), "+f"(d[45]), "+f"(d[46]), "+f"(d[47]), "+f"(d[48]), "+f"(d[49]), "+f"(d[50]), "+f"(d[51]), "+f"(d[52]), "+f"(d[53]), "+f"(d[54]), "+f"(d[55]), "+f"(d[56]), "+f"(d[57]), "+f"(d[58]), "+f"(d[59]), "+f"(d[60]), "+f"(d[61]), "+f"(d[62]), "+f"(d[63])
        : "r"(a[0]), "r"(a[1]), "r"(a[2]), "r"(a[3]), "l"(db), "n"(TB));
}
template <int TB>
__device__ __forceinline__ void wgmma_rs128_first(float* d, const uint32_t* a, uint64_t db) {
    asm volatile("wgmma.mma_async.sync.aligned.m64n128k16.f32.bf16.bf16 "
        "{%0, %1, %2, %3, %4, %5, %6, %7, %8, %9, %10, %11, %12, %13, %14, %15, %16, %17, %18, %19, %20, %21, %22, %23, %24, %25, %26, %27, %28, %29, %30, %31, %32, %33, %34, %35, %36, %37, %38, %39, %40, %41, %42, %43, %44, %45, %46, %47, %48, %49, %50, %51, %52, %53, %54, %55, %56, %57, %58, %59, %60, %61, %62, %63}, {%64, %65, %66, %67}, %68, 0, 1, 1, %69;"
        : "=f"(d[0]), "=f"(d[1]), "=f"(d[2]), "=f"(d[3]), "=f"(d[4]), "=f"(d[5]), "=f"(d[6]), "=f"(d[7]), "=f"(d[8]), "=f"(d[9]), "=f"(d[10]), "=f"(d[11]), "=f"(d[12]), "=f"(d[13]), "=f"(d[14]), "=f"(d[15]), "=f"(d[16]), "=f"(d[17]), "=f"(d[18]), "=f"(d[19]), "=f"(d[20]), "=f"(d[21]), "=f"(d[22]), "=f"(d[23]), "=f"(d[24]), "=f"(d[25]), "=f"(d[26]), "=f"(d[27]), "=f"(d[28]), "=f"(d[29]), "=f"(d[30]), "=f"(d[31]), "=f"(d[32]), "=f"(d[33]), "=f"(d[34]), "=f"(d[35]), "=f"(d[36]), "=f"(d[37]), "=f"(d[38]), "=f"(d[39]), "=f"(d[40]), "=f"(d[41]), "=f"(d[42]), "=f"(d[43]), "=f"(d[44]), "=f"(d[45]), "=f"(d[46]), "=f"(d[47]), "=f"(d[48]), "=f"(d[49]), "=f"(d[50]), "=f"(d[51]), "=f"(d[52]), "=f"(d[53]), "=f"(d[54]), "=f"(d[55]), "=f"(d[56]), "=f"(d[57]), "=f"(d[58]), "=f"(d[59]), "=f"(d[60]), "=f"(d[61]), "=f"(d[62]), "=f"(d[63])
        : "r"(a[0]), "r"(a[1]), "r"(a[2]), "r"(a[3]), "l"(db), "n"(TB));
}
template <int TB>
__device__ __forceinline__ void wgmma_rs64(float* d, const uint32_t* a, uint64_t db) {
    asm volatile("wgmma.mma_async.sync.aligned.m64n64k16.f32.bf16.bf16 "
        "{%0, %1, %2, %3, %4, %5, %6, %7, %8, %9, %10, %11, %12, %13, %14, %15, %16, %17, %18, %19, %20, %21, %22, %23, %24, %25, %26, %27, %28, %29, %30, %31}, {%32, %33, %34, %35}, %36, 1, 1, 1, %37;"
        : "+f"(d[0]), "+f"(d[1]), "+f"(d[2]), "+f"(d[3]), "+f"(d[4]), "+f"(d[5]), "+f"(d[6]), "+f"(d[7]), "+f"(d[8]), "+f"(d[9]), "+f"(d[10]), "+f"(d[11]), "+f"(d[12]), "+f"(d[13]), "+f"(d[14]), "+f"(d[15]), "+f"(d[16]), "+f"(d[17]), "+f"(d[18]), "+f"(d[19]), "+f"(d[20]), "+f"(d[21]), "+f"(d[22]), "+f"(d[23]), "+f"(d[24]), "+f"(d[25]), "+f"(d[26]), "+f"(d[27]), "+f"(d[28]), "+f"(d[29]), "+f"(d[30]), "+f"(d[31])
        : "r"(a[0]), "r"(a[1]), "r"(a[2]), "r"(a[3]), "l"(db), "n"(TB));
}
template <int TB>
__device__ __forceinline__ void wgmma_rs64_first(float* d, const uint32_t* a, uint64_t db) {
    asm volatile("wgmma.mma_async.sync.aligned.m64n64k16.f32.bf16.bf16 "
        "{%0, %1, %2, %3, %4, %5, %6, %7, %8, %9, %10, %11, %12, %13, %14, %15, %16, %17, %18, %19, %20, %21, %22, %23, %24, %25, %26, %27, %28, %29, %30, %31}, {%32, %33, %34, %35}, %36, 0, 1, 1, %37;"
        : "=f"(d[0]), "=f"(d[1]), "=f"(d[2]), "=f"(d[3]), "=f"(d[4]), "=f"(d[5]), "=f"(d[6]), "=f"(d[7]), "=f"(d[8]), "=f"(d[9]), "=f"(d[10]), "=f"(d[11]), "=f"(d[12]), "=f"(d[13]), "=f"(d[14]), "=f"(d[15]), "=f"(d[16]), "=f"(d[17]), "=f"(d[18]), "=f"(d[19]), "=f"(d[20]), "=f"(d[21]), "=f"(d[22]), "=f"(d[23]), "=f"(d[24]), "=f"(d[25]), "=f"(d[26]), "=f"(d[27]), "=f"(d[28]), "=f"(d[29]), "=f"(d[30]), "=f"(d[31])
        : "r"(a[0]), "r"(a[1]), "r"(a[2]), "r"(a[3]), "l"(db), "n"(TB));
}
template <int TB>
__device__ __forceinline__ void wgmma_rs16(float* d, const uint32_t* a, uint64_t db) {
    asm volatile("wgmma.mma_async.sync.aligned.m64n16k16.f32.bf16.bf16 "
        "{%0, %1, %2, %3, %4, %5, %6, %7}, {%8, %9, %10, %11}, %12, 1, 1, 1, %13;"
        : "+f"(d[0]), "+f"(d[1]), "+f"(d[2]), "+f"(d[3]), "+f"(d[4]), "+f"(d[5]), "+f"(d[6]), "+f"(d[7])
        : "r"(a[0]), "r"(a[1]), "r"(a[2]), "r"(a[3]), "l"(db), "n"(TB));
}
template <int TB>
__device__ __forceinline__ void wgmma_rs16_first(float* d, const uint32_t* a, uint64_t db) {
    asm volatile("wgmma.mma_async.sync.aligned.m64n16k16.f32.bf16.bf16 "
        "{%0, %1, %2, %3, %4, %5, %6, %7}, {%8, %9, %10, %11}, %12, 0, 1, 1, %13;"
        : "=f"(d[0]), "=f"(d[1]), "=f"(d[2]), "=f"(d[3]), "=f"(d[4]), "=f"(d[5]), "=f"(d[6]), "=f"(d[7])
        : "r"(a[0]), "r"(a[1]), "r"(a[2]), "r"(a[3]), "l"(db), "n"(TB));
}

__device__ __forceinline__ uint32_t delay_loop(int n, uint32_t x0) {
    uint32_t z;
    asm volatile("{\n.reg .pred P;\n.reg .u32 c, x;\nmov.u32 c, %1;\nmov.u32 x, %2;\nDL: mad.lo.u32 x, x, 1664525, 1013904223;\nadd.u32 c, c, -1;\nsetp.gt.s32 P, c, 0;\n@P bra DL;\n"
                 "setp.eq.u32 P, x, 0x7fffffff;\nselp.u32 %0, 16, 0, P;\n}" : "=r"(z) : "r"(n), "r"(x0) : "memory");
    return z;
}
__device__ __forceinline__ uint32_t gtime() { uint32_t t; asm volatile("mov.u32 %0, %%globaltimer_lo;" : "=r"(t)); return t; }
__device__ __forceinline__ void wait_time(uint32_t t, uint32_t sb) { while ((int32_t)(gtime() - t) < (int32_t)delay_loop(2, sb)) {} }
__device__ __forceinline__ uint32_t tpc_gpc(uint32_t t) { return t < 32 ? t & 7 : t < 60 ? (t - 32) % 7 + 1 : (t - 54) & 7; }
__device__ __forceinline__ uint32_t latest_stamp(const uint32_t* p, uint32_t seq, uint32_t ref, int backoff, uint32_t sb) {
    for (int n = 0;; n++) {
        uint32_t bad = 0; int32_t m = INT32_MIN;
#pragma unroll
        for (int i = 0; i < 3; i++) { const uint32_t v = ld_relaxed1(p + i * 256); bad |= (v ^ seq) & 31u; m = max(m, (int32_t)(v - (ref << 5)) >> 5); }
        if (__all_sync(0xffffffffu, bad == 0)) return ref + __reduce_max_sync(0xffffffffu, m);
        wait_time(gtime() + backoff, sb);
        if (n > SPIN_LIMIT) spin_fault();
    }
}
__device__ __forceinline__ void release_at(uint32_t t, uint32_t sb, uint32_t bar, int lane) {
    wait_time(t, sb);
    if (lane == 0) mbar_arrive(sb + bar);
}
__host__ __device__ constexpr int frag_word(int u, int f) { return (u == 0 ? 0 : u < 3 ? 3 * u - 1 : u == 3 ? 14 : 3 * u - 4) + f; }
__host__ __device__ constexpr int word_col(int e) { return ((0x32FED987CBA65410ull >> (4 * e)) & 14) * 64 + ((0x32FED987CBA65410ull >> (4 * e)) & 1) * 8; }

constexpr uint32_t CLEAR_LO = 0xFE000000u, CLEAR_HI = 0x5A7FEFEFu;
__device__ __forceinline__ void clear_slot(const Params& P, int slot, int cta, int lane) {
    const int i = cta * 2 + (lane >> 3), x = i & 63;
    if (lane < 16) st_relaxed4(P.gm + slot * M_SLOT + (x >> 1) * 1024 + (x & 1) * 256 + (i >> 7) * 512 + ((i >> 6) & 1) * 128 + (lane & 7) * 16, CLEAR_LO, CLEAR_HI, CLEAR_LO, CLEAR_HI);
    st_relaxed4(g_f + slot * F_SLOT + cta * 512 + lane * 16, 0, 0, 0, 0);
}
__device__ __forceinline__ void mem0_max(const Params& P, uint32_t sb, int tid) {
    uint32_t m = 0;
#pragma unroll
    for (int i = 0; i < 4; i++) {
        const uint4 x = __ldg((const uint4*)P.mem0 + i * 256 + tid);
        m = __vmaxu2(__vmaxu2(__vmaxu2(x.x & 0x7fff7fffu, x.y & 0x7fff7fffu), __vmaxu2(x.z & 0x7fff7fffu, x.w & 0x7fff7fffu)), m);
    }
    sts32(sb + S_COEF + (tid >> 5) * 4, __reduce_max_sync(0xffffffffu, max(m >> 16, m & 0xffffu)));
    bar_arrive(7, 288);
}
__device__ __forceinline__ uint32_t pack_mem0(const Params& P, uint32_t sb, int cta, int lane) {
    bar_sync(7, 288);
    const uint32_t e = __reduce_max_sync(0xffffffffu, lds32(sb + S_COEF + (lane & 7) * 4)) >> 7;
    if (e < 64 || e > 192) return 0x3F803F80u;
    const int i = cta * 2 + (lane >> 4), u = (i >> 5), x = i & 63, L = (i & 3) * 8 + ((lane & 15) >> 1);
    uint64_t w = 32;
#pragma unroll
    for (int f = 0; f < 3; f++) if (f < 2 || u % 3) {
        const float v = __bfloat162float(P.mem0[(L >> 2) * 1024 + word_col(frag_word(u, f)) + ((i >> 2) & 7) * 16 + (L & 3) * 2 + (lane & 1)]);
        w += (uint64_t)(int64_t)__float2int_rn(v * __uint_as_float((271 - e) << 23)) << (45 - 19 * f);
    }
    st_relaxed2(P.gm + 7 * M_SLOT + (x >> 1) * 1024 + (x & 1) * 256 + (i >> 7) * 512 + ((i >> 6) & 1) * 128 + (lane & 15) * 8, (uint32_t)w, (uint32_t)(w >> 32));
    return (e - 30) * 0x00800080u;
}
__device__ __forceinline__ void pacer(const Params& P, const uint32_t sb, const int lane) {
    constexpr uint32_t base = 2;
    int cta = lds32(sb + S_CTA);
#pragma unroll 1
    for (int i = 0; i < 8; i++) clear_slot(P, i, cta, lane);
    __syncwarp();
    if (lane == 0) { uint32_t smid; asm("mov.u32 %0, %%smid;" : "=r"(smid)); st_relaxed1(g_hint + 6144 + cta, smid >> 1); }
    sts32(sb + S_EPOCH + 4, pack_mem0(P, sb, cta, lane));
    fence_release();
    __syncwarp();
    float rate = 0.58f;
    uint32_t c0 = 0;
#pragma unroll 1
    for (int s = -1; s < 63; s++) {
        cta = lds32(sb + S_CTA);
        const int pair = cta >> 1;
        const uint32_t ahead = s > 0 ? (uint32_t)(rate * (float)(pair >= 32 ? P.dc - P.dv : P.dc)) : 0;
        mbar_wait(sb + B_GO, s & 1);
        SSTAMP(10, lane == 0 && s == 0)
        const uint32_t t0 = gtime();
        if (lane < 4) st_relaxed1(g_hint + ((s & 1) * 4 + lane) * 768 + (cta >> 5) * 256 + (cta & 31), (t0 + ahead + (lds32(sb + S_REDO) == s ? P.extra : 0)) << 5 | ((base + s) & 31u));
        wait_time(t0 + (s < 0 ? 2000 : s == 0 && pair >= 16 ? P.ds0 : P.ds), sb);
        const uint32_t t = latest_stamp(g_hint + ((s & 1) * 4 + (pair & 3)) * 768 + lane, base + s, t0, P.back, sb);
        if (s < 0) {
            fence_acquire();
            const uint32_t g = tpc_gpc(ld_relaxed1(g_hint + 6144 + (lane & 15) * 2));
            const uint32_t key = (__popc(__match_any_sync(0xffffffffu, g)) > 4 ? 0 : g + 1) * 16 + (lane & 15);
            const uint32_t tail = (pair & 48) + __popc(__ballot_sync(0xffffffffu, key < __shfl_sync(0xffffffffu, key, pair & 15))) / 2;
            mbar_wait(sb + B_INIT, 0);
            SSTAMP(4, lane == 0)
            sts32(sb + S_TAIL, tail);
            if (lane < 8) sts32(sb + S_SC + lane * 4, lds32(sb + S_EPOCH + 4));
            __syncwarp();
        }
        release_at(t + P.da, sb, B_RELA, lane);
        SSTAMP(11, lane == 0 && s == 0)
        release_at(t + P.db, sb, B_RELB, lane);
        {
            const uint32_t c1 = clock(), g1 = gtime();
            if (s > 1) rate += P.alpha * (__fdividef((float)(g1 - lds32(sb + S_EPOCH + 4)), (float)(c1 - c0)) - rate);
            __syncwarp();
            c0 = c1; sts32(sb + S_EPOCH + 4, g1);
        }
        if (s == 61) {
            sts32(sb + S_COEF, ITEM(ITEM_OFF(lds32(sb + S_TAIL)) + NPRE + 1) + (uint32_t)(uintptr_t)P.out);
            if (lane < M_CQ) map_prefetch(&P.tm[lane]);
        }
    }
}
__device__ __forceinline__ uint32_t xor_or(uint32_t a, uint32_t b, uint32_t t) { uint32_t d; asm("lop3.b32 %0, %1, %2, %3, 0x7E;" : "=r"(d) : "r"(a), "r"(b), "r"(t)); return d; }
__device__ __forceinline__ bool tags_ok(uint32_t bad) { return __all_sync(0xffffffffu, (bad & 1) == 0); }
#define RETRY(k)
#define RETRY_STAT(a, b)
#define UNIT_STAT(u0)
#define KE 0
#define ES 1
#define Q3 1
#define SFENCE() asm volatile("pmevent 1;" ::: "memory")
#define PF1 10
static_assert(NS == 24, "fragment residency");
__host__ __device__ constexpr bool in_smem(int n) { return n < 4 || n == 12 || n == 13; }
__host__ __device__ constexpr int unit_pos(int n) { return n < 4 ? n : n < 12 ? n - 4 : n < 14 ? n - 8 : n - 6; }

__host__ __device__ constexpr int fill_unit(int q) { return q < 4 ? q : q < 6 ? q + 8 : q < 14 ? q - 2 : q; }
__host__ __device__ constexpr int frag_off(int q) { return (q >> 2) * 16384 + ((q >> 1) & 1) * 8192 + (q & 1) * 512; }

constexpr uint32_t QBITS = 0x4B002000u;
constexpr uint64_t W_BIAS = ((uint64_t)QBITS << 45) + ((uint64_t)QBITS << 26) + (uint32_t)(QBITS << 7), W_CLEAR = 0 - 32 * W_BIAS;
static_assert(W_CLEAR == ((uint64_t)CLEAR_HI << 32 | CLEAR_LO), "clear value");
__host__ __device__ constexpr int unit_off(int u) { return (u & 1) * 16384 + (u >> 2) * 512 + ((u >> 1) & 1) * 128; }
__device__ __forceinline__ void red_add64(const uint8_t* p, uint64_t v) { asm volatile("red.relaxed.gpu.global.add.u64 [%0], %1;" ::"l"(p), "l"(v) : "memory"); }
template <int NF>
__device__ __forceinline__ uint64_t encode(const float* x, float S, uint32_t two26, uint32_t& bad) {
    uint32_t b[3];
#pragma unroll
    for (int i = 0; i < 3; i++) b[i] = i < NF ? __float_as_uint(fmaf(x[i], S, 8396800.f)) : QBITS;
    bad = xor_or(b[0], b[1], 0x4B000000u) | (NF == 3 ? b[2] ^ 0x4B000000u : 0);
    uint64_t w;
    asm("{\n.reg .b64 t;\nmov.b64 t, {%2, %3};\nmad.wide.u32 %0, %1, %4, t;\n}" : "=l"(w) : "r"(b[1]), "r"(b[2] << 7), "r"(b[0] << 13), "r"(two26));
    return w;
}
template <int NF>
__device__ __forceinline__ void emit(uint64_t* w, const float (*x)[3], const float* S, uint32_t two26, uint32_t lim, const uint8_t* p) {
    uint32_t bad[2];
    w[0] = encode<NF>(x[0], S[0], two26, bad[0]); w[1] = encode<NF>(x[1], S[1], two26, bad[1]);
    const bool ok = (bad[0] | bad[1]) < lim;
    w[0] |= ok; w[1] |= ok;
    red_add64(p, w[0]); red_add64(p + 1024, w[1]);
}
template <int NF>
__device__ __forceinline__ void repair(const uint64_t* w, const float (*x)[3], const float* S, const uint8_t* p, const uint8_t* pf) {
    if (!(w[0] & 1)) {
#pragma unroll
        for (int j = 0; j < 2; j++) {
            const float T = S[j] * 8192.f;
            asm volatile("red.relaxed.gpu.global.add.v4.f32 [%0], {%1,%2,%3,%4};" ::"l"(pf + j * 512), "f"(x[j][0] * T), "f"(x[j][1] * T), "f"(NF == 3 ? x[j][2] * T : 0.f), "f"(0.f) : "memory");
        }
        fence_release();
#pragma unroll
        for (int j = 0; j < 2; j++) {
            asm volatile("red.relaxed.gpu.global.or.b64 [%0], 64;" ::"l"(p + j * 1024) : "memory");
            red_add64(p + j * 1024, W_BIAS + 1 - w[j]);
        }
    }
    __syncwarp();
}
__device__ __forceinline__ void ld_words(uint32_t* v, const uint8_t* p) {
    asm volatile("{\n.reg .b64 a, b;\nld.relaxed.gpu.global.L1::no_allocate.v2.b64 {a, b}, [%4];\nmov.b64 {%0,%1}, a;\nmov.b64 {%2,%3}, b;\n}" : "=r"(v[0]), "=r"(v[1]), "=r"(v[2]), "=r"(v[3]) : "l"(p) : "memory");
}
__device__ __forceinline__ float field(const uint32_t* w, int f) { return __int2float_rn((int)(f == 0 ? w[1] : f == 1 ? __funnelshift_l(w[0], w[1], 19) : w[0] << 6)); }
template <int U>
__device__ __forceinline__ void decode(uint32_t* b, const uint32_t* v) {
#pragma unroll
    for (int f = 0; f < (U % 3 ? 3 : 2); f++) b[frag_word(U, f)] = pack2(field(v, f), field(v + 2, f));
}
__device__ __forceinline__ uint32_t status(const uint32_t (*v)[4], uint32_t c32) { return xor_or(v[0][0], v[0][2], c32) | xor_or(v[1][0], v[1][2], c32) | xor_or(v[2][0], v[2][2], c32); }
__device__ __forceinline__ void gather_slow(const Params& P, uint32_t* b, const uint8_t* pm, int s, int warp, uint32_t ln, uint32_t u2) {
    if (s == 0 && u2 == 0x3F803F80u) {
#pragma unroll
        for (int i = 0; i < 16; i++) b[i] = __ldg((const uint32_t*)(P.mem0 + (ln >> 2) * 1024 + word_col(i) + warp * 16 + (ln & 3) * 2));
        return;
    }
    uint32_t v[6][4], st;
    for (int n = 0;; n++) {
#pragma unroll
        for (int u = 0; u < 6; u++) ld_words(v[u], pm + unit_off(u));
        st = status(v, 32) | status(v + 3, 32);
        if (!__any_sync(0xffffffffu, st & 32)) break;
        __nanosleep(200);
        if (n > SPIN_LIMIT) spin_fault();
    }
    const bool side = __any_sync(0xffffffffu, st & 64);
    if (side) fence_acquire();
    const uint8_t* pf = g_f + ((s + 7) & 7) * F_SLOT + warp * 1024 + ln * 32;
#pragma unroll
    for (int u = 0; u < 6; u++) {
        float x[2][4] = {};
#pragma unroll
        for (int k = 0; k < 2; k++)
            asm volatile("{\n.reg .pred P;\nsetp.ne.u32 P, %5, 0;\n@P ld.relaxed.gpu.global.v4.f32 {%0,%1,%2,%3}, [%4];\n}"
                         : "+f"(x[k][0]), "+f"(x[k][1]), "+f"(x[k][2]), "+f"(x[k][3]) : "l"(pf + u * 8192 + k * 16), "r"((uint32_t)side) : "memory");
#pragma unroll
        for (int f = 0; f < (u % 3 ? 3 : 2); f++) b[frag_word(u, f)] = pack2(field(v[u], f) + x[0][f], field(v[u] + 2, f) + x[1][f]);
    }
}
__device__ __forceinline__ uint32_t max_abs2(uint32_t a, uint32_t b) { uint32_t d; asm("max.NaN.xorsign.abs.bf16x2 %0, %1, %2;" : "=r"(d) : "r"(a), "r"(b)); return d; }
__device__ __forceinline__ uint32_t max6(const uint32_t* b) {
    const uint32_t m = max_abs2(max_abs2(max_abs2(b[0], b[1]), max_abs2(b[2], b[3])), max_abs2(b[4], b[5]));
    return max(m & 0x7fff0000u, (m << 16) & 0x7fff0000u);
}

template <bool TR>
__device__ __forceinline__ void put_partials(uint32_t a, const float* x, const float* y) {
    if (TR) stsm4t(a, pack2(x[0], x[1]), pack2(x[2], x[3]), pack2(y[0], y[1]), pack2(y[2], y[3]));
    else stsm4(a, pack2(x[0], x[1]), pack2(x[2], x[3]), pack2(y[0], y[1]), pack2(y[2], y[3]));
}
__device__ __forceinline__ void reduce_load(uint32_t (*x)[4], uint32_t a) { ldsm4t(x[0], a); ldsm4t(x[1], a + 512); }
__device__ __forceinline__ uint32_t reduce8(const uint32_t (*x)[4], uint32_t l8, uint32_t u2) {
    uint32_t p[2];
#pragma unroll
    for (int i = 0; i < 2; i++) {
        float d[4] = {};
        mma16816(d, x[i][0], x[i][1], x[i][2], x[i][3], (l8 & 32) ? 0u : u2, (l8 & 32) ? u2 : 0u);
        p[i] = pack2((l8 & 8) ? d[2] : d[0], (l8 & 8) ? d[3] : d[1]);
    }
    return (l8 & 16) ? p[1] : p[0];
}
__device__ __forceinline__ void score_half(float (*a)[4], const uint32_t (*qa)[4], const uint32_t (*kf)[4]) {
#pragma unroll
    for (int w = 0; w < 2; w++) {
        mma16816(a[w], qa[w][0], qa[w][1], qa[w][2], qa[w][3], kf[w][0], kf[w][1]);
        mma16816(a[2 + w], qa[w][0], qa[w][1], qa[w][2], qa[w][3], kf[w][2], kf[w][3]);
    }
}
__device__ __forceinline__ void score_sum(float* S, const float (*a)[4]) {
    S[0] = (a[0][0] + a[1][0]) + (a[2][2] + a[3][2]);
    S[1] = (a[0][1] + a[1][1]) + (a[2][3] + a[3][3]);
}
__device__ __forceinline__ float quad_max(float m) {
    return fmaxf(fmaxf(m, __shfl_xor_sync(0xffffffffu, m, 1)), fmaxf(__shfl_xor_sync(0xffffffffu, m, 2), __shfl_xor_sync(0xffffffffu, m, 3)));
}

#define ISTAMP(i)
__device__ __forceinline__ float next_scale(uint32_t sb, int slot, int warp, uint32_t u2) {
    uint32_t x[2][4];
    lds128(x[0], sb + S_MX + slot * 32); lds128(x[1], sb + S_MX + slot * 32 + 16);
    const uint32_t mx = max(max(max(x[0][0], x[0][1]), max(x[0][2], x[0][3])), max(max(x[1][0], x[1][1]), max(x[1][2], x[1][3])));
    const float top = fminf(fmaxf(__uint_as_float(mx) * bf_hi(u2), 0x1p-40f), 0x1p40f) * (1.f / (12288.f * 8192.f));
    const uint32_t un = pack2(top, top);
    sts32(sb + S_SC + warp * 4, un);
    return rcp(bf_hi(un) * 8192.f);
}
#define NEARLY 0
#define U3POS 1
#define VPOS 1
#define ROT 0
#define BPOS 1
#define ONLINE 0
#define NBAR 4
#define ORD3 0
#define F2 0
#define LOOPB 1
#define TK 4
#define OBN 4
#define CH4 1
#define SPOS 5
#define RPOS 1
#define AF 0
#define AFENCE(i) if ((AF >> (i)) & 1) SFENCE();
#define FPOS 99
#define PACE 1
#define PF2 12
__host__ __device__ constexpr int w2_t(int i) { return i < 16 ? i & 1 : 2; }
__host__ __device__ constexpr int w2_k(int i) { return i < 16 ? i >> 1 : i - 16; }
template <typename G>
__device__ __forceinline__ void load_weights(uint32_t (*wr)[4], const uint32_t sb, const int warp, const int lane, G stores_read) {
    const uint32_t frag = sb + warp * 1024 + (lane >> 4) * 8192 + (lane & 7) * 128 + ((((lane >> 3) & 1) ^ (lane & 7)) << 4);
    const uint32_t rel = mapa(sb + B_EMPTY, cluster_rank() ^ (lane & 1));
#define RELEASE(st) { if ((st) >= 2) fence_async_smem(); __syncwarp(); if (lane < 2) mbar_arrive_cluster(rel + (st) * 8); }
    mbar_wait(sb + B_FULL, 0); mbar_wait(sb + B_FULL + 8, 0);
    RELEASE(0) RELEASE(1)
#pragma unroll
    for (int st = 2; st < 4; st++) {
        mbar_wait(sb + B_FULL + st * 8, 0);
        ISTAMP(st - 2)
#pragma unroll
        for (int f = 0; f < 12; f++) ldsm4t(wr[st * 12 - 24 + f], (frag ^ ((f & 3) << 5)) + st * STAGE + (f >> 2) * 16384);
        RELEASE(st)
    }
#pragma unroll 2
    for (int u = 0; u < 6; u++) {
        uint32_t x[4][4];
#pragma unroll
        for (int i = 0; i < 4; i++) lds128(x[i], (frag ^ (i << 5)) + u * 16384);
        __syncwarp();
#pragma unroll
        for (int i = 0; i < 4; i++) sts128(sb + warp * 1024 + lane * 16 + u * 16384 + frag_off(i), x[i]);
    }
    SSTAMP(0, threadIdx.x == 0)
    stores_read();
    SSTAMP(2, threadIdx.x == 0)
    mbar_wait(sb + B_FULL, 1); mbar_wait(sb + B_FULL + 8, 1);
    RELEASE(0) RELEASE(1)
#pragma unroll
    for (int st = 2; st < 4; st++) {
        mbar_wait(sb + B_FULL + st * 8, 1);
#pragma unroll
        for (int f = 0; f < (st == 2 ? 12 : 4); f++) ldsm4t(wr[st * 12 + f], (frag ^ ((f & 3) << 5)) + st * STAGE + (f >> 2) * 16384);
        RELEASE(st)
    }
    ISTAMP(2)
    bar_sync(1, 256);
    if (warp == 7 && lane < 3) mbar_arrive_cluster(mapa(sb + B_INIT, (cluster_rank() & 1) + lane * 2));
}
template <int ROLE>
__device__ __forceinline__ void chain_role(const Params& P, const uint32_t (*wr)[4], const uint32_t sb, const int h, const int warp, const int lane) {
    constexpr int NU = ROLE == 0 ? 2 : 3;
    const bool att = ROLE == 0 && warp < 4;
    uint32_t l8 = opq(sb + lane * 8, lane);
#define PERSIST() { mbar_wait(sb + B_KVGO, slot ^ 1); const uint32_t pa_ = ((l8 - sb) >> 1) + (sb + S_QX + warp * 128); sts32(pa_, r0); sts32(pa_ + 1024, r1); \
                    fence_async_smem(); __syncwarp(); if (l8 == sb) mbar_arrive(sb + B_PERS); }
    if (ROLE) sts32(sb + S_SX + warp * 128 + lane * 4, warp >= 2 ? 0 : (lane & 1) ? CLEAR_HI : CLEAR_LO);
    const uint32_t rdelta = __shfl_sync(0xffffffffu, mapa(sb, (cluster_rank() + (ROLE == 1 ? 4 : 2)) % 6) - sb, 0);
    const uint32_t vdelta = ROLE ? 0 : __shfl_sync(0xffffffffu, mapa(sb, (cluster_rank() + 4) % 6) - sb, 0);
    ISTAMP(3)
    __syncwarp();
#define GATHER_OFF(s) ((((s) + 7) & 7) * M_SLOT + warp * 2048 + (l8 & 56) * 2 + (l8 & 64) * 4 + (l8 & 128) * 8)
    uint32_t mo = GATHER_OFF(0);
    sts32(sb + S_SC + 32 + warp * 4, 0);
    if (ROT) mbar_wait(sb + B_RELA, 0);
    for (int s = 0; s < (ROLE == 0 ? 63 : 64);) {
        const int slot = s & 1;
        l8 += s & P.zero;
        const uint32_t w1a = l8 * 2 + (S_W1 + warp * 1024 - sb);
        PROF(9)
        uint32_t u2, r0, r1, pld, pub, pbar, x[2][4];
        {
#define pm (P.gm + mo)
            uint32_t as[24][4], b[16], v[6][4];
            float acc[8][4];
#define W1LD(n) _Pragma("unroll") for (int i_ = 0; i_ < 4; i_++) ldsm4t(as[unit_pos(n) * 4 + i_], w1a + frag_off(unit_pos(n) * 4 + i_));
#define W1LD2(n, p) { const uint32_t wa_ = w1a + (as[unit_pos(p) * 4][0] & as[unit_pos(p) * 4 + 1][0] & as[unit_pos(p) * 4 + 2][0] & as[unit_pos(p) * 4 + 3][0] & P.zero); \
                      _Pragma("unroll") for (int i_ = 0; i_ < 4; i_++) ldsm4t(as[unit_pos(n) * 4 + i_], wa_ + frag_off(unit_pos(n) * 4 + i_)); }
#define W1MMA(n) _Pragma("unroll") for (int i_ = 0; i_ < 4; i_++) { const uint32_t* a_ = in_smem(n) ? as[unit_pos(n) * 4 + i_] : wr[unit_pos(n) * 4 + i_]; \
                                                                   mma16816(acc[((n) & 1) * 4 + i_], a_[0], a_[1], a_[2], a_[3], b[(n) & 14], b[(n) | 1]); }
#pragma unroll
            for (int T = 0; T < 8; T++) { acc[T][0] = acc[T][1] = acc[T][2] = acc[T][3] = 0.f; }
            if (!ROT) mbar_wait(sb + B_RELA, slot);
            PROF(12)
#pragma unroll
            for (int u = 0; u < 3; u++) ld_words(v[u], pm + unit_off(u));
            __syncwarp();
#pragma unroll
            for (int i = 0; i < PF1; i++) ldsm4t(as[i], w1a + frag_off(i));
            __syncwarp();
            mo += mbar_try(sb + B_RELB, slot) & P.zero;
            PROF(13)
#pragma unroll
            for (int u = 3; u < 6; u++) ld_words(v[u], pm + unit_off(u));
            uint32_t st = status(v, ((uint32_t)((uintptr_t)pm >> 32) & P.zero) + 32);
            pin<1>(&st);
            SFENCE();
            UNIT_STAT(0)
            PROF(0)
            decode<0>(b, v[0]); decode<1>(b, v[1]); decode<2>(b, v[2]);
#pragma unroll
            for (int i = PF1; i < 12; i++) ldsm4t(as[i], w1a + frag_off(i));
            W1MMA(0) W1MMA(1) W1MMA(2)
            if (TK & 1) W1LD2(3, 2) else { W1LD(3) }
            SFENCE();
            if (TK & 8) { W1MMA(5) W1MMA(4) W1MMA(3) W1MMA(6) } else { W1MMA(5) W1MMA(4) W1MMA(6) W1MMA(3) }
            if (U3POS == 0) W1MMA(7)
            if (TK & 2) W1LD2(12, 3) else { W1LD(12) }
            uint32_t mx = max6(b);
            pin<1>(&mx);
            SFENCE();
            PROF(10)
            if (U3POS == 1) W1MMA(7)
            const uint32_t mxa = sb + S_MX + slot * 32 + warp * 4;
            sts32(mxa, __reduce_max_sync(0xffffffffu, mx));
            UNIT_STAT(3)
            st |= status(v + 3, 32);
            const bool redo = __any_sync(0xffffffffu, st & 96);
            const bool kvok = ROLE || mbar_test(sb + B_KVFULL + slot * 8, (s >> 1) & 1);
            decode<4>(b, v[4]); decode<5>(b, v[5]); decode<3>(b, v[3]);
            u2 = lds32(sb + S_SC + warp * 4);
            W1MMA(8) W1MMA(10) if (ORD3) { W1MMA(14) W1MMA(12) } else { W1MMA(12) W1MMA(14) }
            if (TK & 4) W1LD2(13, 12) else { W1LD(13) }
            if (__builtin_expect(redo || !kvok, 0)) {
                if (redo) {
                    if (LOOPB && lds32(sb + S_SC + 32 + warp * 4) != s) {
                        RETRY(4)
                        __syncwarp();
                        sts32(sb + S_SC + 32 + warp * 4, s);
                        if (LOOPB == 2) sts32(sb + S_REDO, s);
                        mo = GATHER_OFF(s);
                        continue;
                    }
                    RETRY(3)
                    sts32(sb + S_REDO, s);
                    gather_slow(P, b, P.gm + GATHER_OFF(s), s, warp, (l8 - sb) >> 3, u2);
                    sts32(mxa, __reduce_max_sync(0xffffffffu, max6(b)));
#pragma unroll
                    for (int T = 0; T < 8; T++) { acc[T][0] = acc[T][1] = acc[T][2] = acc[T][3] = 0.f; }
#pragma unroll
                    for (int n = 0; n < 15; n += n < 8 ? 1 : 2) {
                        if (in_smem(n)) { W1LD(n) }
                        W1MMA(n)
                    }
                    W1LD(13)
                }
                if (ROLE == 0) mbar_wait(sb + B_KVFULL + slot * 8, (s >> 1) & 1);
            }
#undef pm
            SSTAMP(7, threadIdx.x == 0 && s == 0)
            PROF(14)
            const uint32_t pst = (l8 - sb) * 16 + ((warp * 16) ^ ((l8 * 2) & 112)) + (sb + S_P1);
            put_partials<ROLE == 2>(pst, acc[0], acc[1]); put_partials<ROLE == 2>(pst + 4096, acc[2], acc[3]);
            W1MMA(9)
            SFENCE();
            pld = (l8 & 64) * 4 + (l8 & 128) + (l8 & 56) * 2 + (sb + S_P1 + warp * 1024);
            const uint32_t rd = s == 63 ? 0 : rdelta;
            pub = ((l8 - sb) >> 1) + (ROLE ? sb + rd + (ROLE == 1 ? S_KL : S_VL) + warp * 128 : sb + S_QX + (warp & 4) * 128 + (warp & 1) * 256 + (warp & 2) * 64);
            pbar = sb + rd + (ROLE == 1 && s != 63 ? B_K : B_V);
#define PUBLISH0() { r0 = reduce8(x, l8, u2); if (ROLE) st_async1(pub, r0, KE && ROLE == 1 && s != 63 ? pbar + (B_PERS - B_K) : pbar); else sts32(pub, r0); }
            if (RPOS == 0) { bar_sync(1, 256); reduce_load(x, pld); SFENCE(); }
            W1MMA(11)
            if (RPOS == 1) { bar_sync(1, 256); reduce_load(x, pld); }
            if (RPOS != 2 || F2) SFENCE();
#define W1MMH(n, o) _Pragma("unroll") for (int i_ = o; i_ < o + 2; i_++) { const uint32_t* a_ = in_smem(n) ? as[unit_pos(n) * 4 + i_] : wr[unit_pos(n) * 4 + i_]; \
                                                                   mma16816(acc[((n) & 1) * 4 + i_], a_[0], a_[1], a_[2], a_[3], b[(n) & 14], b[(n) | 1]); }
            if (ES) { W1MMH(15, 0) W1MMH(15, 2) W1MMH(13, 0) } else W1MMA(15)
            if (RPOS == 0) PUBLISH0()
            if (RPOS == 2) { bar_sync(1, 256); reduce_load(x, pld); }
            if (RPOS != 1 || F2) SFENCE();
            if (ES) { W1MMH(13, 2) put_partials<ROLE == 2>(pst + 8192, acc[4], acc[5]); } else W1MMA(13)
            if (RPOS == 1) PUBLISH0()
            if (!ES) put_partials<ROLE == 2>(pst + 8192, acc[4], acc[5]);
            put_partials<ROLE == 2>(pst + 12288, acc[6], acc[7]);
            if (RPOS == 2) PUBLISH0()
        }
        SSTAMP(8, threadIdx.x == 0 && s == 0)
        PROF(1)
        if (ROLE) {
            bar_sync(1, 256);
            reduce_load(x, pld + 8192);
            r1 = reduce8(x, l8, u2);
            st_async1(pub + 1024, r1, pbar);
            if (s == 63) {
                PERSIST()
                mbar_wait(sb + B_V, 0);
                break;
            }
            PROF(2)
        }
        uint32_t ln, w2a, ro;
#define W2ADDR(late) { l8 += pub & P.zero; ln = (l8 - sb) >> 3; \
        w2a = sb + S_W2 + (ROLE ? (warp >> 2) * 16384 : late * 32768) + ((((ln & 7) + (ln >> 4) * 8) * 128 + ((((ln >> 3) & 1) ^ (ln & 7)) << 4)) ^ ((warp & 3) << 5)); \
        ro = (s & 7) * M_SLOT + (ROLE ? warp * 2048 + unit_off(ROLE) : (warp & 3) * 2048 + late * unit_off(3)) + (ln & 2) * 128 + (ln & 1) * 64 + (ln >> 2) * 8; }
        constexpr int RO2 = ROLE ? unit_off(ROLE + 3) - unit_off(ROLE) : 8192;
        float Sj[2];
        uint32_t w[24][4], ob[4][4];
        float S;
#define W2LD(i) ldsm4t(w[i], w2a + w2_t(i) * (ROLE ? 32768 : 16384) + (w2_k(i) & 1) * 8192 + (w2_k(i) >> 1) * 2048)
#define W2MMA(d, i) mma16816(d, w[i][0], w[i][1], w[i][2], w[i][3], ob[w2_k(i) >> 1][(w2_k(i) & 1) * 2], ob[w2_k(i) >> 1][(w2_k(i) & 1) * 2 + 1])
#define LEADER(wp) (l8 == sb + ((wp) - warp) * 256)
        if (att) {
            const float cs = 0.08838834764831845f * 1.4426950408889634f;
            uint32_t qa[4][4], kf[4][4], vf[4][4], vv[4];
            float T[5][2], sa[4][4] = {};
            const uint32_t l16 = l8 * 2 - sb;
            const uint32_t kaddr = (l8 & 56) * 16 + (((l8 >> 2) ^ (l8 * 2)) & 48) + ((l8 * 2) & 64) + (sb + S_KV + warp * 1024 + slot * 16384);
            bar_sync(1, 256);
            reduce_load(x, pld + 8192);
            __syncwarp();
#pragma unroll
            for (int i = 0; i < 2; i++) { ldsm4(qa[i], l16 + S_QX + i * 512); ldsm4(kf[i], kaddr ^ (i * 64)); }
            AFENCE(0)
            sts32(pub + 1024, reduce8(x, l8, u2));
            __syncwarp();
#pragma unroll
            for (int i = 2; i < 4; i++) ldsm4(kf[i], (kaddr ^ ((i & 1) * 64)) + 4096);
            score_half(sa, qa, kf);
            bar_sync(2, 256);
            PROF(2)
#pragma unroll
            for (int i = 2; i < 4; i++) ldsm4(qa[i], l16 + S_QX + i * 512);
            float sm[4][4] = {};
            const bool kearly = KE && mbar_try(sb + B_PERS, slot);
            score_half(sa, qa + 2, kf + 2);
            score_sum(T[0], sa);
            sts64(l8 + S_SX + warp * 256, __float_as_uint(T[0][0]), __float_as_uint(T[0][1]));
            PROF(4)
            if (KE) {
                if (!kearly) mbar_wait(sb + B_PERS, slot);
                ldsm4(kf[0], l16 + S_KL); ldsm4(kf[1], l16 + S_KL + 512);
                score_half(sm, qa, kf);
            }
            if (BPOS == 0) bar_sync(4, 128);
            mbar_wait(sb + B_K, slot);
            PROF(11)
#pragma unroll
            for (int i = KE ? 2 : 0; i < 4; i++) ldsm4(kf[i], l16 + S_KL + i * 512);
            if (BPOS == 1) bar_sync(4, 128); else __syncwarp();
#pragma unroll
            for (int n = 0; n < 4; n++) lds64f(T[n], l8 + S_SX + n * 256);
            if (!KE) score_half(sm, qa, kf);
            score_half(sm, qa + 2, kf + 2);
            const uint32_t vaddr = (l8 & 56) * 16 + (l8 & 128) * 8 + (((warp & 1) * 64 + ((l8 >> 2) & 16)) ^ ((l8 * 2) & 112)) + (sb + S_KV + 8192 + (warp >> 1) * 4096 + slot * 16384);
            float mx = fmaxf(fmaxf(fmaxf(T[0][0], T[0][1]), fmaxf(T[1][0], T[1][1])), fmaxf(fmaxf(T[2][0], T[2][1]), fmaxf(T[3][0], T[3][1])));
            score_sum(T[4], sm);
            float m = quad_max(fmaxf(mx, fmaxf(T[4][0], T[4][1])));
            if (VPOS == 0) {
#pragma unroll
                for (int i = 0; i < 4; i++) ldsm4t(vf[i], (vaddr ^ ((i & 1) << 5)) + (i >> 1) * 2048);
            }
            mbar_wait(sb + B_V, slot);
            if (VPOS == 1) {
#pragma unroll
                for (int i = 0; i < 4; i++) ldsm4t(vf[i], (vaddr ^ ((i & 1) << 5)) + (i >> 1) * 2048);
            }
            ldsm4(vv, l16 + S_VL + warp * 512);
            uint32_t pa[5];
#pragma unroll
            for (int n = 0; n < 5; n++) { T[n][0] = ex2((T[n][0] - m) * cs); T[n][1] = ex2((T[n][1] - m) * cs); pa[n] = pack2(T[n][0], T[n][1]); }
            float sum = (((T[0][0] + T[0][1]) + (T[1][0] + T[1][1])) + ((T[2][0] + T[2][1]) + (T[3][0] + T[3][1]))) + (T[4][0] + T[4][1]);
            PROF(3)
            W2ADDR(1)
            const uint32_t lo = sb + S_O + warp * 512 + (ln & 3) * 64 + (ln >> 2) * 8, ls = sb + S_SUM + (ln & 3) * 32 + (ln & 4) * 4 + (ln >> 3) * 4;
            const uint32_t sdelta = warp < 2 ? rdelta : vdelta;
            if (Q3 & 2) sum = (sum + __shfl_xor_sync(0xffffffffu, sum, 1)) + (__shfl_xor_sync(0xffffffffu, sum, 2) + __shfl_xor_sync(0xffffffffu, sum, 3));
            else { sum += __shfl_xor_sync(0xffffffffu, sum, 1); sum += __shfl_xor_sync(0xffffffffu, sum, 2); }
            float O[2][4];
#pragma unroll
            for (int i = 0; i < 2; i++) { O[i][0] = O[i][1] = O[i][2] = O[i][3] = 0.f; }
#pragma unroll
            for (int i = 0; i < 2; i++) {
                mma16816(O[0], vf[2 * i][0], vf[2 * i][1], vf[2 * i][2], vf[2 * i][3], pa[2 * i], pa[2 * i + 1]);
                mma16816(O[1], vf[2 * i + 1][0], vf[2 * i + 1][1], vf[2 * i + 1][2], vf[2 * i + 1][3], pa[2 * i], pa[2 * i + 1]);
            }
            mma1688(O[0], vv[0], vv[1], pa[4]);
            mma1688(O[1], vv[2], vv[3], pa[4]);
            uint32_t o[2][2];
#pragma unroll
            for (int j = 0; j < 2; j++) { o[j][0] = pack2(O[0][j], O[0][2 + j]); o[j][1] = pack2(O[1][j], O[1][2 + j]); }
#pragma unroll
            for (int j = 0; j < 2; j++) st_async2(lo + rdelta + j * 256, o[j][0], o[j][1], sb + rdelta + B_K);
            st_async1(ls + sdelta + (warp & 1) * 128, __float_as_uint(sum), sb + sdelta + B_K);
#pragma unroll
            for (int j = 0; j < 2; j++) st_async2(lo + vdelta + j * 256, o[j][0], o[j][1], sb + vdelta + B_K);
#pragma unroll
            for (int j = 0; j < 2; j++) sts64(lo + j * 256, o[j][0], o[j][1]);
            sts32(ls + warp * 128, __float_as_uint(sum));
            PROF(5)
            bar_sync(3, 256);
            if (LEADER(0)) { mbar_expect(sb + B_K, KE ? 1024 : 2048); if (KE) mbar_expect(sb + B_PERS, 1024); mbar_expect(sb + B_V, 2048); mbar_arrive(sb + B_KVGO + slot * 8); }
            S = next_scale(sb, slot, warp, u2);
            if (s == 0) mbar_wait(sb + B_WO, 0);
            pin<1>(&S);
            SFENCE();
#pragma unroll
            for (int j = 0; j < 4; j++) lds128(ob[j], l8 * 2 - sb + S_O + j * 512);
            lds64f(Sj, sb + S_SUM + (l8 & 24));
#pragma unroll
            for (int i = 0; i < PF2; i++) W2LD(i);
        } else {
            if (ROLE == 0) { bar_sync(1, 256); reduce_load(x, pld + 8192); sts32(pub + 1024, reduce8(x, l8, u2)); bar_arrive(2, 256); }
            if (LEADER(7)) { if (s) mbar_arrive(sb + B_GO); if (ROLE) mbar_expect(sb + B_K, 2304); }
            S = next_scale(sb, slot, warp, u2);
            if (s == 0) mbar_wait(sb + B_WO, 0);
            if (ROLE != 0) PERSIST()
            W2ADDR(0)
#pragma unroll
            for (int i = 0; i < PF2; i++) {
                W2LD(i);
                if (ROLE == 0 && (i & PACE) == PACE) w2a += w[i][0] & P.zero;
            }
            ro = opq(ro, ln);
            const uint32_t sa = opq(sb + S_SUM + (l8 & 24), ln), oa = opq(l8 * 2 - sb + S_O, ln);
            if (ROLE == 0) bar_sync(3, 256); else mbar_wait(sb + B_K, slot);
            if (OBN == 4 || !ROLE) lds64f(Sj, sa);
#pragma unroll
            for (int j = 0; j < 4; j++) { if (ROLE && j == OBN) SFENCE(); lds128(ob[j], oa + j * 512); }
            if (OBN < 4 && ROLE) lds64f(Sj, sa);
        }
        SSTAMP(9, threadIdx.x == 224 && s == 0)
        if (OBN == 4 || !ROLE) SFENCE();
        PROF(6)
        {
            const uint8_t* pr = P.gm + ro;
            float c[4][4];
            uint32_t lim = 0;
#pragma unroll
            for (int i = 0; i < 4; i++) { c[i][0] = c[i][1] = c[i][2] = c[i][3] = 0.f; }
#pragma unroll
            for (int i = 0; i < 16; i++) {
                W2MMA(c[i & (ROLE && !CH4 ? 1 : 3)], i);
                if (i + PF2 < (ROLE ? 16 + NEARLY : 16)) W2LD(i + PF2);
                if (i == SPOS) {
                    const uint32_t z = __float_as_uint(c[1][0]) & P.zero;
                    Sj[0] = S * rcp(__uint_as_float(__float_as_uint(Sj[0]) | z)); Sj[1] = S * rcp(__uint_as_float(__float_as_uint(Sj[1]) | z));
                }
                if (i == SPOS) lim = __any_sync(0xffffffffu, fmaxf(fmaxf(fabsf(c[0][0]), fabsf(c[0][2])), fmaxf(fabsf(c[1][0]), fabsf(c[1][2]))) * Sj[0] >= (ROLE && !CH4 ? 24.f : 20.f)) ? 16384 : 0;
                if (i == FPOS && ROLE) SFENCE();
            }
            if (ROLE == 0 || CH4) {
#pragma unroll
                for (int i = 0; i < 8; i++) { c[i >> 2][i & 3] += c[2 + (i >> 2)][i & 3]; c[2 + (i >> 2)][i & 3] = 0.f; }
            }
            const float xa[2][3] = {{c[0][0], c[0][2], c[1][0]}, {c[0][1], c[0][3], c[1][1]}};
            uint64_t wa[2], wb[2];
            emit<NU>(wa, xa, Sj, P.two26, lim, pr);
            PROF(7)
            mo = GATHER_OFF(s + 1);
            pin<1>(&mo);
            if (ROLE) {
                SFENCE();
#pragma unroll
                for (int i = 16 + NEARLY; i < 24; i++) { if (i == 16 + NBAR) bar_sync(2, 256); W2LD(i); __syncwarp(); }
                SFENCE();
#pragma unroll
                for (int i = 16; i < 24; i++) W2MMA(c[2 + (i & 1)], i);
#pragma unroll
                for (int i = 0; i < 4; i++) c[2][i] += c[3][i];
            }
            const float y[2][3] = {{ROLE ? c[1][2] : c[1][0], ROLE ? c[2][0] : c[1][2], c[2][2]}, {ROLE ? c[1][3] : c[1][1], ROLE ? c[2][1] : c[1][3], c[2][3]}};
            const bool released = !ROT || mbar_test(sb + B_RELA, slot ^ 1);
            emit<NU>(wb, y, Sj, P.two26, lim, pr + RO2);
            PROF(8)
            if (!__all_sync(0xffffffffu, (wa[0] & wb[0] & 1) && released && s)) {
                if (__builtin_expect(!__all_sync(0xffffffffu, wa[0] & wb[0] & 1), 0)) {
                    RETRY(5)
                    const uint8_t* pf = g_f + (s & 7) * F_SLOT + (ROLE ? ROLE * 8192 + warp * 1024 : (warp & 3) * 1024 + (att ? 24576 : 0)) + (ln & 3) * 128 + (ln >> 2) * 16;
                    repair<NU>(wa, xa, Sj, pr, pf);
                    repair<NU>(wb, y, Sj, pr + RO2, pf + (ROLE ? 24576 : 4096));
                }
                if (s == 0) { bar_sync(1, 256); if (LEADER(7)) mbar_arrive(sb + B_GO); }
                if (ROT) mbar_wait(sb + B_RELA, slot ^ 1);
            }
        }
        s++;
    }
}
struct Pipe { uint32_t stage, phase; };
struct Cons {
    uint32_t sb, rel;
    int wg, wq, lane, rank, pair;
    uint32_t nst;
    Pipe p;
};
__device__ __forceinline__ void pipe_next(Pipe& p) { p.stage = (p.stage + 1) & (NSTAGE - 1); p.phase ^= (p.stage == 0); }
__device__ __forceinline__ void release(const Cons& c, uint32_t stage) { if (c.lane < 2) mbar_arrive_cluster(c.rel + stage * 8); }

enum { PEND_NONE = 0, PEND_KVO = 1, PEND_HT = 2, PEND_OUT = 3, PEND_OUTH = 4 };
struct Pend { uint32_t pk[64]; int kind, row, col, cnt; };

__device__ __forceinline__ void staging_wait(const Cons& c) { if (c.nst) mbar_wait(c.sb + B_SFREE + c.wg * 8, (c.nst - 1) & 1); }
__device__ __forceinline__ void staging_post(Cons& c, int kind, int row, int col, int cnt) {
    __syncwarp();
    if (c.lane == 0) {
        if (c.wq == 0) { const uint32_t x[4] = {(uint32_t)kind, (uint32_t)row, (uint32_t)col, (uint32_t)cnt}; sts128(c.sb + S_DESC + c.wg * 16, x); }
        mbar_arrive(c.sb + B_SFULL + c.wg * 8);
    }
    c.nst++;
}
template <int HF, bool KVONLY = false>
__device__ __forceinline__ void drain(const Params& P, Cons& c, const Pend& d) {
    const uint32_t* pk = d.pk + HF * 32;
    if (!KVONLY && d.kind >= PEND_OUT) {
        if (HF == 1 && d.kind == PEND_OUTH) return;
        float* o = P.out + (size_t)(d.row + c.wq * 16 + (c.lane >> 2)) * 2048 + d.col + HF * 128 + (c.lane & 3) * 2;
#pragma unroll
        for (int j = 0; j < 16; j++) {
            st_stream2(o + j * 8, bf_lo(pk[j * 2]), bf_hi(pk[j * 2]));
            st_stream2(o + 8 * 2048 + j * 8, bf_lo(pk[j * 2 + 1]), bf_hi(pk[j * 2 + 1]));
        }
    } else if (d.kind != PEND_NONE) {
        const bool ht = !KVONLY && d.kind == PEND_HT;
        const int hi = (c.lane >> 3) & 1;
        const uint32_t base = c.sb + S_STG + c.wg * 16384 + ((ht ? hi * 32 + c.wq * 8 : c.wq * 16 + hi * 8) + (c.lane & 7)) * 128;
        staging_wait(c);
#pragma unroll
        for (int j = 0; j < 8; j++) {
            const int ch = (j & 3) * 2 + (c.lane >> 4);
            stsm4(base + (j >> 2) * 8192 + ((ch ^ (c.lane & 7)) << 4), pk[j * 4], pk[j * 4 + 1], pk[j * 4 + 2], pk[j * 4 + 3]);
        }
        fence_async_smem();
        staging_post(c, d.kind, d.row, d.col + HF * 128, HF ? d.cnt : -1);
    }
}
__device__ __forceinline__ void drain_all(const Params& P, Cons& c, Pend& d) { drain<0>(P, c, d); drain<1>(P, c, d); d.kind = PEND_NONE; }

__device__ __forceinline__ void store_warp(const Params& P, uint32_t sb, int wg) {
    const uint32_t stg = sb + S_STG + wg * 16384;
#pragma unroll 1
    for (uint32_t n = 0;; n++) {
        mbar_wait(sb + B_SFULL + wg * 8, n & 1);
        uint32_t x[4];
        lds128(x, sb + S_DESC + wg * 16);
        if (x[0] == PEND_NONE) break;
        const bool ht = x[0] == PEND_HT;
        const CUtensorMap* m = &P.tm[ht ? M_HTS : M_KVO];
#pragma unroll 1
        for (int i = 0; i < 4; i++) if (!(DBGF(128) && gridDim.x != 96)) tma_store2d(m, x[2] + (i >> 1) * 64, x[1] + (i & 1) * (ht ? 1024 : 32), stg + i * 4096, ht ? EVICT_NORMAL : x[1] < 4096 ? POL(4) : POL(5));
        bulk_commit();
        bulk_wait_read();
        mbar_arrive(sb + B_SFREE + wg * 8);
        if ((int)x[3] >= 0) {
            bulk_wait_all(); fence_async();
            asm volatile("red.relaxed.gpu.global.add.u32 [%0], 1;" ::"l"(&g_cnt(x[3])) : "memory");
        }
    }
}

template <int N, int TA, int TB, bool FIRST>
__device__ __forceinline__ void issue_ktile(float* acc, const Cons& c) {
    mbar_wait(c.sb + B_FULL + c.p.stage * 8, c.p.phase);
    const uint32_t a = c.sb + c.p.stage * STAGE + c.wg * 8192, b = c.sb + c.p.stage * STAGE + 16384;
    const uint64_t da = mkdesc(a, TA ? 8192 : 16, 1024, 1), db = mkdesc(b, TB ? 8192 : 16, 1024, 1);
    wg_fence();
#pragma unroll
    for (int k = 0; k < 4; k++) {
        const uint64_t x = da + (TA ? 128 : 2) * k, y = db + (TB ? 128 : 2) * k;
        if (N == 256) { if (FIRST && k == 0) wgmma_ss256_first<TA, TB>(acc, x, y); else wgmma_ss256<TA, TB>(acc, x, y); }
        else { if (FIRST && k == 0) wgmma_ss128_first<TA, TB>(acc, x, y); else wgmma_ss128<TA, TB>(acc, x, y); }
    }
    wg_commit();
}
template <int N, bool FIRST>
__device__ __forceinline__ void issue_any(float* acc, const Cons& c, int type) {
    if (N == 256 && type == T_A1) issue_ktile<N, 0, 0, FIRST>(acc, c);
    else if (type == (N == 256 ? T_A2 : T_A2H)) issue_ktile<N, 1, 0, FIRST>(acc, c);
    else issue_ktile<N, 0, 1, FIRST>(acc, c);
}
template <int N, bool KVONLY = false>
__device__ __forceinline__ void mainloop(float* acc, const Params& P, Cons& c, Pend& d, int type) {
    const int nk = (type == T_OP || type == T_OPH) ? 64 : (type == T_A2 || type == T_A2H) ? 32 : 16;
    issue_any<N, true>(acc, c, type);
    drain<0, KVONLY>(P, c, d);
    uint32_t prev = c.p.stage;
    pipe_next(c.p);
    const int hold = c.wg ? nk - (int)((P.lag >> (4 * type)) & 7) : -1;
    for (int kt = 1; kt < nk; kt++) {
        if (kt == hold) bar_sync(8, 256);
        issue_any<N, false>(acc, c, type);
        wg_wait<1>();
        release(c, prev);
        if (kt == 2) drain<1, KVONLY>(P, c, d);
        prev = c.p.stage;
        pipe_next(c.p);
    }
    if (c.wg == 0 && ((P.lag >> (4 * type)) & 7)) bar_arrive(8, 256);
    d.kind = PEND_NONE;
    wg_wait<0>();
    pin<N / 2>(acc);
    release(c, prev);
}
__device__ __forceinline__ void pack_half(uint32_t* pk, const float* a) {
#pragma unroll
    for (int i = 0; i < 32; i++) pk[i] = pack2(a[2 * i], a[2 * i + 1]);
}

__device__ __forceinline__ void epi_kv(const float* acc, const Cons& c, Pend& d, int mb, int nb) {
    pack_half(d.pk, acc); pack_half(d.pk + 32, acc + 64);
    d.kind = PEND_KVO; d.row = (nb >> 4) * 2048 + mb * 256 + c.rank * 128 + c.wg * 64; d.col = (nb & 15) * 256; d.cnt = C_KV + mb;
}

__device__ __forceinline__ void qa_scores(float* S, float* Sm, uint32_t* q, const Cons& c, const Pipe& p) {
    mbar_wait(c.sb + B_FULL + p.stage * 8, p.phase);
    const uint32_t st = c.sb + p.stage * STAGE;
    const uint64_t dk = mkdesc(st + c.wg * 8192, 16, 1024, 1), dm = mkdesc(st + 32768 + c.wg * 4096, 128, 2048, 0);
    pin<32>(q);
    wg_fence();
    wgmma_rs64_first<0>(S, q, dk);
#pragma unroll
    for (int i = 1; i < 8; i++) wgmma_rs64<0>(S, q + i * 4, dk + (i >> 2) * 1024 + (i & 3) * 2);
    wgmma_rs16_first<0>(Sm, q, dm);
#pragma unroll
    for (int i = 1; i < 8; i++) wgmma_rs16<0>(Sm, q + i * 4, dm + i * 16);
    wg_commit();
}
__device__ __forceinline__ void qa_softmax(uint32_t (*pa)[4], const float* S, const float* Sm, const Cons& c) {
    const int t = c.lane & 3, i0 = (c.wq & 1) * 16 + (c.lane >> 2);
    const bool sg = c.wq >= 2;
    const float cs = 0.08838834764831845f * 1.4426950408889634f, masked = -1e9f / 0.08838834764831845f;
    float x[2][10];
#pragma unroll
    for (int r = 0; r < 2; r++) {
#pragma unroll
        for (int j = 0; j < 4; j++)
#pragma unroll
            for (int e = 0; e < 2; e++) {
                const float v = sg ? S[16 + j * 4 + r * 2 + e] : S[j * 4 + r * 2 + e];
                x[r][j * 2 + e] = (j * 8 + 2 * t + e > i0 + r * 8) ? masked : v;
            }
        x[r][8] = sg ? Sm[4 + r * 2] : Sm[r * 2];
        x[r][9] = sg ? Sm[5 + r * 2] : Sm[1 + r * 2];
        float m = x[r][0];
#pragma unroll
        for (int i = 1; i < 10; i++) m = fmaxf(m, x[r][i]);
        m = fmaxf(m, __shfl_xor_sync(0xffffffffu, m, 1));
        m = fmaxf(m, __shfl_xor_sync(0xffffffffu, m, 2));
        float sum = 0.f;
#pragma unroll
        for (int i = 0; i < 10; i++) { x[r][i] = ex2((x[r][i] - m) * cs); sum += x[r][i]; }
        sum += __shfl_xor_sync(0xffffffffu, sum, 1);
        sum += __shfl_xor_sync(0xffffffffu, sum, 2);
        const float inv = rcp(sum);
#pragma unroll
        for (int i = 0; i < 10; i++) x[r][i] *= inv;
    }
#pragma unroll
    for (int ks = 0; ks < 2; ks++)
#pragma unroll
        for (int i = 0; i < 4; i++) {
            const uint32_t p = pack2(x[i & 1][ks * 4 + (i >> 1) * 2], x[i & 1][ks * 4 + (i >> 1) * 2 + 1]);
            pa[ks][i] = sg ? 0u : p;
            pa[2 + ks][i] = sg ? p : 0u;
        }
#pragma unroll
    for (int r = 0; r < 2; r++) {
        const uint32_t p = pack2(x[r][8], x[r][9]);
        pa[4][r] = sg ? 0u : p;
        pa[4][2 + r] = sg ? p : 0u;
    }
}
__device__ __forceinline__ void qa_values(float* O, uint32_t (*pa)[4], const Cons& c, const Pipe& p) {
    mbar_wait(c.sb + B_FULL + p.stage * 8, p.phase);
    const uint32_t st = c.sb + p.stage * STAGE;
    const uint64_t dv = mkdesc(st + c.wg * 8192, 16384, 1024, 1), dm = mkdesc(st + 32768 + c.wg * 4096, 2048, 128, 0);
    pin<20>(&pa[0][0]);
    wg_fence();
    wgmma_rs128_first<1>(O, pa[0], dv);
#pragma unroll
    for (int ks = 1; ks < 4; ks++) wgmma_rs128<1>(O, pa[ks], dv + ks * 128);
    wgmma_rs128<0>(O, pa[4], dm);
    wg_commit();
}
__device__ __forceinline__ void epi_qa(const float* acc, Cons& c, Pend& d, int mb, int nb) {
    uint32_t* q = d.pk;
    pack_half(q, acc);
    pack_half(q + 32, acc + 64);
#pragma unroll 1
    for (int hh = 0; hh < 2; hh++) {
        uint32_t pa[5][4];
        float S[32], Sm[8], O[64];
        qa_scores(S, Sm, q, c, c.p);
        wg_wait<0>();
        pin<32>(S); pin<8>(Sm);
        release(c, c.p.stage);
        pipe_next(c.p);
        qa_softmax(pa, S, Sm, c);
        qa_values(O, pa, c, c.p);
#pragma unroll
        for (int i = 0; i < 32; i++) q[i] = q[32 + i];
        pin<32>(q);
        wg_wait<0>();
        pin<64>(O);
        release(c, c.p.stage);
        pipe_next(c.p);
        pack_half(q + 32, O);
    }
    d.kind = PEND_KVO; d.row = 4096 + mb * 256 + c.rank * 128 + c.wg * 64; d.col = nb * 256; d.cnt = C_O + mb * 4 + (nb >> 2);
}

__device__ __forceinline__ void epi_op(const float* acc, const Cons& c, Pend& d, int mb, int nb) {
    pack_half(d.pk, acc); pack_half(d.pk + 32, acc + 64);
    d.kind = PEND_OUT; d.row = mb * 256 + c.rank * 128 + c.wg * 64; d.col = 1024 + nb * 256;
}

__device__ __forceinline__ void epi_oph(const float* acc, const Cons& c, Pend& d, int mb, int nb) {
    pack_half(d.pk, acc);
    d.kind = PEND_OUTH; d.row = mb * 256 + c.rank * 128 + c.wg * 64; d.col = 1024 + nb * 128;
}

template <int HF>
__device__ __forceinline__ void epi_a2_half(const float* acc, const Params& P, Cons& c, int mb, int col0) {
    const int g = c.lane >> 2, t = c.lane & 3;
    const int row = mb * 256 + (g >> 1) * 64 + (c.rank * 16 + c.wg * 8 + c.wq * 2) * 2 + (g & 1);
    float* o = P.out + (size_t)row * 2048 + col0 + HF * 128 + t * 2;
    mbar_wait(c.sb + B_FULL + c.p.stage * 8, c.p.phase);
    const uint32_t st = c.sb + c.p.stage * STAGE, da = st + 32768 + (c.lane >> 3) * 16;
    const uint32_t xa = st + (c.wg * 64 + c.wq * 16 + (c.lane & 15)) * 128 + (((c.lane >> 4) ^ (c.lane & 7)) << 4);
#pragma unroll
    for (int j4 = 0; j4 < 4; j4++) {
        uint32_t x[8], dv[4];
        ldsm4(dv, da + j4 * 64);
        ldsm4(x, (xa ^ ((j4 & 1) << 6)) + (j4 >> 1) * 16384);
        ldsm4(x + 4, (xa ^ ((j4 & 1) << 6) ^ 32) + (j4 >> 1) * 16384);
#pragma unroll
        for (int i = 0; i < 4; i++) {
            const int j = j4 * 4 + i;
            const float* a = acc + HF * 64 + j * 4;
            const uint32_t u0 = hmul2(x[2 * i], dv[i]), u1 = hmul2(x[2 * i + 1], dv[i]);
            st_stream2(o + j * 8, a[0] + bf_lo(u0), a[1] + bf_hi(u0));
            st_stream2(o + 2 * 2048 + j * 8, a[2] + bf_lo(u1), a[3] + bf_hi(u1));
        }
    }
    __syncwarp();
    release(c, c.p.stage);
    pipe_next(c.p);
}

#define TSTAMP(i)
__device__ __forceinline__ float2 cmul(float2 a, float2 b) { return make_float2(fmaf(a.x, b.x, -a.y * b.y), fmaf(a.x, b.y, a.y * b.x)); }
__device__ __forceinline__ float2 cfma(float2 a, float2 b, float2 u) { return make_float2(fmaf(a.x, b.x, fmaf(-a.y, b.y, u.x)), fmaf(a.x, b.y, fmaf(a.y, b.x, u.y))); }
__device__ __forceinline__ float4 ssm_coef(float lre, float lim, float logdt) {
    const float dt = __bfloat162float(__float2bfloat16(expf(logdt)));
    const float ea = expf(dt * lre);
    float sn, cn;
    sincosf(dt * lim, &sn, &cn);
    const float br = ea * cn, bi = ea * sn, nr = br - 1.f;
    float cr, ci;
    if (fabsf(lre) >= fabsf(lim)) { const float r = lim / lre, dn = lre + lim * r; cr = (nr + bi * r) / dn; ci = (bi - nr * r) / dn; }
    else { const float r = lre / lim, dn = lre * r + lim; cr = (nr * r + bi) / dn; ci = (bi * r - nr) / dn; }
    return make_float4(br, bi, cr, ci);
}
__device__ __forceinline__ void epi_a1(const float* acc, const Params& P, const Cons& c, Pend& d, int mb, int nb, uint32_t atag) {
    const int t = c.lane & 3;
    const int p = nb * 128 + c.rank * 64 + c.wg * 32 + c.wq * 8 + (c.lane >> 2);
    uint32_t cw[4];
    lds128(cw, c.sb + S_COEF + (p & 63) * 16);
    const float4 cf = make_float4(__uint_as_float(cw[0]), __uint_as_float(cw[1]), __uint_as_float(cw[2]), __uint_as_float(cw[3]));
    TSTAMP(1)
    const float2 lam = make_float2(cf.x, P.swap_ri ? -cf.y : cf.y);
    const float a0 = P.swap_ri ? -2.f * cf.w : 2.f * cf.z, a1 = P.swap_ri ? 2.f * cf.z : -2.f * cf.w;
    const float b0 = P.swap_ri ? -2.f * cf.z : -2.f * cf.w, b1 = P.swap_ri ? -2.f * cf.w : -2.f * cf.z;
    float2 h = make_float2(0.f, 0.f);
#pragma unroll
    for (int round = 0; round < 2; round++) {
#pragma unroll
        for (int j = 0; j < 32; j++) {
            h = cfma(lam, h, make_float2(acc[j * 4], acc[j * 4 + 2]));
            const float r0 = fmaf(a0, h.x, a1 * h.y), m0 = fmaf(b0, h.x, b1 * h.y);
            h = cfma(lam, h, make_float2(acc[j * 4 + 1], acc[j * 4 + 3]));
            d.pk[j * 2] = pack2(r0, fmaf(a0, h.x, a1 * h.y));
            d.pk[j * 2 + 1] = pack2(m0, fmaf(b0, h.x, b1 * h.y));
        }
        if (round) break;
        float2 l64 = lam;
#pragma unroll
        for (int i = 0; i < 6; i++) l64 = cmul(l64, l64);
        const float2 l128 = cmul(l64, l64), l256 = cmul(l128, l128);
        float2 o = make_float2(__shfl_up_sync(0xffffffffu, h.x, 1), __shfl_up_sync(0xffffffffu, h.y, 1));
        if (t >= 1) h = cfma(l64, o, h);
        o = make_float2(__shfl_up_sync(0xffffffffu, h.x, 2), __shfl_up_sync(0xffffffffu, h.y, 2));
        if (t >= 2) h = cfma(l128, o, h);
        TSTAMP(2)
        if (t == 3) st_relaxed2(&g_agg[mb * 1024 + p], (__float_as_uint(h.x) & ~1u) | atag, __float_as_uint(h.y));
        h = make_float2(__shfl_up_sync(0xffffffffu, h.x, 1), __shfl_up_sync(0xffffffffu, h.y, 1));
        if (t == 0) h = make_float2(0.f, 0.f);
        uint32_t ax[7], ay[7];
        int n = 0;
        while (true) {
            uint32_t bad = 0;
#pragma unroll
            for (int j = 0; j < 7; j++) { ax[j] = atag; ay[j] = 0; ld_relaxed2_if(ax[j], ay[j], &g_agg[j * 1024 + p], j < mb); }
#pragma unroll
            for (int j = 0; j < 7; j++) bad |= ax[j] ^ atag;
            if (tags_ok(bad)) break;
            __nanosleep(400);
            if (++n > SPIN_LIMIT) spin_fault();
        }
        float2 carry = make_float2(0.f, 0.f);
#pragma unroll
        for (int j = 0; j < 7; j++) if (j < mb) carry = cfma(l256, carry, make_float2(__uint_as_float(ax[j]), __uint_as_float(ay[j])));
        float2 w = (t & 1) ? l64 : make_float2(1.f, 0.f);
        if (t & 2) w = cmul(w, l128);
        h = cfma(w, carry, h);
        TSTAMP(3)
    }
    TSTAMP(4)
    d.kind = PEND_HT; d.row = nb * 128 + c.rank * 64 + c.wg * 32; d.col = mb * 256; d.cnt = C_HT + mb * 2 + (nb >> 2);
}

__device__ __forceinline__ uint32_t acquire_stage(uint32_t sb, Pipe& p, uint32_t bytes) {
    mbar_wait(sb + B_EMPTY + p.stage * 8, p.phase ^ 1);
    mbar_expect(sb + B_FULL + p.stage * 8, bytes);
    return p.stage;
}
#define AHEAD 1
__device__ __forceinline__ void watcher(const Params& P, const uint32_t sb, const int rank, const int lane) {
    const uint32_t epoch = ld_relaxed1(&g_cnt(C_EPOCH)), e1 = epoch + 1;
    sts32(sb + S_EPOCH, epoch);
    __syncwarp();
    if (lane == 0 && atomicInc(&g_cnt(C_DONE), (DBGF(32) ? 95 : NPAIR * 2 - 1) + (epoch & P.zero)) == (DBGF(32) ? 95 : NPAIR * 2 - 1)) atomicAdd(&g_cnt(C_EPOCH), 1);
    if (gridDim.x != 96) {
        uint32_t v;
        asm("mov.u32 %0, %%smid;" : "=r"(v));
        if (lane == 0 && rank == 0) st_relaxed1(g_hint + 6272 + (blockIdx.x >> 1), e1 << 8 | v >> 1);
        for (int k = 0;; k++) {
            __nanosleep(1000);
            v = ld_relaxed1(g_hint + 6272 + min(lane, 17));
            if (__all_sync(0xffffffffu, (v ^ e1 << 8) < 256)) break;
            if (k > SPIN_LIMIT) spin_fault();
        }
        const uint32_t key = ((v & 255) >= 62 ? 0 : tpc_gpc(v & 255)) * 32 + lane;
        sts32(sb + S_TAIL, 48 + __popc(__ballot_sync(0xffffffffu, key < __shfl_sync(0xffffffffu, key, blockIdx.x >> 1)) & 0x3ffff));
        __syncwarp();
    }
    uint32_t met = 1;
    if (lane == 0) asm volatile("st.release.cta.shared.u32 [%0], 1;" ::"r"(sb + S_DEP) : "memory");
    const int pair = lds32(sb + S_TAIL), first = ITEM_OFF(pair) + (pair < NCHAIN ? NPRE + 1 : 1);
#pragma unroll 1
    for (int it = first; it < ITEM_OFF(pair + 1); it++) {
        const int item = ITEM(it), type = item >> 8, mb = (item >> 5) & 7, nb = item & 31;
        const int n = (0x24021420 >> (type * 4)) & 7;
        for (int k = 0; it > first && (int)lds32(sb + S_CUR) < it - AHEAD; k++) { __nanosleep(200); if (k > SPIN_LIMIT) spin_fault(); }
#pragma unroll 1
        for (int i = 0; i < n; i++) {
            int idx = n == 4 ? C_O + mb * 4 + i : C_HT + mb * 2 + i;
            uint32_t target = e1 * 16;
            if (type == T_A1) { idx = C_COEF; target = e1 * 4; }
            if (type == T_QA) {
                idx = i ? C_FLAG + (lane & 1) * 32 + nb * 2 + ((lane >> 1) & 1) : C_KV + mb;
                target = i ? epoch * 64 + mb * 8 + rank * 4 + 4 : e1 * 128;
            }
            if (lane < 4) { wait_count(&g_cnt(idx), target); fence_async(); }
            __syncwarp();
            if (lane == 0) asm volatile("st.release.cta.shared.u32 [%0], %1;" ::"r"(sb + S_DEP), "r"(++met) : "memory");
        }
    }
}
__device__ __forceinline__ bool dep_met(uint32_t sb, uint32_t n) { uint32_t v; asm volatile("ld.acquire.cta.shared.u32 %0, [%1];" : "=r"(v) : "r"(sb + S_DEP) : "memory"); return v >= n; }
__device__ __forceinline__ void dep_wait(uint32_t sb, uint32_t n) { for (int k = 0; !dep_met(sb, n); k++) { __nanosleep(32); if (k > SPIN_LIMIT * 8) spin_fault(); } }
__device__ __forceinline__ void producer(const Params& P, const uint32_t sb, int pair, const int rank) {
    Pipe p = {0, 0};
    uint32_t dep = 1;
    for (int it = ITEM_OFF(pair); it < ITEM_OFF(pair + 1); it++) {
        const int item = ITEM(it), type = item >> 8, mb = (item >> 5) & 7, nb = item & 31;
        if (type == T_CHAIN) {
            sts32(sb + S_CUR, 0);
            const uint32_t epoch = ld_relaxed1(&g_cnt(C_EPOCH)), e1 = epoch + 1;
            const int role = pair >> 4, h = (pair & 15) * 2 + rank;
#pragma unroll 1
            for (int i = 0, q = 0; i < 8; i++) {
                const int n = (0x13003333 >> (i * 4)) & 3;
                const uint32_t st = acquire_stage(sb, p, n * 16384);
                SSTAMP(1, i == 6) SSTAMP(3, i == 7)
#pragma unroll 1
                for (int k = 0; k < 2 * n; k++, q++)
                    tma3d(sb + st * STAGE + k * 8192, &P.tm[M_CQ + role], h * 128 + (fill_unit(q >> 1) & 1) * 64, word_col((fill_unit(q >> 1) & 14) + (q & 1)) & 8, word_col((fill_unit(q >> 1) & 14) + (q & 1)) >> 4, sb + B_FULL + st * 8, role ? EVICT_NORMAL : POL(3));
                pipe_next(p);
            }
            if (role == 0 && !DBGF(1)) { wait_count(&g_cnt(C_KV), e1 * 128); fence_async(); }
            mbar_wait(sb + B_EMPTY + 16, 1); mbar_wait(sb + B_EMPTY + 24, 1);
            mbar_expect(sb + B_WO, role ? 98304 : 65536);
            if (role == 0) { mbar_expect(sb + B_KVFULL, 16384); mbar_expect(sb + B_KVFULL + 8, 16384); }
#pragma unroll 1
            for (int k = role ? 0 : -4; k < 12; k++) {
                const bool kv = role == 0 && (k & 8);
                const int sg = k > 0;
                tma4d(kv ? sb + S_KV + sg * 16384 + (k & 3) * 4096 : sb + S_W2 + k * 8192, &P.tm[kv ? M_KV4 : M_CO + (k & 1)],
                      kv ? h * 128 + (k & 1) * 64 : (role == 0 ? 0 : role == 1 ? 256 : 640) + (k >> 1) * 64, kv ? (k & 2) * 1024 + sg * 32 : h * 8, sb + (kv ? B_KVFULL + sg * 8 : B_WO), POL(2));
            }
            SSTAMP(5, true)
            if (pair < 16) {
#pragma unroll 1
                for (int s = 2; s < 63; s++) {
                    mbar_wait(sb + B_KVGO + (s & 1) * 8, ((s >> 1) + 1) & 1);
                    wait_time(gtime() + P.dk, sb);
                    SSTAMP(6, s == 2)
                    const uint32_t bar = sb + B_KVFULL + (s & 1) * 8, dst = sb + S_KV + (s & 1) * 16384;
                    if (DBGF(2)) { mbar_arrive(bar); continue; }
                    mbar_expect(bar, 16384);
#pragma unroll 1
                    for (int i = 0; i < 4; i++) tma2d(dst + i * 4096, &P.tm[M_KVO], (pair * 2 + rank) * 128 + (i & 1) * 64, (i >> 1) * 2048 + (DBGF(32 | 512) ? s & 7 : s) * 32, bar, POL(1));
                    if ((s & 7) == 7 && !DBGF(1)) { wait_count(&g_cnt(C_KV + 1 + (s >> 3)), e1 * 128); fence_async(); }
                }
            } else {
                uint32_t* flag = &g_cnt(C_FLAG + pair * 2 + rank - 32);
                const int x = pair * 2 + rank - 32;
#pragma unroll 1
                for (int s = 0; s < 64; s++) {
                    mbar_wait(sb + B_PERS, s & 1);
                    if (s < 63) wait_time(gtime() + P.dp, sb);
                    if (!DBGF(4)) bulk_s2g((role == 1 ? g_km : g_vmt) + (s * 32 + h) * 512, sb + S_QX, 2048);
                    if (s < 57) {
                        uint8_t* m = P.gm + ((s + 6) & 7) * M_SLOT + (x >> 1) * 1024 + (x & 1) * 256;
                        bulk_s2g(m, sb + S_SX, 256); bulk_s2g(m + 512, sb + S_SX, 128);
                        bulk_s2g(g_f + ((s + 6) & 7) * F_SLOT + x * 768, sb + S_SX + 256, 768);
                    }
                    bulk_commit();
                    bulk_wait_read();
                    mbar_arrive(sb + B_KVGO);
                    bulk_wait_all();
                    fence_async();
                    if ((s & 3) == 3) st_relaxed1(flag, epoch * 64 + s + 1);
                }
            }
            mbar_wait(sb + B_RESUME, 0);
            pair = lds32(sb + S_TAIL);
            it = ITEM_OFF(pair) + NPRE;
            continue;
        }
        if (it == ITEM_OFF(pair) && pair >= NCHAIN) it = -1; else sts32(sb + S_CUR, it);
        const int m0 = mb * 256 + rank * 128;
        if (type <= T_OP) {
            const CUtensorMap* ma = &P.tm[type == T_OP ? M_OA : M_BX];
            const CUtensorMap* mw = &P.tm[type == T_OP ? M_WO : type == T_QA ? M_WQ : nb < 16 ? M_WK : M_WV];
            const int nk = type == T_OP ? 64 : 16, nc = (nb & 15) * 4 + rank * 2, ma0 = type == T_OP ? 4096 + m0 : m0;
#pragma unroll 1
            for (int kt = 0; kt < nk; kt++) {
                if (type == T_OP && (kt & 15) == 0) dep_wait(sb, ++dep);
                if (DBGF(256) && pair >= NCHAIN) { acquire_stage(sb, p, 0); pipe_next(p); continue; }
                const uint32_t st = acquire_stage(sb, p, STAGE), bar = sb + B_FULL + st * 8;
                tma2d(sb + st * STAGE, ma, kt * 64, ma0, bar, type == T_OP ? POL(6) : type == T_QA ? POL(12) : POL(13));
                tma3d_mc(sb + st * STAGE + 16384 + rank * 16384, mw, 0, kt * 64, nc, bar, type == T_KV && mb == 7 ? POL(9) : EVICT_NORMAL);
                pipe_next(p);
            }
            if (type == T_QA) {
                dep += 2;
                dep_wait(sb, dep);
#pragma unroll 1
                for (int e = 0; e < 4; e++) {
                    const uint32_t st = acquire_stage(sb, p, 40960), bar = sb + B_FULL + st * 8, dst = sb + st * STAGE;
                    tma2d(dst, &P.tm[M_OA], nb * 256 + (e >> 1) * 128, (e & 1) * 2048 + m0, bar, POL(0));
                    tma2d(dst + 16384, &P.tm[M_OA], nb * 256 + (e >> 1) * 128 + 64, (e & 1) * 2048 + m0, bar, POL(0));
                    const uint32_t* src = ((e & 1) ? g_vmt : g_km) + ((mb * 8 + rank * 4) * 32 + nb * 2 + (e >> 1)) * 512;
#pragma unroll 1
                    for (int i = 0; i < 4; i++) bulk_g2s(dst + 32768 + i * 2048, src + i * 32 * 512, 2048, bar);
                    pipe_next(p);
                }
            }
        } else if (type == T_OPH) {
#pragma unroll 1
            for (int kt = 0; kt < 64; kt++) {
                if ((kt & 15) == 0) dep_wait(sb, ++dep);
                const uint32_t st = acquire_stage(sb, p, 32768), bar = sb + B_FULL + st * 8;
                tma2d(sb + st * STAGE, &P.tm[M_OA], kt * 64, 4096 + m0, bar, POL(6));
                tma2d_mc(sb + st * STAGE + 16384 + rank * 8192, &P.tm[M_WOH], nb * 128 + rank * 64, kt * 64, bar, EVICT_NORMAL);
                pipe_next(p);
            }
        } else if (type == T_A1) {
#pragma unroll 1
            for (int kt = 0; kt < 16; kt++) {
                if (kt == 15) dep_wait(sb, ++dep);
                const uint32_t st = acquire_stage(sb, p, kt == 15 ? STAGE + 1024 : STAGE), bar = sb + B_FULL + st * 8;
                if (kt == 15) bulk_g2s(sb + S_COEF, g_coef + nb * 128 + rank * 64, 1024, bar);
                tma4d(sb + st * STAGE, &P.tm[M_AB], kt * 64, nb * 16 + rank * 8, bar, POL(10));
                tma4d_mc(sb + st * STAGE + 16384 + rank * 16384, &P.tm[M_AX], kt * 64, mb * 128 + rank * 16, bar, POL(10));
                pipe_next(p);
            }
        } else {
            const int hw = type == T_A2H ? 64 : 128;
            const CUtensorMap* mc = &P.tm[type == T_A2H ? M_CREH : M_CRE];
#pragma unroll 1
            for (int kt = 0; kt < 32; kt++) {
                if ((kt & 15) == 0) dep_wait(sb, ++dep);
                const uint32_t st = acquire_stage(sb, p, 16384 + hw * 256), bar = sb + B_FULL + st * 8;
                tma3d(sb + st * STAGE, &P.tm[M_HT], 0, (kt & 1) * 1024 + (kt >> 1) * 64, mb * 4 + rank * 2, bar, POL(7));
                tma2d_mc(sb + st * STAGE + 16384 + rank * hw * 128, mc + (kt & 1), (kt >> 1) * 64, (nb * 2 + rank) * hw, bar, POL(11));
                pipe_next(p);
            }
#pragma unroll 1
            for (int col = nb * 2 * hw; col < (nb + 1) * 2 * hw; col += 128) {
                const uint32_t st = acquire_stage(sb, p, 32768 + 256), bar = sb + B_FULL + st * 8;
                tma4d(sb + st * STAGE, &P.tm[M_AX], col, mb * 128 + rank * 16, bar, POL(8));
                tma4d(sb + st * STAGE + 16384, &P.tm[M_AX], col + 64, mb * 128 + rank * 16, bar, POL(8));
                bulk_g2s(sb + st * STAGE + 32768, P.Dskip + col, 256, bar);
                pipe_next(p);
            }
        }
        if (it < 0) { dep_wait(sb, 1); pair = lds32(sb + S_TAIL); it = ITEM_OFF(pair); }
    }
}

__device__ __forceinline__ uint32_t fresh_tid() { uint32_t t; asm volatile("mov.u32 %0, %%tid.x;" : "=r"(t)); return t; }
__device__ __forceinline__ uint32_t fresh_ctaid() { uint32_t t; asm volatile("mov.u32 %0, %%ctaid.x;" : "=r"(t)); return logical_cta(t); }
__device__ __forceinline__ void reset_state(Cons& c, Pend& d, uint32_t sb, bool resumed) {
    const uint32_t t = fresh_tid(), b = fresh_ctaid();
    const int w = __shfl_sync(0xffffffffu, t >> 5, 0);
    c.sb = sb; c.wg = w >> 2; c.wq = w & 3; c.lane = t & 31;
    c.rank = __shfl_sync(0xffffffffu, b & 1, 0); c.pair = __shfl_sync(0xffffffffu, resumed && b < NCHAIN * 2 ? lds32(sb + S_TAIL) : b >> 1, 0);
    c.rel = mapa(sb + B_EMPTY, cluster_rank() ^ (c.lane & 1));
    c.p.stage = 0; c.p.phase = 0;
    c.nst = resumed && c.pair < NCHAIN ? 2 * NPRE : 0;
    d = Pend{};
}
#define PROF_ITEM(i)
#define PROF_MAIN(i)

__global__ void __launch_bounds__(384, 1) fused_kernel(const __grid_constant__ Params P) {
    extern __shared__ __align__(1024) uint8_t smem[];
    const uint32_t sb = smem_u32(smem);
    asm volatile("griddepcontrol.launch_dependents;");
    const int tid = threadIdx.x, lane = tid & 31;
    const int warp = __shfl_sync(0xffffffffu, tid >> 5, 0);
    const int pair = __shfl_sync(0xffffffffu, logical_cta(blockIdx.x) >> 1, 0), rank = __shfl_sync(0xffffffffu, blockIdx.x & 1, 0);
    if (tid == 0) {
        if (sb & 1023) spin_fault();
        sts32(sb + S_DEP, 0); sts32(sb + S_CUR, 0); sts32(sb + S_TAIL, pair); sts32(sb + S_CTA, pair * 2 + rank);
        for (int i = 0; i < NSTAGE; i++) { mbar_init(sb + B_FULL + i * 8, 1); mbar_init(sb + B_EMPTY + i * 8, 16); }
        mbar_init(sb + B_RESUME, 2);
        mbar_init(sb + B_KVFULL, 1); mbar_init(sb + B_KVFULL + 8, 1);
        mbar_init(sb + B_GO, 1); mbar_init(sb + B_KVGO, 1); mbar_init(sb + B_KVGO + 8, 1); mbar_init(sb + B_K, 1); mbar_init(sb + B_V, 1); mbar_init(sb + B_PERS, pair < 16 ? 1 : 8); mbar_init(sb + B_INIT, 3);
        mbar_init(sb + B_WO, 1);
        for (int i = 0; i < 2; i++) { mbar_init(sb + B_SFULL + i * 8, 4); mbar_init(sb + B_SFREE + i * 8, 1); }
        mbar_init(sb + B_RELA, 1); mbar_init(sb + B_RELB, 1);
        asm volatile("fence.mbarrier_init.release.cluster;" ::: "memory");
        if (pair < 16) { mbar_expect(sb + B_K, KE ? 1024 : 2048); mbar_expect(sb + B_PERS, 1024); }
        mbar_expect(sb + B_V, 2048);
    }
    __syncthreads();
    cluster_arrive();
    if (warp >= 8) {
        asm volatile("setmaxnreg.dec.sync.aligned.u32 24;");
        if (warp != 8) cluster_wait();
        if (warp == 10 && lane < M_COUNT) map_prefetch(&P.tm[lane]);
        if (warp == 11 && lane == 0 && pair < 16) {
            const uint32_t t0 = gtime();
#pragma unroll 1
            for (int i = 0; i < 32; i++) {
                wait_time(t0 + P.pf0 + i * P.pf1, sb);
                asm volatile("cp.async.bulk.prefetch.tensor.3d.L2.global [%0, {%1, %2, %3}];" ::"l"(&P.tm[M_CQ]), "r"((pair * 2 + rank) * 128 + (i & 1) * 64), "r"((i & 2) * 4), "r"((i >> 2) * 8) : "memory");
            }
        }
        if (warp == 9 && pair < NCHAIN) pacer(P, sb, lane);
        if (warp == 9) watcher(P, sb, rank, lane);
        if (warp >= 10 && lane == 0) store_warp(P, sb, warp - 10);
        if (warp == 8) {
            cluster_wait();
            if (lane == 0) producer(P, sb, lds32(sb + S_CTA) >> 1, rank);
            __syncwarp();
            cluster_arrive(); cluster_wait();
        }
    } else {
        asm volatile("setmaxnreg.inc.sync.aligned.u32 240;");
        Cons c;
        Pend d;
        if (pair < NCHAIN) {
            mem0_max(P, sb, tid);
            cluster_wait();
            reset_state(c, d, sb, false);
#pragma unroll 1
            for (int i = 0; i < NPRE; i++) {
                PROF_ITEM(i)
                const int item = ITEM(ITEM_OFF(pair) + i);
                float acc[128];
                mainloop<256, true>(acc, P, c, d, T_KV);
                epi_kv(acc, c, d, (item >> 5) & 7, item & 31);
            }
            ISTAMP(4)
            drain<0, true>(P, c, d);
            drain<1, true>(P, c, d);
            PROF_ITEM(NPRE)
            uint32_t wr[NR][4];
            load_weights(wr, sb, warp, lane, [&]() { staging_wait(c); });
            const int h = (pair & 15) * 2 + rank;
            if (pair < 16) chain_role<0>(P, wr, sb, h, warp, lane);
            else if (pair < 32) chain_role<1>(P, wr, sb, h, warp, lane);
            else chain_role<2>(P, wr, sb, h, warp, lane);
            fence_async_smem();
            bar_sync(1, 256);
            const uint32_t t2 = fresh_tid();
            if (t2 < 2) mbar_arrive_cluster(mapa(sb + B_RESUME, cluster_rank() ^ t2));
        } else if (pair >= NPAIR - 2) {
            const int ch = (pair - (NPAIR - 2)) * 512 + rank * 256 + tid;
            g_coef[ch] = ssm_coef(__bfloat162float(P.Lre[ch]), __bfloat162float(P.Lim[ch]), __bfloat162float(P.logdt[ch]));
            bar_sync(1, 256);
            if (tid == 0) red_release(&g_cnt(C_COEF));
        }
        reset_state(c, d, sb, true);
        if (c.pair >= NCHAIN) cluster_wait();
        for (int it = ITEM_OFF(c.pair) + (c.pair < NCHAIN ? NPRE + 1 : 0);; it++) {
            const bool last = it == ITEM_OFF(c.pair + 1);
            if (d.kind != PEND_NONE && (last || !bar_and(5 + c.wg, mbar_test(sb + B_FULL + c.p.stage * 8, c.p.phase)))) drain_all(P, c, d);
            if (last) break;
            const int item = ITEM(it), type = item >> 8, mb = (item >> 5) & 7, nb = item & 31;
            PROF_ITEM(it - ITEM_OFF(c.pair))
            if (type >= T_OPH) {
                float acc[64];
                mainloop<128>(acc, P, c, d, type);
                PROF_MAIN(it - ITEM_OFF(c.pair))
                if (type == T_OPH) epi_oph(acc, c, d, mb, nb);
                else epi_a2_half<0>(acc, P, c, mb, nb * 128);
            } else {
                float acc[128];
                mainloop<256>(acc, P, c, d, type);
                PROF_MAIN(it - ITEM_OFF(c.pair))
                if (type == T_KV) epi_kv(acc, c, d, mb, nb);
                else if (type == T_QA) epi_qa(acc, c, d, mb, nb);
                else if (type == T_OP) epi_op(acc, c, d, mb, nb);
                else if (type == T_A1) epi_a1(acc, P, c, d, mb, nb, (lds32(sb + S_EPOCH) + 1) & 1);
                else { epi_a2_half<0>(acc, P, c, mb, nb * 256); epi_a2_half<1>(acc, P, c, mb, nb * 256); }
            }
            if (it == ITEM_OFF(c.pair)) { dep_wait(sb, 1); c.pair = __shfl_sync(0xffffffffu, lds32(sb + S_TAIL), 0); it = ITEM_OFF(c.pair); }
        }
        staging_wait(c);
        staging_post(c, PEND_NONE, 0, 0, 0);
        cluster_arrive(); cluster_wait();
    }
}

typedef CUresult (*EncodeFn)(CUtensorMap*, CUtensorMapDataType, cuuint32_t, void*, const cuuint64_t*, const cuuint64_t*, const cuuint32_t*, const cuuint32_t*,
                             CUtensorMapInterleave, CUtensorMapSwizzle, CUtensorMapL2promotion, CUtensorMapFloatOOBfill);
void encode(EncodeFn fn, CUtensorMap* m, const void* base, int rank, const uint64_t* dims, const uint64_t* strides, const uint32_t* box, CUtensorMapSwizzle swz = CU_TENSOR_MAP_SWIZZLE_128B) {
    cuuint64_t d[5], s[5]; cuuint32_t b[5], e[5];
    for (int i = 0; i < rank; i++) { d[i] = dims[i]; b[i] = box[i]; e[i] = 1; if (i) s[i - 1] = strides[i - 1]; }
    fn(m, CU_TENSOR_MAP_DATA_TYPE_BFLOAT16, rank, (void*)base, d, s, b, e, CU_TENSOR_MAP_INTERLEAVE_NONE, swz,
       CU_TENSOR_MAP_L2_PROMOTION_L2_256B, CU_TENSOR_MAP_FLOAT_OOB_FILL_NONE);
}
void map_kmajor(EncodeFn fn, CUtensorMap* m, const void* base, uint64_t rows, uint64_t cols, uint32_t box_rows) {
    const uint64_t d[2] = {cols, rows}, s[1] = {cols * 2}; const uint32_t b[2] = {64, box_rows};
    encode(fn, m, base, 2, d, s, b);
}
void map_mnmajor(EncodeFn fn, CUtensorMap* m, const void* base, uint64_t krows, uint64_t cols) {
    const uint64_t d[3] = {64, krows, cols / 64}, s[2] = {cols * 2, 128}; const uint32_t b[3] = {64, 64, 2};
    encode(fn, m, base, 3, d, s, b);
}

}

extern "C" void kernel_launch(void* const* d_in, const int* in_sizes, int n_in, void* d_out, int out_size) {
    static Params P;
    static EncodeFn fn = nullptr;
    if (!fn) {
        cudaDriverEntryPointQueryResult q;
        cudaGetDriverEntryPoint("cuTensorMapEncodeTiled", (void**)&fn, cudaEnableDefault, &q);
        cudaFuncSetAttribute(fused_kernel, cudaFuncAttributeMaxDynamicSharedMemorySize, S_TOTAL);
    }
    const bf16* in[15];
    for (int i = 0; i < 15; i++) in[i] = (const bf16*)d_in[i];
    void *kvo, *ht, *gm;
    cudaGetSymbolAddress(&gm, g_m);
    P.gm = (uint8_t*)(((uintptr_t)gm + 32767) & ~(uintptr_t)32767);
    cudaGetSymbolAddress(&kvo, g_kvo);
    cudaGetSymbolAddress(&ht, g_ht);
    map_kmajor(fn, &P.tm[M_BX], in[9], 2048, 1024, 128);
    map_mnmajor(fn, &P.tm[M_WQ], in[11], 1024, 4096);
    map_mnmajor(fn, &P.tm[M_WK], in[12], 1024, 4096);
    map_mnmajor(fn, &P.tm[M_WV], in[13], 1024, 4096);
    map_mnmajor(fn, &P.tm[M_WO], in[14], 4096, 1024);
    map_kmajor(fn, &P.tm[M_OA], kvo, 3 * 2048, 4096, 128);
    P.swap_ri = in[4] < in[3];
    {
        const bf16* lo = P.swap_ri ? in[4] : in[3];
        const uint64_t diff = (uint64_t)((const char*)(P.swap_ri ? in[3] : in[4]) - (const char*)lo);
        const uint64_t d[4] = {1024, 8, 2, 128}, s[3] = {2048, diff, 16384}; const uint32_t b[4] = {64, 8, 2, 8};
        encode(fn, &P.tm[M_AB], lo, 4, d, s, b);
    }
    {
        const uint64_t d[4] = {1024, 2, 4, 1024}, s[3] = {2048, 64 * 2048, 4096}; const uint32_t b[4] = {64, 2, 4, 16};
        encode(fn, &P.tm[M_AX], in[0], 4, d, s, b);
    }
    map_mnmajor(fn, &P.tm[M_HT], ht, 2048, 2048);
    map_kmajor(fn, &P.tm[M_CRE], in[5], 1024, 1024, 128);
    map_kmajor(fn, &P.tm[M_CIM], in[6], 1024, 1024, 128);
    map_kmajor(fn, &P.tm[M_KVO], kvo, 3 * 2048, 4096, 32);
    map_kmajor(fn, &P.tm[M_HTS], ht, 2048, 2048, 32);
    map_kmajor(fn, &P.tm[M_WOH], in[14], 4096, 1024, 64);
    map_kmajor(fn, &P.tm[M_CREH], in[5], 1024, 1024, 64);
    map_kmajor(fn, &P.tm[M_CIMH], in[6], 1024, 1024, 64);
    for (int i = 0; i < 3; i++) {
        const uint64_t d[3] = {4096, 16, 64}, s[2] = {8192, 16 * 8192}; const uint32_t b[3] = {64, 8, 8};
        encode(fn, &P.tm[M_CQ + i], in[11 + i], 3, d, s, b);
    }
    {
        const uint64_t d[4] = {4096, 1, 1, 4096}, s[3] = {8192, 8192, 8192}; const uint32_t b[4] = {64, 1, 1, 32};
        encode(fn, &P.tm[M_KV4], kvo, 4, d, s, b);
    }
    for (int e = 0; e < 2; e++) {
        const uint64_t d[4] = {1024, 2, 4, 256}, s[3] = {8 * 2048, 2 * 2048, 16 * 2048}; const uint32_t b[4] = {64, 2, 4, 8};
        encode(fn, &P.tm[M_CO + e], in[14] + e * 1024, 4, d, s, b);
    }
    P.Wq = in[11]; P.Wk = in[12]; P.Wv = in[13]; P.Wo = in[14]; P.mem0 = in[10];
    P.Lre = in[1]; P.Lim = in[2]; P.logdt = in[7]; P.Dskip = in[8];
    P.out = (float*)d_out;
    P.two26 = 1u << 26;
    P.lag = 0x22023302;
    P.ds = 400; P.dc = 1600; P.alpha = 0.3f; P.extra = 200; P.da = 120; P.db = 355; P.dk = 750; P.dp = 1500; P.dv = 60; P.pf0 = 2000; P.pf1 = 250; P.back = 150; P.ds0 = 800;
    for (int i = 0; i < (DBGF(32) ? 1 : 2); i++) {
        cudaLaunchConfig_t cfg = {};
        cfg.gridDim = dim3(i ? 36 : 96); cfg.blockDim = dim3(384); cfg.dynamicSmemBytes = S_TOTAL; cfg.stream = cudaStreamPerThread;
        cudaLaunchAttribute at[2];
        at[0].id = cudaLaunchAttributeClusterDimension; at[0].val.clusterDim.x = i ? 2 : 6; at[0].val.clusterDim.y = at[0].val.clusterDim.z = 1;
        at[1].id = cudaLaunchAttributeProgrammaticStreamSerialization; at[1].val.programmaticStreamSerializationAllowed = 1;
        cfg.attrs = at; cfg.numAttrs = 1 + i;
        cudaLaunchKernelEx(&cfg, fused_kernel, P);
    }
}
```
